```python
import torch

def _softmax(x, axis=-1):
    return torch.softmax(x, dim=axis)

def _gelu(x):
    return torch.nn.functional.gelu(x, approximate='tanh')

def _silu(x):
    return torch.nn.functional.silu(x)

def _sigmoid(x):
    return torch.sigmoid(x)

def _layernorm(x, axis=-1, eps=1e-05):
    m = x.mean(dim=axis, keepdim=True)
    v = x.var(dim=axis, keepdim=True, unbiased=False)
    return (x - m) / torch.sqrt(v + eps)

def _scatter_add(tgt, idx, src, axis=0):
    return tgt.clone().index_add_(axis, idx, src)

def _segment_sum(src, seg, n):
    out = torch.zeros((n,) + src.shape[1:], dtype=src.dtype)
    return out.index_add_(0, seg, src)

def _pad(x, pw):
    flat = tuple((v for pair in reversed(pw) for v in pair))
    return torch.nn.functional.pad(x, flat)
kernel_name = 'concat_heads__ssm_conv_s5__memory_aug_recurrent_mem_tr__prompt'

def setup_inputs():

    _w = lambda a: (lambda t: t.to(torch.bfloat16) if t.is_floating_point() else t)(torch.as_tensor(a))

    def _A_setup():
        B, S, D = (1, 2048, 1024)
        P = D
        Lambda_re = -0.5 * (lambda _x: torch.exp(torch.as_tensor(_x)))((lambda *s: torch.randn(*s, dtype=torch.bfloat16) * 0.8)(P))
        Lambda_im = (lambda *s: torch.randn(*s, dtype=torch.bfloat16) * 0.8)(P) * 1.0
        B_re = (lambda *s: torch.randn(*s, dtype=torch.bfloat16) * 0.8)(P, D) * D ** (-0.5)
        B_im = (lambda *s: torch.randn(*s, dtype=torch.bfloat16) * 0.8)(P, D) * D ** (-0.5)
        C_re = (lambda *s: torch.randn(*s, dtype=torch.bfloat16) * 0.8)(D, P) * P ** (-0.5)
        C_im = (lambda *s: torch.randn(*s, dtype=torch.bfloat16) * 0.8)(D, P) * P ** (-0.5)
        log_dt = (lambda *s: torch.randn(*s, dtype=torch.bfloat16) * 0.8)(P) * 0.3 - 2.0
        Dskip = (lambda *s: torch.randn(*s, dtype=torch.bfloat16) * 0.8)(D)
        return {'x': _w((lambda *s: torch.randn(*s, dtype=torch.bfloat16) * 0.05)(B, S, D)), 'Lambda_re': _w(Lambda_re), 'Lambda_im': _w(Lambda_im), 'B_re': _w(B_re), 'B_im': _w(B_im), 'C_re': _w(C_re), 'C_im': _w(C_im), 'log_dt': _w(log_dt), 'Dskip': _w(Dskip)}
    _A_in = _A_setup()

    def _B_setup():
        B, S, Dm = (1, 2048, 1024)
        H, Dh = (32, 128)
        M, seg = (8, 32)
        seg = min(seg, S)
        S = S // seg * seg
        return {'x': _w((lambda *s: torch.randn(*s, dtype=torch.bfloat16) * 0.05)(B, S, Dm)), 'mem0': _w((lambda *s: torch.randn(*s, dtype=torch.bfloat16) * 0.8)(B, M, Dm)), 'Wq': _w((lambda *s: torch.randn(*s, dtype=torch.bfloat16) * 3.2)(Dm, H, Dh) * Dm ** (-0.5)), 'Wk': _w((lambda *s: torch.randn(*s, dtype=torch.bfloat16) * 3.2)(Dm, H, Dh) * Dm ** (-0.5)), 'Wv': _w((lambda *s: torch.randn(*s, dtype=torch.bfloat16) * 0.8)(Dm, H, Dh) * Dm ** (-0.5)), 'Wo': _w((lambda *s: torch.randn(*s, dtype=torch.bfloat16) * 0.8)(H, Dh, Dm) * (H * Dh) ** (-0.5)), 'seg_len': seg}
    _B_in = _B_setup()
    return {'A_x': _A_in['x'], 'A_Lambda_re': _A_in['Lambda_re'], 'A_Lambda_im': _A_in['Lambda_im'], 'A_B_re': _A_in['B_re'], 'A_B_im': _A_in['B_im'], 'A_C_re': _A_in['C_re'], 'A_C_im': _A_in['C_im'], 'A_log_dt': _A_in['log_dt'], 'A_Dskip': _A_in['Dskip'], 'B_x': _B_in['x'], 'B_mem0': _B_in['mem0'], 'B_Wq': _B_in['Wq'], 'B_Wk': _B_in['Wk'], 'B_Wv': _B_in['Wv'], 'B_Wo': _B_in['Wo'], 'B_seg_len': _B_in['seg_len']}

def reference(A_x, A_Lambda_re, A_Lambda_im, A_B_re, A_B_im, A_C_re, A_C_im, A_log_dt, A_Dskip, B_x, B_mem0, B_Wq, B_Wk, B_Wv, B_Wo, B_seg_len):

    def _A_ref(x, Lambda_re, Lambda_im, B_re, B_im, C_re, C_im, log_dt, Dskip):
        Bsz, L, H = x.shape
        Lam = Lambda_re + 1j * Lambda_im
        Bmat = B_re + 1j * B_im
        Cmat = C_re + 1j * C_im
        dt = torch.exp(log_dt)
        Lam_bar = torch.exp(dt * Lam)
        B_bar = ((Lam_bar - 1.0) / Lam)[:, None] * Bmat
        Bu = torch.einsum('bld,pd->blp', x + 0j, B_bar)
        h = torch.zeros_like(Bu[:, 0, :])
        hs = []
        for t in range(L):
            h = Lam_bar[None, :] * h + Bu[:, t, :]
            hs.append(h)
        hseq = torch.stack(hs, 1)
        y = 2.0 * torch.einsum('blp,dp->bld', hseq, Cmat).real + x * Dskip[None, None, :]
        return y

    def _B_ref(x, mem0, Wq, Wk, Wv, Wo, seg_len):
        B, S, Dm = x.shape
        H, Dh = (Wq.shape[1], Wq.shape[2])
        M = mem0.shape[1]
        scale = Dh ** (-0.5)
        n_seg = S // seg_len
        L = M + seg_len
        idx = torch.arange(L)
        mask = (idx[:, None] < M) | (idx[:, None] >= idx[None, :])
        mem = mem0
        outs = []
        for s in range(n_seg):
            xs = x[:, s * seg_len:(s + 1) * seg_len, :].clone()
            h = torch.concatenate([mem, xs], axis=1)
            q = torch.einsum('btd,dhe->bhte', h, Wq)
            k = torch.einsum('btd,dhe->bhte', h, Wk)
            v = torch.einsum('btd,dhe->bhte', h, Wv)
            scores = torch.einsum('bhqe,bhke->bhqk', q, k) * scale
            scores = torch.where(mask[None, None], scores, -1000000000.0)
            p = _softmax(scores, axis=-1)
            o = torch.einsum('bhqk,bhke->bhqe', p, v)
            o = torch.einsum('bhte,hed->btd', o, Wo)
            mem = o[:, :M, :].clone()
            outs.append(o[:, M:, :])
        return torch.concatenate(outs, axis=1)
    a = _A_ref(A_x, A_Lambda_re, A_Lambda_im, A_B_re, A_B_im, A_C_re, A_C_im, A_log_dt, A_Dskip)
    b = _B_ref(B_x, B_mem0, B_Wq, B_Wk, B_Wv, B_Wo, B_seg_len)
    return torch.concatenate([a, b], axis=-1)
```

```cpp
#include <cuda_runtime.h>
#include <cuda_bf16.h>
#include <cuda.h>
#include <stdint.h>
#include <string.h>

typedef __nv_bfloat16 bf16;

namespace {

constexpr int SPIN_LIMIT = 1 << 22;
constexpr int NPAIR = 66;
constexpr int NCHAIN = 48;
enum { T_KV = 0, T_QA = 1, T_OP = 2, T_A1 = 3, T_A2 = 4, T_CHAIN = 5, T_OPH = 6, T_A2H = 7 };
constexpr int URGENT = 2048;
enum { M_BX = 0, M_WQ, M_WK, M_WV, M_WO, M_OA, M_AB, M_AX, M_HT, M_CRE, M_CIM, M_KVO, M_HTS, M_WOH, M_CREH, M_CIMH, M_C3, M_C5 = M_C3 + 3, M_CO = M_C5 + 3, M_SEG, M_COUNT };
enum { C_KV = 0, C_O = 8, C_HT = 16, C_DONE = 24, C_EPOCH = 25, C_COEF = 26, C_FLAG = 32 };

struct Params {
    CUtensorMap tm[M_COUNT];
    const bf16 *Wq, *Wk, *Wv, *Wo, *mem0, *Ax, *Lre, *Lim, *logdt, *Dskip;
    float* out;
    uint8_t* xb;
    int swap_ri, zero;
    int dly[2], mrg[2], rd, guard, clampv, clamp0, kvd;
    uint16_t cta0;
};

__constant__ uint16_t c_off[67] = {0, 5, 10, 15, 20, 25, 30, 35, 40, 45, 50, 55, 60, 65, 70, 75, 80, 85, 90, 95, 100, 105, 110, 115, 120, 125, 130, 135, 140, 145, 150, 154, 158, 161, 164, 167, 170, 173, 176, 179, 182, 185, 188, 191, 194, 197, 200, 203, 206, 226, 246, 266, 286, 306, 326, 346, 366, 386, 406, 427, 448, 468, 488, 507, 526, 546, 566};
__constant__ uint16_t c_items[640] = {
    0, 1280, 768, 2946, 1024, 1, 1280, 769, 2947, 1025, 2, 1280, 770, 2948, 1026, 32, 1280, 771, 2949, 1027, 33, 1280, 772, 2950,
    1056, 34, 1280, 773, 2951, 1057, 3, 1280, 774, 2976, 1058, 4, 1280, 775, 2977, 1059, 5, 1280, 800, 2978, 1088, 35, 1280, 801,
    2979, 1089, 36, 1280, 802, 2980, 1090, 37, 1280, 803, 2981, 1091, 6, 1280, 804, 2982, 1120, 7, 1280, 805, 2983, 1121, 8, 1280,
    806, 3008, 1122, 38, 1280, 807, 3009, 1123, 39, 1280, 832, 3010, 1152, 40, 1280, 833, 3011, 1153, 9, 1280, 834, 3012, 1154, 10,
    1280, 835, 3013, 1155, 11, 1280, 836, 3014, 1184, 41, 1280, 837, 3015, 1185, 42, 1280, 838, 3040, 1186, 43, 1280, 839, 3041, 1187,
    12, 1280, 864, 3042, 1216, 13, 1280, 865, 3043, 1217, 14, 1280, 866, 3044, 1218, 44, 1280, 867, 3045, 1219, 45, 1280, 868, 3046,
    1248, 46, 1280, 869, 3047, 1249, 15, 1280, 870, 1766, 16, 1280, 871, 1767, 17, 1280, 611, 47, 1280, 610, 48, 1280, 609, 49,
    1280, 608, 18, 1280, 579, 19, 1280, 578, 20, 1280, 577, 50, 1280, 576, 51, 1280, 547, 52, 1280, 546, 21, 1280, 545, 22,
    1280, 544, 23, 1280, 515, 53, 1280, 514, 54, 1280, 513, 55, 1280, 512, 24, 66, 84, 102, 256, 124, 142, 145, 162, 177,
    192, 208, 328, 239, 332, 366, 416, 450, 2532, 640, 56, 67, 85, 103, 257, 125, 288, 146, 163, 178, 193, 211, 224, 242,
    335, 385, 419, 453, 2535, 643, 25, 68, 86, 104, 258, 126, 289, 147, 164, 179, 194, 212, 225, 243, 352, 386, 420, 454,
    2536, 672, 57, 69, 87, 105, 259, 127, 290, 148, 165, 180, 195, 213, 226, 244, 353, 387, 421, 455, 2537, 673, 26, 70,
    88, 106, 260, 128, 291, 149, 166, 181, 196, 214, 227, 245, 354, 388, 422, 456, 2538, 674, 58, 71, 89, 107, 261, 129,
    292, 150, 167, 182, 197, 215, 228, 246, 355, 389, 423, 457, 2539, 675, 27, 72, 90, 108, 262, 130, 293, 151, 168, 183,
    198, 216, 229, 247, 356, 390, 424, 458, 2540, 704, 59, 73, 91, 109, 263, 131, 294, 152, 169, 184, 199, 217, 230, 248,
    357, 391, 425, 459, 2541, 705, 28, 74, 92, 110, 264, 132, 295, 153, 170, 185, 200, 218, 231, 249, 358, 392, 426, 460,
    2542, 706, 60, 75, 93, 111, 265, 133, 296, 154, 171, 186, 201, 219, 232, 250, 359, 393, 427, 461, 2543, 707, 29, 76,
    94, 112, 266, 134, 297, 155, 172, 187, 202, 220, 233, 251, 360, 394, 428, 462, 2944, 1764, 2020, 61, 77, 95, 113, 267,
    135, 298, 156, 173, 188, 203, 221, 234, 252, 361, 395, 429, 463, 2945, 1765, 2021, 30, 78, 96, 114, 268, 136, 299, 157,
    174, 189, 204, 222, 235, 253, 362, 396, 430, 2528, 1760, 2022, 62, 79, 97, 115, 269, 137, 300, 158, 320, 190, 205, 223,
    236, 254, 363, 397, 431, 2529, 1761, 2023, 31, 80, 98, 116, 270, 138, 301, 159, 321, 191, 206, 326, 237, 255, 364, 398,
    448, 2530, 1762, 63, 81, 99, 117, 271, 139, 302, 303, 322, 323, 207, 327, 238, 331, 365, 399, 449, 2531, 1763, 64, 82,
    100, 118, 120, 122, 140, 143, 160, 175, 324, 209, 329, 240, 333, 367, 417, 451, 2533, 641, 65, 83, 101, 119, 121, 123,
    141, 144, 161, 176, 325, 210, 330, 241, 334, 384, 418, 452, 2534, 642,
};
#define ITEM_OFF(p) c_off[p]
#define ITEM(i) c_items[i]

__device__ __align__(1024) bf16 g_kvo[3 * 2048 * 4096];
__device__ __align__(1024) bf16 g_ht[2048 * 2048];
__device__ __align__(1024) uint8_t g_x[4 << 20];
__device__ __align__(1024) uint32_t g_km[64 * 32 * 512];
__device__ __align__(1024) uint32_t g_vmt[64 * 32 * 512];
__device__ __align__(1024) float2 g_agg[8 * 1024];
__device__ __align__(1024) float4 g_coef[1024];
__device__ __align__(1024) uint32_t g_cntl[128 * 32];
#define g_cnt(i) g_cntl[(i) * 32]
__device__ __align__(1024) uint32_t g_hint[96 * 32];
#define PROF(i)
#define PROFDUMP()
#define PROFP(i)
enum { XP_O = 0, XP_M = 128, XP_T = 132, XP_PROBE = 133, XP_MAP = 134, XP_M0 = 135 };
__host__ __device__ constexpr int xpar(int pi) { return (pi ^ (pi >> 3) ^ (pi >> 4) ^ (pi >> 6)) & 1; }
__device__ __forceinline__ uint32_t xblk(int pi, int side) { return pi * 8192 + ((xpar(pi) ^ side) << 12); }

constexpr int STAGE = 49152, NSTAGE = 4;
constexpr int S_STG = NSTAGE * STAGE;
constexpr int S_BAR = S_STG + 32768;
constexpr int B_FULL = S_BAR, B_EMPTY = S_BAR + 32, B_RESUME = S_BAR + 64, B_KVFULL = S_BAR + 72, B_MAP = S_BAR + 80, B_GO = S_BAR + 88, B_X = S_BAR + 96, B_PERS = S_BAR + 104,
              B_INIT = S_BAR + 112, B_RELM = S_BAR + 120, B_RELO = S_BAR + 128, B_READY = S_BAR + 136, B_SFULL = S_BAR + 144, B_SFREE = S_BAR + 160, S_DESC = S_BAR + 176, S_SIDES = S_BAR + 208, B_RED = S_BAR + 216;
constexpr int S_XV = S_BAR + 256, S_LOG = S_XV + 2048;
constexpr int S_TOTAL = S_LOG + 768;
constexpr int S_W1 = 0;
constexpr int S_W2 = 4 * (20480 + 12288);
constexpr int S_KV = S_W2 + 28 * 2048;
constexpr int S_P1 = S_KV + 16384;
constexpr int S_X = S_P1 + 16384;
constexpr int S_SX = S_P1, S_OX = S_P1 + 2048;
static_assert(S_X + 4096 <= S_BAR && S_KV % 1024 == 0 && S_TOTAL <= 232448, "chain smem layout");

template <int V> struct IC { static constexpr int value = V; };
template <int B, int E, typename F> __device__ __forceinline__ void static_for(F&& f) { if constexpr (B < E) { f(IC<B>{}); static_for<B + 1, E>(f); } }
__device__ __forceinline__ uint32_t cluster_rank() { uint32_t r; asm volatile("mov.u32 %0, %%cluster_ctarank;" : "=r"(r)); return r; }
__device__ __forceinline__ void spin_fault() { asm volatile("st.global.u32 [%0], 0;" ::"l"(0ull) : "memory"); }
__device__ __forceinline__ uint32_t smem_u32(const void* p) { return (uint32_t)__cvta_generic_to_shared(p); }
__device__ __forceinline__ uint32_t opq(uint32_t x, int lane) { return __shfl_sync(0xffffffffu, x, lane); }
__device__ __forceinline__ uint32_t mapa(uint32_t a, uint32_t r) { uint32_t d; asm volatile("mapa.shared::cluster.u32 %0, %1, %2;" : "=r"(d) : "r"(a), "r"(r)); return d; }
__device__ __forceinline__ void mma16816(float* d, uint32_t a0, uint32_t a1, uint32_t a2, uint32_t a3, uint32_t b0, uint32_t b1) {
    asm("mma.sync.aligned.m16n8k16.row.col.f32.bf16.bf16.f32 {%0,%1,%2,%3}, {%4,%5,%6,%7}, {%8,%9}, {%0,%1,%2,%3};"
        : "+f"(d[0]), "+f"(d[1]), "+f"(d[2]), "+f"(d[3]) : "r"(a0), "r"(a1), "r"(a2), "r"(a3), "r"(b0), "r"(b1));
}
__device__ __forceinline__ void mma1688(float* d, uint32_t a0, uint32_t a1, uint32_t b0) {
    asm("mma.sync.aligned.m16n8k8.row.col.f32.bf16.bf16.f32 {%0,%1,%2,%3}, {%4,%5}, {%6}, {%0,%1,%2,%3};"
        : "+f"(d[0]), "+f"(d[1]), "+f"(d[2]), "+f"(d[3]) : "r"(a0), "r"(a1), "r"(b0));
}
__device__ __forceinline__ void ldsm4(uint32_t* r, uint32_t a) {
    asm volatile("ldmatrix.sync.aligned.m8n8.x4.shared.b16 {%0,%1,%2,%3}, [%4];" : "=r"(r[0]), "=r"(r[1]), "=r"(r[2]), "=r"(r[3]) : "r"(a));
}
__device__ __forceinline__ void ldsm4t(uint32_t* r, uint32_t a) {
    asm volatile("ldmatrix.sync.aligned.m8n8.x4.trans.shared.b16 {%0,%1,%2,%3}, [%4];" : "=r"(r[0]), "=r"(r[1]), "=r"(r[2]), "=r"(r[3]) : "r"(a));
}
__device__ __forceinline__ void stsm4(uint32_t a, uint32_t r0, uint32_t r1, uint32_t r2, uint32_t r3) {
    asm volatile("stmatrix.sync.aligned.m8n8.x4.shared.b16 [%0], {%1,%2,%3,%4};" ::"r"(a), "r"(r0), "r"(r1), "r"(r2), "r"(r3) : "memory");
}
__device__ __forceinline__ void stsm4t(uint32_t a, uint32_t r0, uint32_t r1, uint32_t r2, uint32_t r3) {
    asm volatile("stmatrix.sync.aligned.m8n8.x4.trans.shared.b16 [%0], {%1,%2,%3,%4};" ::"r"(a), "r"(r0), "r"(r1), "r"(r2), "r"(r3) : "memory");
}
__device__ __forceinline__ uint32_t movm(uint32_t a) { uint32_t d; asm volatile("movmatrix.sync.aligned.m8n8.trans.b16 %0, %1;" : "=r"(d) : "r"(a)); return d; }
__device__ __forceinline__ uint32_t pack2(float lo, float hi) { uint32_t d; asm("cvt.rn.bf16x2.f32 %0, %1, %2;" : "=r"(d) : "f"(hi), "f"(lo)); return d; }
__device__ __forceinline__ float bf_lo(uint32_t u) { return __uint_as_float(u << 16); }
__device__ __forceinline__ float bf_hi(uint32_t u) { return __uint_as_float(u & 0xffff0000u); }
__device__ __forceinline__ float ex2(float x) { float y; asm("ex2.approx.ftz.f32 %0, %1;" : "=f"(y) : "f"(x)); return y; }
__device__ __forceinline__ float rcp(float x) { float y; asm("rcp.approx.ftz.f32 %0, %1;" : "=f"(y) : "f"(x)); return y; }
__device__ __forceinline__ void st_relaxed4(const void* p, uint32_t a, uint32_t b, uint32_t c, uint32_t d) {
    asm volatile("{\n.reg .b128 t;\nmov.b128 t, {%1,%2,%3,%4};\nst.relaxed.gpu.global.b128 [%0], t;\n}" ::"l"(p), "r"(a), "r"(b), "r"(c), "r"(d) : "memory");
}
__device__ __forceinline__ void st_relaxed2(const void* p, uint32_t a, uint32_t b) {
    asm volatile("{\n.reg .b64 t;\nmov.b64 t, {%1,%2};\nst.relaxed.gpu.global.b64 [%0], t;\n}" ::"l"(p), "r"(a), "r"(b) : "memory");
}
__device__ __forceinline__ void ld_relaxed2_if(uint32_t& a, uint32_t& b, const void* p, bool on) {
    asm volatile("{\n.reg .pred P;\n.reg .b64 t;\nsetp.ne.u32 P, %3, 0;\nmov.b64 t, {%0,%1};\n@P ld.relaxed.gpu.global.b64 t, [%2];\nmov.b64 {%0,%1}, t;\n}" : "+r"(a), "+r"(b) : "l"(p), "r"((uint32_t)on) : "memory");
}
__device__ __forceinline__ void ld_relaxed2(uint32_t* v, const void* p) {
    asm volatile("{\n.reg .b64 t;\nld.relaxed.gpu.global.L1::no_allocate.b64 t, [%2];\nmov.b64 {%0,%1}, t;\n}" : "=r"(v[0]), "=r"(v[1]) : "l"(p) : "memory");
}
__device__ __forceinline__ uint32_t ld_relaxed1(const void* p) { uint32_t v; asm volatile("ld.relaxed.gpu.global.u32 %0, [%1];" : "=r"(v) : "l"(p) : "memory"); return v; }
__device__ __forceinline__ void st_relaxed1(const void* p, uint32_t v) { asm volatile("st.relaxed.gpu.global.u32 [%0], %1;" ::"l"(p), "r"(v) : "memory"); }
__device__ __forceinline__ uint32_t ld_acquire(const void* p) { uint32_t v; asm volatile("ld.acquire.gpu.global.u32 %0, [%1];" : "=r"(v) : "l"(p) : "memory"); return v; }
__device__ __forceinline__ void red_relaxed(void* p) { asm volatile("red.relaxed.gpu.global.add.u32 [%0], 1;" ::"l"(p) : "memory"); }
__device__ __forceinline__ void red_release(void* p) { asm volatile("red.release.gpu.global.add.u32 [%0], 1;" ::"l"(p) : "memory"); }
__device__ __forceinline__ void st_stream2(float* p, float a, float b) { asm volatile("st.global.cs.v2.f32 [%0], {%1, %2};" ::"l"(p), "f"(a), "f"(b) : "memory"); }
__device__ __forceinline__ void fence_async() { asm volatile("fence.proxy.async.global;" ::: "memory"); }
__device__ __forceinline__ void fence_async_smem() { asm volatile("fence.proxy.async.shared::cta;" ::: "memory"); }
__device__ __forceinline__ void wait_count(const uint32_t* p, uint32_t target) {
    int n = 0;
    while ((int32_t)(ld_acquire(p) - target) < 0) { __nanosleep(200); if (++n > SPIN_LIMIT) spin_fault(); }
}
__device__ __forceinline__ void bar_sync(int id, int n) { asm volatile("bar.sync %0, %1;" ::"r"(id), "r"(n) : "memory"); }
__device__ __forceinline__ bool bar_and(int id, bool v) {
    uint32_t r;
    asm volatile("{\n.reg .pred P, Q;\nsetp.ne.u32 Q, %2, 0;\nbar.red.and.pred P, %1, 128, Q;\nselp.u32 %0, 1, 0, P;\n}" : "=r"(r) : "r"(id), "r"((uint32_t)v) : "memory");
    return r;
}
__device__ __forceinline__ void bar_arrive(int id, int n) { asm volatile("bar.arrive %0, %1;" ::"r"(id), "r"(n) : "memory"); }
__device__ __forceinline__ void lds128(uint32_t* v, uint32_t a) { asm volatile("ld.shared.v4.b32 {%0,%1,%2,%3}, [%4];" : "=r"(v[0]), "=r"(v[1]), "=r"(v[2]), "=r"(v[3]) : "r"(a) : "memory"); }
__device__ __forceinline__ uint32_t lds32(uint32_t a) { uint32_t v; asm volatile("ld.shared.b32 %0, [%1];" : "=r"(v) : "r"(a) : "memory"); return v; }
__device__ __forceinline__ void lds64(uint32_t* v, uint32_t a) { asm volatile("ld.shared.v2.b32 {%0,%1}, [%2];" : "=r"(v[0]), "=r"(v[1]) : "r"(a) : "memory"); }
__device__ __forceinline__ void lds64f(float* v, uint32_t a) { asm volatile("ld.shared.v2.f32 {%0,%1}, [%2];" : "=f"(v[0]), "=f"(v[1]) : "r"(a) : "memory"); }
__device__ __forceinline__ void sts128(uint32_t a, const uint32_t* v) { asm volatile("st.shared.v4.b32 [%0], {%1,%2,%3,%4};" ::"r"(a), "r"(v[0]), "r"(v[1]), "r"(v[2]), "r"(v[3]) : "memory"); }
__device__ __forceinline__ void sts64(uint32_t a, uint32_t x, uint32_t y) { asm volatile("st.shared.v2.b32 [%0], {%1,%2};" ::"r"(a), "r"(x), "r"(y) : "memory"); }
__device__ __forceinline__ void sts32(uint32_t a, uint32_t x) { asm volatile("st.shared.b32 [%0], %1;" ::"r"(a), "r"(x) : "memory"); }
__device__ __forceinline__ bool mbar_try(uint32_t b, uint32_t par) {
    uint32_t ok;
    asm volatile("{\n.reg .pred P;\nmbarrier.try_wait.parity.shared::cta.b64 P, [%1], %2;\nselp.u32 %0, 1, 0, P;\n}" : "=r"(ok) : "r"(b), "r"(par) : "memory");
    return ok;
}
__device__ __forceinline__ void mbar_wait(uint32_t b, uint32_t par) {
    asm volatile("{\n.reg .pred P, Q;\n.reg .u32 n;\nmov.u32 n, %2;\nW: mbarrier.try_wait.parity.shared::cta.b64 P, [%0], %1;\n"
                 "add.u32 n, n, -1;\nsetp.eq.u32 Q, n, 0;\n@Q st.global.u32 [%3], 0;\n@!P bra W;\n}" ::"r"(b), "r"(par), "n"(SPIN_LIMIT), "l"(0ull) : "memory");
}
__device__ __forceinline__ void declare_fence(int zero) { asm volatile(".reg .pred PNEVER;\nsetp.ne.u32 PNEVER, %0, 0;" ::"r"(zero)); }
__device__ __forceinline__ void sched_fence() { asm volatile("{\n.reg .pred Q;\n.reg .u32 x;\n@!PNEVER bra D;\nF: ld.volatile.global.u32 x, [%0];\nsetp.ne.u32 Q, x, 0;\n@Q bra F;\nD:\n}" ::"l"(0ull) : "memory"); }
__device__ __forceinline__ void mbar_init(uint32_t b, uint32_t n) { asm volatile("mbarrier.init.shared::cta.b64 [%0], %1;" ::"r"(b), "r"(n) : "memory"); }
__device__ __forceinline__ void mbar_expect(uint32_t b, uint32_t bytes) { asm volatile("mbarrier.arrive.expect_tx.shared::cta.b64 _, [%0], %1;" ::"r"(b), "r"(bytes) : "memory"); }
__device__ __forceinline__ void mbar_arrive(uint32_t b) { asm volatile("mbarrier.arrive.shared::cta.b64 _, [%0];" ::"r"(b) : "memory"); }
__device__ __forceinline__ void mbar_arrive_cluster(uint32_t b) { asm volatile("mbarrier.arrive.shared::cluster.b64 _, [%0];" ::"r"(b) : "memory"); }
__device__ __forceinline__ void cluster_sync() { asm volatile("barrier.cluster.arrive.aligned;\nbarrier.cluster.wait.aligned;" ::: "memory"); }
__device__ __forceinline__ void tma2d(uint32_t dst, const CUtensorMap* m, int c0, int c1, uint32_t bar) {
    asm volatile("cp.async.bulk.tensor.2d.shared::cluster.global.mbarrier::complete_tx::bytes [%0], [%1, {%2, %3}], [%4];" ::"r"(dst), "l"(m), "r"(c0), "r"(c1), "r"(bar) : "memory");
}
__device__ __forceinline__ void tma2d_mc(uint32_t dst, const CUtensorMap* m, int c0, int c1, uint32_t bar, uint16_t mask) {
    asm volatile("cp.async.bulk.tensor.2d.shared::cluster.global.mbarrier::complete_tx::bytes.multicast::cluster [%0], [%1, {%2, %3}], [%4], %5;" ::"r"(dst), "l"(m), "r"(c0), "r"(c1), "r"(bar), "h"(mask) : "memory");
}
__device__ __forceinline__ void tma3d(uint32_t dst, const CUtensorMap* m, int c0, int c1, int c2, uint32_t bar) {
    asm volatile("cp.async.bulk.tensor.3d.shared::cluster.global.mbarrier::complete_tx::bytes [%0], [%1, {%2, %3, %4}], [%5];" ::"r"(dst), "l"(m), "r"(c0), "r"(c1), "r"(c2), "r"(bar) : "memory");
}
__device__ __forceinline__ void tma3d_mc(uint32_t dst, const CUtensorMap* m, int c0, int c1, int c2, uint32_t bar, uint16_t mask) {
    asm volatile("cp.async.bulk.tensor.3d.shared::cluster.global.mbarrier::complete_tx::bytes.multicast::cluster [%0], [%1, {%2, %3, %4}], [%5], %6;" ::"r"(dst), "l"(m), "r"(c0), "r"(c1), "r"(c2), "r"(bar), "h"(mask) : "memory");
}
__device__ __forceinline__ void tma4d(uint32_t dst, const CUtensorMap* m, int c0, int c3, uint32_t bar) {
    asm volatile("cp.async.bulk.tensor.4d.shared::cluster.global.mbarrier::complete_tx::bytes [%0], [%1, {%2, 0, 0, %3}], [%4];" ::"r"(dst), "l"(m), "r"(c0), "r"(c3), "r"(bar) : "memory");
}
__device__ __forceinline__ void tma4d_mc(uint32_t dst, const CUtensorMap* m, int c0, int c3, uint32_t bar, uint16_t mask) {
    asm volatile("cp.async.bulk.tensor.4d.shared::cluster.global.mbarrier::complete_tx::bytes.multicast::cluster [%0], [%1, {%2, 0, 0, %3}], [%4], %5;" ::"r"(dst), "l"(m), "r"(c0), "r"(c3), "r"(bar), "h"(mask) : "memory");
}
__device__ __forceinline__ void tma_prefetch3d(const CUtensorMap* m, int c0, int c1, int c2) {
    asm volatile("cp.async.bulk.prefetch.tensor.3d.L2.global [%0, {%1, %2, %3}];" ::"l"(m), "r"(c0), "r"(c1), "r"(c2) : "memory");
}
__device__ __forceinline__ void tma_prefetch2d(const CUtensorMap* m, int c0, int c1) {
    asm volatile("cp.async.bulk.prefetch.tensor.2d.L2.global [%0, {%1, %2}];" ::"l"(m), "r"(c0), "r"(c1) : "memory");
}
__device__ __forceinline__ void l2_prefetch(const void* src, uint32_t bytes) { asm volatile("cp.async.bulk.prefetch.L2.global [%0], %1;" ::"l"(src), "r"(bytes) : "memory"); }
__device__ __forceinline__ void bulk_g2s(uint32_t dst, const void* src, uint32_t bytes, uint32_t bar) {
    asm volatile("cp.async.bulk.shared::cluster.global.mbarrier::complete_tx::bytes [%0], [%1], %2, [%3];" ::"r"(dst), "l"(src), "r"(bytes), "r"(bar) : "memory");
}
__device__ __forceinline__ void mbar_expect_e(uint32_t b, uint32_t bytes) {
    asm volatile("{\n.reg .pred E;\nelect.sync _|E, 0xffffffff;\n@E mbarrier.arrive.expect_tx.shared::cta.b64 _, [%0], %1;\n}" ::"r"(b), "r"(bytes) : "memory");
}
__device__ __forceinline__ void tma2d_e(uint32_t dst, const CUtensorMap* m, int c0, int c1, uint32_t bar) {
    asm volatile("{\n.reg .pred E;\nelect.sync _|E, 0xffffffff;\n@E cp.async.bulk.tensor.2d.shared::cluster.global.mbarrier::complete_tx::bytes [%0], [%1, {%2, %3}], [%4];\n}" ::"r"(dst), "l"(m), "r"(c0), "r"(c1), "r"(bar) : "memory");
}
__device__ __forceinline__ void tma2d_mc_e(uint32_t dst, const CUtensorMap* m, int c0, int c1, uint32_t bar, uint16_t mask) {
    asm volatile("{\n.reg .pred E;\nelect.sync _|E, 0xffffffff;\n@E cp.async.bulk.tensor.2d.shared::cluster.global.mbarrier::complete_tx::bytes.multicast::cluster [%0], [%1, {%2, %3}], [%4], %5;\n}" ::"r"(dst), "l"(m), "r"(c0), "r"(c1), "r"(bar), "h"(mask) : "memory");
}
__device__ __forceinline__ void tma3d_e(uint32_t dst, const CUtensorMap* m, int c0, int c1, int c2, uint32_t bar) {
    asm volatile("{\n.reg .pred E;\nelect.sync _|E, 0xffffffff;\n@E cp.async.bulk.tensor.3d.shared::cluster.global.mbarrier::complete_tx::bytes [%0], [%1, {%2, %3, %4}], [%5];\n}" ::"r"(dst), "l"(m), "r"(c0), "r"(c1), "r"(c2), "r"(bar) : "memory");
}
__device__ __forceinline__ void tma3d_mc_e(uint32_t dst, const CUtensorMap* m, int c0, int c1, int c2, uint32_t bar, uint16_t mask) {
    asm volatile("{\n.reg .pred E;\nelect.sync _|E, 0xffffffff;\n@E cp.async.bulk.tensor.3d.shared::cluster.global.mbarrier::complete_tx::bytes.multicast::cluster [%0], [%1, {%2, %3, %4}], [%5], %6;\n}" ::"r"(dst), "l"(m), "r"(c0), "r"(c1), "r"(c2), "r"(bar), "h"(mask) : "memory");
}
__device__ __forceinline__ void tma4d_e(uint32_t dst, const CUtensorMap* m, int c0, int c3, uint32_t bar) {
    asm volatile("{\n.reg .pred E;\nelect.sync _|E, 0xffffffff;\n@E cp.async.bulk.tensor.4d.shared::cluster.global.mbarrier::complete_tx::bytes [%0], [%1, {%2, 0, 0, %3}], [%4];\n}" ::"r"(dst), "l"(m), "r"(c0), "r"(c3), "r"(bar) : "memory");
}
__device__ __forceinline__ void tma4d_mc_e(uint32_t dst, const CUtensorMap* m, int c0, int c3, uint32_t bar, uint16_t mask) {
    asm volatile("{\n.reg .pred E;\nelect.sync _|E, 0xffffffff;\n@E cp.async.bulk.tensor.4d.shared::cluster.global.mbarrier::complete_tx::bytes.multicast::cluster [%0], [%1, {%2, 0, 0, %3}], [%4], %5;\n}" ::"r"(dst), "l"(m), "r"(c0), "r"(c3), "r"(bar), "h"(mask) : "memory");
}
__device__ __forceinline__ void tma_prefetch2d_e(const CUtensorMap* m, int c0, int c1) {
    asm volatile("{\n.reg .pred E;\nelect.sync _|E, 0xffffffff;\n@E cp.async.bulk.prefetch.tensor.2d.L2.global [%0, {%1, %2}];\n}" ::"l"(m), "r"(c0), "r"(c1) : "memory");
}
__device__ __forceinline__ void tma_prefetch3d_e(const CUtensorMap* m, int c0, int c1, int c2) {
    asm volatile("{\n.reg .pred E;\nelect.sync _|E, 0xffffffff;\n@E cp.async.bulk.prefetch.tensor.3d.L2.global [%0, {%1, %2, %3}];\n}" ::"l"(m), "r"(c0), "r"(c1), "r"(c2) : "memory");
}
__device__ __forceinline__ void l2_prefetch_e(const void* src, uint32_t bytes) {
    asm volatile("{\n.reg .pred E;\nelect.sync _|E, 0xffffffff;\n@E cp.async.bulk.prefetch.L2.global [%0], %1;\n}" ::"l"(src), "r"(bytes) : "memory");
}
__device__ __forceinline__ void bulk_g2s_e(uint32_t dst, const void* src, uint32_t bytes, uint32_t bar) {
    asm volatile("{\n.reg .pred E;\nelect.sync _|E, 0xffffffff;\n@E cp.async.bulk.shared::cluster.global.mbarrier::complete_tx::bytes [%0], [%1], %2, [%3];\n}" ::"r"(dst), "l"(src), "r"(bytes), "r"(bar) : "memory");
}
__device__ __forceinline__ bool elect_one() {
    uint32_t r;
    asm volatile("{\n.reg .pred E;\nelect.sync _|E, 0xffffffff;\nselp.u32 %0, 1, 0, E;\n}" : "=r"(r));
    return r;
}
__device__ __forceinline__ void tma_store2d(const CUtensorMap* m, int c0, int c1, uint32_t src) {
    asm volatile("cp.async.bulk.tensor.2d.global.shared::cta.bulk_group [%0, {%1, %2}], [%3];" ::"l"(m), "r"(c0), "r"(c1), "r"(src) : "memory");
}
__device__ __forceinline__ void bulk_commit() { asm volatile("cp.async.bulk.commit_group;" ::: "memory"); }
__device__ __forceinline__ void bulk_wait_read() { asm volatile("cp.async.bulk.wait_group.read 0;" ::: "memory"); }
__device__ __forceinline__ void bulk_wait_all() { asm volatile("cp.async.bulk.wait_group 0;" ::: "memory"); }
__device__ __forceinline__ uint64_t mkdesc(uint32_t addr, uint32_t lbo, uint32_t sbo, uint32_t swz) {
    return (uint64_t)((addr & 0x3FFFF) >> 4) | ((uint64_t)(lbo >> 4) << 16) | ((uint64_t)(sbo >> 4) << 32) | ((uint64_t)swz << 62);
}
__device__ __forceinline__ void wg_fence() { asm volatile("wgmma.fence.sync.aligned;" ::: "memory"); }
__device__ __forceinline__ void wg_commit() { asm volatile("wgmma.commit_group.sync.aligned;" ::: "memory"); }
template <int N> __device__ __forceinline__ void wg_wait() { asm volatile("wgmma.wait_group.sync.aligned %0;" ::"n"(N) : "memory"); }
template <typename T> __device__ __forceinline__ void pin_ptr(T*& p) { asm volatile("" : "+l"(p)); }
template <int N> __device__ __forceinline__ void pin(uint32_t* d) {
#pragma unroll
    for (int i = 0; i < N; i++) asm volatile("" : "+r"(d[i])::"memory");
}
template <int N> __device__ __forceinline__ void pin(float* d) {
#pragma unroll
    for (int i = 0; i < N; i++) asm volatile("" : "+f"(d[i])::"memory");
}

template <int TA, int TB>
__device__ __forceinline__ void wgmma_ss256(float* d, uint64_t da, uint64_t db) {
    asm volatile("wgmma.mma_async.sync.aligned.m64n256k16.f32.bf16.bf16 "
        "{%0, %1, %2, %3, %4, %5, %6, %7, %8, %9, %10, %11, %12, %13, %14, %15, %16, %17, %18, %19, %20, %21, %22, %23, %24, %25, %26, %27, %28, %29, %30, %31, %32, %33, %34, %35, %36, %37, %38, %39, %40, %41, %42, %43, %44, %45, %46, %47, %48, %49, %50, %51, %52, %53, %54, %55, %56, %57, %58, %59, %60, %61, %62, %63, %64, %65, %66, %67, %68, %69, %70, %71, %72, %73, %74, %75, %76, %77, %78, %79, %80, %81, %82, %83, %84, %85, %86, %87, %88, %89, %90, %91, %92, %93, %94, %95, %96, %97, %98, %99, %100, %101, %102, %103, %104, %105, %106, %107, %108, %109, %110, %111, %112, %113, %114, %115, %116, %117, %118, %119, %120, %121, %122, %123, %124, %125, %126, %127}, %128, %129, 1, 1, 1, %130, %131;"
        : "+f"(d[0]), "+f"(d[1]), "+f"(d[2]), "+f"(d[3]), "+f"(d[4]), "+f"(d[5]), "+f"(d[6]), "+f"(d[7]), "+f"(d[8]), "+f"(d[9]), "+f"(d[10]), "+f"(d[11]), "+f"(d[12]), "+f"(d[13]), "+f"(d[14]), "+f"(d[15]), "+f"(d[16]), "+f"(d[17]), "+f"(d[18]), "+f"(d[19]), "+f"(d[20]), "+f"(d[21]), "+f"(d[22]), "+f"(d[23]), "+f"(d[24]), "+f"(d[25]), "+f"(d[26]), "+f"(d[27]), "+f"(d[28]), "+f"(d[29]), "+f"(d[30]), "+f"(d[31]), "+f"(d[32]), "+f"(d[33]), "+f"(d[34]), "+f"(d[35]), "+f"(d[36]), "+f"(d[37]), "+f"(d[38]), "+f"(d[39]), "+f"(d[40]), "+f"(d[41]), "+f"(d[42]), "+f"(d[43]), "+f"(d[44]), "+f"(d[45]), "+f"(d[46]), "+f"(d[47]), "+f"(d[48]), "+f"(d[49]), "+f"(d[50]), "+f"(d[51]), "+f"(d[52]), "+f"(d[53]), "+f"(d[54]), "+f"(d[55]), "+f"(d[56]), "+f"(d[57]), "+f"(d[58]), "+f"(d[59]), "+f"(d[60]), "+f"(d[61]), "+f"(d[62]), "+f"(d[63]), "+f"(d[64]), "+f"(d[65]), "+f"(d[66]), "+f"(d[67]), "+f"(d[68]), "+f"(d[69]), "+f"(d[70]), "+f"(d[71]), "+f"(d[72]), "+f"(d[73]), "+f"(d[74]), "+f"(d[75]), "+f"(d[76]), "+f"(d[77]), "+f"(d[78]), "+f"(d[79]), "+f"(d[80]), "+f"(d[81]), "+f"(d[82]), "+f"(d[83]), "+f"(d[84]), "+f"(d[85]), "+f"(d[86]), "+f"(d[87]), "+f"(d[88]), "+f"(d[89]), "+f"(d[90]), "+f"(d[91]), "+f"(d[92]), "+f"(d[93]), "+f"(d[94]), "+f"(d[95]), "+f"(d[96]), "+f"(d[97]), "+f"(d[98]), "+f"(d[99]), "+f"(d[100]), "+f"(d[101]), "+f"(d[102]), "+f"(d[103]), "+f"(d[104]), "+f"(d[105]), "+f"(d[106]), "+f"(d[107]), "+f"(d[108]), "+f"(d[109]), "+f"(d[110]), "+f"(d[111]), "+f"(d[112]), "+f"(d[113]), "+f"(d[114]), "+f"(d[115]), "+f"(d[116]), "+f"(d[117]), "+f"(d[118]), "+f"(d[119]), "+f"(d[120]), "+f"(d[121]), "+f"(d[122]), "+f"(d[123]), "+f"(d[124]), "+f"(d[125]), "+f"(d[126]), "+f"(d[127])
        : "l"(da), "l"(db), "n"(TA), "n"(TB));
}
template <int TA, int TB>
__device__ __forceinline__ void wgmma_ss256_first(float* d, uint64_t da, uint64_t db) {
    asm volatile("wgmma.mma_async.sync.aligned.m64n256k16.f32.bf16.bf16 "
        "{%0, %1, %2, %3, %4, %5, %6, %7, %8, %9, %10, %11, %12, %13, %14, %15, %16, %17, %18, %19, %20, %21, %22, %23, %24, %25, %26, %27, %28, %29, %30, %31, %32, %33, %34, %35, %36, %37, %38, %39, %40, %41, %42, %43, %44, %45, %46, %47, %48, %49, %50, %51, %52, %53, %54, %55, %56, %57, %58, %59, %60, %61, %62, %63, %64, %65, %66, %67, %68, %69, %70, %71, %72, %73, %74, %75, %76, %77, %78, %79, %80, %81, %82, %83, %84, %85, %86, %87, %88, %89, %90, %91, %92, %93, %94, %95, %96, %97, %98, %99, %100, %101, %102, %103, %104, %105, %106, %107, %108, %109, %110, %111, %112, %113, %114, %115, %116, %117, %118, %119, %120, %121, %122, %123, %124, %125, %126, %127}, %128, %129, 0, 1, 1, %130, %131;"
        : "=f"(d[0]), "=f"(d[1]), "=f"(d[2]), "=f"(d[3]), "=f"(d[4]), "=f"(d[5]), "=f"(d[6]), "=f"(d[7]), "=f"(d[8]), "=f"(d[9]), "=f"(d[10]), "=f"(d[11]), "=f"(d[12]), "=f"(d[13]), "=f"(d[14]), "=f"(d[15]), "=f"(d[16]), "=f"(d[17]), "=f"(d[18]), "=f"(d[19]), "=f"(d[20]), "=f"(d[21]), "=f"(d[22]), "=f"(d[23]), "=f"(d[24]), "=f"(d[25]), "=f"(d[26]), "=f"(d[27]), "=f"(d[28]), "=f"(d[29]), "=f"(d[30]), "=f"(d[31]), "=f"(d[32]), "=f"(d[33]), "=f"(d[34]), "=f"(d[35]), "=f"(d[36]), "=f"(d[37]), "=f"(d[38]), "=f"(d[39]), "=f"(d[40]), "=f"(d[41]), "=f"(d[42]), "=f"(d[43]), "=f"(d[44]), "=f"(d[45]), "=f"(d[46]), "=f"(d[47]), "=f"(d[48]), "=f"(d[49]), "=f"(d[50]), "=f"(d[51]), "=f"(d[52]), "=f"(d[53]), "=f"(d[54]), "=f"(d[55]), "=f"(d[56]), "=f"(d[57]), "=f"(d[58]), "=f"(d[59]), "=f"(d[60]), "=f"(d[61]), "=f"(d[62]), "=f"(d[63]), "=f"(d[64]), "=f"(d[65]), "=f"(d[66]), "=f"(d[67]), "=f"(d[68]), "=f"(d[69]), "=f"(d[70]), "=f"(d[71]), "=f"(d[72]), "=f"(d[73]), "=f"(d[74]), "=f"(d[75]), "=f"(d[76]), "=f"(d[77]), "=f"(d[78]), "=f"(d[79]), "=f"(d[80]), "=f"(d[81]), "=f"(d[82]), "=f"(d[83]), "=f"(d[84]), "=f"(d[85]), "=f"(d[86]), "=f"(d[87]), "=f"(d[88]), "=f"(d[89]), "=f"(d[90]), "=f"(d[91]), "=f"(d[92]), "=f"(d[93]), "=f"(d[94]), "=f"(d[95]), "=f"(d[96]), "=f"(d[97]), "=f"(d[98]), "=f"(d[99]), "=f"(d[100]), "=f"(d[101]), "=f"(d[102]), "=f"(d[103]), "=f"(d[104]), "=f"(d[105]), "=f"(d[106]), "=f"(d[107]), "=f"(d[108]), "=f"(d[109]), "=f"(d[110]), "=f"(d[111]), "=f"(d[112]), "=f"(d[113]), "=f"(d[114]), "=f"(d[115]), "=f"(d[116]), "=f"(d[117]), "=f"(d[118]), "=f"(d[119]), "=f"(d[120]), "=f"(d[121]), "=f"(d[122]), "=f"(d[123]), "=f"(d[124]), "=f"(d[125]), "=f"(d[126]), "=f"(d[127])
        : "l"(da), "l"(db), "n"(TA), "n"(TB));
}
template <int TA, int TB>
__device__ __forceinline__ void wgmma_ss128(float* d, uint64_t da, uint64_t db) {
    asm volatile("wgmma.mma_async.sync.aligned.m64n128k16.f32.bf16.bf16 "
        "{%0, %1, %2, %3, %4, %5, %6, %7, %8, %9, %10, %11, %12, %13, %14, %15, %16, %17, %18, %19, %20, %21, %22, %23, %24, %25, %26, %27, %28, %29, %30, %31, %32, %33, %34, %35, %36, %37, %38, %39, %40, %41, %42, %43, %44, %45, %46, %47, %48, %49, %50, %51, %52, %53, %54, %55, %56, %57, %58, %59, %60, %61, %62, %63}, %64, %65, 1, 1, 1, %66, %67;"
        : "+f"(d[0]), "+f"(d[1]), "+f"(d[2]), "+f"(d[3]), "+f"(d[4]), "+f"(d[5]), "+f"(d[6]), "+f"(d[7]), "+f"(d[8]), "+f"(d[9]), "+f"(d[10]), "+f"(d[11]), "+f"(d[12]), "+f"(d[13]), "+f"(d[14]), "+f"(d[15]), "+f"(d[16]), "+f"(d[17]), "+f"(d[18]), "+f"(d[19]), "+f"(d[20]), "+f"(d[21]), "+f"(d[22]), "+f"(d[23]), "+f"(d[24]), "+f"(d[25]), "+f"(d[26]), "+f"(d[27]), "+f"(d[28]), "+f"(d[29]), "+f"(d[30]), "+f"(d[31]), "+f"(d[32]), "+f"(d[33]), "+f"(d[34]), "+f"(d[35]), "+f"(d[36]), "+f"(d[37]), "+f"(d[38]), "+f"(d[39]), "+f"(d[40]), "+f"(d[41]), "+f"(d[42]), "+f"(d[43]), "+f"(d[44]), "+f"(d[45]), "+f"(d[46]), "+f"(d[47]), "+f"(d[48]), "+f"(d[49]), "+f"(d[50]), "+f"(d[51]), "+f"(d[52]), "+f"(d[53]), "+f"(d[54]), "+f"(d[55]), "+f"(d[56]), "+f"(d[57]), "+f"(d[58]), "+f"(d[59]), "+f"(d[60]), "+f"(d[61]), "+f"(d[62]), "+f"(d[63])
        : "l"(da), "l"(db), "n"(TA), "n"(TB));
}
template <int TA, int TB>
__device__ __forceinline__ void wgmma_ss128_first(float* d, uint64_t da, uint64_t db) {
    asm volatile("wgmma.mma_async.sync.aligned.m64n128k16.f32.bf16.bf16 "
        "{%0, %1, %2, %3, %4, %5, %6, %7, %8, %9, %10, %11, %12, %13, %14, %15, %16, %17, %18, %19, %20, %21, %22, %23, %24, %25, %26, %27, %28, %29, %30, %31, %32, %33, %34, %35, %36, %37, %38, %39, %40, %41, %42, %43, %44, %45, %46, %47, %48, %49, %50, %51, %52, %53, %54, %55, %56, %57, %58, %59, %60, %61, %62, %63}, %64, %65, 0, 1, 1, %66, %67;"
        : "=f"(d[0]), "=f"(d[1]), "=f"(d[2]), "=f"(d[3]), "=f"(d[4]), "=f"(d[5]), "=f"(d[6]), "=f"(d[7]), "=f"(d[8]), "=f"(d[9]), "=f"(d[10]), "=f"(d[11]), "=f"(d[12]), "=f"(d[13]), "=f"(d[14]), "=f"(d[15]), "=f"(d[16]), "=f"(d[17]), "=f"(d[18]), "=f"(d[19]), "=f"(d[20]), "=f"(d[21]), "=f"(d[22]), "=f"(d[23]), "=f"(d[24]), "=f"(d[25]), "=f"(d[26]), "=f"(d[27]), "=f"(d[28]), "=f"(d[29]), "=f"(d[30]), "=f"(d[31]), "=f"(d[32]), "=f"(d[33]), "=f"(d[34]), "=f"(d[35]), "=f"(d[36]), "=f"(d[37]), "=f"(d[38]), "=f"(d[39]), "=f"(d[40]), "=f"(d[41]), "=f"(d[42]), "=f"(d[43]), "=f"(d[44]), "=f"(d[45]), "=f"(d[46]), "=f"(d[47]), "=f"(d[48]), "=f"(d[49]), "=f"(d[50]), "=f"(d[51]), "=f"(d[52]), "=f"(d[53]), "=f"(d[54]), "=f"(d[55]), "=f"(d[56]), "=f"(d[57]), "=f"(d[58]), "=f"(d[59]), "=f"(d[60]), "=f"(d[61]), "=f"(d[62]), "=f"(d[63])
        : "l"(da), "l"(db), "n"(TA), "n"(TB));
}
template <int TB>
__device__ __forceinline__ void wgmma_rs128(float* d, const uint32_t* a, uint64_t db, uint32_t acc) {
    asm volatile("{\n.reg .pred P;\nsetp.ne.u32 P, %69, 0;\nwgmma.mma_async.sync.aligned.m64n128k16.f32.bf16.bf16 "
        "{%0, %1, %2, %3, %4, %5, %6, %7, %8, %9, %10, %11, %12, %13, %14, %15, %16, %17, %18, %19, %20, %21, %22, %23, %24, %25, %26, %27, %28, %29, %30, %31, %32, %33, %34, %35, %36, %37, %38, %39, %40, %41, %42, %43, %44, %45, %46, %47, %48, %49, %50, %51, %52, %53, %54, %55, %56, %57, %58, %59, %60, %61, %62, %63}, {%64, %65, %66, %67}, %68, P, 1, 1, %70;\n}"
        : "+f"(d[0]), "+f"(d[1]), "+f"(d[2]), "+f"(d[3]), "+f"(d[4]), "+f"(d[5]), "+f"(d[6]), "+f"(d[7]), "+f"(d[8]), "+f"(d[9]), "+f"(d[10]), "+f"(d[11]), "+f"(d[12]), "+f"(d[13]), "+f"(d[14]), "+f"(d[15]), "+f"(d[16]), "+f"(d[17]), "+f"(d[18]), "+f"(d[19]), "+f"(d[20]), "+f"(d[21]), "+f"(d[22]), "+f"(d[23]), "+f"(d[24]), "+f"(d[25]), "+f"(d[26]), "+f"(d[27]), "+f"(d[28]), "+f"(d[29]), "+f"(d[30]), "+f"(d[31]), "+f"(d[32]), "+f"(d[33]), "+f"(d[34]), "+f"(d[35]), "+f"(d[36]), "+f"(d[37]), "+f"(d[38]), "+f"(d[39]), "+f"(d[40]), "+f"(d[41]), "+f"(d[42]), "+f"(d[43]), "+f"(d[44]), "+f"(d[45]), "+f"(d[46]), "+f"(d[47]), "+f"(d[48]), "+f"(d[49]), "+f"(d[50]), "+f"(d[51]), "+f"(d[52]), "+f"(d[53]), "+f"(d[54]), "+f"(d[55]), "+f"(d[56]), "+f"(d[57]), "+f"(d[58]), "+f"(d[59]), "+f"(d[60]), "+f"(d[61]), "+f"(d[62]), "+f"(d[63])
        : "r"(a[0]), "r"(a[1]), "r"(a[2]), "r"(a[3]), "l"(db), "r"(acc), "n"(TB));
}
template <int TB>
__device__ __forceinline__ void wgmma_rs64(float* d, const uint32_t* a, uint64_t db, uint32_t acc) {
    asm volatile("{\n.reg .pred P;\nsetp.ne.u32 P, %37, 0;\nwgmma.mma_async.sync.aligned.m64n64k16.f32.bf16.bf16 "
        "{%0, %1, %2, %3, %4, %5, %6, %7, %8, %9, %10, %11, %12, %13, %14, %15, %16, %17, %18, %19, %20, %21, %22, %23, %24, %25, %26, %27, %28, %29, %30, %31}, {%32, %33, %34, %35}, %36, P, 1, 1, %38;\n}"
        : "+f"(d[0]), "+f"(d[1]), "+f"(d[2]), "+f"(d[3]), "+f"(d[4]), "+f"(d[5]), "+f"(d[6]), "+f"(d[7]), "+f"(d[8]), "+f"(d[9]), "+f"(d[10]), "+f"(d[11]), "+f"(d[12]), "+f"(d[13]), "+f"(d[14]), "+f"(d[15]), "+f"(d[16]), "+f"(d[17]), "+f"(d[18]), "+f"(d[19]), "+f"(d[20]), "+f"(d[21]), "+f"(d[22]), "+f"(d[23]), "+f"(d[24]), "+f"(d[25]), "+f"(d[26]), "+f"(d[27]), "+f"(d[28]), "+f"(d[29]), "+f"(d[30]), "+f"(d[31])
        : "r"(a[0]), "r"(a[1]), "r"(a[2]), "r"(a[3]), "l"(db), "r"(acc), "n"(TB));
}
template <int TB>
__device__ __forceinline__ void wgmma_rs16(float* d, const uint32_t* a, uint64_t db, uint32_t acc) {
    asm volatile("{\n.reg .pred P;\nsetp.ne.u32 P, %13, 0;\nwgmma.mma_async.sync.aligned.m64n16k16.f32.bf16.bf16 "
        "{%0, %1, %2, %3, %4, %5, %6, %7}, {%8, %9, %10, %11}, %12, P, 1, 1, %14;\n}"
        : "+f"(d[0]), "+f"(d[1]), "+f"(d[2]), "+f"(d[3]), "+f"(d[4]), "+f"(d[5]), "+f"(d[6]), "+f"(d[7])
        : "r"(a[0]), "r"(a[1]), "r"(a[2]), "r"(a[3]), "l"(db), "r"(acc), "n"(TB));
}

__device__ __forceinline__ uint32_t delay_loop(int n, uint32_t x0) {
    uint32_t z;
    asm volatile("{\n.reg .pred P;\n.reg .u32 c, x;\nmov.u32 c, %1;\nmov.u32 x, %2;\nDL: mad.lo.u32 x, x, 1664525, 1013904223;\nadd.u32 c, c, -1;\nsetp.gt.s32 P, c, 0;\n@P bra DL;\n"
                 "setp.eq.u32 P, x, 0x7fffffff;\nselp.u32 %0, 16, 0, P;\n}" : "=r"(z) : "r"(n), "r"(x0) : "memory");
    return z;
}
__device__ __forceinline__ void wait_clocks(uint32_t n) {
    asm volatile("{\n.reg .pred P;\n.reg .u32 a, b;\nmov.u32 a, %%clock;\nW: mov.u32 b, %%clock;\nsub.u32 b, b, a;\nsetp.lt.u32 P, b, %0;\n@P bra W;\n}" ::"r"(n) : "memory");
}
__device__ __forceinline__ uint32_t gtime() { uint32_t t; asm volatile("mov.u32 %0, %%globaltimer_lo;" : "=r"(t)); return t; }
#define COUNT_RETRY(i)
__device__ __forceinline__ uint32_t stamp_word(uint32_t seq) { return (gtime() & ~31u) | (seq & 31u); }
__device__ __forceinline__ void wait_time(uint32_t t, uint32_t sb) { while ((int32_t)(gtime() - t) < 0) {} }
template <int STRIDE>
__device__ __forceinline__ uint32_t latest_stamp(const uint32_t* p, uint32_t seq, uint32_t ref, uint32_t sb) {
    int n = 0;
    while (true) {
        uint32_t bad = 0; int32_t m = INT32_MIN;
#pragma unroll
        for (int i = 0; i < 3; i++) { const uint32_t v = ld_relaxed1(p + i * STRIDE); bad |= (v ^ seq) & 31u; m = max(m, (int32_t)((v & ~31u) - ref)); }
        if (__all_sync(0xffffffffu, bad == 0)) return ref + __reduce_max_sync(0xffffffffu, m);
        p += delay_loop(20, sb);
        if (++n > SPIN_LIMIT) spin_fault();
    }
}
__device__ __forceinline__ uint32_t mrow_off(uint32_t l8) { return (l8 & 128) | ((l8 & 96) >> 2); }
__device__ __forceinline__ uint32_t reducer_block(int unit, int side) { return xblk(XP_O + (unit >> 4) * 8 + ((unit >> 3) & 1) + (unit & 3) * 2, side) + (unit & 4) * 512; }
__device__ __forceinline__ uint32_t find_sides(const Params& P, const int cta, const int lane, const uint32_t epoch) {
    const uint32_t key = (epoch + 1) << 1;
    uint32_t* tab = (uint32_t*)(P.xb + XP_MAP * 8192);
    if (cta % 6 == 0 && lane == 0) {
        uint32_t best[2] = {1u << 30, 1u << 30}, z = 0;
#pragma unroll 1
        for (int r = 0; r < 12; r++)
#pragma unroll
            for (int x = 0; x < 2; x++) {
                uint32_t v, c0, c1;
                asm volatile("mov.u32 %0, %%clock;" : "=r"(c0)::"memory");
                asm volatile("atom.relaxed.gpu.global.exch.b32 %0, [%1], %2;" : "=r"(v) : "l"(P.xb + xblk(XP_PROBE, x) + cta / 6 * 128 + z), "r"(r) : "memory");
                asm volatile("{\n.reg .pred P;\nsetp.ne.u32 P, %1, 0xffffffff;\nmov.u32 %0, 0;\n@P mov.u32 %0, %%clock;\n}" : "=r"(c1) : "r"(v) : "memory");
                z = (c1 == c0) * 4;
                best[x] = min(best[x], c1 - c0);
            }
        st_relaxed1(tab + cta / 6, key | (best[0] > best[1]));
    }
    __syncwarp();
    int n = 0;
    while (true) {
        const uint32_t e = ld_relaxed1(tab + (lane & 15));
        if (__all_sync(0xffffffffu, (e ^ key) < 2)) return __ballot_sync(0xffffffffu, e & 1);
        __nanosleep(500);
        if (++n > SPIN_LIMIT) spin_fault();
    }
}
__device__ __forceinline__ void pacer(const Params& P, const uint32_t sb, const int cta, const int lane, const uint32_t epoch) {
    const uint32_t sides = find_sides(P, cta, lane, epoch);
    if (lane == 0) { sts32(sb + S_SIDES, sides); mbar_arrive(sb + B_MAP); }
    {
        const int h = cta / 3, role = cta - h * 3;
        if (cta < 64) {
            const uint32_t* m = (const uint32_t*)(P.mem0 + (lane >> 2) * 1024 + cta * 16 + (lane & 3) * 2);
            st_relaxed2(P.xb + XP_M0 * 8192 + cta * 256 + (mrow_off(lane * 8) | ((lane & 3) << 5)), m[0], m[4]);
        }
#pragma unroll 1
        for (int j = 0; j < (role == 2 ? 8 : 12); j++)
            st_relaxed4(P.xb + reducer_block(h * 8 + role * 3 + (j >> 2), (sides >> (h >> 1)) & 1) + (j & 3) * 512 + lane * 16, epoch & 1, 0, epoch & 1, 0);
        __threadfence();
    }
    const uint32_t* ts = (const uint32_t*)(P.xb + xblk(XP_T, (sides >> (cta / 6)) & 1)) + lane;
    int32_t d0 = P.dly[0], d1 = P.dly[1];
    const uint32_t go = mapa(sb + B_GO, (cta / 3 & 1) * 3 + 1 + (lane & 1));
    auto free_segment = [&]() { if (lane == 0) mbar_expect(sb + B_KVFULL, 16384); __syncwarp(); if (lane < 2) mbar_arrive_cluster(go); };
    mbar_wait(sb + B_READY, 0);
    free_segment();
    if (lane == 0) st_relaxed1(g_hint + cta * 32, stamp_word(epoch + 1));
    uint32_t a = latest_stamp<1024>(g_hint + lane * 32, epoch + 1, gtime(), sb);
    wait_time(a, sb);
    if (lane == 0) mbar_arrive(sb + B_RELM);
#pragma unroll 1
    for (int s = 0; s < 63; s++) {
        const uint32_t t0 = a + d0, t1 = t0 + d1;
        mbar_wait(sb + B_X, s & 1);
        wait_time(t0, sb);
        if (lane == 0) mbar_arrive(sb + B_RELO);
        { const uint32_t t = t0; PROFP(1) }
        mbar_wait(sb + B_RED, s & 1);
        const uint32_t g = gtime() + P.guard;
        if (P.kvd < 0 && s < 62) free_segment();
        wait_time((int32_t)(g - t1) > 0 ? g : t1, sb);
        if (lane == 0) mbar_arrive(sb + B_RELM);
        { const uint32_t t = t1; PROFP(2) }
        if (s == 62) break;
        if (P.kvd >= 0) { wait_time(gtime() + P.kvd, sb); free_segment(); }
        wait_time(gtime() + P.rd, sb);
        const int32_t e0 = latest_stamp<32>(ts + (s & 1) * 256, epoch * 63 + s + 1, t0, sb) + P.mrg[0] - t0;
        const int32_t e1 = latest_stamp<32>(ts + (s & 1) * 256 + 128, epoch * 63 + s + 1, t1, sb) + P.mrg[1] - t1, lim = s < 6 ? P.clamp0 : P.clampv;
        if (s >= 1) { d0 += min(max(e0, -lim), P.clampv) / 2; d1 += min(max(e1 - max(e0, 0), -lim), P.clampv) / 2; }
        a = t1 + max(e1, 0);
    }
}
__device__ __forceinline__ void st_async2(uint32_t a, uint32_t x, uint32_t y, uint32_t bar) {
    asm volatile("st.async.weak.shared::cluster.mbarrier::complete_tx::bytes.v2.b32 [%0], {%1,%2}, [%3];" ::"r"(a), "r"(x), "r"(y), "r"(bar) : "memory");
}
__device__ __forceinline__ uint32_t xor_or(uint32_t a, uint32_t b, uint32_t t) { uint32_t d; asm("lop3.b32 %0, %1, %2, %3, 0x7E;" : "=r"(d) : "r"(a), "r"(b), "r"(t)); return d; }
__device__ __forceinline__ uint32_t or3(uint32_t a, uint32_t b, uint32_t c) { uint32_t d; asm("lop3.b32 %0, %1, %2, %3, 0xFE;" : "=r"(d) : "r"(a), "r"(b), "r"(c)); return d; }
__device__ __forceinline__ bool tags_ok(uint32_t bad) {
    uint32_t r;
    asm volatile("{\n.reg .pred P;\n.reg .b32 x;\nand.b32 x, %1, 1;\nsetp.ne.b32 P, x, 0;\nvote.sync.any.pred P, P, 0xffffffff;\nselp.u32 %0, 0, 1, P;\n}" : "=r"(r) : "r"(bad));
    return r;
}
__device__ __forceinline__ void gather8(uint32_t (*v)[2], const uint8_t* p, uint32_t tag, uint32_t check) {
#define LD8(i) "ld.relaxed.gpu.global.L1::no_allocate.b64 t" #i ", [%16 + " #i " * 256];\n"
    asm volatile("{\n.reg .pred P, Q;\n.reg .b32 a, b, c, d, n;\n.reg .b64 t0, t1, t2, t3, t4, t5, t6, t7;\nmov.u32 n, %18;\nL:\n"
                 LD8(0) LD8(1) LD8(2) LD8(3) LD8(4) LD8(5) LD8(6) LD8(7)
                 "add.u32 n, n, -1;\nsetp.eq.u32 Q, n, 0;\n@Q st.global.u32 [%19], 0;\n"
                 "mov.b64 {%0, %1}, t0;\nmov.b64 {%2, %3}, t1;\nmov.b64 {%4, %5}, t2;\nmov.b64 {%6, %7}, t3;\n"
                 "mov.b64 {%8, %9}, t4;\nmov.b64 {%10, %11}, t5;\nmov.b64 {%12, %13}, t6;\nmov.b64 {%14, %15}, t7;\n"
                 "lop3.b32 a, %0, %2, %17, 0x7E;\nlop3.b32 b, %4, %6, %17, 0x7E;\nlop3.b32 c, %8, %10, %17, 0x7E;\nlop3.b32 d, %12, %14, %17, 0x7E;\n"
                 "lop3.b32 a, a, b, c, 0xFE;\nlop3.b32 a, a, d, %20, 0xA8;\nsetp.ne.b32 P, a, 0;\nvote.sync.any.pred P, P, 0xffffffff;\n@P bra L;\n}"
                 : "=&r"(v[0][0]), "=&r"(v[0][1]), "=&r"(v[1][0]), "=&r"(v[1][1]), "=&r"(v[2][0]), "=&r"(v[2][1]), "=&r"(v[3][0]), "=&r"(v[3][1]),
                   "=&r"(v[4][0]), "=&r"(v[4][1]), "=&r"(v[5][0]), "=&r"(v[5][1]), "=&r"(v[6][0]), "=&r"(v[6][1]), "=&r"(v[7][0]), "=&r"(v[7][1])
                 : "l"(p), "r"(tag), "n"(SPIN_LIMIT), "l"(0ull), "r"(check) : "memory");
#undef LD8
}
constexpr int SROW = 56;
#define PREA 10
#define PREB 11
#define RING1 5
#define RING2 9
#define OFENCE 1
#define PRE2 12
#define PRE2A 0
#define LAG 4
#define PROG 16
#define HOLD 1
#define XDELAY 330
#define FENCE1 32
#define FENCE2 0x122
__host__ __device__ constexpr bool round_smem(int r, int NR) { return ((r + 1) * (8 - NR) + 3) / 8 != (r * (8 - NR) + 3) / 8; }
__host__ __device__ constexpr int kord(int r, int NR) { int c = 0; for (int i = 0; i < r; i++) c += round_smem(i, NR) == round_smem(r, NR); return round_smem(r, NR) ? NR + c : c; }
__host__ __device__ constexpr int slot_k(int n, int NR) { return kord(n < 32 ? n >> 2 : (((n & 31) >> 2) + ((n & 3) * 3 >> 1)) & 7, NR); }
__host__ __device__ constexpr int slot_sord(int n, int NR) { int c = 0; for (int i = 0; i < n; i++) c += slot_k(i, NR) >= NR; return c; }
__host__ __device__ constexpr int sfrag_slot(int q, int NR) { for (int n = 0; n < 64; n++) if (slot_k(n, NR) >= NR && slot_sord(n, NR) == q) return n; return -1; }
template <int Q, int NR>
__device__ __forceinline__ void load_w1(uint32_t* w, const uint32_t* a) {
    constexpr int n = sfrag_slot(Q, NR);
    ldsm4t(w, a[n & 3] + ((n >> 5) * (8 - NR) + slot_k(n, NR) - NR) * 2048);
}
__host__ __device__ constexpr int w2_kstep(int i) { return ((i >> 3) & 1) * 4 + ((i >> 1) & 1) * 2 + ((i >> 2) & 1); }
__host__ __device__ constexpr bool w2_perm(int n) { return n < 32 && (n & 8); }
__host__ __device__ constexpr int w2_sord(int n) { return n < 8 ? n : n < 24 ? n - 8 : n < 32 ? 16 : n - 16; }
__host__ __device__ constexpr int w2_used(int n) { return n < 8 ? n + 1 : n < 16 ? 8 : n < 24 ? n - 7 : n < 32 ? 16 : n - 15; }
__host__ __device__ constexpr int w2_loaded(int n, int end) { int q = PRE2; for (int i = 0; i <= n; i++) q += q < end && q - w2_used(i) < RING2; return q; }
template <int Q>
__device__ __forceinline__ void load_w2(uint32_t* w, const uint32_t* a) { ldsm4t(w, a[Q & 1] + (Q >> 3) * 4096 + (w2_kstep(Q & 7)) * 1024); }
__device__ __forceinline__ int w1_base(int warp) { return S_W1 + (warp < 4 ? warp * 20480 : 81920 + (warp - 4) * 12288); }
__device__ __forceinline__ int w2_base(int warp) { return S_W2 + warp * 16384; }
__device__ __forceinline__ int w2_blocks(int role, int warp) { return warp < (role == 2 ? 2 : 3) ? 3 : 2; }
__device__ __forceinline__ void chain_load(const Params& P, uint32_t sb, int cta, int warp, int lane, int round) {
    const int role = cta % 3, h = cta / 3, nh = round ? w2_blocks(role, warp) * 2 - 2 : 2;
    const bool five = (warp >= 4) != round;
    if (lane == 0) {
        mbar_expect(sb + B_INIT, (five ? 20480 : 12288) + (warp < 4 ? nh * 4096 : 0));
        tma3d(sb + (round ? w1_base(warp) : warp * 20480), &P.tm[(five ? M_C5 : M_C3) + role], 0, warp * 128 + (round ? (five ? 48 : 80) : 0), h * 2, sb + B_INIT);
        if (warp < 4) {
#pragma unroll 1
            for (int i = 0; i < nh; i++)
                tma2d(sb + (round ? w2_base(warp) : warp * 20480 + 12288) + i * 4096, &P.tm[M_CO], (role * 11 + warp + 4 * min(i, 2)) * 32, h * 128 + (round && i < 3 ? 0 : 64), sb + B_INIT);
        }
    }
    __syncwarp();
}

__device__ __forceinline__ void put_partials(bool TR, uint32_t a, const float* x, const float* y) {
    if (TR) stsm4t(a, pack2(x[0], x[1]), pack2(x[2], x[3]), pack2(y[0], y[1]), pack2(y[2], y[3]));
    else stsm4(a, pack2(x[0], x[1]), pack2(x[2], x[3]), pack2(y[0], y[1]), pack2(y[2], y[3]));
}
template <int NR, int PRE, int B, int E>
__device__ __forceinline__ void project(float (*acc)[4], bool TR, const uint32_t (*wr)[4], uint32_t (*as)[4], const uint32_t (*v)[2], const uint32_t* w1a, uint32_t pp) {
    static_for<B, E>([&](auto I) {
        constexpr int n = I.value, kk = slot_k(n, NR), T = (n >> 5) * 4 + (n & 3), so = slot_sord(n, NR), q = so + RING1;
        constexpr bool sm = kk >= NR;
        const uint32_t* w = sm ? as[so] : wr[sm ? 0 : ((n >> 5) * NR + kk) * 4 + (n & 3)];
        if constexpr ((n & 31) < 4) acc[T][0] = acc[T][1] = acc[T][2] = acc[T][3] = 0.f;
        mma16816(acc[T], w[0], w[1], w[2], w[3], v[kk][0], v[kk][1]);
        if constexpr (sm && q >= PRE && q < (8 - NR) * 8) load_w1<q, NR>(as[q], w1a);
        if constexpr (n == 35) { put_partials(TR, pp, acc[0], acc[1]); put_partials(TR, pp + 4096, acc[2], acc[3]); }
        if constexpr (n % FENCE1 == FENCE1 - 1 && n < 56 && n != E - 1) sched_fence();
    });
    if constexpr (E == 64) { put_partials(TR, pp + 8192, acc[4], acc[5]); put_partials(TR, pp + 12288, acc[6], acc[7]); }
}
__device__ __forceinline__ void reduce8(const uint32_t (*x)[4], uint32_t l8, uint32_t& r0, uint32_t& r1) {
    float d[4][4];
#pragma unroll
    for (int i = 0; i < 4; i++) {
        d[i][0] = d[i][1] = d[i][2] = d[i][3] = 0.f;
        mma16816(d[i], x[i][0], x[i][1], x[i][2], x[i][3], (l8 & 224) == i * 64 ? 0x3F803F80u : 0u, (l8 & 224) == i * 64 + 32 ? 0x3F803F80u : 0u);
    }
    r0 = pack2((d[0][0] + d[1][0]) + (d[2][0] + d[3][0]), (d[0][1] + d[1][1]) + (d[2][1] + d[3][1]));
    r1 = pack2((d[0][2] + d[1][2]) + (d[2][2] + d[3][2]), (d[0][3] + d[1][3]) + (d[2][3] + d[3][3]));
}

#define ISTAMP(i)
template <int NB>
__device__ __forceinline__ void wo_blocks(uint32_t (*w)[4], const uint32_t (*wp)[4], uint32_t oa, const uint32_t* wa, const uint8_t* dst, const uint32_t* op, uint32_t tag) {
    float a[NB][4][4];
    uint32_t o[4][4];
    bar_sync(3, 256);
#pragma unroll
    for (int i = 0; i < 4; i++) ldsm4(o[i], oa + i * 512);
    if (OFENCE) sched_fence();
    static_for<0, NB * 16>([&](auto I) {
        constexpr int n = I.value, i = n & 15, so = w2_sord(n), end = NB * 16 - 16, q = w2_loaded(n - 1, end), kk = w2_kstep(i);
        constexpr bool perm = w2_perm(n);
        const uint32_t* b = o[kk >> 1] + (kk & 1) * 2;
        const uint32_t* x = perm ? wp[perm ? (n >> 4) * 8 + (kk - 4) * 2 + (n & 1) : 0] : w[so];
        float* d = a[n >> 4][i & 3];
        if constexpr (i < 4) d[0] = d[1] = d[2] = d[3] = 0.f;
        mma16816(d, x[0], x[1], x[2], x[3], b[0], b[1]);
        if constexpr (w2_loaded(n, end) > q) load_w2<q>(w[q], wa);
        if constexpr (n == NB * 16 - 1 || (n >= 16 && i == LAG - 1)) {
            constexpr int k = n == NB * 16 - 1 ? NB - 1 : (n >> 4) - 1;
            const float (*e)[4] = a[k];
            st_relaxed2(dst + op[k], (movm(pack2(e[0][0] + e[2][0], e[0][1] + e[2][1])) & ~1u) | tag, movm(pack2(e[0][2] + e[2][2], e[0][3] + e[2][3])));
            st_relaxed2(dst + op[k] + 2048, (movm(pack2(e[1][0] + e[3][0], e[1][1] + e[3][1])) & ~1u) | tag, movm(pack2(e[1][2] + e[3][2], e[1][3] + e[3][3])));
        }
        if constexpr (((FENCE2 >> (n >> 2)) & 1) && (n & 3) == 3 && end > PRE2) sched_fence();
    });
}
template <bool ATT>
__device__ __forceinline__ void chain_role(const Params& P, const uint32_t sb, const int cta, const int warp, const int lane, const uint32_t epoch) {
    constexpr int NR = ATT ? 5 : 3, PRE = ATT ? PREA : PREB;
    const int h = cta / 3, ROLE = cta - h * 3;
    uint32_t wr[40][4];
#define FRAG1(ln) ((((ln) & 7) + ((ln) >> 4) * 8) * 128 + ((((((ln) >> 3) & 1) << (ROLE == 1)) ^ ((ln) & 7)) << 4))
#define FRAG2(ln) ((((ln) & 7) + ((ln) >> 4) * 8) * 64 + (((((ln) >> 3) & 1) ^ (((ln) >> 1) & 3)) << 4))
#define TILE_X(i) (ROLE == 1 ? (((i) >> 1) << 6) | (((i) & 1) << 4) : (i) << 5)
    {
        const uint32_t st = sb + warp * 20480;
        mbar_wait(sb + B_INIT, 0);
        ISTAMP(0)
#pragma unroll
        for (int f = 0; f < 40; f++)
            ldsm4t(wr[f], f < NR * 8 ? st + (f >> 2) * 2048 + (FRAG1(lane) ^ TILE_X(f & 3)) : st + 12288 + ((f - 24) >> 1) * 1024 + (FRAG2(lane) ^ ((f & 1) << 5)));
        fence_async_smem();
        bar_sync(1, 256);
        chain_load(P, sb, cta, warp, lane, 1);
        ISTAMP(1)
    }
    ISTAMP(6)
    uint32_t l8 = opq(sb + lane * 8, lane);
    const uint8_t* persu = (const uint8_t*)((ROLE == 1 ? g_km + (warp >> 1) * 128 + (warp & 1) * 32 : g_vmt + warp * 64) + h * 512) - (sb >> 1);
#define PERS_STORE() if (ROLE != 0) { uint32_t* pp = (uint32_t*)(persu + s * 65536 + (l8 >> 1)); pp[0] = r0; pp[ROLE == 1 ? 64 : 32] = r1; }
    mbar_wait(sb + B_MAP, 0);
    const uint32_t sides = __shfl_sync(0xffffffffu, lds32(sb + S_SIDES), 0), side = (sides >> (h >> 1)) & 1;
    const uint32_t rk0 = (h & 1) * 3, rd1 = __shfl_sync(0xffffffffu, mapa(sb, rk0 + (ROLE + 1) % 3) - sb, 0), rd2 = __shfl_sync(0xffffffffu, mapa(sb, rk0 + (ROLE + 2) % 3) - sb, 0);
    const uint32_t xo = (ROLE == 2 ? S_XV : S_X + ROLE * 2048) + warp * 256;
    uint32_t op[3];
#pragma unroll
    for (int i = 0; i < 3; i++) { const int b = ROLE * 11 + warp + 4 * i; op[i] = xblk(XP_O + (b >> 1) * 8 + (b & 1), (sides >> (b >> 1)) & 1) + h * 64; }
    const bool reducer = ATT && warp < (ROLE == 2 ? 6 : 7), third = w2_blocks(ROLE, warp) == 3;
    const int unit = h * 8 + ROLE * 3 + warp - 4;
    const uint32_t og = reducer_block(unit, side);
    const uint32_t mp = xblk(XP_M + (unit >> 6), 0), mo = ((unit >> 2) & 15) * 256 + (unit & 3) * 32;
    const uint32_t w1o = sb + w1_base(warp), w2o = sb + w2_base(warp);
    uint32_t* const tsp = (uint32_t*)(P.xb + XP_T * 8192) + cta;
#define STAMP(i) if (l8 - sb < 16) st_relaxed1(tsp + (s & 1) * 256 + (i) * 128 + (l8 - sb) * 128, stamp_word(epoch * 63 + s + 1));
    const uint32_t mg = xblk(XP_M + (warp >> 1), side) + (warp & 1) * 2048, mg0 = XP_M0 * 8192 + warp * 2048;
    mbar_wait(sb + B_INIT, 1);
    ISTAMP(2)
    if (lane == 0) mbar_arrive(sb + B_READY);
#pragma unroll 1
    for (int s = 0;; s++) {
        const uint32_t tag = (epoch + 1 + s) & 1;
        l8 += s & P.zero;
        uint32_t r0, r1, ad[3];
        {
            uint32_t v[8][2], as[(8 - NR) * 8][4], w1a[4];
            float acc[8][4];
            const uint8_t* pm = P.xb + (s ? mg : mg0) + (mrow_off(l8) | ((l8 & 24) << 2));
            const uint32_t pst = sb + S_P1 + (l8 - sb) * 16 + ((warp * 16) ^ ((l8 & 56) * 2));
#pragma unroll
            for (int i = 0; i < 4; i++) w1a[i] = w1o + (FRAG1((l8 - sb) >> 3) ^ TILE_X(i));
            auto preload = [&]() { static_for<0, PRE>([&](auto I) { load_w1<I.value, NR>(as[I.value], w1a); }); };
            preload();
            uint32_t chk[2] = {tag ^ 1, s != 0};
            pin_ptr(pm); pin<2>(chk);
            mbar_wait(sb + B_RELM, s & 1);
            PROF(10)
            for (int n = 0;; n++) {
                static_for<0, 8>([&](auto I) { constexpr int k = kord(I.value, NR); ld_relaxed2(v[k], pm + k * 256); });
                project<NR, PRE, 0, PROG>(acc, ROLE == 2, wr, as, v, w1a, pst);
                const uint32_t bad = or3(xor_or(v[0][0], v[1][0], chk[0]), xor_or(v[2][0], v[3][0], chk[0]), xor_or(v[4][0], v[5][0], chk[0])) | xor_or(v[6][0], v[7][0], chk[0]);
                if (tags_ok(bad & chk[1])) break;
                if (n > SPIN_LIMIT) spin_fault();
                preload();
            }
            PROF(0)
            project<NR, PRE, PROG, 64>(acc, ROLE == 2, wr, as, v, w1a, pst);
            PROF(1)
            const uint32_t lq = l8 + ((s >> 3) & P.zero);
            const uint32_t pld = sb + S_P1 + warp * 2048 + (lq & 64) * 16 + (lq & 128) + (lq & 56) * 2;
            uint32_t x[4][4], xd = l8 + xo;
            if (ATT) {
                const uint32_t ln = (lq - sb) >> 3;
                ad[0] = sb + S_KV + 8192 + ((warp >> 1) & 1) * 4096 + ((ln & 7) + (ln >> 4) * 8) * 128 + ((((warp & 1) * 4 + ((ln >> 3) & 1)) ^ (ln & 7)) << 4);
                ad[1] = sb + S_KV + (warp & 1) * 2048 + (ln & 15) * 128 + (((ln >> 4) ^ (ln & 7)) << 4);
                ad[2] = sb + S_SX + (ln & 3) * (8 * SROW) + (ln >> 2) * 4 + (warp < 6 ? (warp - 4) * 64 : 128 + (warp - 6) * 32);
                pin<3>(ad);
            }
            pin<1>(&xd);
            bar_sync(1, 256);
#pragma unroll
            for (int i = 0; i < 4; i++) ldsm4t(x[i], pld + i * 256);
            reduce8(x, lq, r0, r1);
            if (s == 63) { PERS_STORE() break; }
            st_async2(xd + rd1, r0, r1, sb + B_X + rd1);
            st_async2(xd + rd2, r0, r1, sb + B_X + rd2);
            sts64(xd, r0, r1);
            __syncwarp();
            if (l8 == sb) mbar_arrive(sb + B_X);
            PROF(2)
        }
        const uint32_t oa = l8 * 2 + (S_OX - sb);
        if constexpr (ATT) {
            const uint32_t va = ad[0], ka = ad[1], sa = ad[2];
            uint32_t vf[4][4], vm[2][2], q[8][2];
            float S[4][4];
#pragma unroll
            for (int n = 0; n < 4; n++) { S[n][0] = S[n][1] = S[n][2] = S[n][3] = 0.f; }
            mbar_wait(sb + B_KVFULL, s & 1);
            if (warp < 6) {
                uint32_t kf[8][4];
#pragma unroll
                for (int k = 0; k < 8; k++) ldsm4(kf[k], (ka ^ ((k & 3) << 5)) + (k >> 2) * 4096);
#pragma unroll
                for (int i = 0; i < 4; i++) ldsm4t(vf[i], (va ^ ((i & 1) << 5)) + (i >> 1) * 2048);
                mbar_wait(sb + B_X, s & 1);
                PROF(11)
#pragma unroll
                for (int k = 0; k < 8; k++) lds64(q[k], l8 + S_X + k * 256);
#pragma unroll
                for (int k = 0; k < 8; k++) mma16816(S[k & 3], kf[k][0], kf[k][1], kf[k][2], kf[k][3], q[k][0], q[k][1]);
                sts32(sa, __float_as_uint((S[0][0] + S[1][0]) + (S[2][0] + S[3][0])));
                sts32(sa + 4 * SROW, __float_as_uint((S[0][1] + S[1][1]) + (S[2][1] + S[3][1])));
                sts32(sa + 32, __float_as_uint((S[0][2] + S[1][2]) + (S[2][2] + S[3][2])));
                sts32(sa + 4 * SROW + 32, __float_as_uint((S[0][3] + S[1][3]) + (S[2][3] + S[3][3])));
            } else {
#pragma unroll
                for (int i = 0; i < 4; i++) ldsm4t(vf[i], (va ^ ((i & 1) << 5)) + (i >> 1) * 2048);
                uint32_t xa = l8 + S_X + (warp - 6) * 1024;
                pin<1>(&xa);
                mbar_wait(sb + B_X, s & 1);
                PROF(11)
#pragma unroll
                for (int k = 0; k < 8; k++) lds64(q[k], xa + (k >> 2) * 2048 + (k & 3) * 256);
#pragma unroll
                for (int k = 0; k < 4; k++) mma16816(S[k], q[4 + (k & 2)][0], q[4 + (k & 2)][1], q[5 + (k & 2)][0], q[5 + (k & 2)][1], q[k][0], q[k][1]);
                sts32(sa, __float_as_uint((S[0][0] + S[2][0]) + (S[1][2] + S[3][2])));
                sts32(sa + 4 * SROW, __float_as_uint((S[0][1] + S[2][1]) + (S[1][3] + S[3][3])));
            }
            lds64(vm[0], l8 + S_XV + (warp - 4) * 512); lds64(vm[1], l8 + S_XV + 256 + (warp - 4) * 512);
            PROF(7)
            const uint32_t sr = l8 + S_SX + ((l8 - sb) >> 5) * (4 * SROW - 32);
            bar_sync(2, 128);
            const float cs = 0.08838834764831845f * 1.4426950408889634f;
            float E[6][2];
#pragma unroll
            for (int i = 0; i < 6; i++) lds64f(E[(i + 4) % 6], sr + ((i + 4) % 6) * 32);
            E[4][0] += E[5][0]; E[4][1] += E[5][1];
            float m = fmaxf(fmaxf(fmaxf(fmaxf(E[0][0], E[0][1]), fmaxf(E[1][0], E[1][1])), fmaxf(fmaxf(E[2][0], E[2][1]), fmaxf(E[3][0], E[3][1]))), fmaxf(E[4][0], E[4][1]));
            m = fmaxf(m, __shfl_xor_sync(0xffffffffu, m, 1));
            m = fmaxf(m, __shfl_xor_sync(0xffffffffu, m, 2));
            m *= cs;
            uint32_t pa[5];
#pragma unroll
            for (int i = 0; i < 5; i++) { const int k = (i + 4) % 5; E[k][0] = ex2(fmaf(E[k][0], cs, -m)); E[k][1] = ex2(fmaf(E[k][1], cs, -m)); pa[k] = pack2(E[k][0], E[k][1]); }
            float O[2][4], Z[4];
#pragma unroll
            for (int i = 0; i < 4; i++) { O[0][i] = O[1][i] = Z[i] = 0.f; }
#pragma unroll
            for (int i = 0; i < 2; i++) {
                mma1688(O[i], vm[i][0], vm[i][1], pa[4]);
                mma16816(O[i], vf[i][0], vf[i][1], vf[i][2], vf[i][3], pa[0], pa[1]);
                mma16816(O[i], vf[2 + i][0], vf[2 + i][1], vf[2 + i][2], vf[2 + i][3], pa[2], pa[3]);
            }
            const float z = (((E[4][0] + E[4][1]) + (E[0][0] + E[0][1])) + ((E[1][0] + E[1][1]) + (E[2][0] + E[2][1]))) + (E[3][0] + E[3][1]);
            const float zh = __uint_as_float(__float_as_uint(z) & 0xffff0000u);
            mma1688(Z, 0x3F803F80u, 0x3F803F80u, pack2(zh, z - zh));
            const float i0 = rcp(Z[0]), i1 = rcp(Z[1]);
            stsm4t(oa + (warp - 4) * 512, pack2(O[0][0] * i0, O[0][1] * i1), pack2(O[0][2] * i0, O[0][3] * i1), pack2(O[1][0] * i0, O[1][1] * i1), pack2(O[1][2] * i0, O[1][3] * i1));
            bar_arrive(3, 256);
            PROF(4)
            PERS_STORE()
            if (warp == 7 && l8 == sb) mbar_expect(sb + B_X, 4096);
            if (reducer) {
                const uint32_t lr = l8 + ((s >> 1) & P.zero);
                const uint8_t* pg = P.xb + og + (((lr & 24) << 3) | ((lr & 224) >> 2));
                const uint8_t* pubm = P.xb + (mp ^ ((lr & 8) << 9)) + mo + mrow_off(lr);
                uint32_t sel = (lr & 32) ? 0x3F800000u : 0x3F80u;
                pin_ptr(pg); pin_ptr(pubm); pin<1>(&sel);
                mbar_wait(sb + B_RELO, s & 1);
                PROF(9)
                uint32_t y[8][2];
                gather8(y, pg, tag, 1);
                PROF(6)
                float d[4][4];
#pragma unroll
                for (int j = 0; j < 4; j++) { d[j][0] = d[j][1] = d[j][2] = d[j][3] = 0.f; mma16816(d[j], y[2 * j][0], y[2 * j][1], y[2 * j + 1][0], y[2 * j + 1][1], sel, sel); }
                const uint32_t m0 = pack2((d[0][0] + d[1][0]) + (d[2][0] + d[3][0]), (d[0][1] + d[1][1]) + (d[2][1] + d[3][1]));
                const uint32_t m1 = pack2((d[0][2] + d[1][2]) + (d[2][2] + d[3][2]), (d[0][3] + d[1][3]) + (d[2][3] + d[3][3]));
                if ((l8 & 16) == 0) st_relaxed2(pubm, (m0 & ~1u) | tag, m1);
                if (l8 == sb) mbar_arrive(sb + B_RED);
                PROF(8)
                if (warp == 4) { STAMP(1) }
            }
        } else {
            PERS_STORE()
            uint32_t w[32][4];
            const uint32_t lo = l8 + ((s >> 2) & P.zero);
            const uint32_t w2a[2] = {w2o + FRAG2((lo - sb) >> 3), w2o + (FRAG2((lo - sb) >> 3) ^ 32)};
            static_for<0, PRE2A>([&](auto I) { load_w2<I.value>(w[I.value], w2a); });
            const uint8_t* po = P.xb + (((lo & 24) << 11) | ((lo & 224) >> 2));
            pin_ptr(po);
            if (PRE2A < PRE2) { mbar_wait(sb + B_X, s & 1); wait_clocks(XDELAY); }
            static_for<PRE2A, PRE2>([&](auto I) { load_w2<I.value>(w[I.value], w2a); });
            if (third) wo_blocks<3>(w, wr + 24, oa, w2a, po, op, tag);
            else wo_blocks<2>(w, wr + 24, oa, w2a, po, op, tag);
            PROF(5)
            if (warp == 0) { STAMP(0) }
        }
        if (HOLD && !reducer) mbar_wait(sb + B_RELO, s & 1);
        if (ROLE != 0 && (s & 3) == 3 && l8 == sb) mbar_arrive(sb + B_PERS);
        if (ROLE == 0 && s == 62) return;
    }
    __syncwarp();
    if (l8 == sb) mbar_arrive(sb + B_PERS);
}
#define WGLAG 0
struct Pipe { uint32_t stage, phase; };
struct Cons {
    uint32_t sb, rel;
    int wg, wq, lane, rank, pair;
    uint32_t atag, nst;
    Pipe p;
};
__device__ __forceinline__ void pipe_next(Pipe& p) { p.stage = (p.stage + 1) & (NSTAGE - 1); p.phase ^= (p.stage == 0); }
__device__ __forceinline__ void release(const Cons& c, uint32_t stage) { if (c.lane < 2) mbar_arrive_cluster(c.rel + stage * 8); }

enum { PEND_NONE = 0, PEND_KVO = 1, PEND_HT = 2, PEND_OUT = 3, PEND_OUTH = 4 };
struct Pend { uint32_t pk[64]; int kind, row, col, cnt; };

__device__ __forceinline__ void staging_wait(const Cons& c) { if (c.nst) mbar_wait(c.sb + B_SFREE + c.wg * 8, (c.nst - 1) & 1); }
__device__ __forceinline__ void staging_post(Cons& c, int kind, int row, int col, int cnt) {
    __syncwarp();
    if (c.lane == 0) {
        if (c.wq == 0) { const uint32_t x[4] = {(uint32_t)kind, (uint32_t)row, (uint32_t)col, (uint32_t)cnt}; sts128(c.sb + S_DESC + c.wg * 16, x); }
        mbar_arrive(c.sb + B_SFULL + c.wg * 8);
    }
    c.nst++;
}
template <int HF, bool KVONLY = false>
__device__ __forceinline__ void drain(const Params& P, Cons& c, const Pend& d) {
    const uint32_t* pk = d.pk + HF * 32;
    if (!KVONLY && d.kind >= PEND_OUT) {
        if (HF == 1 && d.kind == PEND_OUTH) return;
        float* o = P.out + (size_t)(d.row + c.wq * 16 + (c.lane >> 2)) * 2048 + d.col + HF * 128 + (c.lane & 3) * 2;
#pragma unroll
        for (int j = 0; j < 16; j++) {
            st_stream2(o + j * 8, bf_lo(pk[j * 2]), bf_hi(pk[j * 2]));
            st_stream2(o + 8 * 2048 + j * 8, bf_lo(pk[j * 2 + 1]), bf_hi(pk[j * 2 + 1]));
        }
    } else if (d.kind != PEND_NONE) {
        const bool ht = !KVONLY && d.kind == PEND_HT;
        const int hi = (c.lane >> 3) & 1;
        const uint32_t base = c.sb + S_STG + c.wg * 16384 + ((ht ? hi * 32 + c.wq * 8 : c.wq * 16 + hi * 8) + (c.lane & 7)) * 128;
        staging_wait(c);
#pragma unroll
        for (int j = 0; j < 8; j++) {
            const int ch = (j & 3) * 2 + (c.lane >> 4);
            stsm4(base + (j >> 2) * 8192 + ((ch ^ (c.lane & 7)) << 4), pk[j * 4], pk[j * 4 + 1], pk[j * 4 + 2], pk[j * 4 + 3]);
        }
        fence_async_smem();
        staging_post(c, d.kind, d.row, d.col + HF * 128, HF ? d.cnt : -1);
    }
}
__device__ __forceinline__ void drain_all(const Params& P, Cons& c, Pend& d) { drain<0>(P, c, d); drain<1>(P, c, d); d.kind = PEND_NONE; }

__device__ __forceinline__ void store_warp(const Params& P, uint32_t sb, int wg) {
    const uint32_t stg = sb + S_STG + wg * 16384;
#pragma unroll 1
    for (uint32_t n = 0;; n++) {
        mbar_wait(sb + B_SFULL + wg * 8, n & 1);
        uint32_t x[4];
        lds128(x, sb + S_DESC + wg * 16);
#pragma unroll
        for (int i = 0; i < 4; i++) x[i] = __shfl_sync(0xffffffffu, x[i], 0);
        if (x[0] == PEND_NONE) break;
        const bool ht = x[0] == PEND_HT;
        const CUtensorMap* m = &P.tm[ht ? M_HTS : M_KVO];
        if (elect_one()) {
#pragma unroll
            for (int i = 0; i < 4; i++) tma_store2d(m, x[2] + (i >> 1) * 64, x[1] + (i & 1) * (ht ? 1024 : 32), stg + i * 4096);
            bulk_commit();
            bulk_wait_read();
            mbar_arrive(sb + B_SFREE + wg * 8);
            if ((int)x[3] >= 0) { bulk_wait_all(); fence_async(); red_release(&g_cnt(x[3])); }
        }
        __syncwarp();
    }
}

template <int N, int TA, int TB, bool FIRST>
__device__ __forceinline__ void issue_ktile(float* acc, const Cons& c) {
    mbar_wait(c.sb + B_FULL + c.p.stage * 8, c.p.phase);
    const uint32_t a = c.sb + c.p.stage * STAGE + c.wg * 8192, b = c.sb + c.p.stage * STAGE + 16384;
    const uint64_t da = mkdesc(a, TA ? 8192 : 16, 1024, 1), db = mkdesc(b, TB ? 8192 : 16, 1024, 1);
    wg_fence();
#pragma unroll
    for (int k = 0; k < 4; k++) {
        const uint64_t x = da + (TA ? 128 : 2) * k, y = db + (TB ? 128 : 2) * k;
        if (N == 256) { if (FIRST && k == 0) wgmma_ss256_first<TA, TB>(acc, x, y); else wgmma_ss256<TA, TB>(acc, x, y); }
        else { if (FIRST && k == 0) wgmma_ss128_first<TA, TB>(acc, x, y); else wgmma_ss128<TA, TB>(acc, x, y); }
    }
    wg_commit();
}
template <int N, bool FIRST>
__device__ __forceinline__ void issue_any(float* acc, const Cons& c, int type) {
    if (N == 256 && type == T_A1) issue_ktile<N, 0, 0, FIRST>(acc, c);
    else if (type == (N == 256 ? T_A2 : T_A2H)) issue_ktile<N, 1, 0, FIRST>(acc, c);
    else issue_ktile<N, 0, 1, FIRST>(acc, c);
}
template <int N, bool KVONLY = false>
__device__ __forceinline__ void mainloop(float* acc, const Params& P, Cons& c, Pend& d, int type) {
    const int nk = (type == T_OP || type == T_OPH) ? 64 : (type == T_A2 || type == T_A2H) ? 32 : 16;
    if (WGLAG && c.wg) bar_sync(7, 256);
    issue_any<N, true>(acc, c, type);
    if (WGLAG == 1 && !c.wg) bar_arrive(7, 256);
    drain<0, KVONLY>(P, c, d);
    uint32_t prev = c.p.stage;
    pipe_next(c.p);
    for (int kt = 1; kt < nk; kt++) {
        issue_any<N, false>(acc, c, type);
        if (WGLAG > 1 && kt == WGLAG - 1 && !c.wg) bar_arrive(7, 256);
        wg_wait<1>();
        release(c, prev);
        if (kt == 2) drain<1, KVONLY>(P, c, d);
        prev = c.p.stage;
        pipe_next(c.p);
    }
    d.kind = PEND_NONE;
    wg_wait<0>();
    pin<N / 2>(acc);
    release(c, prev);
}
__device__ __forceinline__ void pack_half(uint32_t* pk, const float* a) {
#pragma unroll
    for (int i = 0; i < 32; i++) pk[i] = pack2(a[2 * i], a[2 * i + 1]);
}

__device__ __forceinline__ void epi_kv(const float* acc, const Cons& c, Pend& d, int mb, int nb) {
    pack_half(d.pk, acc); pack_half(d.pk + 32, acc + 64);
    d.kind = PEND_KVO; d.row = (nb >> 4) * 2048 + mb * 256 + c.rank * 128 + c.wg * 64; d.col = (nb & 15) * 256; d.cnt = C_KV + mb;
}

__device__ __forceinline__ void qa_scores(float* S, float* Sm, const uint32_t* q, Cons& c) {
    mbar_wait(c.sb + B_FULL + c.p.stage * 8, c.p.phase);
    const uint32_t st = c.sb + c.p.stage * STAGE;
    const uint64_t dk = mkdesc(st + c.wg * 8192, 16, 1024, 1), dm = mkdesc(st + 32768 + c.wg * 4096, 128, 2048, 0);
    wg_fence();
#pragma unroll
    for (int i = 0; i < 8; i++) wgmma_rs64<0>(S, q + i * 4, dk + (i >> 2) * 1024 + (i & 3) * 2, i != 0);
#pragma unroll
    for (int i = 0; i < 8; i++) wgmma_rs16<0>(Sm, q + i * 4, dm + i * 16, i != 0);
    wg_commit();
    pipe_next(c.p);
}
__device__ __forceinline__ void qa_softmax(uint32_t (*pa)[4], const float* S, const float* Sm, const Cons& c) {
    const int t = c.lane & 3, i0 = (c.wq & 1) * 16 + (c.lane >> 2) - 2 * t;
    const bool sg = c.wq >= 2;
    const float cs = 0.08838834764831845f * 1.4426950408889634f;
    float x[2][10];
#pragma unroll
    for (int r = 0; r < 2; r++) {
#pragma unroll
        for (int j = 0; j < 4; j++)
#pragma unroll
            for (int e = 0; e < 2; e++) {
                const float v = sg ? S[16 + j * 4 + r * 2 + e] : S[j * 4 + r * 2 + e];
                x[r][j * 2 + e] = (j * 8 + e - r * 8 > i0) ? -1e9f / 0.08838834764831845f : v;
            }
        x[r][8] = sg ? Sm[4 + r * 2] : Sm[r * 2];
        x[r][9] = sg ? Sm[5 + r * 2] : Sm[1 + r * 2];
        float m = fmaxf(fmaxf(fmaxf(fmaxf(x[r][0], x[r][1]), fmaxf(x[r][2], x[r][3])), fmaxf(fmaxf(x[r][4], x[r][5]), fmaxf(x[r][6], x[r][7]))), fmaxf(x[r][8], x[r][9]));
        m = fmaxf(m, __shfl_xor_sync(0xffffffffu, m, 1));
        m = fmaxf(m, __shfl_xor_sync(0xffffffffu, m, 2));
        m *= -cs;
#pragma unroll
        for (int i = 0; i < 10; i++) x[r][i] = ex2(fmaf(x[r][i], cs, m));
        float sum = (((x[r][0] + x[r][1]) + (x[r][2] + x[r][3])) + ((x[r][4] + x[r][5]) + (x[r][6] + x[r][7]))) + (x[r][8] + x[r][9]);
        sum += __shfl_xor_sync(0xffffffffu, sum, 1);
        sum += __shfl_xor_sync(0xffffffffu, sum, 2);
        const float inv = rcp(sum);
#pragma unroll
        for (int i = 0; i < 10; i++) x[r][i] *= inv;
    }
#pragma unroll
    for (int ks = 0; ks < 2; ks++)
#pragma unroll
        for (int i = 0; i < 4; i++) {
            const uint32_t p = pack2(x[i & 1][ks * 4 + (i >> 1) * 2], x[i & 1][ks * 4 + (i >> 1) * 2 + 1]);
            pa[ks][i] = sg ? 0u : p;
            pa[2 + ks][i] = sg ? p : 0u;
        }
#pragma unroll
    for (int r = 0; r < 2; r++) {
        const uint32_t p = pack2(x[r][8], x[r][9]);
        pa[4][r] = sg ? 0u : p;
        pa[4][2 + r] = sg ? p : 0u;
    }
}
__device__ __forceinline__ void qa_values(float* O, uint32_t (*pa)[4], Cons& c) {
    mbar_wait(c.sb + B_FULL + c.p.stage * 8, c.p.phase);
    const uint32_t st = c.sb + c.p.stage * STAGE;
    const uint64_t dv = mkdesc(st + c.wg * 8192, 16384, 1024, 1), dm = mkdesc(st + 32768 + c.wg * 4096, 2048, 128, 0);
    pin<20>(&pa[0][0]);
    wg_fence();
#pragma unroll
    for (int ks = 0; ks < 4; ks++) wgmma_rs128<1>(O, pa[ks], dv + ks * 128, ks != 0);
    wgmma_rs128<0>(O, pa[4], dm, 1);
    wg_commit();
    pipe_next(c.p);
}
__device__ __forceinline__ void epi_qa(const float* acc, Cons& c, Pend& d, int mb, int nb) {
    uint32_t q[64], pa[2][5][4];
    float S0[32] = {}, M0[8] = {}, S1[32] = {}, M1[8] = {}, O0[64] = {}, O1[64] = {};
    const uint32_t k0 = c.p.stage;
    pack_half(q, acc);
    pin<32>(q); pin<32>(S0); pin<8>(M0);
    qa_scores(S0, M0, q, c);
    pack_half(q + 32, acc + 64);
    pin<32>(q + 32); pin<32>(S1); pin<8>(M1);
    qa_scores(S1, M1, q + 32, c);
    wg_wait<1>();
    pin<32>(S0); pin<8>(M0);
    release(c, k0);
    qa_softmax(pa[0], S0, M0, c);
    wg_wait<0>();
    pin<32>(S1); pin<8>(M1); pin<64>(q);
    release(c, (k0 + 1) & (NSTAGE - 1));
    pin<64>(O0);
    qa_values(O0, pa[0], c);
    qa_softmax(pa[1], S1, M1, c);
    pin<64>(O1);
    qa_values(O1, pa[1], c);
    wg_wait<1>();
    pin<64>(O0); pin<20>(&pa[0][0][0]);
    release(c, (k0 + 2) & (NSTAGE - 1));
    pack_half(d.pk, O0);
    wg_wait<0>();
    pin<64>(O1); pin<20>(&pa[1][0][0]);
    release(c, (k0 + 3) & (NSTAGE - 1));
    pack_half(d.pk + 32, O1);
    d.kind = PEND_KVO; d.row = 4096 + mb * 256 + c.rank * 128 + c.wg * 64; d.col = nb * 256; d.cnt = C_O + mb;
}

__device__ __forceinline__ void epi_op(const float* acc, const Cons& c, Pend& d, int mb, int nb) {
    pack_half(d.pk, acc); pack_half(d.pk + 32, acc + 64);
    d.kind = PEND_OUT; d.row = mb * 256 + c.rank * 128 + c.wg * 64; d.col = 1024 + nb * 256;
}

__device__ __forceinline__ void epi_oph(const float* acc, const Cons& c, Pend& d, int mb, int nb) {
    pack_half(d.pk, acc);
    d.kind = PEND_OUTH; d.row = mb * 256 + c.rank * 128 + c.wg * 64; d.col = 1024 + nb * 128;
}

template <int HF>
__device__ __forceinline__ void epi_a2_half(const float* acc, const Params& P, Cons& c, int mb, int col0) {
    const int g = c.lane >> 2, t = c.lane & 3;
    const int row = mb * 256 + (g >> 1) * 64 + (c.rank * 16 + c.wg * 8 + c.wq * 2) * 2 + (g & 1);
    float* o = P.out + (size_t)row * 2048 + col0 + HF * 128 + t * 2;
    mbar_wait(c.sb + B_FULL + c.p.stage * 8, c.p.phase);
    const uint32_t st = c.sb + c.p.stage * STAGE, xa = st + (c.wg * 64 + c.wq * 16 + g) * 128 + t * 4 + (g << 4), da = st + 32768 + t * 4;
#pragma unroll
    for (int j = 0; j < 16; j++) {
        const float* a = acc + HF * 64 + j * 4;
        const uint32_t ad = (xa ^ ((j & 7) << 4)) + (j >> 3) * 16384;
        const uint32_t x0 = lds32(ad), x1 = lds32(ad + 1024), dv = lds32(da + j * 16);
        const uint32_t u0 = pack2(bf_lo(x0) * bf_lo(dv), bf_hi(x0) * bf_hi(dv)), u1 = pack2(bf_lo(x1) * bf_lo(dv), bf_hi(x1) * bf_hi(dv));
        st_stream2(o + j * 8, a[0] + bf_lo(u0), a[1] + bf_hi(u0));
        st_stream2(o + 2 * 2048 + j * 8, a[2] + bf_lo(u1), a[3] + bf_hi(u1));
    }
    __syncwarp();
    release(c, c.p.stage);
    pipe_next(c.p);
}

#define TSTAMP(i)
__device__ __forceinline__ float2 cmul(float2 a, float2 b) { return make_float2(fmaf(a.x, b.x, -a.y * b.y), fmaf(a.x, b.y, a.y * b.x)); }
__device__ __forceinline__ float2 cfma(float2 a, float2 b, float2 u) { return make_float2(fmaf(a.x, b.x, fmaf(-a.y, b.y, u.x)), fmaf(a.x, b.y, fmaf(a.y, b.x, u.y))); }
__device__ __forceinline__ float4 ssm_coef(float lre, float lim, float logdt) {
    const float dt = __bfloat162float(__float2bfloat16(expf(logdt)));
    const float ea = expf(dt * lre);
    float sn, cn;
    sincosf(dt * lim, &sn, &cn);
    const float br = ea * cn, bi = ea * sn, nr = br - 1.f;
    float cr, ci;
    if (fabsf(lre) >= fabsf(lim)) { const float r = lim / lre, dn = lre + lim * r; cr = (nr + bi * r) / dn; ci = (bi - nr * r) / dn; }
    else { const float r = lre / lim, dn = lre * r + lim; cr = (nr * r + bi) / dn; ci = (bi * r - nr) / dn; }
    return make_float4(br, bi, cr, ci);
}
__device__ __forceinline__ void epi_a1(const float* acc, const Params& P, const Cons& c, Pend& d, int mb, int nb, uint32_t atag) {
    const int t = c.lane & 3;
    const int p = nb * 128 + c.rank * 64 + c.wg * 32 + c.wq * 8 + (c.lane >> 2);
    const float4 cf = __ldcg(&g_coef[p]);
    TSTAMP(1)
    const float2 lam = make_float2(cf.x, P.swap_ri ? -cf.y : cf.y);
    const float a0 = P.swap_ri ? -2.f * cf.w : 2.f * cf.z, a1 = P.swap_ri ? 2.f * cf.z : -2.f * cf.w;
    const float b0 = P.swap_ri ? -2.f * cf.z : -2.f * cf.w, b1 = P.swap_ri ? -2.f * cf.w : -2.f * cf.z;
    float2 h = make_float2(0.f, 0.f);
#pragma unroll
    for (int round = 0; round < 2; round++) {
#pragma unroll
        for (int j = 0; j < 32; j++) {
            h = cfma(lam, h, make_float2(acc[j * 4], acc[j * 4 + 2]));
            const float r0 = fmaf(a0, h.x, a1 * h.y), m0 = fmaf(b0, h.x, b1 * h.y);
            h = cfma(lam, h, make_float2(acc[j * 4 + 1], acc[j * 4 + 3]));
            d.pk[j * 2] = pack2(r0, fmaf(a0, h.x, a1 * h.y));
            d.pk[j * 2 + 1] = pack2(m0, fmaf(b0, h.x, b1 * h.y));
        }
        if (round) break;
        float2 l64 = lam;
#pragma unroll
        for (int i = 0; i < 6; i++) l64 = cmul(l64, l64);
        const float2 l128 = cmul(l64, l64), l256 = cmul(l128, l128);
        float2 o = make_float2(__shfl_up_sync(0xffffffffu, h.x, 1), __shfl_up_sync(0xffffffffu, h.y, 1));
        if (t >= 1) h = cfma(l64, o, h);
        o = make_float2(__shfl_up_sync(0xffffffffu, h.x, 2), __shfl_up_sync(0xffffffffu, h.y, 2));
        if (t >= 2) h = cfma(l128, o, h);
        TSTAMP(2)
        if (t == 3) st_relaxed2(&g_agg[mb * 1024 + p], (__float_as_uint(h.x) & ~1u) | atag, __float_as_uint(h.y));
        h = make_float2(__shfl_up_sync(0xffffffffu, h.x, 1), __shfl_up_sync(0xffffffffu, h.y, 1));
        if (t == 0) h = make_float2(0.f, 0.f);
        uint32_t ax[7], ay[7];
        int n = 0;
        while (true) {
            uint32_t bad = 0;
#pragma unroll
            for (int j = 0; j < 7; j++) { ax[j] = atag; ay[j] = 0; ld_relaxed2_if(ax[j], ay[j], &g_agg[j * 1024 + p], j < mb); }
#pragma unroll
            for (int j = 0; j < 7; j++) bad |= ax[j] ^ atag;
            if (tags_ok(bad)) break;
            __nanosleep(400);
            if (++n > SPIN_LIMIT) spin_fault();
        }
        float2 carry = make_float2(0.f, 0.f);
#pragma unroll
        for (int j = 0; j < 7; j++) if (j < mb) carry = cfma(l256, carry, make_float2(__uint_as_float(ax[j]), __uint_as_float(ay[j])));
        float2 w = (t & 1) ? l64 : make_float2(1.f, 0.f);
        if (t & 2) w = cmul(w, l128);
        h = cfma(w, carry, h);
        TSTAMP(3)
    }
    TSTAMP(4)
    d.kind = PEND_HT; d.row = nb * 128 + c.rank * 64 + c.wg * 32; d.col = mb * 256; d.cnt = C_HT + mb;
}

__device__ __forceinline__ uint32_t acquire_stage(uint32_t sb, Pipe& p, uint32_t bytes) {
    mbar_wait(sb + B_EMPTY + p.stage * 8, p.phase ^ 1);
    mbar_expect_e(sb + B_FULL + p.stage * 8, bytes);
    return p.stage;
}
__device__ __forceinline__ void producer(const Params& P, const uint32_t sb, const int cta, const uint32_t epoch) {
    Pipe p = {0, 0};
    const uint32_t e1 = epoch + 1;
    const int rank = cta & 1;
    const uint16_t both = 3 << (__shfl_sync(0xffffffffu, cluster_rank(), 0) & ~1u);
    for (int it = ITEM_OFF(cta >> 1); it < ITEM_OFF((cta >> 1) + 1); it++) {
        const int item = ITEM(it), type = (item >> 8) & 7, mb = (item >> 5) & 7, nb = item & 31;
        if (type == T_CHAIN) {
            const int h = cta / 3, role = cta - h * 3;
            uint32_t* flag = &g_cnt(C_FLAG + (role == 2 ? 32 : 0) + h);
            if (role) { wait_count(&g_cnt(C_KV), e1 * 128); fence_async(); }
#pragma unroll 1
            for (int s = 0; s < 64 && role != 0; s++) {
                if (s < 63) {
                    mbar_wait(sb + B_GO, s & 1);
                    tma3d_mc_e(sb + S_KV + (role - 1) * 8192, &P.tm[M_SEG], 0, (role - 1) * 2048 + s * 32, h * 2, sb + B_KVFULL, 7 << ((h & 1) * 3));
                    if ((s & 7) == 7) { wait_count(&g_cnt(C_KV + 1 + (s >> 3)), e1 * 128); fence_async(); }
                    tma_prefetch3d_e(&P.tm[M_SEG], 0, (role - 1) * 2048 + s * 32 + 32, h * 2);
                }
                if (s > 0 && ((s & 3) == 0 || s == 63)) {
                    const int i = (s - 1) >> 2;
                    mbar_wait(sb + B_PERS, i & 1);
                    asm volatile("{\n.reg .pred E;\nelect.sync _|E, 0xffffffff;\n@E st.release.gpu.global.u32 [%0], %1;\n}" ::"l"(flag), "r"(epoch * 64 + i * 4 + 4) : "memory");
                }
            }
            mbar_wait(sb + B_RESUME, 0);
            continue;
        }
        const int m0 = mb * 256 + rank * 128;
        if (type <= T_OP) {
            const CUtensorMap* ma = &P.tm[type == T_OP ? M_OA : M_BX];
            const CUtensorMap* mw = &P.tm[type == T_OP ? M_WO : type == T_QA ? M_WQ : nb < 16 ? M_WK : M_WV];
            const int nk = type == T_OP ? 64 : 16, nc = (nb & 15) * 4 + rank * 2, ma0 = type == T_OP ? 4096 + m0 : m0;
            if (type == T_OP) { wait_count(&g_cnt(C_O + mb), e1 * 64); fence_async(); }
            if (type == T_QA) {
                wait_count(&g_cnt(C_KV + mb), e1 * 128);
                fence_async();
            }
#pragma unroll 1
            for (int kt = 0; kt < nk; kt++) {
                const uint32_t st = acquire_stage(sb, p, STAGE), bar = sb + B_FULL + st * 8;
                tma2d_e(sb + st * STAGE, ma, kt * 64, ma0, bar);
                tma3d_mc_e(sb + st * STAGE + 16384 + rank * 16384, mw, 0, kt * 64, nc, bar, both);
                if (type == T_QA && kt < 8) tma_prefetch2d_e(&P.tm[M_OA], nb * 256 + (kt & 3) * 64, (kt >> 2) * 2048 + m0);
                pipe_next(p);
            }
            if (type == T_QA) {
                const uint32_t need = epoch * 64 + mb * 8 + rank * 4 + 4;
#pragma unroll 1
                for (int i = 0; i < 4; i++) wait_count(&g_cnt(C_FLAG + (i >> 1) * 32 + nb * 2 + (i & 1)), need);
                fence_async();
#pragma unroll 1
                for (int e = 0; e < 4; e++) {
                    const uint32_t st = acquire_stage(sb, p, 40960), bar = sb + B_FULL + st * 8, dst = sb + st * STAGE;
                    tma2d_e(dst, &P.tm[M_OA], nb * 256 + (e & 1) * 128, (e >> 1) * 2048 + m0, bar);
                    tma2d_e(dst + 16384, &P.tm[M_OA], nb * 256 + (e & 1) * 128 + 64, (e >> 1) * 2048 + m0, bar);
                    const uint32_t* src = ((e >> 1) ? g_vmt : g_km) + ((mb * 8 + rank * 4) * 32 + nb * 2 + (e & 1)) * 512;
#pragma unroll 1
                    for (int i = 0; i < 4; i++) bulk_g2s_e(dst + 32768 + i * 2048, src + i * 32 * 512, 2048, bar);
                    pipe_next(p);
                }
            }
        } else if (type == T_OPH) {
            wait_count(&g_cnt(C_O + mb), e1 * 64);
            fence_async();
#pragma unroll 1
            for (int kt = 0; kt < 64; kt++) {
                const uint32_t st = acquire_stage(sb, p, 32768), bar = sb + B_FULL + st * 8;
                tma2d_e(sb + st * STAGE, &P.tm[M_OA], kt * 64, 4096 + m0, bar);
                tma2d_mc_e(sb + st * STAGE + 16384 + rank * 8192, &P.tm[M_WOH], nb * 128 + rank * 64, kt * 64, bar, both);
                pipe_next(p);
            }
        } else if (type == T_A1) {
            wait_count(&g_cnt(C_COEF), e1 * 4);
#pragma unroll 1
            for (int kt = 0; kt < 16; kt++) {
                const uint32_t st = acquire_stage(sb, p, STAGE), bar = sb + B_FULL + st * 8;
                tma4d_e(sb + st * STAGE, &P.tm[M_AB], kt * 64, nb * 16 + rank * 8, bar);
                tma4d_mc_e(sb + st * STAGE + 16384 + rank * 16384, &P.tm[M_AX], kt * 64, mb * 128 + rank * 16, bar, both);
                pipe_next(p);
            }
        } else {
            wait_count(&g_cnt(C_HT + mb), e1 * 32);
            fence_async();
            const int hw = type == T_A2H ? 64 : 128;
            const CUtensorMap* mc = &P.tm[type == T_A2H ? M_CREH : M_CRE];
#pragma unroll 1
            for (int kt = 0; kt < 32; kt++) {
                const uint32_t st = acquire_stage(sb, p, 16384 + hw * 256), bar = sb + B_FULL + st * 8;
                tma3d_e(sb + st * STAGE, &P.tm[M_HT], 0, kt * 64, mb * 4 + rank * 2, bar);
                tma2d_mc_e(sb + st * STAGE + 16384 + rank * hw * 128, mc + (kt >> 4), (kt & 15) * 64, (nb * 2 + rank) * hw, bar, both);
                pipe_next(p);
            }
#pragma unroll 1
            for (int col = nb * 2 * hw; col < (nb + 1) * 2 * hw; col += 128) {
                const uint32_t st = acquire_stage(sb, p, 32768 + 256), bar = sb + B_FULL + st * 8;
                tma4d_e(sb + st * STAGE, &P.tm[M_AX], col, mb * 128 + rank * 16, bar);
                tma4d_e(sb + st * STAGE + 16384, &P.tm[M_AX], col + 64, mb * 128 + rank * 16, bar);
                bulk_g2s_e(sb + st * STAGE + 32768, P.Dskip + col, 256, bar);
                pipe_next(p);
            }
        }
    }
}

__device__ __forceinline__ uint32_t fresh_tid() { uint32_t t; asm volatile("mov.u32 %0, %%tid.x;" : "=r"(t)); return t; }
__device__ __forceinline__ uint32_t fresh_ctaid() { uint32_t t; asm volatile("mov.u32 %0, %%ctaid.x;" : "=r"(t)); return t; }
__device__ __forceinline__ void reset_state(const Params& P, Cons& c, Pend& d, uint32_t sb, bool resumed) {
    const uint32_t t = fresh_tid(), b = fresh_ctaid() + P.cta0;
    const int w = __shfl_sync(0xffffffffu, t >> 5, 0);
    c.sb = sb; c.wg = w >> 2; c.wq = w & 3; c.lane = t & 31;
    c.rank = __shfl_sync(0xffffffffu, b & 1, 0); c.pair = __shfl_sync(0xffffffffu, b >> 1, 0);
    c.rel = mapa(sb + B_EMPTY, cluster_rank() ^ (c.lane & 1));
    c.atag = (ld_acquire(&g_cnt(C_EPOCH)) + 1) & 1;
    c.p.stage = 0; c.p.phase = 0;
    c.nst = resumed && c.pair < NCHAIN ? 2 : 0;
    d = Pend{};
}
#define PROF_ITEM(i, item)

__global__ void __launch_bounds__(384, 1) fused_kernel(const __grid_constant__ Params P) {
    extern __shared__ __align__(1024) uint8_t smem[];
    const uint32_t sb = smem_u32(smem);
    asm volatile("griddepcontrol.launch_dependents;");
    declare_fence(P.zero);
    const int tid = threadIdx.x, lane = tid & 31;
    const int warp = __shfl_sync(0xffffffffu, tid >> 5, 0);
    const int cta = __shfl_sync(0xffffffffu, blockIdx.x + P.cta0, 0), pair = cta >> 1, rank = cta & 1;
    if (tid == 0) {
        if (sb & 1023) spin_fault();
        for (int i = 0; i < NSTAGE; i++) { mbar_init(sb + B_FULL + i * 8, 1); mbar_init(sb + B_EMPTY + i * 8, 16); }
        mbar_init(sb + B_RESUME, 2);
        mbar_init(sb + B_KVFULL, 1); mbar_init(sb + B_MAP, 1);
        mbar_init(sb + B_GO, 3); mbar_init(sb + B_RED, cta % 3 == 2 ? 2 : 3); mbar_init(sb + B_PERS, 8); mbar_init(sb + B_INIT, 8);
        mbar_init(sb + B_READY, 8);
        for (int i = 0; i < 2; i++) { mbar_init(sb + B_SFULL + i * 8, 4); mbar_init(sb + B_SFREE + i * 8, 1); }
        mbar_init(sb + B_RELM, 1); mbar_init(sb + B_X, 9); mbar_init(sb + B_RELO, 1);
        asm volatile("fence.mbarrier_init.release.cluster;" ::: "memory");
        mbar_expect(sb + B_X, 4096);
    }
    cluster_sync();
    if (warp >= 8) {
        asm volatile("setmaxnreg.dec.sync.aligned.u32 24;");
        if (warp == 8) {
            producer(P, sb, cta, __shfl_sync(0xffffffffu, ld_acquire(&g_cnt(C_EPOCH)), 0));
            asm volatile("barrier.cluster.arrive.relaxed.aligned;\nbarrier.cluster.wait.aligned;" ::: "memory");
        } else if (warp == 9) {
            if (pair < 64) l2_prefetch((const char*)(rank ? P.Wo : P.Wq) + (size_t)(pair * 32 + lane) * 4096, 4096);
            if (pair < NCHAIN) pacer(P, sb, cta, lane, __shfl_sync(0xffffffffu, ld_acquire(&g_cnt(C_EPOCH)), 0));
        } else {
            store_warp(P, sb, warp - 10);
        }
    } else {
        asm volatile("setmaxnreg.inc.sync.aligned.u32 240;");
        Cons c;
        Pend d;
        if (pair < NCHAIN) {
            reset_state(P, c, d, sb, false);
            {
                const int item = ITEM(ITEM_OFF(pair));
                PROF_ITEM(0, item)
                float acc[128];
                mainloop<256, true>(acc, P, c, d, T_KV);
                epi_kv(acc, c, d, (item >> 5) & 7, item & 31);
            }
            ISTAMP(4)
            bar_sync(1, 256);
            chain_load(P, sb, cta, warp, lane, 0);
            ISTAMP(9)
            drain<0, true>(P, c, d);
            drain<1, true>(P, c, d);
            ISTAMP(10)
            staging_wait(c);
            ISTAMP(11)
            PROF_ITEM(1, T_CHAIN << 8)
            const uint32_t epoch = __shfl_sync(0xffffffffu, ld_acquire(&g_cnt(C_EPOCH)), 0);
            if (warp < 4) chain_role<false>(P, sb, cta, warp, lane, epoch);
            else chain_role<true>(P, sb, cta, warp, lane, epoch);
            fence_async_smem();
            bar_sync(1, 256);
            const uint32_t t2 = fresh_tid();
            if (t2 < 2) mbar_arrive_cluster(mapa(sb + B_RESUME, cluster_rank() ^ t2));
        } else if (pair >= NPAIR - 2) {
            const int ch = (pair - (NPAIR - 2)) * 512 + rank * 256 + tid;
            g_coef[ch] = ssm_coef(__bfloat162float(P.Lre[ch]), __bfloat162float(P.Lim[ch]), __bfloat162float(P.logdt[ch]));
            bar_sync(1, 256);
            if (tid == 0) red_release(&g_cnt(C_COEF));
        }
        reset_state(P, c, d, sb, true);
        for (int it = ITEM_OFF(c.pair) + (c.pair < NCHAIN ? 2 : 0);; it++) {
            const bool last = it == ITEM_OFF(c.pair + 1);
            if (d.kind != PEND_NONE && (last || !bar_and(5 + c.wg, mbar_try(sb + B_FULL + c.p.stage * 8, c.p.phase)))) drain_all(P, c, d);
            if (last) break;
            const int item = ITEM(it), type = (item >> 8) & 7, mb = (item >> 5) & 7, nb = item & 31;
            PROF_ITEM(it - ITEM_OFF(c.pair), item)
            if (type >= T_OPH) {
                float acc[64];
                mainloop<128>(acc, P, c, d, type);
                if (type == T_OPH) epi_oph(acc, c, d, mb, nb);
                else epi_a2_half<0>(acc, P, c, mb, nb * 128);
            } else {
                float acc[128];
                mainloop<256>(acc, P, c, d, type);
                if (type == T_KV) epi_kv(acc, c, d, mb, nb);
                else if (type == T_QA) epi_qa(acc, c, d, mb, nb);
                else if (type == T_OP) epi_op(acc, c, d, mb, nb);
                else if (type == T_A1) epi_a1(acc, P, c, d, mb, nb, c.atag);
                else { epi_a2_half<0>(acc, P, c, mb, nb * 256); epi_a2_half<1>(acc, P, c, mb, nb * 256); }
                if (item & URGENT) drain_all(P, c, d);
            }
        }
        staging_wait(c);
        staging_post(c, PEND_NONE, 0, 0, 0);
        cluster_sync();
        if (c.wg == 0 && c.wq == 0 && c.lane == 0 && atomicInc(&g_cnt(C_DONE), NPAIR * 2 - 1) == NPAIR * 2 - 1) { __threadfence(); atomicAdd(&g_cnt(C_EPOCH), 1); }
    }
}

typedef CUresult (*EncodeFn)(CUtensorMap*, CUtensorMapDataType, cuuint32_t, void*, const cuuint64_t*, const cuuint64_t*, const cuuint32_t*, const cuuint32_t*,
                             CUtensorMapInterleave, CUtensorMapSwizzle, CUtensorMapL2promotion, CUtensorMapFloatOOBfill);
void encode(EncodeFn fn, CUtensorMap* m, const void* base, int rank, const uint64_t* dims, const uint64_t* strides, const uint32_t* box, CUtensorMapSwizzle swz = CU_TENSOR_MAP_SWIZZLE_128B) {
    cuuint64_t d[5], s[5]; cuuint32_t b[5], e[5];
    for (int i = 0; i < rank; i++) { d[i] = dims[i]; b[i] = box[i]; e[i] = 1; if (i) s[i - 1] = strides[i - 1]; }
    fn(m, CU_TENSOR_MAP_DATA_TYPE_BFLOAT16, rank, (void*)base, d, s, b, e, CU_TENSOR_MAP_INTERLEAVE_NONE, swz,
       CU_TENSOR_MAP_L2_PROMOTION_L2_256B, CU_TENSOR_MAP_FLOAT_OOB_FILL_NONE);
}
void map_kmajor(EncodeFn fn, CUtensorMap* m, const void* base, uint64_t rows, uint64_t cols, uint32_t box_rows) {
    const uint64_t d[2] = {cols, rows}, s[1] = {cols * 2}; const uint32_t b[2] = {64, box_rows};
    encode(fn, m, base, 2, d, s, b);
}
void map_mnmajor(EncodeFn fn, CUtensorMap* m, const void* base, uint64_t krows, uint64_t cols) {
    const uint64_t d[3] = {64, krows, cols / 64}, s[2] = {cols * 2, 128}; const uint32_t b[3] = {64, 64, 2};
    encode(fn, m, base, 3, d, s, b);
}

}

extern "C" void kernel_launch(void* const* d_in, const int* in_sizes, int n_in, void* d_out, int out_size) {
    static Params P;
    static EncodeFn fn = nullptr;
    if (!fn) {
        cudaDriverEntryPointQueryResult q;
        cudaGetDriverEntryPoint("cuTensorMapEncodeTiled", (void**)&fn, cudaEnableDefault, &q);
        cudaFuncSetAttribute(fused_kernel, cudaFuncAttributeMaxDynamicSharedMemorySize, S_TOTAL);
    }
    const bf16* in[15];
    for (int i = 0; i < 15; i++) in[i] = (const bf16*)d_in[i];
    void *kvo, *ht;
    cudaGetSymbolAddress(&kvo, g_kvo);
    cudaGetSymbolAddress(&ht, g_ht);
    map_kmajor(fn, &P.tm[M_BX], in[9], 2048, 1024, 128);
    map_mnmajor(fn, &P.tm[M_WQ], in[11], 1024, 4096);
    map_mnmajor(fn, &P.tm[M_WK], in[12], 1024, 4096);
    map_mnmajor(fn, &P.tm[M_WV], in[13], 1024, 4096);
    map_mnmajor(fn, &P.tm[M_WO], in[14], 4096, 1024);
    map_kmajor(fn, &P.tm[M_OA], kvo, 3 * 2048, 4096, 128);
    P.swap_ri = in[4] < in[3];
    {
        const bf16* lo = P.swap_ri ? in[4] : in[3];
        const uint64_t diff = (uint64_t)((const char*)(P.swap_ri ? in[3] : in[4]) - (const char*)lo);
        const uint64_t d[4] = {1024, 8, 2, 128}, s[3] = {2048, diff, 16384}; const uint32_t b[4] = {64, 8, 2, 8};
        encode(fn, &P.tm[M_AB], lo, 4, d, s, b);
    }
    {
        const uint64_t d[4] = {1024, 2, 4, 1024}, s[3] = {2048, 64 * 2048, 4096}; const uint32_t b[4] = {64, 2, 4, 16};
        encode(fn, &P.tm[M_AX], in[0], 4, d, s, b);
    }
    map_mnmajor(fn, &P.tm[M_HT], ht, 2048, 2048);
    map_kmajor(fn, &P.tm[M_CRE], in[5], 1024, 1024, 128);
    map_kmajor(fn, &P.tm[M_CIM], in[6], 1024, 1024, 128);
    map_kmajor(fn, &P.tm[M_KVO], kvo, 3 * 2048, 4096, 32);
    map_kmajor(fn, &P.tm[M_HTS], ht, 2048, 2048, 32);
    map_kmajor(fn, &P.tm[M_WOH], in[14], 4096, 1024, 64);
    map_kmajor(fn, &P.tm[M_CREH], in[5], 1024, 1024, 64);
    map_kmajor(fn, &P.tm[M_CIMH], in[6], 1024, 1024, 64);
    for (int i = 0; i < 6; i++) {
        const uint64_t d[3] = {64, 1024, 64}, s[2] = {8192, 128}; const uint32_t b[3] = {64, i < 3 ? 48u : 80u, 2};
        encode(fn, &P.tm[M_C3 + i], in[11 + i % 3], 3, d, s, b);
    }
    {
        const uint64_t d[2] = {1024, 4096}, s[1] = {2048}; const uint32_t b[2] = {32, 64};
        encode(fn, &P.tm[M_CO], in[14], 2, d, s, b, CU_TENSOR_MAP_SWIZZLE_64B);
    }
    {
        const uint64_t d[3] = {64, 3 * 2048, 64}, s[2] = {8192, 128}; const uint32_t b[3] = {64, 32, 2};
        encode(fn, &P.tm[M_SEG], kvo, 3, d, s, b);
    }
    void* xs;
    cudaGetSymbolAddress(&xs, g_x);
    P.xb = (uint8_t*)(((uintptr_t)xs + (2u << 20) - 1) & ~(uintptr_t)((2u << 20) - 1));
    P.Wq = in[11]; P.Wk = in[12]; P.Wv = in[13]; P.Wo = in[14]; P.mem0 = in[10];
    P.Ax = in[0]; P.Lre = in[1]; P.Lim = in[2]; P.logdt = in[7]; P.Dskip = in[8];
    P.out = (float*)d_out;
    int pv[10] = {2200, 480, 48, 16, 100, 30, 32, 300, 0, 0};
    for (int i = 0; i < 2; i++) { P.dly[i] = pv[i]; P.mrg[i] = pv[2 + i]; }
    P.rd = pv[4]; P.guard = pv[5]; P.clampv = pv[6]; P.clamp0 = pv[7]; P.kvd = pv[9];
    cudaLaunchConfig_t cfg = {};
    cudaLaunchAttribute at[2];
    cfg.blockDim = dim3(384); cfg.dynamicSmemBytes = S_TOTAL; cfg.stream = cudaStreamPerThread; cfg.attrs = at;
    at[0].id = cudaLaunchAttributeClusterDimension;
    at[0].val.clusterDim.y = at[0].val.clusterDim.z = 1;
    at[1].id = cudaLaunchAttributeProgrammaticStreamSerialization;
    at[1].val.programmaticStreamSerializationAllowed = 1;
    for (int i = 0; i < 2; i++) {
        P.cta0 = i ? 2 * NCHAIN : 0;
        cfg.gridDim = dim3(i ? 2 * (NPAIR - NCHAIN) : 2 * NCHAIN);
        at[0].val.clusterDim.x = i ? 2 : 6;
        cfg.numAttrs = 1 + i;
        cudaLaunchKernelEx(&cfg, fused_kernel, P);
    }
}
```

```cpp
#include <cuda_runtime.h>
#include <cuda_bf16.h>
#include <cuda.h>
#include <stdint.h>
#include <string.h>

typedef __nv_bfloat16 bf16;

namespace {

constexpr int SPIN_LIMIT = 1 << 22;
constexpr int NPAIR = 66;
constexpr int NCHAIN = 48;
enum { T_KV = 0, T_QA = 1, T_OP = 2, T_A1 = 3, T_A2 = 4, T_CHAIN = 5, T_OPH = 6, T_A2H = 7 };
constexpr int URGENT = 2048;
enum { M_BX = 0, M_WQ, M_WK, M_WV, M_WO, M_OA, M_AB, M_AX, M_HT, M_CRE, M_CIM, M_KVO, M_HTS, M_WOH, M_CREH, M_CIMH, M_C1, M_CO = M_C1 + 3, M_SEG, M_COUNT };
enum { C_KV = 0, C_O = 8, C_HT = 16, C_DONE = 24, C_EPOCH = 25, C_COEF = 26, C_XMAX = 27, C_XCNT = 28, C_FLAG = 32 };

struct Params {
    CUtensorMap tm[M_COUNT];
    const bf16 *Wq, *Wk, *Wv, *Wo, *mem0, *Bx, *Ax, *Lre, *Lim, *logdt, *Dskip;
    float* out;
    uint8_t* xb;
    int swap_ri, zero;
    int dly, mrg, rd, guard, clampv, clamp0, kvd, zd;
    uint16_t cta0;
};

__constant__ uint16_t c_off[67] = {0, 5, 10, 15, 20, 25, 30, 35, 40, 45, 50, 55, 60, 65, 70, 75, 80, 85, 90, 95, 100, 105, 110, 115, 120, 125, 130, 135, 140, 145, 150, 155, 160, 165, 170, 175, 180, 185, 190, 195, 200, 205, 210, 214, 218, 222, 226, 230, 234, 253, 272, 291, 310, 329, 348, 367, 386, 405, 424, 443, 462, 481, 500, 519, 537, 556, 574};
__constant__ uint16_t c_items[640] = {
    0, 1280, 2497, 3008, 1728, 1, 1280, 2498, 3009, 1729, 2, 1280, 2499, 3010, 1730, 32, 1280, 2500, 3011, 1731, 33, 1280, 2501, 3012,
    1732, 34, 1280, 2502, 3013, 1733, 3, 1280, 2503, 3014, 1734, 4, 1280, 2504, 3015, 1735, 5, 1280, 2505, 3040, 1760, 35, 1280, 2506,
    3041, 1761, 36, 1280, 2507, 3042, 1762, 37, 1280, 2508, 3043, 1763, 6, 1280, 2509, 3044, 1764, 7, 1280, 2510, 3045, 1765, 8, 1280,
    2511, 3046, 1766, 38, 1280, 2528, 3047, 1767, 39, 1280, 2529, 2886, 1024, 40, 1280, 2530, 2887, 1025, 9, 1280, 2531, 2912, 1026, 10,
    1280, 2532, 2913, 1027, 11, 1280, 2533, 2914, 1056, 41, 1280, 2534, 2915, 1057, 42, 1280, 2535, 2916, 1058, 43, 1280, 2536, 2917, 1059,
    12, 1280, 2537, 2918, 1088, 13, 1280, 2538, 2919, 1089, 14, 1280, 2539, 2944, 1090, 44, 1280, 2540, 2945, 1091, 45, 1280, 2541, 2946,
    1120, 46, 1280, 2542, 2947, 1121, 15, 1280, 2543, 2948, 1122, 16, 1280, 2821, 2949, 1123, 17, 1280, 2822, 2950, 1152, 47, 1280, 2823,
    2951, 1153, 48, 1280, 2848, 2976, 1154, 49, 1280, 2849, 2977, 1155, 18, 1280, 2850, 2978, 1184, 19, 1280, 2851, 2979, 1185, 20, 1280,
    2852, 2980, 1186, 50, 1280, 2853, 2981, 1187, 51, 1280, 2854, 2982, 1216, 52, 1280, 2855, 2983, 1217, 21, 1280, 2885, 642, 22, 1280,
    2884, 643, 23, 1280, 2883, 672, 53, 1280, 2882, 673, 54, 1280, 2881, 674, 55, 1280, 2880, 675, 24, 66, 84, 102, 256, 124,
    142, 160, 175, 191, 207, 224, 239, 298, 332, 366, 416, 2817, 610, 56, 67, 85, 103, 257, 125, 143, 161, 176, 192, 208,
    225, 240, 299, 333, 367, 417, 2818, 611, 25, 68, 86, 104, 258, 126, 144, 162, 177, 193, 209, 226, 241, 300, 334, 384,
    418, 2819, 640, 57, 69, 87, 105, 259, 127, 145, 163, 178, 194, 210, 227, 242, 301, 335, 385, 419, 2820, 641, 26, 70,
    88, 106, 260, 128, 146, 164, 179, 195, 211, 228, 243, 302, 352, 386, 420, 512, 1988, 58, 71, 89, 107, 261, 129, 147,
    165, 180, 196, 212, 229, 244, 303, 353, 387, 421, 513, 1989, 27, 72, 90, 108, 262, 130, 148, 166, 181, 197, 213, 230,
    245, 320, 354, 388, 422, 514, 1990, 59, 73, 91, 109, 263, 131, 149, 167, 182, 198, 214, 231, 246, 321, 355, 389, 423,
    515, 1991, 28, 74, 92, 110, 264, 132, 150, 168, 183, 199, 215, 232, 247, 322, 356, 390, 424, 544, 2016, 60, 75, 93,
    111, 265, 133, 151, 169, 184, 200, 216, 233, 248, 323, 357, 391, 425, 545, 2017, 29, 76, 94, 112, 266, 134, 152, 170,
    185, 201, 217, 234, 249, 324, 358, 392, 426, 546, 2018, 61, 77, 95, 113, 267, 135, 153, 171, 186, 202, 218, 235, 250,
    325, 359, 393, 427, 547, 2019, 30, 78, 96, 114, 268, 136, 154, 172, 187, 203, 219, 236, 251, 326, 360, 394, 428, 576,
    2020, 62, 79, 97, 115, 269, 137, 155, 173, 188, 204, 220, 237, 252, 327, 361, 395, 429, 577, 2021, 31, 80, 98, 116,
    270, 138, 156, 174, 189, 205, 221, 238, 253, 328, 362, 396, 430, 578, 2022, 63, 81, 99, 117, 271, 139, 157, 288, 190,
    292, 293, 296, 297, 331, 365, 399, 2816, 609, 64, 82, 100, 118, 120, 122, 140, 158, 289, 206, 222, 294, 254, 329, 363,
    397, 431, 579, 2023, 65, 83, 101, 119, 121, 123, 141, 159, 290, 291, 223, 295, 255, 330, 364, 398, 2496, 608,
};
#define ITEM_OFF(p) c_off[p]
#define ITEM(i) c_items[i]

__device__ __align__(1024) bf16 g_kvo[3 * 2048 * 4096];
__device__ __align__(1024) bf16 g_ht[2048 * 2048];
__device__ __align__(1024) uint8_t g_x[4 << 20];
__device__ __align__(1024) uint32_t g_km[64 * 32 * 512];
__device__ __align__(1024) uint32_t g_vmt[64 * 32 * 512];
__device__ __align__(1024) float2 g_agg[8 * 1024];
__device__ __align__(1024) float4 g_coef[1024];
__device__ __align__(1024) uint32_t g_cntl[128 * 32];
#define g_cnt(i) g_cntl[(i) * 32]
__device__ __align__(1024) uint32_t g_hint[96 * 32];
#define PROF(i)
#define PROFDUMP()
#define PROFP(i)
constexpr int XG_SIDE = 65536, XG_T = 98304;
__device__ __forceinline__ uint32_t xg_buf(int b) { return (b & 1) * 128 + (b & 2) * 256 + (b & 4) * 32768; }
__device__ __forceinline__ uint32_t xg_lane(uint32_t lane) { return (lane >> 4) * 1024 + (lane & 8) * 32 + (lane & 7) * 16; }
__device__ __forceinline__ uint32_t xg_side(int b) { return XG_SIDE + (b >> 1) * 1024 + (b & 1) * 256; }

constexpr int STAGE = 49152, NSTAGE = 4;
constexpr int S_STG = NSTAGE * STAGE;
constexpr int S_BAR = S_STG + 32768;
constexpr int B_FULL = S_BAR, B_EMPTY = S_BAR + 32, B_RESUME = S_BAR + 64, B_KVFULL = S_BAR + 72, B_GO = S_BAR + 88, B_X = S_BAR + 96, B_PERS = S_BAR + 104,
              B_INIT = S_BAR + 112, B_RELM = S_BAR + 120, B_READY = S_BAR + 136, B_SFULL = S_BAR + 144, B_SFREE = S_BAR + 160, S_DESC = S_BAR + 176, B_RED = S_BAR + 216;
constexpr int S_EV = S_BAR + 80, S_EO = S_BAR + 84, B_INIT2 = S_BAR + 128, S_SC = S_BAR + 208, S_ISC = S_EV;
constexpr int S_XV = S_BAR + 256, S_LOG = S_XV + 2048;
constexpr int S_TOTAL = S_LOG + 768;
#define NRA 5
#define NRB 3
constexpr int S_W1 = 0;
constexpr int S_W2 = 4 * 4096 * (16 - NRA - NRB);
constexpr int S_KV = 188416;
constexpr int S_P1 = S_KV + 16384;
constexpr int S_X = S_P1 + 16384;
constexpr int S_SX = S_P1, S_OX = S_P1 + 2048;
constexpr int S_EM = S_X + 4096, S_TO = S_EM + 1024, S_RETRY = S_BAR + 224, B_P1 = S_BAR + 232;
static_assert(S_TO + 32 <= S_BAR && S_KV % 1024 == 0 && S_TOTAL <= 232448, "chain smem layout");

template <int V> struct IC { static constexpr int value = V; };
template <int B, int E, typename F> __device__ __forceinline__ void static_for(F&& f) { if constexpr (B < E) { f(IC<B>{}); static_for<B + 1, E>(f); } }
__device__ __forceinline__ uint32_t cluster_rank() { uint32_t r; asm volatile("mov.u32 %0, %%cluster_ctarank;" : "=r"(r)); return r; }
__device__ __forceinline__ void spin_fault() { asm volatile("st.global.u32 [%0], 0;" ::"l"(0ull) : "memory"); }
__device__ __forceinline__ uint32_t smem_u32(const void* p) { return (uint32_t)__cvta_generic_to_shared(p); }
__device__ __forceinline__ uint32_t opq(uint32_t x, int lane) { return __shfl_sync(0xffffffffu, x, lane); }
__device__ __forceinline__ uint32_t mapa(uint32_t a, uint32_t r) { uint32_t d; asm volatile("mapa.shared::cluster.u32 %0, %1, %2;" : "=r"(d) : "r"(a), "r"(r)); return d; }
__device__ __forceinline__ void mma16816(float* d, uint32_t a0, uint32_t a1, uint32_t a2, uint32_t a3, uint32_t b0, uint32_t b1) {
    asm("mma.sync.aligned.m16n8k16.row.col.f32.bf16.bf16.f32 {%0,%1,%2,%3}, {%4,%5,%6,%7}, {%8,%9}, {%0,%1,%2,%3};"
        : "+f"(d[0]), "+f"(d[1]), "+f"(d[2]), "+f"(d[3]) : "r"(a0), "r"(a1), "r"(a2), "r"(a3), "r"(b0), "r"(b1));
}
__device__ __forceinline__ void mma1688(float* d, uint32_t a0, uint32_t a1, uint32_t b0) {
    asm("mma.sync.aligned.m16n8k8.row.col.f32.bf16.bf16.f32 {%0,%1,%2,%3}, {%4,%5}, {%6}, {%0,%1,%2,%3};"
        : "+f"(d[0]), "+f"(d[1]), "+f"(d[2]), "+f"(d[3]) : "r"(a0), "r"(a1), "r"(b0));
}
__device__ __forceinline__ void ldsm4(uint32_t* r, uint32_t a) {
    asm volatile("ldmatrix.sync.aligned.m8n8.x4.shared.b16 {%0,%1,%2,%3}, [%4];" : "=r"(r[0]), "=r"(r[1]), "=r"(r[2]), "=r"(r[3]) : "r"(a));
}
__device__ __forceinline__ void ldsm4t(uint32_t* r, uint32_t a) {
    asm volatile("ldmatrix.sync.aligned.m8n8.x4.trans.shared.b16 {%0,%1,%2,%3}, [%4];" : "=r"(r[0]), "=r"(r[1]), "=r"(r[2]), "=r"(r[3]) : "r"(a));
}
__device__ __forceinline__ void stsm4(uint32_t a, uint32_t r0, uint32_t r1, uint32_t r2, uint32_t r3) {
    asm volatile("stmatrix.sync.aligned.m8n8.x4.shared.b16 [%0], {%1,%2,%3,%4};" ::"r"(a), "r"(r0), "r"(r1), "r"(r2), "r"(r3) : "memory");
}
__device__ __forceinline__ void stsm4t(uint32_t a, uint32_t r0, uint32_t r1, uint32_t r2, uint32_t r3) {
    asm volatile("stmatrix.sync.aligned.m8n8.x4.trans.shared.b16 [%0], {%1,%2,%3,%4};" ::"r"(a), "r"(r0), "r"(r1), "r"(r2), "r"(r3) : "memory");
}
__device__ __forceinline__ uint32_t movm(uint32_t a) { uint32_t d; asm volatile("movmatrix.sync.aligned.m8n8.trans.b16 %0, %1;" : "=r"(d) : "r"(a)); return d; }
__device__ __forceinline__ uint32_t pack2(float lo, float hi) { uint32_t d; asm("cvt.rn.bf16x2.f32 %0, %1, %2;" : "=r"(d) : "f"(hi), "f"(lo)); return d; }
__device__ __forceinline__ uint32_t prmt(uint32_t a, uint32_t b, uint32_t s) { uint32_t d; asm("prmt.b32 %0, %1, %2, %3;" : "=r"(d) : "r"(a), "r"(b), "r"(s)); return d; }
__device__ __forceinline__ uint32_t pack2h(float lo, float hi) { uint32_t d; asm("cvt.rn.f16x2.f32 %0, %1, %2;" : "=r"(d) : "f"(hi), "f"(lo)); return d; }
__device__ __forceinline__ uint32_t h2bf(uint32_t a, uint32_t b) {
    uint32_t d;
    asm("{\n.reg .b16 l, h, u;\n.reg .f32 x, y;\nmov.b32 {l, u}, %1;\ncvt.f32.f16 x, l;\nmov.b32 {u, h}, %2;\ncvt.f32.f16 y, h;\ncvt.rn.bf16x2.f32 %0, y, x;\n}" : "=r"(d) : "r"(a), "r"(b));
    return d;
}
__device__ __forceinline__ void cvt_block(uint32_t* u, uint32_t& x, uint32_t sel) {
    const uint32_t a = prmt(u[0], u[0], sel), b = prmt(u[1], u[1], sel), c = prmt(u[2], u[2], sel), d = prmt(u[3], x, sel);
    x ^= u[3] ^ d;
    u[0] = h2bf(a, a); u[1] = h2bf(b, b); u[2] = h2bf(c, c); u[3] = h2bf(d, d);
}
__device__ __forceinline__ uint32_t amax(uint32_t a, uint32_t b) { uint32_t d; asm("max.xorsign.abs.bf16x2 %0, %1, %2;" : "=r"(d) : "r"(a), "r"(b)); return d; }
__device__ __forceinline__ uint32_t amax4(uint32_t m, const uint32_t* v) { return amax(amax(m, amax(v[0], v[1])), amax(v[2], v[3])); }
__device__ __forceinline__ uint32_t warp_exp(uint32_t m) { return __reduce_max_sync(0xffffffffu, max(m & 0x7f80u, (m >> 16) & 0x7f80u)) >> 7; }
__device__ __forceinline__ void red_max_shared(uint32_t a, uint32_t x) { asm volatile("red.shared.max.u32 [%0], %1;" ::"r"(a), "r"(x) : "memory"); }
__device__ __forceinline__ uint32_t mul_bf2(uint32_t a, uint32_t b) { uint32_t d; asm("mul.rn.bf16x2 %0, %1, %2;" : "=r"(d) : "r"(a), "r"(b)); return d; }
__device__ __forceinline__ float bf_lo(uint32_t u) { return __uint_as_float(u << 16); }
__device__ __forceinline__ float bf_hi(uint32_t u) { return __uint_as_float(u & 0xffff0000u); }
__device__ __forceinline__ float ex2(float x) { float y; asm("ex2.approx.ftz.f32 %0, %1;" : "=f"(y) : "f"(x)); return y; }
__device__ __forceinline__ float rcp(float x) { float y; asm("rcp.approx.ftz.f32 %0, %1;" : "=f"(y) : "f"(x)); return y; }
__device__ __forceinline__ void st_relaxed4(const void* p, uint32_t a, uint32_t b, uint32_t c, uint32_t d) {
    asm volatile("{\n.reg .b128 t;\nmov.b128 t, {%1,%2,%3,%4};\nst.relaxed.gpu.global.b128 [%0], t;\n}" ::"l"(p), "r"(a), "r"(b), "r"(c), "r"(d) : "memory");
}
__device__ __forceinline__ void st_relaxed2(const void* p, uint32_t a, uint32_t b) {
    asm volatile("{\n.reg .b64 t;\nmov.b64 t, {%1,%2};\nst.relaxed.gpu.global.b64 [%0], t;\n}" ::"l"(p), "r"(a), "r"(b) : "memory");
}
__device__ __forceinline__ void ld_relaxed2_if(uint32_t& a, uint32_t& b, const void* p, bool on) {
    asm volatile("{\n.reg .pred P;\n.reg .b64 t;\nsetp.ne.u32 P, %3, 0;\nmov.b64 t, {%0,%1};\n@P ld.relaxed.gpu.global.b64 t, [%2];\nmov.b64 {%0,%1}, t;\n}" : "+r"(a), "+r"(b) : "l"(p), "r"((uint32_t)on) : "memory");
}
__device__ __forceinline__ void ld_relaxed4(uint32_t* v, const void* p) {
    asm volatile("ld.relaxed.gpu.global.L1::no_allocate.v4.b32 {%0,%1,%2,%3}, [%4];" : "=r"(v[0]), "=r"(v[1]), "=r"(v[2]), "=r"(v[3]) : "l"(p) : "memory");
}
__device__ __forceinline__ void ld_relaxed1n(uint32_t& v, const void* p) { asm volatile("ld.relaxed.gpu.global.L1::no_allocate.b32 %0, [%1];" : "=r"(v) : "l"(p) : "memory"); }
__device__ __forceinline__ void red_add4(const void* p, uint32_t a, uint32_t b, uint32_t c, uint32_t d) {
    asm volatile("red.relaxed.gpu.global.add.noftz.v4.f16x2 [%0], {%1,%2,%3,%4};" ::"l"(p), "r"(a), "r"(b), "r"(c), "r"(d) : "memory");
}
__device__ __forceinline__ void red_add1(const void* p, uint32_t a) { asm volatile("red.relaxed.gpu.global.add.noftz.f16x2 [%0], %1;" ::"l"(p), "r"(a) : "memory"); }
__device__ __forceinline__ void ld_relaxed2(uint32_t* v, const void* p) {
    asm volatile("{\n.reg .b64 t;\nld.relaxed.gpu.global.L1::no_allocate.b64 t, [%2];\nmov.b64 {%0,%1}, t;\n}" : "=r"(v[0]), "=r"(v[1]) : "l"(p) : "memory");
}
__device__ __forceinline__ uint32_t ld_relaxed1(const void* p) { uint32_t v; asm volatile("ld.relaxed.gpu.global.u32 %0, [%1];" : "=r"(v) : "l"(p) : "memory"); return v; }
__device__ __forceinline__ void st_relaxed1(const void* p, uint32_t v) { asm volatile("st.relaxed.gpu.global.u32 [%0], %1;" ::"l"(p), "r"(v) : "memory"); }
__device__ __forceinline__ uint32_t ld_acquire(const void* p) { uint32_t v; asm volatile("ld.acquire.gpu.global.u32 %0, [%1];" : "=r"(v) : "l"(p) : "memory"); return v; }
__device__ __forceinline__ void red_relaxed(void* p) { asm volatile("red.relaxed.gpu.global.add.u32 [%0], 1;" ::"l"(p) : "memory"); }
__device__ __forceinline__ void red_release(void* p) { asm volatile("red.release.gpu.global.add.u32 [%0], 1;" ::"l"(p) : "memory"); }
__device__ __forceinline__ void st_stream2(float* p, float a, float b) { asm volatile("st.global.cs.v2.f32 [%0], {%1, %2};" ::"l"(p), "f"(a), "f"(b) : "memory"); }
__device__ __forceinline__ void fence_async() { asm volatile("fence.proxy.async.global;" ::: "memory"); }
__device__ __forceinline__ void fence_async_smem() { asm volatile("fence.proxy.async.shared::cta;" ::: "memory"); }
__device__ __forceinline__ void wait_count(const uint32_t* p, uint32_t target) {
    int n = 0;
    while ((int32_t)(ld_acquire(p) - target) < 0) { __nanosleep(200); if (++n > SPIN_LIMIT) spin_fault(); }
}
__device__ __forceinline__ void bar_sync(int id, int n) { asm volatile("bar.sync %0, %1;" ::"r"(id), "r"(n) : "memory"); }
__device__ __forceinline__ bool bar_and(int id, bool v) {
    uint32_t r;
    asm volatile("{\n.reg .pred P, Q;\nsetp.ne.u32 Q, %2, 0;\nbar.red.and.pred P, %1, 128, Q;\nselp.u32 %0, 1, 0, P;\n}" : "=r"(r) : "r"(id), "r"((uint32_t)v) : "memory");
    return r;
}
__device__ __forceinline__ void bar_arrive(int id, int n) { asm volatile("bar.arrive %0, %1;" ::"r"(id), "r"(n) : "memory"); }
__device__ __forceinline__ void lds128(uint32_t* v, uint32_t a) { asm volatile("ld.shared.v4.b32 {%0,%1,%2,%3}, [%4];" : "=r"(v[0]), "=r"(v[1]), "=r"(v[2]), "=r"(v[3]) : "r"(a) : "memory"); }
__device__ __forceinline__ uint32_t lds32(uint32_t a) { uint32_t v; asm volatile("ld.shared.b32 %0, [%1];" : "=r"(v) : "r"(a) : "memory"); return v; }
__device__ __forceinline__ void lds64(uint32_t* v, uint32_t a) { asm volatile("ld.shared.v2.b32 {%0,%1}, [%2];" : "=r"(v[0]), "=r"(v[1]) : "r"(a) : "memory"); }
__device__ __forceinline__ void lds64f(float* v, uint32_t a) { asm volatile("ld.shared.v2.f32 {%0,%1}, [%2];" : "=f"(v[0]), "=f"(v[1]) : "r"(a) : "memory"); }
__device__ __forceinline__ void sts128(uint32_t a, const uint32_t* v) { asm volatile("st.shared.v4.b32 [%0], {%1,%2,%3,%4};" ::"r"(a), "r"(v[0]), "r"(v[1]), "r"(v[2]), "r"(v[3]) : "memory"); }
__device__ __forceinline__ void sts64(uint32_t a, uint32_t x, uint32_t y) { asm volatile("st.shared.v2.b32 [%0], {%1,%2};" ::"r"(a), "r"(x), "r"(y) : "memory"); }
__device__ __forceinline__ void sts32(uint32_t a, uint32_t x) { asm volatile("st.shared.b32 [%0], %1;" ::"r"(a), "r"(x) : "memory"); }
__device__ __forceinline__ bool mbar_try(uint32_t b, uint32_t par) {
    uint32_t ok;
    asm volatile("{\n.reg .pred P;\nmbarrier.try_wait.parity.shared::cta.b64 P, [%1], %2;\nselp.u32 %0, 1, 0, P;\n}" : "=r"(ok) : "r"(b), "r"(par) : "memory");
    return ok;
}
__device__ __forceinline__ void mbar_wait(uint32_t b, uint32_t par) {
    asm volatile("{\n.reg .pred P, Q;\n.reg .u32 n;\nmov.u32 n, %2;\nW: mbarrier.try_wait.parity.shared::cta.b64 P, [%0], %1;\n"
                 "add.u32 n, n, -1;\nsetp.eq.u32 Q, n, 0;\n@Q st.global.u32 [%3], 0;\n@!P bra W;\n}" ::"r"(b), "r"(par), "n"(SPIN_LIMIT), "l"(0ull) : "memory");
}
__device__ __forceinline__ void declare_fence(int zero) { asm volatile(".reg .pred PNEVER;\nsetp.ne.u32 PNEVER, %0, 0;" ::"r"(zero)); }
__device__ __forceinline__ void sched_fence() { asm volatile("{\n.reg .pred Q;\n.reg .u32 x;\n@!PNEVER bra D;\nF: ld.volatile.global.u32 x, [%0];\nsetp.ne.u32 Q, x, 0;\n@Q bra F;\nD:\n}" ::"l"(0ull) : "memory"); }
__device__ __forceinline__ void mbar_init(uint32_t b, uint32_t n) { asm volatile("mbarrier.init.shared::cta.b64 [%0], %1;" ::"r"(b), "r"(n) : "memory"); }
__device__ __forceinline__ void mbar_expect(uint32_t b, uint32_t bytes) { asm volatile("mbarrier.arrive.expect_tx.shared::cta.b64 _, [%0], %1;" ::"r"(b), "r"(bytes) : "memory"); }
__device__ __forceinline__ void mbar_arrive(uint32_t b) { asm volatile("mbarrier.arrive.shared::cta.b64 _, [%0];" ::"r"(b) : "memory"); }
__device__ __forceinline__ void mbar_arrive_cluster(uint32_t b) { asm volatile("mbarrier.arrive.shared::cluster.b64 _, [%0];" ::"r"(b) : "memory"); }
__device__ __forceinline__ void cluster_sync() { asm volatile("barrier.cluster.arrive.aligned;\nbarrier.cluster.wait.aligned;" ::: "memory"); }
__device__ __forceinline__ void tma2d(uint32_t dst, const CUtensorMap* m, int c0, int c1, uint32_t bar) {
    asm volatile("cp.async.bulk.tensor.2d.shared::cluster.global.mbarrier::complete_tx::bytes [%0], [%1, {%2, %3}], [%4];" ::"r"(dst), "l"(m), "r"(c0), "r"(c1), "r"(bar) : "memory");
}
__device__ __forceinline__ void tma2d_mc(uint32_t dst, const CUtensorMap* m, int c0, int c1, uint32_t bar, uint16_t mask) {
    asm volatile("cp.async.bulk.tensor.2d.shared::cluster.global.mbarrier::complete_tx::bytes.multicast::cluster [%0], [%1, {%2, %3}], [%4], %5;" ::"r"(dst), "l"(m), "r"(c0), "r"(c1), "r"(bar), "h"(mask) : "memory");
}
__device__ __forceinline__ void tma3d(uint32_t dst, const CUtensorMap* m, int c0, int c1, int c2, uint32_t bar) {
    asm volatile("cp.async.bulk.tensor.3d.shared::cluster.global.mbarrier::complete_tx::bytes [%0], [%1, {%2, %3, %4}], [%5];" ::"r"(dst), "l"(m), "r"(c0), "r"(c1), "r"(c2), "r"(bar) : "memory");
}
__device__ __forceinline__ void tma3d_mc(uint32_t dst, const CUtensorMap* m, int c0, int c1, int c2, uint32_t bar, uint16_t mask) {
    asm volatile("cp.async.bulk.tensor.3d.shared::cluster.global.mbarrier::complete_tx::bytes.multicast::cluster [%0], [%1, {%2, %3, %4}], [%5], %6;" ::"r"(dst), "l"(m), "r"(c0), "r"(c1), "r"(c2), "r"(bar), "h"(mask) : "memory");
}
__device__ __forceinline__ void tma4d(uint32_t dst, const CUtensorMap* m, int c0, int c3, uint32_t bar) {
    asm volatile("cp.async.bulk.tensor.4d.shared::cluster.global.mbarrier::complete_tx::bytes [%0], [%1, {%2, 0, 0, %3}], [%4];" ::"r"(dst), "l"(m), "r"(c0), "r"(c3), "r"(bar) : "memory");
}
__device__ __forceinline__ void tma4d_mc(uint32_t dst, const CUtensorMap* m, int c0, int c3, uint32_t bar, uint16_t mask) {
    asm volatile("cp.async.bulk.tensor.4d.shared::cluster.global.mbarrier::complete_tx::bytes.multicast::cluster [%0], [%1, {%2, 0, 0, %3}], [%4], %5;" ::"r"(dst), "l"(m), "r"(c0), "r"(c3), "r"(bar), "h"(mask) : "memory");
}
__device__ __forceinline__ void tma_prefetch3d(const CUtensorMap* m, int c0, int c1, int c2) {
    asm volatile("cp.async.bulk.prefetch.tensor.3d.L2.global [%0, {%1, %2, %3}];" ::"l"(m), "r"(c0), "r"(c1), "r"(c2) : "memory");
}
__device__ __forceinline__ void tma_prefetch2d(const CUtensorMap* m, int c0, int c1) {
    asm volatile("cp.async.bulk.prefetch.tensor.2d.L2.global [%0, {%1, %2}];" ::"l"(m), "r"(c0), "r"(c1) : "memory");
}
__device__ __forceinline__ void l2_prefetch(const void* src, uint32_t bytes) { asm volatile("cp.async.bulk.prefetch.L2.global [%0], %1;" ::"l"(src), "r"(bytes) : "memory"); }
__device__ __forceinline__ void bulk_g2s(uint32_t dst, const void* src, uint32_t bytes, uint32_t bar) {
    asm volatile("cp.async.bulk.shared::cluster.global.mbarrier::complete_tx::bytes [%0], [%1], %2, [%3];" ::"r"(dst), "l"(src), "r"(bytes), "r"(bar) : "memory");
}
__device__ __forceinline__ void mbar_expect_e(uint32_t b, uint32_t bytes) {
    asm volatile("{\n.reg .pred E;\nelect.sync _|E, 0xffffffff;\n@E mbarrier.arrive.expect_tx.shared::cta.b64 _, [%0], %1;\n}" ::"r"(b), "r"(bytes) : "memory");
}
__device__ __forceinline__ void tma2d_e(uint32_t dst, const CUtensorMap* m, int c0, int c1, uint32_t bar) {
    asm volatile("{\n.reg .pred E;\nelect.sync _|E, 0xffffffff;\n@E cp.async.bulk.tensor.2d.shared::cluster.global.mbarrier::complete_tx::bytes [%0], [%1, {%2, %3}], [%4];\n}" ::"r"(dst), "l"(m), "r"(c0), "r"(c1), "r"(bar) : "memory");
}
__device__ __forceinline__ void tma2d_mc_e(uint32_t dst, const CUtensorMap* m, int c0, int c1, uint32_t bar, uint16_t mask) {
    asm volatile("{\n.reg .pred E;\nelect.sync _|E, 0xffffffff;\n@E cp.async.bulk.tensor.2d.shared::cluster.global.mbarrier::complete_tx::bytes.multicast::cluster [%0], [%1, {%2, %3}], [%4], %5;\n}" ::"r"(dst), "l"(m), "r"(c0), "r"(c1), "r"(bar), "h"(mask) : "memory");
}
__device__ __forceinline__ void tma3d_e(uint32_t dst, const CUtensorMap* m, int c0, int c1, int c2, uint32_t bar) {
    asm volatile("{\n.reg .pred E;\nelect.sync _|E, 0xffffffff;\n@E cp.async.bulk.tensor.3d.shared::cluster.global.mbarrier::complete_tx::bytes [%0], [%1, {%2, %3, %4}], [%5];\n}" ::"r"(dst), "l"(m), "r"(c0), "r"(c1), "r"(c2), "r"(bar) : "memory");
}
__device__ __forceinline__ void tma3d_mc_e(uint32_t dst, const CUtensorMap* m, int c0, int c1, int c2, uint32_t bar, uint16_t mask) {
    asm volatile("{\n.reg .pred E;\nelect.sync _|E, 0xffffffff;\n@E cp.async.bulk.tensor.3d.shared::cluster.global.mbarrier::complete_tx::bytes.multicast::cluster [%0], [%1, {%2, %3, %4}], [%5], %6;\n}" ::"r"(dst), "l"(m), "r"(c0), "r"(c1), "r"(c2), "r"(bar), "h"(mask) : "memory");
}
__device__ __forceinline__ void tma4d_e(uint32_t dst, const CUtensorMap* m, int c0, int c3, uint32_t bar) {
    asm volatile("{\n.reg .pred E;\nelect.sync _|E, 0xffffffff;\n@E cp.async.bulk.tensor.4d.shared::cluster.global.mbarrier::complete_tx::bytes [%0], [%1, {%2, 0, 0, %3}], [%4];\n}" ::"r"(dst), "l"(m), "r"(c0), "r"(c3), "r"(bar) : "memory");
}
__device__ __forceinline__ void tma4d_mc_e(uint32_t dst, const CUtensorMap* m, int c0, int c3, uint32_t bar, uint16_t mask) {
    asm volatile("{\n.reg .pred E;\nelect.sync _|E, 0xffffffff;\n@E cp.async.bulk.tensor.4d.shared::cluster.global.mbarrier::complete_tx::bytes.multicast::cluster [%0], [%1, {%2, 0, 0, %3}], [%4], %5;\n}" ::"r"(dst), "l"(m), "r"(c0), "r"(c3), "r"(bar), "h"(mask) : "memory");
}
__device__ __forceinline__ void tma_prefetch2d_e(const CUtensorMap* m, int c0, int c1) {
    asm volatile("{\n.reg .pred E;\nelect.sync _|E, 0xffffffff;\n@E cp.async.bulk.prefetch.tensor.2d.L2.global [%0, {%1, %2}];\n}" ::"l"(m), "r"(c0), "r"(c1) : "memory");
}
__device__ __forceinline__ void tma_prefetch3d_e(const CUtensorMap* m, int c0, int c1, int c2) {
    asm volatile("{\n.reg .pred E;\nelect.sync _|E, 0xffffffff;\n@E cp.async.bulk.prefetch.tensor.3d.L2.global [%0, {%1, %2, %3}];\n}" ::"l"(m), "r"(c0), "r"(c1), "r"(c2) : "memory");
}
__device__ __forceinline__ void l2_prefetch_e(const void* src, uint32_t bytes) {
    asm volatile("{\n.reg .pred E;\nelect.sync _|E, 0xffffffff;\n@E cp.async.bulk.prefetch.L2.global [%0], %1;\n}" ::"l"(src), "r"(bytes) : "memory");
}
__device__ __forceinline__ void bulk_g2s_e(uint32_t dst, const void* src, uint32_t bytes, uint32_t bar) {
    asm volatile("{\n.reg .pred E;\nelect.sync _|E, 0xffffffff;\n@E cp.async.bulk.shared::cluster.global.mbarrier::complete_tx::bytes [%0], [%1], %2, [%3];\n}" ::"r"(dst), "l"(src), "r"(bytes), "r"(bar) : "memory");
}
__device__ __forceinline__ bool elect_one() {
    uint32_t r;
    asm volatile("{\n.reg .pred E;\nelect.sync _|E, 0xffffffff;\nselp.u32 %0, 1, 0, E;\n}" : "=r"(r));
    return r;
}
__device__ __forceinline__ void tma_store2d(const CUtensorMap* m, int c0, int c1, uint32_t src) {
    asm volatile("cp.async.bulk.tensor.2d.global.shared::cta.bulk_group [%0, {%1, %2}], [%3];" ::"l"(m), "r"(c0), "r"(c1), "r"(src) : "memory");
}
__device__ __forceinline__ void bulk_commit() { asm volatile("cp.async.bulk.commit_group;" ::: "memory"); }
__device__ __forceinline__ void bulk_wait_read() { asm volatile("cp.async.bulk.wait_group.read 0;" ::: "memory"); }
__device__ __forceinline__ void bulk_wait_all() { asm volatile("cp.async.bulk.wait_group 0;" ::: "memory"); }
__device__ __forceinline__ uint64_t mkdesc(uint32_t addr, uint32_t lbo, uint32_t sbo, uint32_t swz) {
    return (uint64_t)((addr & 0x3FFFF) >> 4) | ((uint64_t)(lbo >> 4) << 16) | ((uint64_t)(sbo >> 4) << 32) | ((uint64_t)swz << 62);
}
__device__ __forceinline__ void wg_fence() { asm volatile("wgmma.fence.sync.aligned;" ::: "memory"); }
__device__ __forceinline__ void wg_commit() { asm volatile("wgmma.commit_group.sync.aligned;" ::: "memory"); }
template <int N> __device__ __forceinline__ void wg_wait() { asm volatile("wgmma.wait_group.sync.aligned %0;" ::"n"(N) : "memory"); }
template <typename T> __device__ __forceinline__ void pin_ptr(T*& p) { asm volatile("" : "+l"(p)); }
template <int N> __device__ __forceinline__ void pin(uint32_t* d) {
#pragma unroll
    for (int i = 0; i < N; i++) asm volatile("" : "+r"(d[i])::"memory");
}
template <int N> __device__ __forceinline__ void pin(float* d) {
#pragma unroll
    for (int i = 0; i < N; i++) asm volatile("" : "+f"(d[i])::"memory");
}

template <int TA, int TB>
__device__ __forceinline__ void wgmma_ss256(float* d, uint64_t da, uint64_t db) {
    asm volatile("wgmma.mma_async.sync.aligned.m64n256k16.f32.bf16.bf16 "
        "{%0, %1, %2, %3, %4, %5, %6, %7, %8, %9, %10, %11, %12, %13, %14, %15, %16, %17, %18, %19, %20, %21, %22, %23, %24, %25, %26, %27, %28, %29, %30, %31, %32, %33, %34, %35, %36, %37, %38, %39, %40, %41, %42, %43, %44, %45, %46, %47, %48, %49, %50, %51, %52, %53, %54, %55, %56, %57, %58, %59, %60, %61, %62, %63, %64, %65, %66, %67, %68, %69, %70, %71, %72, %73, %74, %75, %76, %77, %78, %79, %80, %81, %82, %83, %84, %85, %86, %87, %88, %89, %90, %91, %92, %93, %94, %95, %96, %97, %98, %99, %100, %101, %102, %103, %104, %105, %106, %107, %108, %109, %110, %111, %112, %113, %114, %115, %116, %117, %118, %119, %120, %121, %122, %123, %124, %125, %126, %127}, %128, %129, 1, 1, 1, %130, %131;"
        : "+f"(d[0]), "+f"(d[1]), "+f"(d[2]), "+f"(d[3]), "+f"(d[4]), "+f"(d[5]), "+f"(d[6]), "+f"(d[7]), "+f"(d[8]), "+f"(d[9]), "+f"(d[10]), "+f"(d[11]), "+f"(d[12]), "+f"(d[13]), "+f"(d[14]), "+f"(d[15]), "+f"(d[16]), "+f"(d[17]), "+f"(d[18]), "+f"(d[19]), "+f"(d[20]), "+f"(d[21]), "+f"(d[22]), "+f"(d[23]), "+f"(d[24]), "+f"(d[25]), "+f"(d[26]), "+f"(d[27]), "+f"(d[28]), "+f"(d[29]), "+f"(d[30]), "+f"(d[31]), "+f"(d[32]), "+f"(d[33]), "+f"(d[34]), "+f"(d[35]), "+f"(d[36]), "+f"(d[37]), "+f"(d[38]), "+f"(d[39]), "+f"(d[40]), "+f"(d[41]), "+f"(d[42]), "+f"(d[43]), "+f"(d[44]), "+f"(d[45]), "+f"(d[46]), "+f"(d[47]), "+f"(d[48]), "+f"(d[49]), "+f"(d[50]), "+f"(d[51]), "+f"(d[52]), "+f"(d[53]), "+f"(d[54]), "+f"(d[55]), "+f"(d[56]), "+f"(d[57]), "+f"(d[58]), "+f"(d[59]), "+f"(d[60]), "+f"(d[61]), "+f"(d[62]), "+f"(d[63]), "+f"(d[64]), "+f"(d[65]), "+f"(d[66]), "+f"(d[67]), "+f"(d[68]), "+f"(d[69]), "+f"(d[70]), "+f"(d[71]), "+f"(d[72]), "+f"(d[73]), "+f"(d[74]), "+f"(d[75]), "+f"(d[76]), "+f"(d[77]), "+f"(d[78]), "+f"(d[79]), "+f"(d[80]), "+f"(d[81]), "+f"(d[82]), "+f"(d[83]), "+f"(d[84]), "+f"(d[85]), "+f"(d[86]), "+f"(d[87]), "+f"(d[88]), "+f"(d[89]), "+f"(d[90]), "+f"(d[91]), "+f"(d[92]), "+f"(d[93]), "+f"(d[94]), "+f"(d[95]), "+f"(d[96]), "+f"(d[97]), "+f"(d[98]), "+f"(d[99]), "+f"(d[100]), "+f"(d[101]), "+f"(d[102]), "+f"(d[103]), "+f"(d[104]), "+f"(d[105]), "+f"(d[106]), "+f"(d[107]), "+f"(d[108]), "+f"(d[109]), "+f"(d[110]), "+f"(d[111]), "+f"(d[112]), "+f"(d[113]), "+f"(d[114]), "+f"(d[115]), "+f"(d[116]), "+f"(d[117]), "+f"(d[118]), "+f"(d[119]), "+f"(d[120]), "+f"(d[121]), "+f"(d[122]), "+f"(d[123]), "+f"(d[124]), "+f"(d[125]), "+f"(d[126]), "+f"(d[127])
        : "l"(da), "l"(db), "n"(TA), "n"(TB));
}
template <int TA, int TB>
__device__ __forceinline__ void wgmma_ss256_first(float* d, uint64_t da, uint64_t db) {
    asm volatile("wgmma.mma_async.sync.aligned.m64n256k16.f32.bf16.bf16 "
        "{%0, %1, %2, %3, %4, %5, %6, %7, %8, %9, %10, %11, %12, %13, %14, %15, %16, %17, %18, %19, %20, %21, %22, %23, %24, %25, %26, %27, %28, %29, %30, %31, %32, %33, %34, %35, %36, %37, %38, %39, %40, %41, %42, %43, %44, %45, %46, %47, %48, %49, %50, %51, %52, %53, %54, %55, %56, %57, %58, %59, %60, %61, %62, %63, %64, %65, %66, %67, %68, %69, %70, %71, %72, %73, %74, %75, %76, %77, %78, %79, %80, %81, %82, %83, %84, %85, %86, %87, %88, %89, %90, %91, %92, %93, %94, %95, %96, %97, %98, %99, %100, %101, %102, %103, %104, %105, %106, %107, %108, %109, %110, %111, %112, %113, %114, %115, %116, %117, %118, %119, %120, %121, %122, %123, %124, %125, %126, %127}, %128, %129, 0, 1, 1, %130, %131;"
        : "=f"(d[0]), "=f"(d[1]), "=f"(d[2]), "=f"(d[3]), "=f"(d[4]), "=f"(d[5]), "=f"(d[6]), "=f"(d[7]), "=f"(d[8]), "=f"(d[9]), "=f"(d[10]), "=f"(d[11]), "=f"(d[12]), "=f"(d[13]), "=f"(d[14]), "=f"(d[15]), "=f"(d[16]), "=f"(d[17]), "=f"(d[18]), "=f"(d[19]), "=f"(d[20]), "=f"(d[21]), "=f"(d[22]), "=f"(d[23]), "=f"(d[24]), "=f"(d[25]), "=f"(d[26]), "=f"(d[27]), "=f"(d[28]), "=f"(d[29]), "=f"(d[30]), "=f"(d[31]), "=f"(d[32]), "=f"(d[33]), "=f"(d[34]), "=f"(d[35]), "=f"(d[36]), "=f"(d[37]), "=f"(d[38]), "=f"(d[39]), "=f"(d[40]), "=f"(d[41]), "=f"(d[42]), "=f"(d[43]), "=f"(d[44]), "=f"(d[45]), "=f"(d[46]), "=f"(d[47]), "=f"(d[48]), "=f"(d[49]), "=f"(d[50]), "=f"(d[51]), "=f"(d[52]), "=f"(d[53]), "=f"(d[54]), "=f"(d[55]), "=f"(d[56]), "=f"(d[57]), "=f"(d[58]), "=f"(d[59]), "=f"(d[60]), "=f"(d[61]), "=f"(d[62]), "=f"(d[63]), "=f"(d[64]), "=f"(d[65]), "=f"(d[66]), "=f"(d[67]), "=f"(d[68]), "=f"(d[69]), "=f"(d[70]), "=f"(d[71]), "=f"(d[72]), "=f"(d[73]), "=f"(d[74]), "=f"(d[75]), "=f"(d[76]), "=f"(d[77]), "=f"(d[78]), "=f"(d[79]), "=f"(d[80]), "=f"(d[81]), "=f"(d[82]), "=f"(d[83]), "=f"(d[84]), "=f"(d[85]), "=f"(d[86]), "=f"(d[87]), "=f"(d[88]), "=f"(d[89]), "=f"(d[90]), "=f"(d[91]), "=f"(d[92]), "=f"(d[93]), "=f"(d[94]), "=f"(d[95]), "=f"(d[96]), "=f"(d[97]), "=f"(d[98]), "=f"(d[99]), "=f"(d[100]), "=f"(d[101]), "=f"(d[102]), "=f"(d[103]), "=f"(d[104]), "=f"(d[105]), "=f"(d[106]), "=f"(d[107]), "=f"(d[108]), "=f"(d[109]), "=f"(d[110]), "=f"(d[111]), "=f"(d[112]), "=f"(d[113]), "=f"(d[114]), "=f"(d[115]), "=f"(d[116]), "=f"(d[117]), "=f"(d[118]), "=f"(d[119]), "=f"(d[120]), "=f"(d[121]), "=f"(d[122]), "=f"(d[123]), "=f"(d[124]), "=f"(d[125]), "=f"(d[126]), "=f"(d[127])
        : "l"(da), "l"(db), "n"(TA), "n"(TB));
}
template <int TA, int TB>
__device__ __forceinline__ void wgmma_ss128(float* d, uint64_t da, uint64_t db) {
    asm volatile("wgmma.mma_async.sync.aligned.m64n128k16.f32.bf16.bf16 "
        "{%0, %1, %2, %3, %4, %5, %6, %7, %8, %9, %10, %11, %12, %13, %14, %15, %16, %17, %18, %19, %20, %21, %22, %23, %24, %25, %26, %27, %28, %29, %30, %31, %32, %33, %34, %35, %36, %37, %38, %39, %40, %41, %42, %43, %44, %45, %46, %47, %48, %49, %50, %51, %52, %53, %54, %55, %56, %57, %58, %59, %60, %61, %62, %63}, %64, %65, 1, 1, 1, %66, %67;"
        : "+f"(d[0]), "+f"(d[1]), "+f"(d[2]), "+f"(d[3]), "+f"(d[4]), "+f"(d[5]), "+f"(d[6]), "+f"(d[7]), "+f"(d[8]), "+f"(d[9]), "+f"(d[10]), "+f"(d[11]), "+f"(d[12]), "+f"(d[13]), "+f"(d[14]), "+f"(d[15]), "+f"(d[16]), "+f"(d[17]), "+f"(d[18]), "+f"(d[19]), "+f"(d[20]), "+f"(d[21]), "+f"(d[22]), "+f"(d[23]), "+f"(d[24]), "+f"(d[25]), "+f"(d[26]), "+f"(d[27]), "+f"(d[28]), "+f"(d[29]), "+f"(d[30]), "+f"(d[31]), "+f"(d[32]), "+f"(d[33]), "+f"(d[34]), "+f"(d[35]), "+f"(d[36]), "+f"(d[37]), "+f"(d[38]), "+f"(d[39]), "+f"(d[40]), "+f"(d[41]), "+f"(d[42]), "+f"(d[43]), "+f"(d[44]), "+f"(d[45]), "+f"(d[46]), "+f"(d[47]), "+f"(d[48]), "+f"(d[49]), "+f"(d[50]), "+f"(d[51]), "+f"(d[52]), "+f"(d[53]), "+f"(d[54]), "+f"(d[55]), "+f"(d[56]), "+f"(d[57]), "+f"(d[58]), "+f"(d[59]), "+f"(d[60]), "+f"(d[61]), "+f"(d[62]), "+f"(d[63])
        : "l"(da), "l"(db), "n"(TA), "n"(TB));
}
template <int TA, int TB>
__device__ __forceinline__ void wgmma_ss128_first(float* d, uint64_t da, uint64_t db) {
    asm volatile("wgmma.mma_async.sync.aligned.m64n128k16.f32.bf16.bf16 "
        "{%0, %1, %2, %3, %4, %5, %6, %7, %8, %9, %10, %11, %12, %13, %14, %15, %16, %17, %18, %19, %20, %21, %22, %23, %24, %25, %26, %27, %28, %29, %30, %31, %32, %33, %34, %35, %36, %37, %38, %39, %40, %41, %42, %43, %44, %45, %46, %47, %48, %49, %50, %51, %52, %53, %54, %55, %56, %57, %58, %59, %60, %61, %62, %63}, %64, %65, 0, 1, 1, %66, %67;"
        : "=f"(d[0]), "=f"(d[1]), "=f"(d[2]), "=f"(d[3]), "=f"(d[4]), "=f"(d[5]), "=f"(d[6]), "=f"(d[7]), "=f"(d[8]), "=f"(d[9]), "=f"(d[10]), "=f"(d[11]), "=f"(d[12]), "=f"(d[13]), "=f"(d[14]), "=f"(d[15]), "=f"(d[16]), "=f"(d[17]), "=f"(d[18]), "=f"(d[19]), "=f"(d[20]), "=f"(d[21]), "=f"(d[22]), "=f"(d[23]), "=f"(d[24]), "=f"(d[25]), "=f"(d[26]), "=f"(d[27]), "=f"(d[28]), "=f"(d[29]), "=f"(d[30]), "=f"(d[31]), "=f"(d[32]), "=f"(d[33]), "=f"(d[34]), "=f"(d[35]), "=f"(d[36]), "=f"(d[37]), "=f"(d[38]), "=f"(d[39]), "=f"(d[40]), "=f"(d[41]), "=f"(d[42]), "=f"(d[43]), "=f"(d[44]), "=f"(d[45]), "=f"(d[46]), "=f"(d[47]), "=f"(d[48]), "=f"(d[49]), "=f"(d[50]), "=f"(d[51]), "=f"(d[52]), "=f"(d[53]), "=f"(d[54]), "=f"(d[55]), "=f"(d[56]), "=f"(d[57]), "=f"(d[58]), "=f"(d[59]), "=f"(d[60]), "=f"(d[61]), "=f"(d[62]), "=f"(d[63])
        : "l"(da), "l"(db), "n"(TA), "n"(TB));
}
template <int TB>
__device__ __forceinline__ void wgmma_rs128(float* d, const uint32_t* a, uint64_t db, uint32_t acc) {
    asm volatile("{\n.reg .pred P;\nsetp.ne.u32 P, %69, 0;\nwgmma.mma_async.sync.aligned.m64n128k16.f32.bf16.bf16 "
        "{%0, %1, %2, %3, %4, %5, %6, %7, %8, %9, %10, %11, %12, %13, %14, %15, %16, %17, %18, %19, %20, %21, %22, %23, %24, %25, %26, %27, %28, %29, %30, %31, %32, %33, %34, %35, %36, %37, %38, %39, %40, %41, %42, %43, %44, %45, %46, %47, %48, %49, %50, %51, %52, %53, %54, %55, %56, %57, %58, %59, %60, %61, %62, %63}, {%64, %65, %66, %67}, %68, P, 1, 1, %70;\n}"
        : "+f"(d[0]), "+f"(d[1]), "+f"(d[2]), "+f"(d[3]), "+f"(d[4]), "+f"(d[5]), "+f"(d[6]), "+f"(d[7]), "+f"(d[8]), "+f"(d[9]), "+f"(d[10]), "+f"(d[11]), "+f"(d[12]), "+f"(d[13]), "+f"(d[14]), "+f"(d[15]), "+f"(d[16]), "+f"(d[17]), "+f"(d[18]), "+f"(d[19]), "+f"(d[20]), "+f"(d[21]), "+f"(d[22]), "+f"(d[23]), "+f"(d[24]), "+f"(d[25]), "+f"(d[26]), "+f"(d[27]), "+f"(d[28]), "+f"(d[29]), "+f"(d[30]), "+f"(d[31]), "+f"(d[32]), "+f"(d[33]), "+f"(d[34]), "+f"(d[35]), "+f"(d[36]), "+f"(d[37]), "+f"(d[38]), "+f"(d[39]), "+f"(d[40]), "+f"(d[41]), "+f"(d[42]), "+f"(d[43]), "+f"(d[44]), "+f"(d[45]), "+f"(d[46]), "+f"(d[47]), "+f"(d[48]), "+f"(d[49]), "+f"(d[50]), "+f"(d[51]), "+f"(d[52]), "+f"(d[53]), "+f"(d[54]), "+f"(d[55]), "+f"(d[56]), "+f"(d[57]), "+f"(d[58]), "+f"(d[59]), "+f"(d[60]), "+f"(d[61]), "+f"(d[62]), "+f"(d[63])
        : "r"(a[0]), "r"(a[1]), "r"(a[2]), "r"(a[3]), "l"(db), "r"(acc), "n"(TB));
}
template <int TB>
__device__ __forceinline__ void wgmma_rs64(float* d, const uint32_t* a, uint64_t db, uint32_t acc) {
    asm volatile("{\n.reg .pred P;\nsetp.ne.u32 P, %37, 0;\nwgmma.mma_async.sync.aligned.m64n64k16.f32.bf16.bf16 "
        "{%0, %1, %2, %3, %4, %5, %6, %7, %8, %9, %10, %11, %12, %13, %14, %15, %16, %17, %18, %19, %20, %21, %22, %23, %24, %25, %26, %27, %28, %29, %30, %31}, {%32, %33, %34, %35}, %36, P, 1, 1, %38;\n}"
        : "+f"(d[0]), "+f"(d[1]), "+f"(d[2]), "+f"(d[3]), "+f"(d[4]), "+f"(d[5]), "+f"(d[6]), "+f"(d[7]), "+f"(d[8]), "+f"(d[9]), "+f"(d[10]), "+f"(d[11]), "+f"(d[12]), "+f"(d[13]), "+f"(d[14]), "+f"(d[15]), "+f"(d[16]), "+f"(d[17]), "+f"(d[18]), "+f"(d[19]), "+f"(d[20]), "+f"(d[21]), "+f"(d[22]), "+f"(d[23]), "+f"(d[24]), "+f"(d[25]), "+f"(d[26]), "+f"(d[27]), "+f"(d[28]), "+f"(d[29]), "+f"(d[30]), "+f"(d[31])
        : "r"(a[0]), "r"(a[1]), "r"(a[2]), "r"(a[3]), "l"(db), "r"(acc), "n"(TB));
}
template <int TB>
__device__ __forceinline__ void wgmma_rs16(float* d, const uint32_t* a, uint64_t db, uint32_t acc) {
    asm volatile("{\n.reg .pred P;\nsetp.ne.u32 P, %13, 0;\nwgmma.mma_async.sync.aligned.m64n16k16.f32.bf16.bf16 "
        "{%0, %1, %2, %3, %4, %5, %6, %7}, {%8, %9, %10, %11}, %12, P, 1, 1, %14;\n}"
        : "+f"(d[0]), "+f"(d[1]), "+f"(d[2]), "+f"(d[3]), "+f"(d[4]), "+f"(d[5]), "+f"(d[6]), "+f"(d[7])
        : "r"(a[0]), "r"(a[1]), "r"(a[2]), "r"(a[3]), "l"(db), "r"(acc), "n"(TB));
}

__device__ __forceinline__ uint32_t delay_loop(int n, uint32_t x0) {
    uint32_t z;
    asm volatile("{\n.reg .pred P;\n.reg .u32 c, x;\nmov.u32 c, %1;\nmov.u32 x, %2;\nDL: mad.lo.u32 x, x, 1664525, 1013904223;\nadd.u32 c, c, -1;\nsetp.gt.s32 P, c, 0;\n@P bra DL;\n"
                 "setp.eq.u32 P, x, 0x7fffffff;\nselp.u32 %0, 16, 0, P;\n}" : "=r"(z) : "r"(n), "r"(x0) : "memory");
    return z;
}
__device__ __forceinline__ void wait_clocks(uint32_t n) {
    asm volatile("{\n.reg .pred P;\n.reg .u32 a, b;\nmov.u32 a, %%clock;\nW: mov.u32 b, %%clock;\nsub.u32 b, b, a;\nsetp.lt.u32 P, b, %0;\n@P bra W;\n}" ::"r"(n) : "memory");
}
__device__ __forceinline__ uint32_t gtime() { uint32_t t; asm volatile("mov.u32 %0, %%globaltimer_lo;" : "=r"(t)); return t; }
#define COUNT_RETRY(i)
__device__ __forceinline__ uint32_t stamp_word(uint32_t seq) { return (gtime() & ~31u) | (seq & 31u); }
__device__ __forceinline__ void wait_time(uint32_t t, uint32_t sb) { while ((int32_t)(gtime() - t) < 0) {} }
#define NAPMODE 1
__device__ __forceinline__ void nap(uint32_t ns) { if (NAPMODE) wait_clocks(ns * 7 / 4); else __nanosleep(ns); }
template <int STRIDE>
__device__ __forceinline__ uint32_t latest_stamp(const uint32_t* p, uint32_t seq, uint32_t ref, uint32_t sb) {
    int n = 0;
    while (true) {
        uint32_t bad = 0; int32_t m = INT32_MIN;
#pragma unroll
        for (int i = 0; i < 3; i++) { const uint32_t v = ld_relaxed1(p + i * STRIDE); bad |= (v ^ seq) & 31u; m = max(m, (int32_t)((v & ~31u) - ref)); }
        if (__all_sync(0xffffffffu, bad == 0)) return ref + __reduce_max_sync(0xffffffffu, m);
        nap(100);
        if (++n > SPIN_LIMIT) spin_fault();
    }
}
constexpr uint32_t ONES = 0x3C003C00u, FULL = 0x50005000u;
__device__ __forceinline__ void pacer(const Params& P, const uint32_t sb, const int cta, const int lane, const uint32_t epoch) {
    uint8_t* const zp = P.xb + cta * 2048 + xg_lane(lane);
    uint32_t e0 = 0;
#pragma unroll 2
    for (int i = 0; i < 32; i++) { const uint4 u = __ldg((const uint4*)P.mem0 + i * 32 + lane); e0 = amax(amax(e0, amax(u.x, u.y)), amax(u.z, u.w)); }
    e0 = min(max(warp_exp(e0), 31u), 253u) - 14;
    if (cta < 32) {
        const uint32_t* m = (const uint32_t*)(P.mem0 + (lane >> 2) * 1024 + cta * 32 + (lane & 3) * 2);
        const float sc = __uint_as_float((254 - e0) << 23);
        auto cv = [&](uint32_t u) { return pack2h(bf_lo(u) * sc, bf_hi(u) * sc); };
        const uint32_t y = cv(m[12]);
        st_relaxed4(zp, cv(m[0]), cv(m[4]), cv(m[8]), prmt(y, FULL, 0x7610));
        st_relaxed1(P.xb + xg_side(cta) + lane * 4, prmt(y, FULL, 0x3254));
    }
    if (cta < 40) {
#pragma unroll 1
        for (int b = 1; b < 8; b++) st_relaxed4(zp + xg_buf(b), 0, 0, 0, 0);
    }
    __threadfence();
    const uint32_t* ts = (const uint32_t*)(P.xb + XG_T) + lane;
    int32_t d0 = P.dly;
    const uint32_t go = mapa(sb + B_GO, (cta / 3 & 1) * 3 + 1 + (lane & 1));
    auto free_segment = [&]() { if (lane == 0) mbar_expect(sb + B_KVFULL, 16384); __syncwarp(); if (lane < 2) mbar_arrive_cluster(go); };
    wait_count(&g_cnt(C_XCNT), (epoch + 1) * 256);
    const uint32_t ex = max(ld_relaxed1(&g_cnt(C_XMAX)) & 255, 67u);
    mbar_wait(sb + B_READY, 0);
    free_segment();
    if (lane == 0) st_relaxed2(g_hint + cta * 32, stamp_word(epoch + 1), lds32(sb + S_EV) | lds32(sb + S_EO) << 16);
    uint32_t a = gtime();
    for (int n = 0;; n++) {
        uint32_t bad = 0, e = 0; int32_t m = INT32_MIN;
#pragma unroll
        for (int i = 0; i < 3; i++) {
            uint32_t v[2];
            ld_relaxed2(v, g_hint + lane * 32 + i * 1024);
            bad |= (v[0] ^ (epoch + 1)) & 31u; m = max(m, (int32_t)((v[0] & ~31u) - a)); e = __vmaxu2(e, v[1]);
        }
        if (__all_sync(0xffffffffu, bad == 0)) {
            a += __reduce_max_sync(0xffffffffu, m);
            const uint32_t ev = __reduce_max_sync(0xffffffffu, e & 255), eo = __reduce_max_sync(0xffffffffu, e >> 16);
            if (lane == 0) { sts64(sb + S_SC, max(ev, 97u) + max(eo, 97u) - 244, ex); sts32(sb + S_ISC, e0 * 0x800080u); }
            break;
        }
        wait_clocks(100);
        if (n > SPIN_LIMIT) spin_fault();
    }
    wait_time(a, sb);
    if (lane == 0) mbar_arrive(sb + B_RELM);
#pragma unroll 1
    for (int s = 0; s < 63; s++) {
        const uint32_t seq = epoch * 63 + s + 1;
        mbar_wait(sb + B_P1, s & 1);
        const uint32_t tx = gtime();
        if (lane == 0) st_relaxed1(ts + (s & 1) * 256 + cta, (tx & ~31u) | (seq & 31u));
        { const uint32_t t = tx; PROFP(3) }
        if (s > 0) {
            const int32_t e0 = latest_stamp<32>(ts + (~s & 1) * 256 + 128, seq - 1, a, sb) + P.mrg - a;
            d0 += s < 3 ? e0 : min(max(e0, -P.clamp0), P.clampv) / 2;
        }
        while ((int32_t)(gtime() - tx) < P.rd) nap(20);
        a = latest_stamp<32>(ts + (s & 1) * 256, seq, tx, sb) + d0;
        { const uint32_t t = gtime(); PROFP(0) }
        mbar_wait(sb + B_RED, s & 1);
        { const uint32_t t = gtime(); PROFP(1) }
        const uint32_t g = tx + __reduce_max_sync(0xffffffffu, lds32(sb + S_TO + (lane & 7) * 4) - tx);
        if (lane == 0) st_relaxed1(ts + (s & 1) * 256 + 128 + cta, (g & ~31u) | (seq & 31u));
        if (P.kvd < 0 && s < 62) free_segment();
        wait_time((int32_t)(g + P.guard - a) > 0 ? g + P.guard : a, sb);
        if (lane == 0) mbar_arrive(sb + B_RELM);
        { const uint32_t t = a; PROFP(2) }
        if (P.kvd >= 0 && s < 62) { if (P.kvd) nap(P.kvd); free_segment(); }
    }
}
__device__ __forceinline__ void st_async2(uint32_t a, uint32_t x, uint32_t y, uint32_t bar, bool on) {
    asm volatile("{\n.reg .pred P;\nsetp.ne.u32 P, %4, 0;\n@P st.async.weak.shared::cluster.mbarrier::complete_tx::bytes.v2.b32 [%0], {%1,%2}, [%3];\n}" ::"r"(a), "r"(x), "r"(y), "r"(bar), "r"((uint32_t)on) : "memory");
}
__device__ __forceinline__ uint32_t xor_or(uint32_t a, uint32_t b, uint32_t t) { uint32_t d; asm("lop3.b32 %0, %1, %2, %3, 0x7E;" : "=r"(d) : "r"(a), "r"(b), "r"(t)); return d; }
__device__ __forceinline__ uint32_t or3(uint32_t a, uint32_t b, uint32_t c) { uint32_t d; asm("lop3.b32 %0, %1, %2, %3, 0xFE;" : "=r"(d) : "r"(a), "r"(b), "r"(c)); return d; }
__device__ __forceinline__ bool tags_ok(uint32_t bad, uint32_t mask = 1) {
    uint32_t r;
    asm volatile("{\n.reg .pred P;\n.reg .b32 x;\nand.b32 x, %1, %2;\nsetp.ne.b32 P, x, 0;\nvote.sync.any.pred P, P, 0xffffffff;\nselp.u32 %0, 0, 1, P;\n}" : "=r"(r) : "r"(bad), "r"(mask));
    return r;
}
constexpr int SROW = 56;
#define PREA 8
#define PREB 9
#define RING1 6
#define RING2 7
#define RING3 8
#define PRE2 10
#define PRE2A 0
#define PRE3 0
#define EFENCE 0
#define RFENCE 1
#define PROG 16
#define EARLY 0
#define LAG 4
#define PUT1 33
#define DEPS 3
#define ADELAY 120
#define BDELAY 0
#define HOLD 1
#define XDELAY 330
#define FENCEA 0x80
#define FENCEB 0x80
#define FENCE2 0x110
#define OFENCE 1
#define MASK3 0x57
#define MASK4 0x55
#define MASK5 0x25
#define OFF3 0x5320
#define OFF4 0x6420
#define OFF5 0x0520
#define RESA (NRA == 3 ? 15 : NRA == 4 ? 3 : 0)
#define RESB (NRB == 3 ? 0xcc : NRB == 4 ? 0x30 : 0)
#define RESB1 (NRB == 3 ? 0xcc : NRB == 4 ? 0xc : 0)
__host__ __device__ constexpr int smem_mask(int NR) { return NR == 3 ? MASK3 : NR == 4 ? MASK4 : MASK5; }
__host__ __device__ constexpr bool round_smem(int r, int NR) { return smem_mask(NR) >> r & 1; }
__host__ __device__ constexpr int kord(int r, int NR) { int c = 0; for (int i = 0; i < r; i++) c += round_smem(i, NR) == round_smem(r, NR); return round_smem(r, NR) ? NR + c : c; }
__host__ __device__ constexpr int slot_r(int n, int NR) { return n < 32 ? n >> 2 : (((n & 31) >> 2) + ((NR == 3 ? OFF3 : NR == 4 ? OFF4 : OFF5) >> (n & 3) * 4)) & 7; }
__host__ __device__ constexpr int slot_k(int n, int NR) { return kord(slot_r(n, NR), NR); }
__host__ __device__ constexpr int slot_sord(int n, int NR) { int c = 0; for (int i = 0; i < n; i++) c += slot_k(i, NR) >= NR; return c; }
__host__ __device__ constexpr int sfrag_slot(int q, int NR) { for (int n = 0; n < 64; n++) if (slot_k(n, NR) >= NR && slot_sord(n, NR) == q) return n; return -1; }
__host__ __device__ constexpr int w1_loaded(int n, int NR, int PRE) {
    int q = PRE;
    for (int i = 0; i <= n; i++) q += q < (8 - NR) * 8 && q - slot_sord(i + 1, NR) < (i < 32 ? RING1 : RING2);
    return q;
}
template <int Q, int NR>
__device__ __forceinline__ void load_w1(uint32_t* w, const uint32_t* a) {
    constexpr int n = sfrag_slot(Q, NR);
    ldsm4t(w, a[n & 3] + ((slot_k(n, NR) - NR) * 2 + (n >> 5)) * 2048);
}
constexpr int AB = NRA < 5, BB = 3 - AB;
__device__ __forceinline__ bool w2_full(int role, int warp) { return warp < (role == 2 ? 2 : 3); }
__device__ __forceinline__ int w2_nblk(int role, int warp) { return warp < 4 ? BB - !w2_full(role, warp) : AB; }
__host__ __device__ constexpr int w2_step(bool full, int i) { return AB ? (full ? -2 * i : 0) : full ? (i == 0 ? 0 : i == 1 ? 16 - 2 * EARLY : 18 - 2 * EARLY) : i; }
__device__ __forceinline__ int w2_block(int role, int warp) {
    const int f = role * 3 + warp, g = role == 2 ? warp : role;
    if (AB) return warp >= 4 ? 16 + role * 4 + (warp - 4) : w2_full(role, warp) ? 4 * (f >> 1) + (f & 1) + 2 : 28 + g;
    return w2_full(role, warp) ? EARLY + 4 * (f >> 1) + (f & 1) : EARLY + 2 + 4 * g;
}
__device__ __forceinline__ int w2_res(int role, int warp) { return warp >= 4 ? RESA : w2_full(role, warp) ? RESB : RESB1; }
__device__ __forceinline__ int w2_units(int role, int warp) { return w2_nblk(role, warp) * 4 - (5 - (warp < 4 ? NRB : NRA)) * 2; }
constexpr int W2B = (BB * 4 - (5 - NRB) * 2) * 2048, W2A = (AB * 4 - (5 - NRA) * 2) * 2048;
static_assert(S_W2 + 4 * W2B - 8192 + 4 * W2A == S_KV, "weights");
__device__ __forceinline__ int w1_base(int warp) { return S_W1 + (warp < 4 ? warp * (8 - NRB) : 4 * (8 - NRB) + (warp - 4) * (8 - NRA)) * 4096; }
__device__ __forceinline__ int w2_base(int warp) { return S_W2 + (warp < 4 ? warp * W2B : 4 * W2B - 8192 + (warp - 4) * W2A); }
__device__ __forceinline__ void chain_load(const Params& P, uint32_t sb, int cta, int warp, int lane, int round) {
    const int role = cta % 3, h = cta / 3;
    if (lane == 0) {
        mbar_expect(sb + B_INIT, round ? (8 - (warp < 4 ? NRB : NRA)) * 4096 : 20480);
        if (round) mbar_expect(sb + B_INIT2, w2_units(role, warp) * 2048);
        int mask = (warp < 4 ? smem_mask(NRB) : smem_mask(NRA)) ^ (round ? 0 : 255);
        uint32_t dst = sb + (round ? w1_base(warp) : warp * 20480);
#pragma unroll 1
        for (int r = 0; r < 8; r++)
            if (mask >> r & 1) { tma3d(dst, &P.tm[M_C1 + role], 0, warp * 128 + r * 16, h * 2, sb + B_INIT); dst += 4096; }
        if (round) dst = sb + w2_base(warp);
        mask = w2_res(role, warp) ^ (round ? 0xfff : 0);
#pragma unroll 1
        for (int i = 0; i < w2_nblk(role, warp) * 4; i++)
            if (mask >> i & 1) { tma2d(dst, &P.tm[M_CO], (w2_block(role, warp) + w2_step(w2_full(role, warp), i >> 2)) * 32, h * 128 + (i & 3) * 32, sb + (round ? B_INIT2 : B_INIT)); dst += 2048; }
    }
    __syncwarp();
}

__device__ __forceinline__ void put_partials(bool TR, uint32_t a, const float* x, const float* y) {
    if (TR) stsm4t(a, pack2(x[0], x[1]), pack2(x[2], x[3]), pack2(y[0], y[1]), pack2(y[2], y[3]));
    else stsm4(a, pack2(x[0], x[1]), pack2(x[2], x[3]), pack2(y[0], y[1]), pack2(y[2], y[3]));
}
template <int NR, int PRE, int FM, int B, int E>
__device__ __forceinline__ void project(float (*acc)[4], bool TR, const uint32_t (*wr)[4], uint32_t (*as)[4], uint32_t (*v)[4], uint32_t* x, const uint32_t* w1a, uint32_t pp, uint32_t zero) {
    static_for<B, E>([&](auto I) {
        constexpr int n = I.value, kk = slot_k(n, NR), T = (n >> 5) * 4 + (n & 3), so = slot_sord(n, NR), q = w1_loaded(n - 1, NR, PRE);
        constexpr bool sm = kk >= NR;
        const uint32_t* w = sm ? as[so] : wr[sm ? 0 : (kk * 2 + (n >> 5)) * 4 + (n & 3)];
        if constexpr (n == 32 && PUT1 < 32) { put_partials(TR, pp, acc[0], acc[1]); put_partials(TR, pp + 4096, acc[2], acc[3]); }
        if constexpr (n == 0) {
            const uint32_t c = prmt(v[0][3], x[0], 0x3254);
            v[0][0] = h2bf(v[0][0], v[0][0]); v[0][1] = h2bf(v[0][1], v[0][1]); v[0][2] = h2bf(v[0][2], v[0][2]); v[0][3] = h2bf(v[0][3], x[0]);
            x[0] = c;
        }
        if constexpr ((n & 31) < 4) acc[T][0] = acc[T][1] = acc[T][2] = acc[T][3] = 0.f;
        mma16816(acc[T], w[0], w[1], w[2], w[3], v[slot_r(n, NR) >> 1][(slot_r(n, NR) & 1) * 2], v[slot_r(n, NR) >> 1][(slot_r(n, NR) & 1) * 2 + 1]);
        if constexpr (n == DEPS) {
            const uint32_t sel = __float_as_uint(acc[T][0]) * zero + 0x7610;
#pragma unroll
            for (int b = 1; b < 4; b++) cvt_block(v[b], x[b], sel);
        }
        if constexpr (w1_loaded(n, NR, PRE) > q) load_w1<q, NR>(as[q], w1a);
        if constexpr (n == PUT1 && n >= 32) { put_partials(TR, pp, acc[0], acc[1]); put_partials(TR, pp + 4096, acc[2], acc[3]); }
        if constexpr (n % 4 == 3 && (FM >> (n / 4) & 1) && n != E - 1) sched_fence();
    });
    if constexpr (E == 64) { put_partials(TR, pp + 8192, acc[4], acc[5]); put_partials(TR, pp + 12288, acc[6], acc[7]); }
}
__device__ __forceinline__ void reduce8(const uint32_t (*x)[4], const uint32_t* sel, float sc, uint32_t& r0, uint32_t& r1) {
    float d[4][4];
#pragma unroll
    for (int i = 0; i < 4; i++) {
        d[i][0] = d[i][1] = d[i][2] = d[i][3] = 0.f;
        mma16816(d[i], x[i][0], x[i][1], x[i][2], x[i][3], sel[2 * i], sel[2 * i + 1]);
    }
    r0 = pack2(((d[0][0] + d[1][0]) + (d[2][0] + d[3][0])) * sc, ((d[0][1] + d[1][1]) + (d[2][1] + d[3][1])) * sc);
    r1 = pack2(((d[0][2] + d[1][2]) + (d[2][2] + d[3][2])) * sc, ((d[0][3] + d[1][3]) + (d[2][3] + d[3][3])) * sc);
}

#define ISTAMP(i)
__host__ __device__ constexpr int wo_count(int n, int RES, bool res) { int c = 0; for (int i = 0; i < n; i++) c += (RES >> (i >> 2) & 1) == res; return c; }
__host__ __device__ constexpr int wo_loaded(int n, int RES, int PRE, int end) { int q = PRE; for (int i = 0; i <= n; i++) q += q < end && q - wo_count(i + 1, RES, false) < RING3; return q; }
template <int Q>
__device__ __forceinline__ void load_w2(uint32_t* w, const uint32_t* a) { ldsm4t(w, a[Q & 1] + (Q >> 1) * 1024); }
template <int NB, int RES, int PRE, int FM>
__device__ __forceinline__ void wo_blocks(uint32_t (*w)[4], const uint32_t (*wp)[4], uint32_t oa, const uint32_t* wa, const uint8_t* dst, const uint8_t* dsd, bool odd) {
    float a[NB][4][4];
    uint32_t o[4][4];
    bar_sync(3, 256);
#pragma unroll
    for (int i = 0; i < 4; i++) ldsm4(o[i], oa + i * 512);
    if (FM & 1) sched_fence();
    static_for<0, NB * 16>([&](auto I) {
        constexpr int n = I.value, i = n & 15, end = wo_count(NB * 16, RES, false), q = wo_loaded(n - 1, RES, PRE, end);
        constexpr bool res = RES >> (n >> 2) & 1;
        const uint32_t* b = o[i >> 2] + (i & 2);
        const uint32_t* x = res ? wp[wo_count(n, RES, true)] : w[wo_count(n, RES, false)];
        float* d = a[n >> 4][i & 3];
        if constexpr (i < 4) d[0] = d[1] = d[2] = d[3] = 0.f;
        mma16816(d, x[0], x[1], x[2], x[3], b[0], b[1]);
        if constexpr (wo_loaded(n, RES, PRE, end) > q) load_w2<q>(w[q], wa);
        if constexpr (n == NB * 16 - 1 || (n >= 16 && i == LAG - 1)) {
            constexpr int k = n == NB * 16 - 1 ? NB - 1 : (n >> 4) - 1;
            const float (*e)[4] = a[k];
            const uint32_t y = pack2h(e[1][2] + e[3][2], e[1][3] + e[3][3]);
            constexpr int bs = w2_step(NB == BB, k);
            red_add4(dst + bs * 2048, movm(pack2h(e[0][0] + e[2][0], e[0][1] + e[2][1])), movm(pack2h(e[0][2] + e[2][2], e[0][3] + e[2][3])),
                     movm(pack2h(e[1][0] + e[3][0], e[1][1] + e[3][1])), movm(odd ? ONES : y));
            red_add1(dsd + (bs >> 1) * 1024 + (bs & 1) * 256, movm(odd ? y : ONES));
        }
        if constexpr (((FM >> (n / 4 + 1)) & 1) && (n & 3) == 3 && n != NB * 16 - 1) sched_fence();
    });
}
template <bool ATT>
__device__ __forceinline__ void chain_role(const Params& P, const uint32_t sb, const int cta, const int warp, const int lane, const uint32_t epoch) {
    constexpr int NR = ATT ? NRA : NRB, PRE = ATT ? PREA : PREB;
    const int h = cta / 3, ROLE = cta - h * 3;
    uint32_t wr[40][4];
#define FRAG1(ln) ((((ln) & 7) + ((ln) >> 4) * 8) * 128 + ((((((ln) >> 3) & 1) << (ROLE == 1)) ^ ((ln) & 7)) << 4))
#define FRAG2(ln) ((((ln) & 7) + ((ln) >> 4) * 8) * 64 + (((((ln) >> 3) & 1) ^ (((ln) >> 1) & 3)) << 4))
#define TILE_X(i) (ROLE == 1 ? (((i) >> 1) << 6) | (((i) & 1) << 4) : (i) << 5)
    {
        const uint32_t st = sb + warp * 20480;
        mbar_wait(sb + B_INIT, 0);
        ISTAMP(0)
#pragma unroll
        for (int f = 0; f < 40; f++)
            ldsm4t(wr[f], f < NR * 8 ? st + (f >> 2) * 2048 + (FRAG1(lane) ^ TILE_X(f & 3)) : st + NR * 4096 + ((f - NR * 8) >> 1) * 1024 + (FRAG2(lane) ^ ((f & 1) << 5)));
        fence_async_smem();
        bar_sync(1, 256);
        chain_load(P, sb, cta, warp, lane, 1);
        ISTAMP(1)
        uint32_t m1 = 0, m2 = 0, u[4];
#pragma unroll
        for (int f = 0; f < 40; f++) { if (f < NR * 8) m1 = amax4(m1, wr[f]); else m2 = amax4(m2, wr[f]); }
        ISTAMP(5)
        mbar_wait(sb + B_INIT, 1);
        ISTAMP(3)
        if (ROLE == 2) {
#pragma unroll 4
            for (int i = 0; i < S_W2 / 4096; i++) { lds128(u, sb + S_W1 + warp * (S_W2 / 8) + i * 512 + lane * 16); m1 = amax4(m1, u); }
        }
        mbar_wait(sb + B_INIT2, 0);
        ISTAMP(7)
        const int n = w2_units(ROLE, warp) * 4;
#pragma unroll 8
        for (int i = 0; i < n; i++) { lds128(u, sb + w2_base(warp) + i * 512 + lane * 16); m2 = amax4(m2, u); }
        m1 = warp_exp(m1); m2 = warp_exp(m2);
        if (lane == 0) { if (ROLE == 2) red_max_shared(sb + S_EV, m1); red_max_shared(sb + S_EO, m2); }
    }
    ISTAMP(6)
    uint32_t l8 = opq(sb + lane * 8, lane);
    const uint8_t* persu = (const uint8_t*)((ROLE == 1 ? g_km : g_vmt) + h * 512) - (sb >> 1);
    auto persist = [&](int s, int tile, uint32_t r0, uint32_t r1) {
        uint32_t* pp = (uint32_t*)(persu + s * 65536 + (ROLE == 1 ? (tile >> 1) * 512 + (tile & 1) * 128 : tile * 256) + (l8 >> 1));
        pp[0] = r0; pp[ROLE == 1 ? 64 : 32] = r1;
    };
    const uint32_t rk0 = (h & 1) * 3, rd1 = __shfl_sync(0xffffffffu, mapa(sb, rk0 + (ROLE + 1) % 3) - sb, 0), rd2 = __shfl_sync(0xffffffffu, mapa(sb, rk0 + (ROLE + 2) % 3) - sb, 0);
    const uint32_t xo = (ROLE == 2 ? S_XV : S_X + ROLE * 2048) + warp * 256;
    const bool full = w2_full(ROLE, warp);
    const int blk = w2_block(ROLE, warp);
    const uint32_t om = blk * 2048, os = xg_side(blk);
    const uint32_t w1o = sb + w1_base(warp), w2o = sb + w2_base(warp);
    ISTAMP(2)
    if (lane == 0) mbar_arrive(sb + B_READY);
#pragma unroll 1
    for (int s = 0;; s++) {
        l8 += s & P.zero;
        uint32_t r0, r1;
        {
            uint32_t v[4][4], as[(8 - NR) * 8][4], w1a[4];
            float acc[8][4];
            const uint32_t pst = sb + S_P1 + (l8 - sb) * 16 + ((warp * 16) ^ ((l8 & 56) * 2));
#pragma unroll
            for (int i = 0; i < 4; i++) w1a[i] = w1o + (FRAG1((l8 - sb) >> 3) ^ TILE_X(i));
            auto preload = [&]() { static_for<0, PRE>([&](auto I) { load_w1<I.value, NR>(as[I.value], w1a); }); };
#pragma unroll 1
            while (true) {
                uint32_t x[4];
                preload();
                const uint32_t lm = opq(l8 - sb, (l8 - sb) >> 3);
                const uint8_t* pm = P.xb + xg_buf(s) + warp * 8192 + xg_lane(lm >> 3);
                const uint8_t* ps = P.xb + xg_buf(s) + XG_SIDE + warp * 2048 + (lm >> 1);
                pin_ptr(pm); pin_ptr(ps);
                mbar_wait(sb + B_RELM, s & 1);
                if (ATT ? ADELAY : BDELAY) wait_clocks(ATT ? ADELAY : BDELAY);
                PROF(10)
#pragma unroll
                for (int b = 0; b < 4; b++) { ld_relaxed4(v[b], pm + b * 2048); ld_relaxed1n(x[b], ps + (b >> 1) * 1024 + (b & 1) * 256); }
                project<NR, PRE, ATT ? FENCEA : FENCEB, 0, PROG>(acc, ROLE == 2, wr, as, v, x, w1a, pst, P.zero);
                const uint32_t bad = xor_or(x[0], x[1], FULL) | xor_or(x[2], x[3], FULL);
                if (tags_ok(bad, 0xffffffffu)) break;
                COUNT_RETRY(warp >> 1)
                uint32_t n;
                asm volatile("atom.shared.add.u32 %0, [%1], 1;" : "=r"(n) : "r"(sb + S_RETRY) : "memory");
                if (n > SPIN_LIMIT) spin_fault();
            }
            PROF(0)
            sts32((l8 >> 1) + (sb - (sb >> 1) + S_EM + warp * 128), amax4(amax4(amax4(amax(amax(v[0][0], v[0][1]), amax(v[0][2], v[0][3])), v[1]), v[2]), v[3]));
            project<NR, PRE, ATT ? FENCEA : FENCEB, PROG, 64>(acc, ROLE == 2, wr, as, v, nullptr, w1a, pst, 0);
            PROF(1)
            const uint32_t isc = lds32(sb + S_ISC + (s & 1) * 4);
            const uint32_t lq = l8 + ((s >> 3) & P.zero);
            uint32_t x[4][4], sel[8], xd[6] = {l8 + xo, l8 + xo + rd1, l8 + xo + rd2, sb + B_X + rd1, sb + B_X + rd2, sb + S_P1 + warp * 2048 + (lq & 64) * 16 + (lq & 128) + (lq & 56) * 2};
#pragma unroll
            for (int i = 0; i < 8; i++) sel[i] = (lq & 224) == i * 32 ? 0x3F803F80u : 0u;
            pin<6>(xd); pin<8>(sel);
            if (RFENCE) sched_fence();
            bar_sync(1, 256);
#pragma unroll
            for (int i = 0; i < 4; i++) ldsm4t(x[i], xd[5] + i * 256);
            if (!ATT && l8 == sb + (warp - 3) * 1024) mbar_arrive(sb + B_P1);
            reduce8(x, sel, bf_hi(isc), r0, r1);
            st_async2(xd[1], r0, r1, xd[3], s != 63);
            st_async2(xd[2], r0, r1, xd[4], s != 63);
            sts64(xd[0], r0, r1);
            if (s == 63) { persist(s, warp, r0, r1); break; }
            if (!ATT && warp == 0) {
                uint32_t sc[2], u[2][4];
                lds64(sc, sb + S_SC);
                lds128(u[0], l8 * 2 + (S_EM - sb)); lds128(u[1], l8 * 2 + (S_EM + 512 - sb));
                const int em = warp_exp(amax4(amax(amax(u[0][0], u[0][1]), amax(u[0][2], u[0][3])), u[1]));
                if (l8 == sb) sts32(sb + S_ISC + (~s & 1) * 4, min(max(em + (int)(isc >> 23) - 127, (int)sc[1]) + (int)sc[0], 253) * 0x800080u);
            }
            __syncwarp();
            if (l8 == sb) mbar_arrive(sb + B_X);
            PROF(2)
        }
        uint32_t w[40][4], w2a[2], odd;
        const uint8_t *po, *pd;
        auto wo_addr = [&]() {
            const uint32_t lo = (l8 + ((s >> 2) & P.zero) - sb) >> 3;
            w2a[0] = w2o + FRAG2(lo); w2a[1] = w2o + (FRAG2(lo) ^ 32);
            po = P.xb + xg_buf(s + 1) + om + xg_lane(lo);
            pd = P.xb + xg_buf(s + 1) + os + lo * 4;
            odd = lo & 4;
            pin_ptr(po); pin_ptr(pd); pin<2>(w2a); pin<1>(&odd);
        };
        uint32_t oa = l8 * 2 + (S_OX - sb);
        if constexpr (ATT) {
            const uint32_t ln = (l8 + ((s >> 4) & P.zero) - sb) >> 3;
            const uint32_t va = sb + S_KV + 8192 + ((warp >> 1) & 1) * 4096 + ((ln & 7) + (ln >> 4) * 8) * 128 + ((((warp & 1) * 4 + ((ln >> 3) & 1)) ^ (ln & 7)) << 4);
            const uint32_t ka = sb + S_KV + (warp & 1) * 2048 + (ln & 15) * 128 + (((ln >> 4) ^ (ln & 7)) << 4);
            uint32_t ad[5] = {sb + S_SX + (ln & 3) * (8 * SROW) + (ln >> 2) * 4 + (warp < 6 ? (warp - 4) * 64 : 128 + (warp - 6) * 32), l8 + S_XV + (warp - 4) * 512,
                              l8 + S_SX + (ln >> 2) * (4 * SROW - 32), oa + (warp - 4) * 512, sb + S_ISC + (~s & 1) * 4};
            if constexpr (AB) { wo_addr(); pin<1>(&oa); }
            pin<5>(ad);
            const uint32_t sa = ad[0], sr = ad[2];
            uint32_t vf[4][4], vm[2][2], q[8][2];
            float S[4][4];
#pragma unroll
            for (int n = 0; n < 4; n++) { S[n][0] = S[n][1] = S[n][2] = S[n][3] = 0.f; }
            mbar_wait(sb + B_KVFULL, s & 1);
            if (warp < 6) {
                uint32_t kf[8][4];
#pragma unroll
                for (int k = 0; k < 8; k++) ldsm4(kf[k], (ka ^ ((k & 3) << 5)) + (k >> 2) * 4096);
#pragma unroll
                for (int i = 0; i < 4; i++) ldsm4t(vf[i], (va ^ ((i & 1) << 5)) + (i >> 1) * 2048);
                mbar_wait(sb + B_X, s & 1);
                PROF(11)
#pragma unroll
                for (int k = 0; k < 8; k++) lds64(q[k], l8 + S_X + k * 256);
#pragma unroll
                for (int k = 0; k < 8; k++) mma16816(S[k & 3], kf[k][0], kf[k][1], kf[k][2], kf[k][3], q[k][0], q[k][1]);
                sts32(sa, __float_as_uint((S[0][0] + S[1][0]) + (S[2][0] + S[3][0])));
                sts32(sa + 4 * SROW, __float_as_uint((S[0][1] + S[1][1]) + (S[2][1] + S[3][1])));
                sts32(sa + 32, __float_as_uint((S[0][2] + S[1][2]) + (S[2][2] + S[3][2])));
                sts32(sa + 4 * SROW + 32, __float_as_uint((S[0][3] + S[1][3]) + (S[2][3] + S[3][3])));
            } else {
#pragma unroll
                for (int i = 0; i < 4; i++) ldsm4t(vf[i], (va ^ ((i & 1) << 5)) + (i >> 1) * 2048);
                uint32_t xa = l8 + S_X + (warp - 6) * 1024;
                pin<1>(&xa);
                mbar_wait(sb + B_X, s & 1);
                PROF(11)
#pragma unroll
                for (int k = 0; k < 8; k++) lds64(q[k], xa + (k >> 2) * 2048 + (k & 3) * 256);
#pragma unroll
                for (int k = 0; k < 4; k++) mma16816(S[k], q[4 + (k & 2)][0], q[4 + (k & 2)][1], q[5 + (k & 2)][0], q[5 + (k & 2)][1], q[k][0], q[k][1]);
                sts32(sa, __float_as_uint((S[0][0] + S[2][0]) + (S[1][2] + S[3][2])));
                sts32(sa + 4 * SROW, __float_as_uint((S[0][1] + S[2][1]) + (S[1][3] + S[3][3])));
            }
            const uint32_t isn = lds32(ad[4]);
            lds64(vm[0], ad[1]); lds64(vm[1], ad[1] + 256);
            PROF(7)
            bar_sync(2, 128);
            const float cs = 0.08838834764831845f * 1.4426950408889634f;
            float E[6][2];
#pragma unroll
            for (int i = 0; i < 6; i++) lds64f(E[(i + 4) % 6], sr + ((i + 4) % 6) * 32);
            E[4][0] += E[5][0]; E[4][1] += E[5][1];
            float m = fmaxf(fmaxf(fmaxf(fmaxf(E[0][0], E[0][1]), fmaxf(E[1][0], E[1][1])), fmaxf(fmaxf(E[2][0], E[2][1]), fmaxf(E[3][0], E[3][1]))), fmaxf(E[4][0], E[4][1]));
            m = fmaxf(m, __shfl_xor_sync(0xffffffffu, m, 1));
            m = fmaxf(m, __shfl_xor_sync(0xffffffffu, m, 2));
            m *= cs;
            if constexpr (AB) static_for<0, PRE3>([&](auto I) { load_w2<I.value>(w[I.value], w2a); });
            uint32_t pa[5];
#pragma unroll
            for (int i = 0; i < 5; i++) { const int k = (i + 4) % 5; E[k][0] = ex2(fmaf(E[k][0], cs, -m)); E[k][1] = ex2(fmaf(E[k][1], cs, -m)); pa[k] = pack2(E[k][0], E[k][1]); }
            if (EFENCE) sched_fence();
            float O[2][4], Z[4];
#pragma unroll
            for (int i = 0; i < 4; i++) { O[0][i] = O[1][i] = Z[i] = 0.f; }
#pragma unroll
            for (int i = 0; i < 2; i++) {
                mma1688(O[i], vm[i][0], vm[i][1], pa[4]);
                mma16816(O[i], vf[i][0], vf[i][1], vf[i][2], vf[i][3], pa[0], pa[1]);
                mma16816(O[i], vf[2 + i][0], vf[2 + i][1], vf[2 + i][2], vf[2 + i][3], pa[2], pa[3]);
            }
            const float z = (((E[4][0] + E[4][1]) + (E[0][0] + E[0][1])) + ((E[1][0] + E[1][1]) + (E[2][0] + E[2][1]))) + (E[3][0] + E[3][1]);
            const float zh = __uint_as_float(__float_as_uint(z) & 0xffff0000u);
            mma1688(Z, isn, isn, pack2(zh, z - zh));
            const float i0 = rcp(Z[0]), i1 = rcp(Z[1]);
            stsm4t(ad[3], pack2(O[0][0] * i0, O[0][1] * i1), pack2(O[0][2] * i0, O[0][3] * i1), pack2(O[1][0] * i0, O[1][1] * i1), pack2(O[1][2] * i0, O[1][3] * i1));
            PROF(4)
            if constexpr (AB) wo_blocks<1, RESA, PRE3, OFENCE / 2>(w, wr + NR * 8, oa, w2a, po, pd, odd);
            else bar_arrive(3, 256);
            if (ROLE != 0) persist(s, warp, r0, r1);
            if (warp == 7 && l8 == sb) mbar_expect(sb + B_X, 4096);
        } else {
            if (ROLE != 0) persist(s, warp, r0, r1);
            wo_addr(); pin<1>(&oa);
            static_for<0, PRE2A>([&](auto I) { load_w2<I.value>(w[I.value], w2a); });
            mbar_wait(sb + B_X, s & 1);
            wait_clocks(XDELAY);
            constexpr int PRE1 = (BB - 1) * 16 - (5 - NRB) * 8 < PRE2 ? (BB - 1) * 16 - (5 - NRB) * 8 : PRE2;
            static_for<PRE2A, PRE1>([&](auto I) { load_w2<I.value>(w[I.value], w2a); });
            if (full) {
                static_for<PRE1, PRE2>([&](auto I) { load_w2<I.value>(w[I.value], w2a); });
                wo_blocks<BB, RESB, PRE2, FENCE2 * 2 + OFENCE % 2>(w, wr + NR * 8, oa, w2a, po, pd, odd);
            } else wo_blocks<BB - 1, RESB1, PRE1, FENCE2 * 2 + OFENCE % 2>(w, wr + NR * 8, oa, w2a, po, pd, odd);
        }
        PROF(5)
        if (l8 == sb) { sts32(sb + S_TO + warp * 4, gtime()); mbar_arrive(sb + B_RED); }
        if (HOLD) mbar_wait(sb + B_RED, s & 1);
        if (ROLE != 0 && (s & 3) == 3 && l8 == sb) mbar_arrive(sb + B_PERS);
        if (ROLE == 0 && s == 62) return;
    }
    __syncwarp();
    if (l8 == sb) mbar_arrive(sb + B_PERS);
}
#define WGLAG 0
#define IP(i)
struct Pipe { uint32_t stage, phase; };
struct Cons {
    uint32_t sb, rel;
    int wg, wq, lane, rank, pair;
    uint32_t atag, nst;
    Pipe p;
};
__device__ __forceinline__ void pipe_next(Pipe& p) { p.stage = (p.stage + 1) & (NSTAGE - 1); p.phase ^= (p.stage == 0); }
__device__ __forceinline__ void release(const Cons& c, uint32_t stage) { if (c.lane < 2) mbar_arrive_cluster(c.rel + stage * 8); }
__device__ __forceinline__ void wait_full(const Cons& c) { mbar_wait(c.sb + B_FULL + c.p.stage * 8, c.p.phase); }

enum { PEND_NONE = 0, PEND_KVO = 1, PEND_HT = 2, PEND_OUT = 3, PEND_OUTH = 4 };
struct Pend { uint32_t pk[64]; int kind, row, col, cnt; };

__device__ __forceinline__ void staging_wait(const Cons& c) { if (c.nst) mbar_wait(c.sb + B_SFREE + c.wg * 8, (c.nst - 1) & 1); }
__device__ __forceinline__ void staging_post(Cons& c, int kind, int row, int col, int cnt) {
    __syncwarp();
    if (c.lane == 0) {
        if (c.wq == 0) { const uint32_t x[4] = {(uint32_t)kind, (uint32_t)row, (uint32_t)col, (uint32_t)cnt}; sts128(c.sb + S_DESC + c.wg * 16, x); }
        mbar_arrive(c.sb + B_SFULL + c.wg * 8);
    }
    c.nst++;
}
template <int HF, bool KVONLY = false>
__device__ __forceinline__ void drain(const Params& P, Cons& c, const Pend& d) {
    const uint32_t* pk = d.pk + HF * 32;
    if (!KVONLY && d.kind >= PEND_OUT) {
        if (HF == 1 && d.kind == PEND_OUTH) return;
        float* o = P.out + (size_t)(d.row + c.wq * 16 + (c.lane >> 2)) * 2048 + d.col + HF * 128 + (c.lane & 3) * 2;
#pragma unroll
        for (int j = 0; j < 16; j++) {
            st_stream2(o + j * 8, bf_lo(pk[j * 2]), bf_hi(pk[j * 2]));
            st_stream2(o + 8 * 2048 + j * 8, bf_lo(pk[j * 2 + 1]), bf_hi(pk[j * 2 + 1]));
        }
    } else if (d.kind != PEND_NONE) {
        const bool ht = !KVONLY && d.kind == PEND_HT;
        const int hi = (c.lane >> 3) & 1;
        const uint32_t base = c.sb + S_STG + c.wg * 16384 + ((ht ? hi * 32 + c.wq * 8 : c.wq * 16 + hi * 8) + (c.lane & 7)) * 128;
        staging_wait(c);
#pragma unroll
        for (int j = 0; j < 8; j++) {
            const int ch = (j & 3) * 2 + (c.lane >> 4);
            stsm4(base + (j >> 2) * 8192 + ((ch ^ (c.lane & 7)) << 4), pk[j * 4], pk[j * 4 + 1], pk[j * 4 + 2], pk[j * 4 + 3]);
        }
        fence_async_smem();
        staging_post(c, d.kind, d.row, d.col + HF * 128, HF ? d.cnt : -1);
    }
}
__device__ __forceinline__ void drain_all(const Params& P, Cons& c, Pend& d) { drain<0>(P, c, d); drain<1>(P, c, d); d.kind = PEND_NONE; }

__device__ __forceinline__ void store_warp(const Params& P, uint32_t sb, int wg, int cta) {
    if (cta < 128) {
        const uint32_t e1 = ld_acquire(&g_cnt(C_EPOCH)) + 1;
        const uint4* x = (const uint4*)P.Bx + (cta * 2 + wg) * 1024 + (threadIdx.x & 31);
        uint32_t m = 0;
#pragma unroll 4
        for (int i = 0; i < 32; i++) { const uint4 u = __ldg(x + i * 32); m = amax(amax(m, amax(u.x, u.y)), amax(u.z, u.w)); }
        m = warp_exp(m);
        if (elect_one()) { atomicMax(&g_cnt(C_XMAX), e1 << 8 | m); red_release(&g_cnt(C_XCNT)); }
        __syncwarp();
    }
    const uint32_t stg = sb + S_STG + wg * 16384;
#pragma unroll 1
    for (uint32_t n = 0;; n++) {
        mbar_wait(sb + B_SFULL + wg * 8, n & 1);
        uint32_t x[4];
        lds128(x, sb + S_DESC + wg * 16);
#pragma unroll
        for (int i = 0; i < 4; i++) x[i] = __shfl_sync(0xffffffffu, x[i], 0);
        if (x[0] == PEND_NONE) break;
        const bool ht = x[0] == PEND_HT;
        const CUtensorMap* m = &P.tm[ht ? M_HTS : M_KVO];
        if (elect_one()) {
#pragma unroll
            for (int i = 0; i < 4; i++) tma_store2d(m, x[2] + (i >> 1) * 64, x[1] + (i & 1) * (ht ? 1024 : 32), stg + i * 4096);
            bulk_commit();
            bulk_wait_read();
            mbar_arrive(sb + B_SFREE + wg * 8);
            if ((int)x[3] >= 0) { bulk_wait_all(); fence_async(); red_release(&g_cnt(x[3])); }
        }
        __syncwarp();
    }
}

template <int N, int TA, int TB, bool FIRST>
__device__ __forceinline__ void issue_ktile(float* acc, const Cons& c) {
    wait_full(c);
    const uint32_t a = c.sb + c.p.stage * STAGE + c.wg * 8192, b = c.sb + c.p.stage * STAGE + 16384;
    const uint64_t da = mkdesc(a, TA ? 8192 : 16, 1024, 1), db = mkdesc(b, TB ? 8192 : 16, 1024, 1);
    wg_fence();
#pragma unroll
    for (int k = 0; k < 4; k++) {
        const uint64_t x = da + (TA ? 128 : 2) * k, y = db + (TB ? 128 : 2) * k;
        if (N == 256) { if (FIRST && k == 0) wgmma_ss256_first<TA, TB>(acc, x, y); else wgmma_ss256<TA, TB>(acc, x, y); }
        else { if (FIRST && k == 0) wgmma_ss128_first<TA, TB>(acc, x, y); else wgmma_ss128<TA, TB>(acc, x, y); }
    }
    wg_commit();
}
template <int N, bool FIRST>
__device__ __forceinline__ void issue_any(float* acc, const Cons& c, int type) {
    if (N == 256 && type == T_A1) issue_ktile<N, 0, 0, FIRST>(acc, c);
    else if (type == (N == 256 ? T_A2 : T_A2H)) issue_ktile<N, 1, 0, FIRST>(acc, c);
    else issue_ktile<N, 0, 1, FIRST>(acc, c);
}
template <int N, bool KVONLY = false>
__device__ __forceinline__ void mainloop(float* acc, const Params& P, Cons& c, Pend& d, int type) {
    const int nk = (type == T_OP || type == T_OPH) ? 64 : (type == T_A2 || type == T_A2H) ? 32 : 16;
    if (WGLAG && c.wg) bar_sync(7, 256);
    issue_any<N, true>(acc, c, type);
    if (!KVONLY) { IP(0) }
    if (WGLAG == 1 && !c.wg) bar_arrive(7, 256);
    drain<0, KVONLY>(P, c, d);
    uint32_t prev = c.p.stage;
    pipe_next(c.p);
    for (int kt = 1; kt < nk; kt++) {
        issue_any<N, false>(acc, c, type);
        if (WGLAG > 1 && kt == WGLAG - 1 && !c.wg) bar_arrive(7, 256);
        wg_wait<1>();
        release(c, prev);
        if (kt == 2) drain<1, KVONLY>(P, c, d);
        prev = c.p.stage;
        pipe_next(c.p);
    }
    d.kind = PEND_NONE;
    wg_wait<0>();
    pin<N / 2>(acc);
    release(c, prev);
    if (!KVONLY) { IP(1) }
}
__device__ __forceinline__ void pack_half(uint32_t* pk, const float* a) {
#pragma unroll
    for (int i = 0; i < 32; i++) pk[i] = pack2(a[2 * i], a[2 * i + 1]);
}

__device__ __forceinline__ void epi_kv(const float* acc, const Cons& c, Pend& d, int mb, int nb) {
    pack_half(d.pk, acc); pack_half(d.pk + 32, acc + 64);
    d.kind = PEND_KVO; d.row = (nb >> 4) * 2048 + mb * 256 + c.rank * 128 + c.wg * 64; d.col = (nb & 15) * 256; d.cnt = C_KV + mb;
}

__device__ __forceinline__ void qa_scores(float* S, float* Sm, const uint32_t* q, Cons& c) {
    wait_full(c);
    const uint32_t st = c.sb + c.p.stage * STAGE;
    const uint64_t dk = mkdesc(st + c.wg * 8192, 16, 1024, 1), dm = mkdesc(st + 32768 + c.wg * 4096, 128, 2048, 0);
    wg_fence();
#pragma unroll
    for (int i = 0; i < 8; i++) wgmma_rs64<0>(S, q + i * 4, dk + (i >> 2) * 1024 + (i & 3) * 2, i != 0);
#pragma unroll
    for (int i = 0; i < 8; i++) wgmma_rs16<0>(Sm, q + i * 4, dm + i * 16, i != 0);
    wg_commit();
    pipe_next(c.p);
}
__device__ __forceinline__ void qa_softmax(uint32_t (*pa)[4], const float* S, const float* Sm, const Cons& c) {
    const int t = c.lane & 3, i0 = (c.wq & 1) * 16 + (c.lane >> 2) - 2 * t;
    const bool sg = c.wq >= 2;
    const float cs = 0.08838834764831845f * 1.4426950408889634f;
    float x[2][10];
#pragma unroll
    for (int r = 0; r < 2; r++) {
#pragma unroll
        for (int j = 0; j < 4; j++)
#pragma unroll
            for (int e = 0; e < 2; e++) {
                const float v = sg ? S[16 + j * 4 + r * 2 + e] : S[j * 4 + r * 2 + e];
                x[r][j * 2 + e] = (j * 8 + e - r * 8 > i0) ? -1e9f / 0.08838834764831845f : v;
            }
        x[r][8] = sg ? Sm[4 + r * 2] : Sm[r * 2];
        x[r][9] = sg ? Sm[5 + r * 2] : Sm[1 + r * 2];
        float m = fmaxf(fmaxf(fmaxf(fmaxf(x[r][0], x[r][1]), fmaxf(x[r][2], x[r][3])), fmaxf(fmaxf(x[r][4], x[r][5]), fmaxf(x[r][6], x[r][7]))), fmaxf(x[r][8], x[r][9]));
        m = fmaxf(m, __shfl_xor_sync(0xffffffffu, m, 1));
        m = fmaxf(m, __shfl_xor_sync(0xffffffffu, m, 2));
        m *= -cs;
#pragma unroll
        for (int i = 0; i < 10; i++) x[r][i] = ex2(fmaf(x[r][i], cs, m));
        float sum = (((x[r][0] + x[r][1]) + (x[r][2] + x[r][3])) + ((x[r][4] + x[r][5]) + (x[r][6] + x[r][7]))) + (x[r][8] + x[r][9]);
        sum += __shfl_xor_sync(0xffffffffu, sum, 1);
        sum += __shfl_xor_sync(0xffffffffu, sum, 2);
        const float inv = rcp(sum);
#pragma unroll
        for (int i = 0; i < 10; i++) x[r][i] *= inv;
    }
#pragma unroll
    for (int ks = 0; ks < 2; ks++)
#pragma unroll
        for (int i = 0; i < 4; i++) {
            const uint32_t p = pack2(x[i & 1][ks * 4 + (i >> 1) * 2], x[i & 1][ks * 4 + (i >> 1) * 2 + 1]);
            pa[ks][i] = sg ? 0u : p;
            pa[2 + ks][i] = sg ? p : 0u;
        }
#pragma unroll
    for (int r = 0; r < 2; r++) {
        const uint32_t p = pack2(x[r][8], x[r][9]);
        pa[4][r] = sg ? 0u : p;
        pa[4][2 + r] = sg ? p : 0u;
    }
}
__device__ __forceinline__ void qa_values(float* O, uint32_t (*pa)[4], Cons& c) {
    wait_full(c);
    const uint32_t st = c.sb + c.p.stage * STAGE;
    const uint64_t dv = mkdesc(st + c.wg * 8192, 16384, 1024, 1), dm = mkdesc(st + 32768 + c.wg * 4096, 2048, 128, 0);
    pin<20>(&pa[0][0]);
    wg_fence();
#pragma unroll
    for (int ks = 0; ks < 4; ks++) wgmma_rs128<1>(O, pa[ks], dv + ks * 128, ks != 0);
    wgmma_rs128<0>(O, pa[4], dm, 1);
    wg_commit();
    pipe_next(c.p);
}
__device__ __forceinline__ void epi_qa(const float* acc, Cons& c, Pend& d, int mb, int nb) {
    uint32_t q[64], pa[2][5][4];
    float S0[32] = {}, M0[8] = {}, S1[32] = {}, M1[8] = {}, O0[64] = {}, O1[64] = {};
    const uint32_t k0 = c.p.stage;
    pack_half(q, acc);
    pin<32>(q); pin<32>(S0); pin<8>(M0);
    qa_scores(S0, M0, q, c);
    pack_half(q + 32, acc + 64);
    pin<32>(q + 32); pin<32>(S1); pin<8>(M1);
    qa_scores(S1, M1, q + 32, c);
    wg_wait<1>();
    pin<32>(S0); pin<8>(M0);
    release(c, k0);
    qa_softmax(pa[0], S0, M0, c);
    wg_wait<0>();
    pin<32>(S1); pin<8>(M1); pin<64>(q);
    release(c, (k0 + 1) & (NSTAGE - 1));
    pin<64>(O0);
    qa_values(O0, pa[0], c);
    qa_softmax(pa[1], S1, M1, c);
    pin<64>(O1);
    qa_values(O1, pa[1], c);
    wg_wait<1>();
    pin<64>(O0); pin<20>(&pa[0][0][0]);
    release(c, (k0 + 2) & (NSTAGE - 1));
    pack_half(d.pk, O0);
    wg_wait<0>();
    pin<64>(O1); pin<20>(&pa[1][0][0]);
    release(c, (k0 + 3) & (NSTAGE - 1));
    pack_half(d.pk + 32, O1);
    d.kind = PEND_KVO; d.row = 4096 + mb * 256 + c.rank * 128 + c.wg * 64; d.col = nb * 256; d.cnt = C_O + mb;
}

__device__ __forceinline__ void epi_op(const float* acc, const Cons& c, Pend& d, int mb, int nb) {
    pack_half(d.pk, acc); pack_half(d.pk + 32, acc + 64);
    d.kind = PEND_OUT; d.row = mb * 256 + c.rank * 128 + c.wg * 64; d.col = 1024 + nb * 256;
}

__device__ __forceinline__ void epi_oph(const float* acc, const Cons& c, Pend& d, int mb, int nb) {
    pack_half(d.pk, acc);
    d.kind = PEND_OUTH; d.row = mb * 256 + c.rank * 128 + c.wg * 64; d.col = 1024 + nb * 128;
}

template <int HF>
__device__ __forceinline__ void epi_a2_half(const float* acc, const Params& P, Cons& c, int mb, int col0) {
    const int g = c.lane >> 2, t = c.lane & 3;
    const int row = mb * 256 + (g >> 1) * 64 + (c.rank * 16 + c.wg * 8 + c.wq * 2) * 2 + (g & 1);
    float* o = P.out + (size_t)row * 2048 + col0 + HF * 128 + t * 2;
    wait_full(c);
    const uint32_t st = c.sb + c.p.stage * STAGE, xa = st + (c.wg * 64 + c.wq * 16 + g) * 128 + t * 4 + (g << 4), da = st + 32768 + t * 4;
#pragma unroll
    for (int j = 0; j < 16; j++) {
        const float* a = acc + HF * 64 + j * 4;
        const uint32_t ad = (xa ^ ((j & 7) << 4)) + (j >> 3) * 16384;
        const uint32_t x0 = lds32(ad), x1 = lds32(ad + 1024), dv = lds32(da + j * 16);
        const uint32_t u0 = mul_bf2(x0, dv), u1 = mul_bf2(x1, dv);
        st_stream2(o + j * 8, a[0] + bf_lo(u0), a[1] + bf_hi(u0));
        st_stream2(o + 2 * 2048 + j * 8, a[2] + bf_lo(u1), a[3] + bf_hi(u1));
    }
    __syncwarp();
    release(c, c.p.stage);
    pipe_next(c.p);
}

#define TSTAMP(i)
__device__ __forceinline__ float2 cmul(float2 a, float2 b) { return make_float2(fmaf(a.x, b.x, -a.y * b.y), fmaf(a.x, b.y, a.y * b.x)); }
__device__ __forceinline__ float2 cfma(float2 a, float2 b, float2 u) { return make_float2(fmaf(a.x, b.x, fmaf(-a.y, b.y, u.x)), fmaf(a.x, b.y, fmaf(a.y, b.x, u.y))); }
__device__ __forceinline__ float4 ssm_coef(float lre, float lim, float logdt) {
    const float dt = __bfloat162float(__float2bfloat16(expf(logdt)));
    const float ea = expf(dt * lre);
    float sn, cn;
    sincosf(dt * lim, &sn, &cn);
    const float br = ea * cn, bi = ea * sn, nr = br - 1.f;
    float cr, ci;
    if (fabsf(lre) >= fabsf(lim)) { const float r = lim / lre, dn = lre + lim * r; cr = (nr + bi * r) / dn; ci = (bi - nr * r) / dn; }
    else { const float r = lre / lim, dn = lre * r + lim; cr = (nr * r + bi) / dn; ci = (bi * r - nr) / dn; }
    return make_float4(br, bi, cr, ci);
}
__device__ __forceinline__ void epi_a1(const float* acc, const Params& P, const Cons& c, Pend& d, int mb, int nb, uint32_t atag, float4 cf) {
    const int t = c.lane & 3;
    const int p = nb * 128 + c.rank * 64 + c.wg * 32 + c.wq * 8 + (c.lane >> 2);
    TSTAMP(1)
    const float2 lam = make_float2(cf.x, P.swap_ri ? -cf.y : cf.y);
    const float a0 = P.swap_ri ? -2.f * cf.w : 2.f * cf.z, a1 = P.swap_ri ? 2.f * cf.z : -2.f * cf.w;
    const float b0 = P.swap_ri ? -2.f * cf.z : -2.f * cf.w, b1 = P.swap_ri ? -2.f * cf.w : -2.f * cf.z;
    float2 h = make_float2(0.f, 0.f);
#pragma unroll
    for (int round = 0; round < 2; round++) {
#pragma unroll
        for (int j = 0; j < 32; j++) {
            h = cfma(lam, h, make_float2(acc[j * 4], acc[j * 4 + 2]));
            const float r0 = fmaf(a0, h.x, a1 * h.y), m0 = fmaf(b0, h.x, b1 * h.y);
            h = cfma(lam, h, make_float2(acc[j * 4 + 1], acc[j * 4 + 3]));
            d.pk[j * 2] = pack2(r0, fmaf(a0, h.x, a1 * h.y));
            d.pk[j * 2 + 1] = pack2(m0, fmaf(b0, h.x, b1 * h.y));
        }
        if (round) break;
        float2 l64 = lam;
#pragma unroll
        for (int i = 0; i < 6; i++) l64 = cmul(l64, l64);
        const float2 l128 = cmul(l64, l64), l256 = cmul(l128, l128);
        float2 o = make_float2(__shfl_up_sync(0xffffffffu, h.x, 1), __shfl_up_sync(0xffffffffu, h.y, 1));
        if (t >= 1) h = cfma(l64, o, h);
        o = make_float2(__shfl_up_sync(0xffffffffu, h.x, 2), __shfl_up_sync(0xffffffffu, h.y, 2));
        if (t >= 2) h = cfma(l128, o, h);
        IP(2)
        if (t == 3) st_relaxed2(&g_agg[mb * 1024 + p], (__float_as_uint(h.x) & ~1u) | atag, __float_as_uint(h.y));
        h = make_float2(__shfl_up_sync(0xffffffffu, h.x, 1), __shfl_up_sync(0xffffffffu, h.y, 1));
        if (t == 0) h = make_float2(0.f, 0.f);
        uint32_t ax[7], ay[7];
        int n = 0;
        while (true) {
            uint32_t bad = 0;
#pragma unroll
            for (int j = 0; j < 7; j++) { ax[j] = atag; ay[j] = 0; ld_relaxed2_if(ax[j], ay[j], &g_agg[j * 1024 + p], j < mb); }
#pragma unroll
            for (int j = 0; j < 7; j++) bad |= ax[j] ^ atag;
            if (tags_ok(bad)) break;
            __nanosleep(400);
            if (++n > SPIN_LIMIT) spin_fault();
        }
        float2 carry = make_float2(0.f, 0.f);
#pragma unroll
        for (int j = 0; j < 7; j++) if (j < mb) carry = cfma(l256, carry, make_float2(__uint_as_float(ax[j]), __uint_as_float(ay[j])));
        float2 w = (t & 1) ? l64 : make_float2(1.f, 0.f);
        if (t & 2) w = cmul(w, l128);
        h = cfma(w, carry, h);
        IP(3)
    }
    IP(4)
    d.kind = PEND_HT; d.row = nb * 128 + c.rank * 64 + c.wg * 32; d.col = mb * 256; d.cnt = C_HT + mb;
}

__device__ __forceinline__ uint32_t fresh_tid() { uint32_t t; asm volatile("mov.u32 %0, %%tid.x;" : "=r"(t)); return t; }
__device__ __forceinline__ uint32_t acquire_stage(uint32_t sb, Pipe& p, uint32_t bytes) {
    mbar_wait(sb + B_EMPTY + p.stage * 8, p.phase ^ 1);
    mbar_expect_e(sb + B_FULL + p.stage * 8, bytes);
    return p.stage;
}
__device__ __forceinline__ void producer(const Params& P, const uint32_t sb, const int cta, const uint32_t epoch) {
    Pipe p = {0, 0};
    const uint32_t e1 = epoch + 1;
    const int rank = cta & 1;
    const uint16_t both = 3 << (__shfl_sync(0xffffffffu, cluster_rank(), 0) & ~1u);
    for (int it = ITEM_OFF(cta >> 1); it < ITEM_OFF((cta >> 1) + 1); it++) {
        const int item = ITEM(it), type = (item >> 8) & 7, mb = (item >> 5) & 7, nb = item & 31;
        if (type == T_CHAIN) {
            const int h = cta / 3, role = cta - h * 3;
            uint32_t* flag = &g_cnt(C_FLAG + (role == 2 ? 32 : 0) + h);
            if (role) { wait_count(&g_cnt(C_KV), e1 * 128); fence_async(); }
#pragma unroll 1
            for (int s = 0; s < 64 && role != 0; s++) {
                if (s < 63) {
                    mbar_wait(sb + B_GO, s & 1);
                    tma3d_mc_e(sb + S_KV + (role - 1) * 8192, &P.tm[M_SEG], 0, (role - 1) * 2048 + s * 32, h * 2, sb + B_KVFULL, 7 << ((h & 1) * 3));
                    if ((s & 7) == 7) { wait_count(&g_cnt(C_KV + 1 + (s >> 3)), e1 * 128); fence_async(); }
                    tma_prefetch3d_e(&P.tm[M_SEG], 0, (role - 1) * 2048 + s * 32 + 32, h * 2);
                }
                if (s > 0 && ((s & 3) == 0 || s == 63)) {
                    const int i = (s - 1) >> 2;
                    mbar_wait(sb + B_PERS, i & 1);
                    asm volatile("{\n.reg .pred E;\nelect.sync _|E, 0xffffffff;\n@E st.release.gpu.global.u32 [%0], %1;\n}" ::"l"(flag), "r"(epoch * 64 + i * 4 + 4) : "memory");
                }
            }
            if (role == 0) {
                const int lane = threadIdx.x & 31;
                if (lane == 0) mbar_arrive(sb + B_RELM);
#pragma unroll 1
                for (int s = 0; s < 63; s++) {
                    mbar_wait(sb + B_P1, s & 1);
                    if (s > 0) {
                        st_relaxed4(P.xb + xg_buf(s - 1) + h * 2048 + xg_lane(lane), 0, 0, 0, 0);
                        st_relaxed1(P.xb + xg_buf(s - 1) + xg_side(h) + lane * 4, 0);
                        __threadfence();
                    }
                    __syncwarp();
                    if (lane == 0) mbar_arrive(sb + B_RELM);
                }
            }
            mbar_wait(sb + B_RESUME, 0);
            continue;
        }
        const int m0 = mb * 256 + rank * 128;
        if (type <= T_OP) {
            const CUtensorMap* ma = &P.tm[type == T_OP ? M_OA : M_BX];
            const CUtensorMap* mw = &P.tm[type == T_OP ? M_WO : type == T_QA ? M_WQ : nb < 16 ? M_WK : M_WV];
            const int nk = type == T_OP ? 64 : 16, nc = (nb & 15) * 4 + rank * 2, ma0 = type == T_OP ? 4096 + m0 : m0;
            if (type == T_OP) { wait_count(&g_cnt(C_O + mb), e1 * 64); fence_async(); }
            if (type == T_QA) {
                wait_count(&g_cnt(C_KV + mb), e1 * 128);
                fence_async();
            }
            auto arrived = [&]() {
                const uint32_t t = fresh_tid();
                return __all_sync(0xffffffffu, (int32_t)(ld_acquire(&g_cnt(C_FLAG + (t & 2) * 16 + nb * 2 + (t & 1))) - (epoch * 64 + mb * 8 + rank * 4 + 4)) >= 0);
            };
            bool passed = false;
#pragma unroll 1
            for (int kt = 0; kt < nk; kt++) {
                if (type == T_QA && kt == 9) passed = arrived();
                const uint32_t st = acquire_stage(sb, p, STAGE), bar = sb + B_FULL + st * 8;
                tma2d_e(sb + st * STAGE, ma, kt * 64, ma0, bar);
                tma3d_mc_e(sb + st * STAGE + 16384 + rank * 16384, mw, 0, kt * 64, nc, bar, both);
                if (type == T_QA && kt < 8) tma_prefetch2d_e(&P.tm[M_OA], nb * 256 + (kt & 3) * 64, (kt >> 2) * 2048 + m0);
                pipe_next(p);
            }
            if (type == T_QA) {
                for (int n = 0; !passed; n++) { passed = arrived(); if (!passed) __nanosleep(200); if (n > SPIN_LIMIT) spin_fault(); }
                fence_async();
#pragma unroll 1
                for (int e = 0; e < 4; e++) {
                    const uint32_t st = acquire_stage(sb, p, 40960), bar = sb + B_FULL + st * 8, dst = sb + st * STAGE;
                    tma2d_e(dst, &P.tm[M_OA], nb * 256 + (e & 1) * 128, (e >> 1) * 2048 + m0, bar);
                    tma2d_e(dst + 16384, &P.tm[M_OA], nb * 256 + (e & 1) * 128 + 64, (e >> 1) * 2048 + m0, bar);
                    const uint32_t* src = ((e >> 1) ? g_vmt : g_km) + ((mb * 8 + rank * 4) * 32 + nb * 2 + (e & 1)) * 512;
#pragma unroll 1
                    for (int i = 0; i < 4; i++) bulk_g2s_e(dst + 32768 + i * 2048, src + i * 32 * 512, 2048, bar);
                    pipe_next(p);
                }
            }
        } else if (type == T_OPH) {
            wait_count(&g_cnt(C_O + mb), e1 * 64);
            fence_async();
#pragma unroll 1
            for (int kt = 0; kt < 64; kt++) {
                const uint32_t st = acquire_stage(sb, p, 32768), bar = sb + B_FULL + st * 8;
                tma2d_e(sb + st * STAGE, &P.tm[M_OA], kt * 64, 4096 + m0, bar);
                tma2d_mc_e(sb + st * STAGE + 16384 + rank * 8192, &P.tm[M_WOH], nb * 128 + rank * 64, kt * 64, bar, both);
                pipe_next(p);
            }
        } else if (type == T_A1) {
            wait_count(&g_cnt(C_COEF), e1 * 4);
#pragma unroll 1
            for (int kt = 0; kt < 16; kt++) {
                const uint32_t st = acquire_stage(sb, p, STAGE), bar = sb + B_FULL + st * 8;
                tma4d_e(sb + st * STAGE, &P.tm[M_AB], kt * 64, nb * 16 + rank * 8, bar);
                tma4d_mc_e(sb + st * STAGE + 16384 + rank * 16384, &P.tm[M_AX], kt * 64, mb * 128 + rank * 16, bar, both);
                pipe_next(p);
            }
        } else {
            wait_count(&g_cnt(C_HT + mb), e1 * 32);
            fence_async();
            const int hw = type == T_A2H ? 64 : 128;
            const CUtensorMap* mc = &P.tm[type == T_A2H ? M_CREH : M_CRE];
#pragma unroll 1
            for (int kt = 0; kt < 32; kt++) {
                const uint32_t st = acquire_stage(sb, p, 16384 + hw * 256), bar = sb + B_FULL + st * 8;
                tma3d_e(sb + st * STAGE, &P.tm[M_HT], 0, kt * 64, mb * 4 + rank * 2, bar);
                tma2d_mc_e(sb + st * STAGE + 16384 + rank * hw * 128, mc + (kt >> 4), (kt & 15) * 64, (nb * 2 + rank) * hw, bar, both);
                pipe_next(p);
            }
#pragma unroll 1
            for (int col = nb * 2 * hw; col < (nb + 1) * 2 * hw; col += 128) {
                const uint32_t st = acquire_stage(sb, p, 32768 + 256), bar = sb + B_FULL + st * 8;
                tma4d_e(sb + st * STAGE, &P.tm[M_AX], col, mb * 128 + rank * 16, bar);
                tma4d_e(sb + st * STAGE + 16384, &P.tm[M_AX], col + 64, mb * 128 + rank * 16, bar);
                bulk_g2s_e(sb + st * STAGE + 32768, P.Dskip + col, 256, bar);
                pipe_next(p);
            }
        }
    }
}

__device__ __forceinline__ uint32_t fresh_ctaid() { uint32_t t; asm volatile("mov.u32 %0, %%ctaid.x;" : "=r"(t)); return t; }
__device__ __forceinline__ void reset_state(const Params& P, Cons& c, Pend& d, uint32_t sb, bool resumed) {
    const uint32_t t = fresh_tid(), b = fresh_ctaid() + P.cta0;
    const int w = __shfl_sync(0xffffffffu, t >> 5, 0);
    c.sb = sb; c.wg = w >> 2; c.wq = w & 3; c.lane = t & 31;
    c.rank = __shfl_sync(0xffffffffu, b & 1, 0); c.pair = __shfl_sync(0xffffffffu, b >> 1, 0);
    c.rel = mapa(sb + B_EMPTY, cluster_rank() ^ (c.lane & 1));
    c.atag = (ld_acquire(&g_cnt(C_EPOCH)) + 1) & 1;
    c.p.stage = 0; c.p.phase = 0;
    c.nst = resumed && c.pair < NCHAIN ? 2 : 0;
    d = Pend{};
}
#define PROF_ITEM(i, item)

__global__ void __launch_bounds__(384, 1) fused_kernel(const __grid_constant__ Params P) {
    extern __shared__ __align__(1024) uint8_t smem[];
    const uint32_t sb = smem_u32(smem);
    asm volatile("griddepcontrol.launch_dependents;");
    declare_fence(P.zero);
    const int tid = threadIdx.x, lane = tid & 31;
    const int warp = __shfl_sync(0xffffffffu, tid >> 5, 0);
    const int cta = __shfl_sync(0xffffffffu, blockIdx.x + P.cta0, 0), pair = cta >> 1, rank = cta & 1;
    if (tid == 0) {
        if (sb & 1023) spin_fault();
        for (int i = 0; i < NSTAGE; i++) { mbar_init(sb + B_FULL + i * 8, 1); mbar_init(sb + B_EMPTY + i * 8, 16); }
        mbar_init(sb + B_RESUME, 2);
        mbar_init(sb + B_KVFULL, 1);
        mbar_init(sb + B_GO, 3); mbar_init(sb + B_RED, 8); mbar_init(sb + B_P1, 1); mbar_init(sb + B_PERS, 8); mbar_init(sb + B_INIT, 8); mbar_init(sb + B_INIT2, 8);
        mbar_init(sb + B_READY, 8);
        for (int i = 0; i < 2; i++) { mbar_init(sb + B_SFULL + i * 8, 4); mbar_init(sb + B_SFREE + i * 8, 1); }
        mbar_init(sb + B_RELM, cta % 3 ? 1 : 2); mbar_init(sb + B_X, 9);
        asm volatile("fence.mbarrier_init.release.cluster;" ::: "memory");
        mbar_expect(sb + B_X, 4096);
        sts64(sb + S_EV, 0, 0); sts32(sb + S_RETRY, 0);
    }
    cluster_sync();
    if (warp >= 8) {
        asm volatile("setmaxnreg.dec.sync.aligned.u32 24;");
        if (warp == 8) {
            producer(P, sb, cta, __shfl_sync(0xffffffffu, ld_acquire(&g_cnt(C_EPOCH)), 0));
            asm volatile("barrier.cluster.arrive.relaxed.aligned;\nbarrier.cluster.wait.aligned;" ::: "memory");
        } else if (warp == 9) {
            if (pair < 64) l2_prefetch((const char*)(rank ? P.Wo : P.Wq) + (size_t)(pair * 32 + lane) * 4096, 4096);
            if (pair < NCHAIN) pacer(P, sb, cta, lane, __shfl_sync(0xffffffffu, ld_acquire(&g_cnt(C_EPOCH)), 0));
        } else {
            store_warp(P, sb, warp - 10, cta);
        }
    } else {
        asm volatile("setmaxnreg.inc.sync.aligned.u32 240;");
        Cons c;
        Pend d;
        if (pair < NCHAIN) {
            reset_state(P, c, d, sb, false);
            {
                const int item = ITEM(ITEM_OFF(pair));
                PROF_ITEM(0, item)
                float acc[128];
                mainloop<256, true>(acc, P, c, d, T_KV);
                epi_kv(acc, c, d, (item >> 5) & 7, item & 31);
            }
            ISTAMP(4)
            bar_sync(1, 256);
            chain_load(P, sb, cta, warp, lane, 0);
            ISTAMP(9)
            drain<0, true>(P, c, d);
            drain<1, true>(P, c, d);
            ISTAMP(10)
            staging_wait(c);
            ISTAMP(11)
            PROF_ITEM(1, T_CHAIN << 8)
            const uint32_t epoch = __shfl_sync(0xffffffffu, ld_acquire(&g_cnt(C_EPOCH)), 0);
            if (warp < 4) chain_role<false>(P, sb, cta, warp, lane, epoch);
            else chain_role<true>(P, sb, cta, warp, lane, epoch);
            fence_async_smem();
            bar_sync(1, 256);
            const uint32_t t2 = fresh_tid();
            if (t2 < 2) mbar_arrive_cluster(mapa(sb + B_RESUME, cluster_rank() ^ t2));
        } else if (pair >= NPAIR - 2) {
            const int ch = (pair - (NPAIR - 2)) * 512 + rank * 256 + tid;
            g_coef[ch] = ssm_coef(__bfloat162float(P.Lre[ch]), __bfloat162float(P.Lim[ch]), __bfloat162float(P.logdt[ch]));
            bar_sync(1, 256);
            if (tid == 0) red_release(&g_cnt(C_COEF));
        }
        reset_state(P, c, d, sb, true);
        for (int it = ITEM_OFF(c.pair) + (c.pair < NCHAIN ? 2 : 0);; it++) {
            const bool last = it == ITEM_OFF(c.pair + 1);
            if (d.kind != PEND_NONE && (last || !bar_and(5 + c.wg, mbar_try(sb + B_FULL + c.p.stage * 8, c.p.phase)))) drain_all(P, c, d);
            if (last) break;
            const int item = ITEM(it), type = (item >> 8) & 7, mb = (item >> 5) & 7, nb = item & 31;
            PROF_ITEM(it - ITEM_OFF(c.pair), item)
            if (type >= T_OPH) {
                float acc[64];
                mainloop<128>(acc, P, c, d, type);
                if (type == T_OPH) epi_oph(acc, c, d, mb, nb);
                else epi_a2_half<0>(acc, P, c, mb, nb * 128);
            } else {
                float acc[128];
                float4 cf = {};
                if (type == T_A1) {
                    wait_full(c);
                    cf = __ldcg(&g_coef[nb * 128 + c.rank * 64 + c.wg * 32 + c.wq * 8 + (c.lane >> 2)]);
                }
                mainloop<256>(acc, P, c, d, type);
                if (type == T_KV) epi_kv(acc, c, d, mb, nb);
                else if (type == T_QA) epi_qa(acc, c, d, mb, nb);
                else if (type == T_OP) epi_op(acc, c, d, mb, nb);
                else if (type == T_A1) epi_a1(acc, P, c, d, mb, nb, c.atag, cf);
                else { epi_a2_half<0>(acc, P, c, mb, nb * 256); epi_a2_half<1>(acc, P, c, mb, nb * 256); }
                if (item & URGENT) drain_all(P, c, d);
            }
        }
        staging_wait(c);
        staging_post(c, PEND_NONE, 0, 0, 0);
        cluster_sync();
        if (c.wg == 0 && c.wq == 0 && c.lane == 0 && atomicInc(&g_cnt(C_DONE), NPAIR * 2 - 1) == NPAIR * 2 - 1) { __threadfence(); atomicAdd(&g_cnt(C_EPOCH), 1); }
    }
}

typedef CUresult (*EncodeFn)(CUtensorMap*, CUtensorMapDataType, cuuint32_t, void*, const cuuint64_t*, const cuuint64_t*, const cuuint32_t*, const cuuint32_t*,
                             CUtensorMapInterleave, CUtensorMapSwizzle, CUtensorMapL2promotion, CUtensorMapFloatOOBfill);
void encode(EncodeFn fn, CUtensorMap* m, const void* base, int rank, const uint64_t* dims, const uint64_t* strides, const uint32_t* box, CUtensorMapSwizzle swz = CU_TENSOR_MAP_SWIZZLE_128B) {
    cuuint64_t d[5], s[5]; cuuint32_t b[5], e[5];
    for (int i = 0; i < rank; i++) { d[i] = dims[i]; b[i] = box[i]; e[i] = 1; if (i) s[i - 1] = strides[i - 1]; }
    fn(m, CU_TENSOR_MAP_DATA_TYPE_BFLOAT16, rank, (void*)base, d, s, b, e, CU_TENSOR_MAP_INTERLEAVE_NONE, swz,
       CU_TENSOR_MAP_L2_PROMOTION_L2_256B, CU_TENSOR_MAP_FLOAT_OOB_FILL_NONE);
}
void map_kmajor(EncodeFn fn, CUtensorMap* m, const void* base, uint64_t rows, uint64_t cols, uint32_t box_rows) {
    const uint64_t d[2] = {cols, rows}, s[1] = {cols * 2}; const uint32_t b[2] = {64, box_rows};
    encode(fn, m, base, 2, d, s, b);
}
void map_mnmajor(EncodeFn fn, CUtensorMap* m, const void* base, uint64_t krows, uint64_t cols) {
    const uint64_t d[3] = {64, krows, cols / 64}, s[2] = {cols * 2, 128}; const uint32_t b[3] = {64, 64, 2};
    encode(fn, m, base, 3, d, s, b);
}

}

extern "C" void kernel_launch(void* const* d_in, const int* in_sizes, int n_in, void* d_out, int out_size) {
    static Params P;
    static EncodeFn fn = nullptr;
    if (!fn) {
        cudaDriverEntryPointQueryResult q;
        cudaGetDriverEntryPoint("cuTensorMapEncodeTiled", (void**)&fn, cudaEnableDefault, &q);
        cudaFuncSetAttribute(fused_kernel, cudaFuncAttributeMaxDynamicSharedMemorySize, S_TOTAL);
    }
    const bf16* in[15];
    for (int i = 0; i < 15; i++) in[i] = (const bf16*)d_in[i];
    void *kvo, *ht;
    cudaGetSymbolAddress(&kvo, g_kvo);
    cudaGetSymbolAddress(&ht, g_ht);
    map_kmajor(fn, &P.tm[M_BX], in[9], 2048, 1024, 128);
    map_mnmajor(fn, &P.tm[M_WQ], in[11], 1024, 4096);
    map_mnmajor(fn, &P.tm[M_WK], in[12], 1024, 4096);
    map_mnmajor(fn, &P.tm[M_WV], in[13], 1024, 4096);
    map_mnmajor(fn, &P.tm[M_WO], in[14], 4096, 1024);
    map_kmajor(fn, &P.tm[M_OA], kvo, 3 * 2048, 4096, 128);
    P.swap_ri = in[4] < in[3];
    {
        const bf16* lo = P.swap_ri ? in[4] : in[3];
        const uint64_t diff = (uint64_t)((const char*)(P.swap_ri ? in[3] : in[4]) - (const char*)lo);
        const uint64_t d[4] = {1024, 8, 2, 128}, s[3] = {2048, diff, 16384}; const uint32_t b[4] = {64, 8, 2, 8};
        encode(fn, &P.tm[M_AB], lo, 4, d, s, b);
    }
    {
        const uint64_t d[4] = {1024, 2, 4, 1024}, s[3] = {2048, 64 * 2048, 4096}; const uint32_t b[4] = {64, 2, 4, 16};
        encode(fn, &P.tm[M_AX], in[0], 4, d, s, b);
    }
    map_mnmajor(fn, &P.tm[M_HT], ht, 2048, 2048);
    map_kmajor(fn, &P.tm[M_CRE], in[5], 1024, 1024, 128);
    map_kmajor(fn, &P.tm[M_CIM], in[6], 1024, 1024, 128);
    map_kmajor(fn, &P.tm[M_KVO], kvo, 3 * 2048, 4096, 32);
    map_kmajor(fn, &P.tm[M_HTS], ht, 2048, 2048, 32);
    map_kmajor(fn, &P.tm[M_WOH], in[14], 4096, 1024, 64);
    map_kmajor(fn, &P.tm[M_CREH], in[5], 1024, 1024, 64);
    map_kmajor(fn, &P.tm[M_CIMH], in[6], 1024, 1024, 64);
    for (int i = 0; i < 3; i++) {
        const uint64_t d[3] = {64, 1024, 64}, s[2] = {8192, 128}; const uint32_t b[3] = {64, 16, 2};
        encode(fn, &P.tm[M_C1 + i], in[11 + i], 3, d, s, b);
    }
    {
        const uint64_t d[2] = {1024, 4096}, s[1] = {2048}; const uint32_t b[2] = {32, 32};
        encode(fn, &P.tm[M_CO], in[14], 2, d, s, b, CU_TENSOR_MAP_SWIZZLE_64B);
    }
    {
        const uint64_t d[3] = {64, 3 * 2048, 64}, s[2] = {8192, 128}; const uint32_t b[3] = {64, 32, 2};
        encode(fn, &P.tm[M_SEG], kvo, 3, d, s, b);
    }
    void* xs;
    cudaGetSymbolAddress(&xs, g_x);
    P.xb = (uint8_t*)(((uintptr_t)xs + (2u << 20) - 1) & ~(uintptr_t)((2u << 20) - 1));
    P.Wq = in[11]; P.Wk = in[12]; P.Wv = in[13]; P.Wo = in[14]; P.mem0 = in[10]; P.Bx = in[9];
    P.Ax = in[0]; P.Lre = in[1]; P.Lim = in[2]; P.logdt = in[7]; P.Dskip = in[8];
    P.out = (float*)d_out;
    int pv[10] = {1300, 0, 140, 0, 330, 0, 32, 32, 250, 0};
    P.dly = pv[0]; P.mrg = pv[2];
    P.rd = pv[4]; P.guard = pv[5]; P.clampv = pv[6]; P.clamp0 = pv[7]; P.kvd = pv[9]; P.zd = pv[8];
    cudaLaunchConfig_t cfg = {};
    cudaLaunchAttribute at[2];
    cfg.blockDim = dim3(384); cfg.dynamicSmemBytes = S_TOTAL; cfg.stream = cudaStreamPerThread; cfg.attrs = at;
    at[0].id = cudaLaunchAttributeClusterDimension;
    at[0].val.clusterDim.y = at[0].val.clusterDim.z = 1;
    at[1].id = cudaLaunchAttributeProgrammaticStreamSerialization;
    at[1].val.programmaticStreamSerializationAllowed = 1;
    for (int i = 0; i < 2; i++) {
        P.cta0 = i ? 2 * NCHAIN : 0;
        cfg.gridDim = dim3(i ? 2 * (NPAIR - NCHAIN) : 2 * NCHAIN);
        at[0].val.clusterDim.x = i ? 2 : 6;
        cfg.numAttrs = 1 + i;
        cudaLaunchKernelEx(&cfg, fused_kernel, P);
    }
}
```

```cpp
#include <cuda_runtime.h>
#include <cuda_bf16.h>
#include <cuda.h>
#include <stdint.h>
#include <string.h>

typedef __nv_bfloat16 bf16;

namespace {

constexpr int SPIN_LIMIT = 1 << 22;
constexpr int NPAIR = 66;
constexpr int NCHAIN = 48;
enum { T_KV = 0, T_QA = 1, T_OP = 2, T_A1 = 3, T_A2 = 4, T_CHAIN = 5, T_OPH = 6, T_A2H = 7 };
constexpr int URGENT = 2048;
enum { M_BX = 0, M_WQ, M_WK, M_WV, M_WO, M_OA, M_AB, M_AX, M_HT, M_CRE, M_CIM, M_KVO, M_HTS, M_OAH, M_HTH, M_C1, M_CO = M_C1 + 3, M_SEG, M_COUNT };
enum { C_KV = 0, C_O = 8, C_HT = 16, C_DONE = 24, C_EPOCH = 25, C_COEF = 26, C_XMAX = 27, C_XCNT = 28, C_FLAG = 32 };

struct Params {
    CUtensorMap tm[M_COUNT];
    const bf16 *Wq, *Wk, *Wv, *Wo, *mem0, *Bx, *Ax, *Lre, *Lim, *logdt, *Dskip;
    float* out;
    uint8_t* xb;
    int swap_ri, zero;
    int dly, mrg, rd, guard, clampv, clamp0, kvd, zd;
    uint16_t cta0;
};

__constant__ uint16_t c_off[67] = {0, 5, 10, 15, 20, 25, 30, 35, 40, 45, 50, 55, 60, 65, 70, 75, 80, 85, 90, 95, 100, 105, 110, 115, 120, 125, 130, 135, 140, 145, 150, 155, 160, 165, 170, 175, 180, 185, 190, 195, 200, 205, 210, 214, 218, 222, 226, 230, 234, 253, 272, 291, 310, 329, 348, 367, 386, 405, 424, 443, 462, 481, 500, 519, 537, 556, 574};
__constant__ uint16_t c_items[640] = {
    0, 1280, 2497, 3008, 1728, 1, 1280, 2498, 3009, 1732, 2, 1280, 2499, 3010, 1729, 32, 1280, 2500, 3011, 1733, 33, 1280, 2501, 3012,
    1730, 34, 1280, 2502, 3013, 1734, 3, 1280, 2503, 3014, 1731, 4, 1280, 2504, 3015, 1735, 5, 1280, 2505, 3040, 1760, 35, 1280, 2506,
    3041, 1764, 36, 1280, 2507, 3042, 1761, 37, 1280, 2508, 3043, 1765, 6, 1280, 2509, 3044, 1762, 7, 1280, 2510, 3045, 1766, 8, 1280,
    2511, 3046, 1763, 38, 1280, 2528, 3047, 1767, 39, 1280, 2529, 2886, 1024, 40, 1280, 2530, 2887, 1025, 9, 1280, 2531, 2912, 1026, 10,
    1280, 2532, 2913, 1027, 11, 1280, 2533, 2914, 1056, 41, 1280, 2534, 2915, 1057, 42, 1280, 2535, 2916, 1058, 43, 1280, 2536, 2917, 1059,
    12, 1280, 2537, 2918, 1088, 13, 1280, 2538, 2919, 1089, 14, 1280, 2539, 2944, 1090, 44, 1280, 2540, 2945, 1091, 45, 1280, 2541, 2946,
    1120, 46, 1280, 2542, 2947, 1121, 15, 1280, 2543, 2948, 1122, 16, 1280, 2821, 2949, 1123, 17, 1280, 2822, 2950, 1152, 47, 1280, 2823,
    2951, 1153, 48, 1280, 2848, 2976, 1154, 49, 1280, 2849, 2977, 1155, 18, 1280, 2850, 2978, 1184, 19, 1280, 2851, 2979, 1185, 20, 1280,
    2852, 2980, 1186, 50, 1280, 2853, 2981, 1187, 51, 1280, 2854, 2982, 1216, 52, 1280, 2855, 2983, 1217, 21, 1280, 2885, 642, 22, 1280,
    2884, 643, 23, 1280, 2883, 672, 53, 1280, 2882, 673, 54, 1280, 2881, 674, 55, 1280, 2880, 675, 24, 66, 84, 102, 256, 124,
    142, 160, 175, 191, 207, 224, 239, 298, 332, 366, 416, 2817, 610, 56, 67, 85, 103, 257, 125, 143, 161, 176, 192, 208,
    225, 240, 299, 333, 367, 417, 2818, 611, 25, 68, 86, 104, 258, 126, 144, 162, 177, 193, 209, 226, 241, 300, 334, 384,
    418, 2819, 640, 57, 69, 87, 105, 259, 127, 145, 163, 178, 194, 210, 227, 242, 301, 335, 385, 419, 2820, 641, 26, 70,
    88, 106, 260, 128, 146, 164, 179, 195, 211, 228, 243, 302, 352, 386, 420, 512, 1986, 58, 71, 89, 107, 261, 129, 147,
    165, 180, 196, 212, 229, 244, 303, 353, 387, 421, 513, 1990, 27, 72, 90, 108, 262, 130, 148, 166, 181, 197, 213, 230,
    245, 320, 354, 388, 422, 514, 1987, 59, 73, 91, 109, 263, 131, 149, 167, 182, 198, 214, 231, 246, 321, 355, 389, 423,
    515, 1991, 28, 74, 92, 110, 264, 132, 150, 168, 183, 199, 215, 232, 247, 322, 356, 390, 424, 544, 2016, 60, 75, 93,
    111, 265, 133, 151, 169, 184, 200, 216, 233, 248, 323, 357, 391, 425, 545, 2020, 29, 76, 94, 112, 266, 134, 152, 170,
    185, 201, 217, 234, 249, 324, 358, 392, 426, 546, 2017, 61, 77, 95, 113, 267, 135, 153, 171, 186, 202, 218, 235, 250,
    325, 359, 393, 427, 547, 2021, 30, 78, 96, 114, 268, 136, 154, 172, 187, 203, 219, 236, 251, 326, 360, 394, 428, 576,
    2018, 62, 79, 97, 115, 269, 137, 155, 173, 188, 204, 220, 237, 252, 327, 361, 395, 429, 577, 2022, 31, 80, 98, 116,
    270, 138, 156, 174, 189, 205, 221, 238, 253, 328, 362, 396, 430, 578, 2019, 63, 81, 99, 117, 271, 139, 157, 288, 190,
    292, 293, 296, 297, 331, 365, 399, 2816, 609, 64, 82, 100, 118, 120, 122, 140, 158, 289, 206, 222, 294, 254, 329, 363,
    397, 431, 579, 2023, 65, 83, 101, 119, 121, 123, 141, 159, 290, 291, 223, 295, 255, 330, 364, 398, 2496, 608,
};
#define ITEM_OFF(p) c_off[p]
#define ITEM(i) c_items[i]

__device__ __align__(1024) bf16 g_kvo[3 * 2048 * 4096];
__device__ __align__(1024) bf16 g_ht[2048 * 2048];
__device__ __align__(1024) uint8_t g_x[4 << 20];
__device__ __align__(1024) uint32_t g_km[64 * 32 * 512];
__device__ __align__(1024) uint32_t g_vmt[64 * 32 * 512];
__device__ __align__(1024) float2 g_agg[8 * 1024];
__device__ __align__(1024) float4 g_coef[1024];
__device__ __align__(1024) uint32_t g_cntl[128 * 32];
#define g_cnt(i) g_cntl[(i) * 32]
__device__ __align__(1024) uint32_t g_hint[96 * 32];
#define PROF(i)
#define PROFDUMP()
#define PROFP(i)
constexpr int XG_SIDE = 65536, XG_T = 98304;
__device__ __forceinline__ uint32_t xg_buf(int b) { return (b & 1) * 128 + (b & 2) * 256 + (b & 4) * 32768; }
__device__ __forceinline__ uint32_t xg_lane(uint32_t lane) { return (lane >> 4) * 1024 + (lane & 8) * 32 + (lane & 7) * 16; }
__device__ __forceinline__ uint32_t xg_side(int b) { return XG_SIDE + (b >> 1) * 1024 + (b & 1) * 256; }

constexpr int STAGE = 49152, NSTAGE = 4;
constexpr int S_STG = NSTAGE * STAGE;
constexpr int S_BAR = S_STG + 32768;
constexpr int B_FULL = S_BAR, B_EMPTY = S_BAR + 32, B_RESUME = S_BAR + 64, B_KVFULL = S_BAR + 72, B_GO = S_BAR + 88, B_X = S_BAR + 96, B_PERS = S_BAR + 104,
              B_INIT = S_BAR + 112, B_RELM = S_BAR + 120, B_READY = S_BAR + 136, B_SFULL = S_BAR + 144, B_SFREE = S_BAR + 160, S_DESC = S_BAR + 176, B_RED = S_BAR + 216;
constexpr int S_EV = S_BAR + 80, S_EO = S_BAR + 84, B_INIT2 = S_BAR + 128, S_SC = S_BAR + 208, S_ISC = S_EV;
constexpr int S_XV = S_BAR + 256, S_LOG = S_XV + 2048;
constexpr int S_TOTAL = S_LOG + 768;
#define NRA 5
#define NRB 3
constexpr int S_W1 = 0;
constexpr int S_W2 = 4 * 4096 * (16 - NRA - NRB);
constexpr int S_KV = 188416;
constexpr int S_P1 = S_KV + 16384;
constexpr int S_X = S_P1 + 16384;
constexpr int S_SX = S_P1, S_OX = S_P1 + 2048;
constexpr int S_EM = S_X + 4096, S_TO = S_EM + 1024, S_RETRY = S_BAR + 224, B_P1 = S_BAR + 232;
static_assert(S_TO + 32 <= S_BAR && S_KV % 1024 == 0 && S_TOTAL <= 232448, "chain smem layout");

template <int V> struct IC { static constexpr int value = V; };
template <int B, int E, typename F> __device__ __forceinline__ void static_for(F&& f) { if constexpr (B < E) { f(IC<B>{}); static_for<B + 1, E>(f); } }
__device__ __forceinline__ uint32_t cluster_rank() { uint32_t r; asm volatile("mov.u32 %0, %%cluster_ctarank;" : "=r"(r)); return r; }
__device__ __forceinline__ void spin_fault() { asm volatile("st.global.u32 [%0], 0;" ::"l"(0ull) : "memory"); }
__device__ __forceinline__ uint32_t smem_u32(const void* p) { return (uint32_t)__cvta_generic_to_shared(p); }
__device__ __forceinline__ uint32_t opq(uint32_t x, int lane) { return __shfl_sync(0xffffffffu, x, lane); }
__device__ __forceinline__ uint32_t mapa(uint32_t a, uint32_t r) { uint32_t d; asm volatile("mapa.shared::cluster.u32 %0, %1, %2;" : "=r"(d) : "r"(a), "r"(r)); return d; }
__device__ __forceinline__ void mma16816(float* d, uint32_t a0, uint32_t a1, uint32_t a2, uint32_t a3, uint32_t b0, uint32_t b1) {
    asm("mma.sync.aligned.m16n8k16.row.col.f32.bf16.bf16.f32 {%0,%1,%2,%3}, {%4,%5,%6,%7}, {%8,%9}, {%0,%1,%2,%3};"
        : "+f"(d[0]), "+f"(d[1]), "+f"(d[2]), "+f"(d[3]) : "r"(a0), "r"(a1), "r"(a2), "r"(a3), "r"(b0), "r"(b1));
}
__device__ __forceinline__ void mma1688(float* d, uint32_t a0, uint32_t a1, uint32_t b0) {
    asm("mma.sync.aligned.m16n8k8.row.col.f32.bf16.bf16.f32 {%0,%1,%2,%3}, {%4,%5}, {%6}, {%0,%1,%2,%3};"
        : "+f"(d[0]), "+f"(d[1]), "+f"(d[2]), "+f"(d[3]) : "r"(a0), "r"(a1), "r"(b0));
}
__device__ __forceinline__ void ldsm4(uint32_t* r, uint32_t a) {
    asm volatile("ldmatrix.sync.aligned.m8n8.x4.shared.b16 {%0,%1,%2,%3}, [%4];" : "=r"(r[0]), "=r"(r[1]), "=r"(r[2]), "=r"(r[3]) : "r"(a));
}
__device__ __forceinline__ void ldsm4t(uint32_t* r, uint32_t a) {
    asm volatile("ldmatrix.sync.aligned.m8n8.x4.trans.shared.b16 {%0,%1,%2,%3}, [%4];" : "=r"(r[0]), "=r"(r[1]), "=r"(r[2]), "=r"(r[3]) : "r"(a));
}
__device__ __forceinline__ void stsm4(uint32_t a, uint32_t r0, uint32_t r1, uint32_t r2, uint32_t r3) {
    asm volatile("stmatrix.sync.aligned.m8n8.x4.shared.b16 [%0], {%1,%2,%3,%4};" ::"r"(a), "r"(r0), "r"(r1), "r"(r2), "r"(r3) : "memory");
}
__device__ __forceinline__ void stsm4t(uint32_t a, uint32_t r0, uint32_t r1, uint32_t r2, uint32_t r3) {
    asm volatile("stmatrix.sync.aligned.m8n8.x4.trans.shared.b16 [%0], {%1,%2,%3,%4};" ::"r"(a), "r"(r0), "r"(r1), "r"(r2), "r"(r3) : "memory");
}
__device__ __forceinline__ uint32_t movm(uint32_t a) { uint32_t d; asm volatile("movmatrix.sync.aligned.m8n8.trans.b16 %0, %1;" : "=r"(d) : "r"(a)); return d; }
__device__ __forceinline__ uint32_t pack2(float lo, float hi) { uint32_t d; asm("cvt.rn.bf16x2.f32 %0, %1, %2;" : "=r"(d) : "f"(hi), "f"(lo)); return d; }
__device__ __forceinline__ uint32_t prmt(uint32_t a, uint32_t b, uint32_t s) { uint32_t d; asm("prmt.b32 %0, %1, %2, %3;" : "=r"(d) : "r"(a), "r"(b), "r"(s)); return d; }
__device__ __forceinline__ uint32_t pack2h(float lo, float hi) { uint32_t d; asm("cvt.rn.f16x2.f32 %0, %1, %2;" : "=r"(d) : "f"(hi), "f"(lo)); return d; }
__device__ __forceinline__ uint32_t h2bf(uint32_t a, uint32_t b) {
    uint32_t d;
    asm("{\n.reg .b16 l, h, u;\n.reg .f32 x, y;\nmov.b32 {l, u}, %1;\ncvt.f32.f16 x, l;\nmov.b32 {u, h}, %2;\ncvt.f32.f16 y, h;\ncvt.rn.bf16x2.f32 %0, y, x;\n}" : "=r"(d) : "r"(a), "r"(b));
    return d;
}
__device__ __forceinline__ void cvt_block(uint32_t* u, uint32_t& x, uint32_t sel) {
    const uint32_t a = prmt(u[0], u[0], sel), b = prmt(u[1], u[1], sel), c = prmt(u[2], u[2], sel), d = prmt(u[3], x, sel);
    x ^= u[3] ^ d;
    u[0] = h2bf(a, a); u[1] = h2bf(b, b); u[2] = h2bf(c, c); u[3] = h2bf(d, d);
}
__device__ __forceinline__ uint32_t amax(uint32_t a, uint32_t b) { uint32_t d; asm("max.xorsign.abs.bf16x2 %0, %1, %2;" : "=r"(d) : "r"(a), "r"(b)); return d; }
__device__ __forceinline__ uint32_t amax4(uint32_t m, const uint32_t* v) { return amax(amax(m, amax(v[0], v[1])), amax(v[2], v[3])); }
__device__ __forceinline__ uint32_t warp_exp(uint32_t m) { return __reduce_max_sync(0xffffffffu, max(m & 0x7f80u, (m >> 16) & 0x7f80u)) >> 7; }
__device__ __forceinline__ void red_max_shared(uint32_t a, uint32_t x) { asm volatile("red.shared.max.u32 [%0], %1;" ::"r"(a), "r"(x) : "memory"); }
__device__ __forceinline__ uint32_t mul_bf2(uint32_t a, uint32_t b) { uint32_t d; asm("mul.rn.bf16x2 %0, %1, %2;" : "=r"(d) : "r"(a), "r"(b)); return d; }
__device__ __forceinline__ float bf_lo(uint32_t u) { return __uint_as_float(u << 16); }
__device__ __forceinline__ float bf_hi(uint32_t u) { return __uint_as_float(u & 0xffff0000u); }
__device__ __forceinline__ float ex2(float x) { float y; asm("ex2.approx.ftz.f32 %0, %1;" : "=f"(y) : "f"(x)); return y; }
__device__ __forceinline__ float rcp(float x) { float y; asm("rcp.approx.ftz.f32 %0, %1;" : "=f"(y) : "f"(x)); return y; }
__device__ __forceinline__ void st_relaxed4(const void* p, uint32_t a, uint32_t b, uint32_t c, uint32_t d) {
    asm volatile("{\n.reg .b128 t;\nmov.b128 t, {%1,%2,%3,%4};\nst.relaxed.gpu.global.b128 [%0], t;\n}" ::"l"(p), "r"(a), "r"(b), "r"(c), "r"(d) : "memory");
}
__device__ __forceinline__ void st_relaxed2(const void* p, uint32_t a, uint32_t b) {
    asm volatile("{\n.reg .b64 t;\nmov.b64 t, {%1,%2};\nst.relaxed.gpu.global.b64 [%0], t;\n}" ::"l"(p), "r"(a), "r"(b) : "memory");
}
__device__ __forceinline__ void ld_relaxed2_if(uint32_t& a, uint32_t& b, const void* p, bool on) {
    asm volatile("{\n.reg .pred P;\n.reg .b64 t;\nsetp.ne.u32 P, %3, 0;\nmov.b64 t, {%0,%1};\n@P ld.relaxed.gpu.global.b64 t, [%2];\nmov.b64 {%0,%1}, t;\n}" : "+r"(a), "+r"(b) : "l"(p), "r"((uint32_t)on) : "memory");
}
__device__ __forceinline__ void ld_relaxed4(uint32_t* v, const void* p) {
    asm volatile("ld.relaxed.gpu.global.L1::no_allocate.v4.b32 {%0,%1,%2,%3}, [%4];" : "=r"(v[0]), "=r"(v[1]), "=r"(v[2]), "=r"(v[3]) : "l"(p) : "memory");
}
__device__ __forceinline__ void ld_relaxed1n(uint32_t& v, const void* p) { asm volatile("ld.relaxed.gpu.global.L1::no_allocate.b32 %0, [%1];" : "=r"(v) : "l"(p) : "memory"); }
__device__ __forceinline__ void red_add4(const void* p, uint32_t a, uint32_t b, uint32_t c, uint32_t d) {
    asm volatile("red.relaxed.gpu.global.add.noftz.v4.f16x2 [%0], {%1,%2,%3,%4};" ::"l"(p), "r"(a), "r"(b), "r"(c), "r"(d) : "memory");
}
__device__ __forceinline__ void red_add1(const void* p, uint32_t a) { asm volatile("red.relaxed.gpu.global.add.noftz.f16x2 [%0], %1;" ::"l"(p), "r"(a) : "memory"); }
__device__ __forceinline__ void ld_relaxed2(uint32_t* v, const void* p) {
    asm volatile("{\n.reg .b64 t;\nld.relaxed.gpu.global.L1::no_allocate.b64 t, [%2];\nmov.b64 {%0,%1}, t;\n}" : "=r"(v[0]), "=r"(v[1]) : "l"(p) : "memory");
}
__device__ __forceinline__ uint32_t ld_relaxed1(const void* p) { uint32_t v; asm volatile("ld.relaxed.gpu.global.u32 %0, [%1];" : "=r"(v) : "l"(p) : "memory"); return v; }
__device__ __forceinline__ void st_relaxed1(const void* p, uint32_t v) { asm volatile("st.relaxed.gpu.global.u32 [%0], %1;" ::"l"(p), "r"(v) : "memory"); }
__device__ __forceinline__ uint32_t ld_acquire(const void* p) { uint32_t v; asm volatile("ld.acquire.gpu.global.u32 %0, [%1];" : "=r"(v) : "l"(p) : "memory"); return v; }
__device__ __forceinline__ void red_relaxed(void* p) { asm volatile("red.relaxed.gpu.global.add.u32 [%0], 1;" ::"l"(p) : "memory"); }
__device__ __forceinline__ void red_release(void* p) { asm volatile("red.release.gpu.global.add.u32 [%0], 1;" ::"l"(p) : "memory"); }
__device__ __forceinline__ void st_stream2(float* p, float a, float b) { asm volatile("st.global.cs.v2.f32 [%0], {%1, %2};" ::"l"(p), "f"(a), "f"(b) : "memory"); }
__device__ __forceinline__ void fence_async() { asm volatile("fence.proxy.async.global;" ::: "memory"); }
__device__ __forceinline__ void fence_async_smem() { asm volatile("fence.proxy.async.shared::cta;" ::: "memory"); }
__device__ __forceinline__ void wait_count(const uint32_t* p, uint32_t target) {
    int n = 0;
    while ((int32_t)(ld_acquire(p) - target) < 0) { __nanosleep(200); if (++n > SPIN_LIMIT) spin_fault(); }
}
__device__ __forceinline__ void bar_sync(int id, int n) { asm volatile("bar.sync %0, %1;" ::"r"(id), "r"(n) : "memory"); }
__device__ __forceinline__ bool bar_and(int id, bool v) {
    uint32_t r;
    asm volatile("{\n.reg .pred P, Q;\nsetp.ne.u32 Q, %2, 0;\nbar.red.and.pred P, %1, 128, Q;\nselp.u32 %0, 1, 0, P;\n}" : "=r"(r) : "r"(id), "r"((uint32_t)v) : "memory");
    return r;
}
__device__ __forceinline__ void bar_arrive(int id, int n) { asm volatile("bar.arrive %0, %1;" ::"r"(id), "r"(n) : "memory"); }
__device__ __forceinline__ void lds128(uint32_t* v, uint32_t a) { asm volatile("ld.shared.v4.b32 {%0,%1,%2,%3}, [%4];" : "=r"(v[0]), "=r"(v[1]), "=r"(v[2]), "=r"(v[3]) : "r"(a) : "memory"); }
__device__ __forceinline__ uint32_t lds32(uint32_t a) { uint32_t v; asm volatile("ld.shared.b32 %0, [%1];" : "=r"(v) : "r"(a) : "memory"); return v; }
__device__ __forceinline__ void lds64(uint32_t* v, uint32_t a) { asm volatile("ld.shared.v2.b32 {%0,%1}, [%2];" : "=r"(v[0]), "=r"(v[1]) : "r"(a) : "memory"); }
__device__ __forceinline__ void lds64f(float* v, uint32_t a) { asm volatile("ld.shared.v2.f32 {%0,%1}, [%2];" : "=f"(v[0]), "=f"(v[1]) : "r"(a) : "memory"); }
__device__ __forceinline__ void sts128(uint32_t a, const uint32_t* v) { asm volatile("st.shared.v4.b32 [%0], {%1,%2,%3,%4};" ::"r"(a), "r"(v[0]), "r"(v[1]), "r"(v[2]), "r"(v[3]) : "memory"); }
__device__ __forceinline__ void sts64(uint32_t a, uint32_t x, uint32_t y) { asm volatile("st.shared.v2.b32 [%0], {%1,%2};" ::"r"(a), "r"(x), "r"(y) : "memory"); }
__device__ __forceinline__ void sts32(uint32_t a, uint32_t x) { asm volatile("st.shared.b32 [%0], %1;" ::"r"(a), "r"(x) : "memory"); }
__device__ __forceinline__ bool mbar_try(uint32_t b, uint32_t par) {
    uint32_t ok;
    asm volatile("{\n.reg .pred P;\nmbarrier.try_wait.parity.shared::cta.b64 P, [%1], %2;\nselp.u32 %0, 1, 0, P;\n}" : "=r"(ok) : "r"(b), "r"(par) : "memory");
    return ok;
}
__device__ __forceinline__ void mbar_wait(uint32_t b, uint32_t par) {
    asm volatile("{\n.reg .pred P, Q;\n.reg .u32 n;\nmov.u32 n, %2;\nW: mbarrier.try_wait.parity.shared::cta.b64 P, [%0], %1;\n"
                 "add.u32 n, n, -1;\nsetp.eq.u32 Q, n, 0;\n@Q st.global.u32 [%3], 0;\n@!P bra W;\n}" ::"r"(b), "r"(par), "n"(SPIN_LIMIT), "l"(0ull) : "memory");
}
__device__ __forceinline__ void declare_fence(int zero) { asm volatile(".reg .pred PNEVER;\nsetp.ne.u32 PNEVER, %0, 0;" ::"r"(zero)); }
__device__ __forceinline__ void sched_fence() { asm volatile("{\n.reg .pred Q;\n.reg .u32 x;\n@!PNEVER bra D;\nF: ld.volatile.global.u32 x, [%0];\nsetp.ne.u32 Q, x, 0;\n@Q bra F;\nD:\n}" ::"l"(0ull) : "memory"); }
__device__ __forceinline__ void mbar_init(uint32_t b, uint32_t n) { asm volatile("mbarrier.init.shared::cta.b64 [%0], %1;" ::"r"(b), "r"(n) : "memory"); }
__device__ __forceinline__ void mbar_expect(uint32_t b, uint32_t bytes) { asm volatile("mbarrier.arrive.expect_tx.shared::cta.b64 _, [%0], %1;" ::"r"(b), "r"(bytes) : "memory"); }
__device__ __forceinline__ void mbar_arrive(uint32_t b) { asm volatile("mbarrier.arrive.shared::cta.b64 _, [%0];" ::"r"(b) : "memory"); }
__device__ __forceinline__ void mbar_arrive_cluster(uint32_t b) { asm volatile("mbarrier.arrive.shared::cluster.b64 _, [%0];" ::"r"(b) : "memory"); }
__device__ __forceinline__ void cluster_sync() { asm volatile("barrier.cluster.arrive.aligned;\nbarrier.cluster.wait.aligned;" ::: "memory"); }
__device__ __forceinline__ void tma2d(uint32_t dst, const CUtensorMap* m, int c0, int c1, uint32_t bar) {
    asm volatile("cp.async.bulk.tensor.2d.shared::cluster.global.mbarrier::complete_tx::bytes [%0], [%1, {%2, %3}], [%4];" ::"r"(dst), "l"(m), "r"(c0), "r"(c1), "r"(bar) : "memory");
}
__device__ __forceinline__ void tma2d_mc(uint32_t dst, const CUtensorMap* m, int c0, int c1, uint32_t bar, uint16_t mask) {
    asm volatile("cp.async.bulk.tensor.2d.shared::cluster.global.mbarrier::complete_tx::bytes.multicast::cluster [%0], [%1, {%2, %3}], [%4], %5;" ::"r"(dst), "l"(m), "r"(c0), "r"(c1), "r"(bar), "h"(mask) : "memory");
}
__device__ __forceinline__ void tma3d(uint32_t dst, const CUtensorMap* m, int c0, int c1, int c2, uint32_t bar) {
    asm volatile("cp.async.bulk.tensor.3d.shared::cluster.global.mbarrier::complete_tx::bytes [%0], [%1, {%2, %3, %4}], [%5];" ::"r"(dst), "l"(m), "r"(c0), "r"(c1), "r"(c2), "r"(bar) : "memory");
}
__device__ __forceinline__ void tma3d_mc(uint32_t dst, const CUtensorMap* m, int c0, int c1, int c2, uint32_t bar, uint16_t mask) {
    asm volatile("cp.async.bulk.tensor.3d.shared::cluster.global.mbarrier::complete_tx::bytes.multicast::cluster [%0], [%1, {%2, %3, %4}], [%5], %6;" ::"r"(dst), "l"(m), "r"(c0), "r"(c1), "r"(c2), "r"(bar), "h"(mask) : "memory");
}
__device__ __forceinline__ void tma4d(uint32_t dst, const CUtensorMap* m, int c0, int c3, uint32_t bar) {
    asm volatile("cp.async.bulk.tensor.4d.shared::cluster.global.mbarrier::complete_tx::bytes [%0], [%1, {%2, 0, 0, %3}], [%4];" ::"r"(dst), "l"(m), "r"(c0), "r"(c3), "r"(bar) : "memory");
}
__device__ __forceinline__ void tma4d_mc(uint32_t dst, const CUtensorMap* m, int c0, int c3, uint32_t bar, uint16_t mask) {
    asm volatile("cp.async.bulk.tensor.4d.shared::cluster.global.mbarrier::complete_tx::bytes.multicast::cluster [%0], [%1, {%2, 0, 0, %3}], [%4], %5;" ::"r"(dst), "l"(m), "r"(c0), "r"(c3), "r"(bar), "h"(mask) : "memory");
}
__device__ __forceinline__ void tma_prefetch3d(const CUtensorMap* m, int c0, int c1, int c2) {
    asm volatile("cp.async.bulk.prefetch.tensor.3d.L2.global [%0, {%1, %2, %3}];" ::"l"(m), "r"(c0), "r"(c1), "r"(c2) : "memory");
}
__device__ __forceinline__ void tma_prefetch2d(const CUtensorMap* m, int c0, int c1) {
    asm volatile("cp.async.bulk.prefetch.tensor.2d.L2.global [%0, {%1, %2}];" ::"l"(m), "r"(c0), "r"(c1) : "memory");
}
__device__ __forceinline__ void l2_prefetch(const void* src, uint32_t bytes) { asm volatile("cp.async.bulk.prefetch.L2.global [%0], %1;" ::"l"(src), "r"(bytes) : "memory"); }
__device__ __forceinline__ void bulk_g2s(uint32_t dst, const void* src, uint32_t bytes, uint32_t bar) {
    asm volatile("cp.async.bulk.shared::cluster.global.mbarrier::complete_tx::bytes [%0], [%1], %2, [%3];" ::"r"(dst), "l"(src), "r"(bytes), "r"(bar) : "memory");
}
__device__ __forceinline__ void mbar_expect_e(uint32_t b, uint32_t bytes) {
    asm volatile("{\n.reg .pred E;\nelect.sync _|E, 0xffffffff;\n@E mbarrier.arrive.expect_tx.shared::cta.b64 _, [%0], %1;\n}" ::"r"(b), "r"(bytes) : "memory");
}
__device__ __forceinline__ void tma2d_e(uint32_t dst, const CUtensorMap* m, int c0, int c1, uint32_t bar) {
    asm volatile("{\n.reg .pred E;\nelect.sync _|E, 0xffffffff;\n@E cp.async.bulk.tensor.2d.shared::cluster.global.mbarrier::complete_tx::bytes [%0], [%1, {%2, %3}], [%4];\n}" ::"r"(dst), "l"(m), "r"(c0), "r"(c1), "r"(bar) : "memory");
}
__device__ __forceinline__ void tma2d_mc_e(uint32_t dst, const CUtensorMap* m, int c0, int c1, uint32_t bar, uint16_t mask) {
    asm volatile("{\n.reg .pred E;\nelect.sync _|E, 0xffffffff;\n@E cp.async.bulk.tensor.2d.shared::cluster.global.mbarrier::complete_tx::bytes.multicast::cluster [%0], [%1, {%2, %3}], [%4], %5;\n}" ::"r"(dst), "l"(m), "r"(c0), "r"(c1), "r"(bar), "h"(mask) : "memory");
}
__device__ __forceinline__ void tma3d_e(uint32_t dst, const CUtensorMap* m, int c0, int c1, int c2, uint32_t bar) {
    asm volatile("{\n.reg .pred E;\nelect.sync _|E, 0xffffffff;\n@E cp.async.bulk.tensor.3d.shared::cluster.global.mbarrier::complete_tx::bytes [%0], [%1, {%2, %3, %4}], [%5];\n}" ::"r"(dst), "l"(m), "r"(c0), "r"(c1), "r"(c2), "r"(bar) : "memory");
}
__device__ __forceinline__ void tma3d_mc_e(uint32_t dst, const CUtensorMap* m, int c0, int c1, int c2, uint32_t bar, uint16_t mask) {
    asm volatile("{\n.reg .pred E;\nelect.sync _|E, 0xffffffff;\n@E cp.async.bulk.tensor.3d.shared::cluster.global.mbarrier::complete_tx::bytes.multicast::cluster [%0], [%1, {%2, %3, %4}], [%5], %6;\n}" ::"r"(dst), "l"(m), "r"(c0), "r"(c1), "r"(c2), "r"(bar), "h"(mask) : "memory");
}
__device__ __forceinline__ void tma4d_e(uint32_t dst, const CUtensorMap* m, int c0, int c3, uint32_t bar) {
    asm volatile("{\n.reg .pred E;\nelect.sync _|E, 0xffffffff;\n@E cp.async.bulk.tensor.4d.shared::cluster.global.mbarrier::complete_tx::bytes [%0], [%1, {%2, 0, 0, %3}], [%4];\n}" ::"r"(dst), "l"(m), "r"(c0), "r"(c3), "r"(bar) : "memory");
}
__device__ __forceinline__ void tma4d_mc_e(uint32_t dst, const CUtensorMap* m, int c0, int c3, uint32_t bar, uint16_t mask) {
    asm volatile("{\n.reg .pred E;\nelect.sync _|E, 0xffffffff;\n@E cp.async.bulk.tensor.4d.shared::cluster.global.mbarrier::complete_tx::bytes.multicast::cluster [%0], [%1, {%2, 0, 0, %3}], [%4], %5;\n}" ::"r"(dst), "l"(m), "r"(c0), "r"(c3), "r"(bar), "h"(mask) : "memory");
}
__device__ __forceinline__ void tma_prefetch2d_e(const CUtensorMap* m, int c0, int c1) {
    asm volatile("{\n.reg .pred E;\nelect.sync _|E, 0xffffffff;\n@E cp.async.bulk.prefetch.tensor.2d.L2.global [%0, {%1, %2}];\n}" ::"l"(m), "r"(c0), "r"(c1) : "memory");
}
__device__ __forceinline__ void tma_prefetch3d_e(const CUtensorMap* m, int c0, int c1, int c2) {
    asm volatile("{\n.reg .pred E;\nelect.sync _|E, 0xffffffff;\n@E cp.async.bulk.prefetch.tensor.3d.L2.global [%0, {%1, %2, %3}];\n}" ::"l"(m), "r"(c0), "r"(c1), "r"(c2) : "memory");
}
__device__ __forceinline__ void l2_prefetch_e(const void* src, uint32_t bytes) {
    asm volatile("{\n.reg .pred E;\nelect.sync _|E, 0xffffffff;\n@E cp.async.bulk.prefetch.L2.global [%0], %1;\n}" ::"l"(src), "r"(bytes) : "memory");
}
__device__ __forceinline__ void bulk_g2s_e(uint32_t dst, const void* src, uint32_t bytes, uint32_t bar) {
    asm volatile("{\n.reg .pred E;\nelect.sync _|E, 0xffffffff;\n@E cp.async.bulk.shared::cluster.global.mbarrier::complete_tx::bytes [%0], [%1], %2, [%3];\n}" ::"r"(dst), "l"(src), "r"(bytes), "r"(bar) : "memory");
}
__device__ __forceinline__ bool elect_one() {
    uint32_t r;
    asm volatile("{\n.reg .pred E;\nelect.sync _|E, 0xffffffff;\nselp.u32 %0, 1, 0, E;\n}" : "=r"(r));
    return r;
}
__device__ __forceinline__ void tma_store2d(const CUtensorMap* m, int c0, int c1, uint32_t src) {
    asm volatile("cp.async.bulk.tensor.2d.global.shared::cta.bulk_group [%0, {%1, %2}], [%3];" ::"l"(m), "r"(c0), "r"(c1), "r"(src) : "memory");
}
__device__ __forceinline__ void bulk_commit() { asm volatile("cp.async.bulk.commit_group;" ::: "memory"); }
__device__ __forceinline__ void bulk_wait_read() { asm volatile("cp.async.bulk.wait_group.read 0;" ::: "memory"); }
__device__ __forceinline__ void bulk_wait_all() { asm volatile("cp.async.bulk.wait_group 0;" ::: "memory"); }
__device__ __forceinline__ uint64_t mkdesc(uint32_t addr, uint32_t lbo, uint32_t sbo, uint32_t swz) {
    return (uint64_t)((addr & 0x3FFFF) >> 4) | ((uint64_t)(lbo >> 4) << 16) | ((uint64_t)(sbo >> 4) << 32) | ((uint64_t)swz << 62);
}
__device__ __forceinline__ void wg_fence() { asm volatile("wgmma.fence.sync.aligned;" ::: "memory"); }
__device__ __forceinline__ void wg_commit() { asm volatile("wgmma.commit_group.sync.aligned;" ::: "memory"); }
template <int N> __device__ __forceinline__ void wg_wait() { asm volatile("wgmma.wait_group.sync.aligned %0;" ::"n"(N) : "memory"); }
template <typename T> __device__ __forceinline__ void pin_ptr(T*& p) { asm volatile("" : "+l"(p)); }
template <int N> __device__ __forceinline__ void pin(uint32_t* d) {
#pragma unroll
    for (int i = 0; i < N; i++) asm volatile("" : "+r"(d[i])::"memory");
}
template <int N> __device__ __forceinline__ void pin(float* d) {
#pragma unroll
    for (int i = 0; i < N; i++) asm volatile("" : "+f"(d[i])::"memory");
}

template <int TA, int TB>
__device__ __forceinline__ void wgmma_ss256(float* d, uint64_t da, uint64_t db) {
    asm volatile("wgmma.mma_async.sync.aligned.m64n256k16.f32.bf16.bf16 "
        "{%0, %1, %2, %3, %4, %5, %6, %7, %8, %9, %10, %11, %12, %13, %14, %15, %16, %17, %18, %19, %20, %21, %22, %23, %24, %25, %26, %27, %28, %29, %30, %31, %32, %33, %34, %35, %36, %37, %38, %39, %40, %41, %42, %43, %44, %45, %46, %47, %48, %49, %50, %51, %52, %53, %54, %55, %56, %57, %58, %59, %60, %61, %62, %63, %64, %65, %66, %67, %68, %69, %70, %71, %72, %73, %74, %75, %76, %77, %78, %79, %80, %81, %82, %83, %84, %85, %86, %87, %88, %89, %90, %91, %92, %93, %94, %95, %96, %97, %98, %99, %100, %101, %102, %103, %104, %105, %106, %107, %108, %109, %110, %111, %112, %113, %114, %115, %116, %117, %118, %119, %120, %121, %122, %123, %124, %125, %126, %127}, %128, %129, 1, 1, 1, %130, %131;"
        : "+f"(d[0]), "+f"(d[1]), "+f"(d[2]), "+f"(d[3]), "+f"(d[4]), "+f"(d[5]), "+f"(d[6]), "+f"(d[7]), "+f"(d[8]), "+f"(d[9]), "+f"(d[10]), "+f"(d[11]), "+f"(d[12]), "+f"(d[13]), "+f"(d[14]), "+f"(d[15]), "+f"(d[16]), "+f"(d[17]), "+f"(d[18]), "+f"(d[19]), "+f"(d[20]), "+f"(d[21]), "+f"(d[22]), "+f"(d[23]), "+f"(d[24]), "+f"(d[25]), "+f"(d[26]), "+f"(d[27]), "+f"(d[28]), "+f"(d[29]), "+f"(d[30]), "+f"(d[31]), "+f"(d[32]), "+f"(d[33]), "+f"(d[34]), "+f"(d[35]), "+f"(d[36]), "+f"(d[37]), "+f"(d[38]), "+f"(d[39]), "+f"(d[40]), "+f"(d[41]), "+f"(d[42]), "+f"(d[43]), "+f"(d[44]), "+f"(d[45]), "+f"(d[46]), "+f"(d[47]), "+f"(d[48]), "+f"(d[49]), "+f"(d[50]), "+f"(d[51]), "+f"(d[52]), "+f"(d[53]), "+f"(d[54]), "+f"(d[55]), "+f"(d[56]), "+f"(d[57]), "+f"(d[58]), "+f"(d[59]), "+f"(d[60]), "+f"(d[61]), "+f"(d[62]), "+f"(d[63]), "+f"(d[64]), "+f"(d[65]), "+f"(d[66]), "+f"(d[67]), "+f"(d[68]), "+f"(d[69]), "+f"(d[70]), "+f"(d[71]), "+f"(d[72]), "+f"(d[73]), "+f"(d[74]), "+f"(d[75]), "+f"(d[76]), "+f"(d[77]), "+f"(d[78]), "+f"(d[79]), "+f"(d[80]), "+f"(d[81]), "+f"(d[82]), "+f"(d[83]), "+f"(d[84]), "+f"(d[85]), "+f"(d[86]), "+f"(d[87]), "+f"(d[88]), "+f"(d[89]), "+f"(d[90]), "+f"(d[91]), "+f"(d[92]), "+f"(d[93]), "+f"(d[94]), "+f"(d[95]), "+f"(d[96]), "+f"(d[97]), "+f"(d[98]), "+f"(d[99]), "+f"(d[100]), "+f"(d[101]), "+f"(d[102]), "+f"(d[103]), "+f"(d[104]), "+f"(d[105]), "+f"(d[106]), "+f"(d[107]), "+f"(d[108]), "+f"(d[109]), "+f"(d[110]), "+f"(d[111]), "+f"(d[112]), "+f"(d[113]), "+f"(d[114]), "+f"(d[115]), "+f"(d[116]), "+f"(d[117]), "+f"(d[118]), "+f"(d[119]), "+f"(d[120]), "+f"(d[121]), "+f"(d[122]), "+f"(d[123]), "+f"(d[124]), "+f"(d[125]), "+f"(d[126]), "+f"(d[127])
        : "l"(da), "l"(db), "n"(TA), "n"(TB));
}
template <int TB>
__device__ __forceinline__ void wgmma_rs128(float* d, const uint32_t* a, uint64_t db, uint32_t acc) {
    asm volatile("{\n.reg .pred P;\nsetp.ne.u32 P, %69, 0;\nwgmma.mma_async.sync.aligned.m64n128k16.f32.bf16.bf16 "
        "{%0, %1, %2, %3, %4, %5, %6, %7, %8, %9, %10, %11, %12, %13, %14, %15, %16, %17, %18, %19, %20, %21, %22, %23, %24, %25, %26, %27, %28, %29, %30, %31, %32, %33, %34, %35, %36, %37, %38, %39, %40, %41, %42, %43, %44, %45, %46, %47, %48, %49, %50, %51, %52, %53, %54, %55, %56, %57, %58, %59, %60, %61, %62, %63}, {%64, %65, %66, %67}, %68, P, 1, 1, %70;\n}"
        : "+f"(d[0]), "+f"(d[1]), "+f"(d[2]), "+f"(d[3]), "+f"(d[4]), "+f"(d[5]), "+f"(d[6]), "+f"(d[7]), "+f"(d[8]), "+f"(d[9]), "+f"(d[10]), "+f"(d[11]), "+f"(d[12]), "+f"(d[13]), "+f"(d[14]), "+f"(d[15]), "+f"(d[16]), "+f"(d[17]), "+f"(d[18]), "+f"(d[19]), "+f"(d[20]), "+f"(d[21]), "+f"(d[22]), "+f"(d[23]), "+f"(d[24]), "+f"(d[25]), "+f"(d[26]), "+f"(d[27]), "+f"(d[28]), "+f"(d[29]), "+f"(d[30]), "+f"(d[31]), "+f"(d[32]), "+f"(d[33]), "+f"(d[34]), "+f"(d[35]), "+f"(d[36]), "+f"(d[37]), "+f"(d[38]), "+f"(d[39]), "+f"(d[40]), "+f"(d[41]), "+f"(d[42]), "+f"(d[43]), "+f"(d[44]), "+f"(d[45]), "+f"(d[46]), "+f"(d[47]), "+f"(d[48]), "+f"(d[49]), "+f"(d[50]), "+f"(d[51]), "+f"(d[52]), "+f"(d[53]), "+f"(d[54]), "+f"(d[55]), "+f"(d[56]), "+f"(d[57]), "+f"(d[58]), "+f"(d[59]), "+f"(d[60]), "+f"(d[61]), "+f"(d[62]), "+f"(d[63])
        : "r"(a[0]), "r"(a[1]), "r"(a[2]), "r"(a[3]), "l"(db), "r"(acc), "n"(TB));
}
template <int TB>
__device__ __forceinline__ void wgmma_rs64(float* d, const uint32_t* a, uint64_t db, uint32_t acc) {
    asm volatile("{\n.reg .pred P;\nsetp.ne.u32 P, %37, 0;\nwgmma.mma_async.sync.aligned.m64n64k16.f32.bf16.bf16 "
        "{%0, %1, %2, %3, %4, %5, %6, %7, %8, %9, %10, %11, %12, %13, %14, %15, %16, %17, %18, %19, %20, %21, %22, %23, %24, %25, %26, %27, %28, %29, %30, %31}, {%32, %33, %34, %35}, %36, P, 1, 1, %38;\n}"
        : "+f"(d[0]), "+f"(d[1]), "+f"(d[2]), "+f"(d[3]), "+f"(d[4]), "+f"(d[5]), "+f"(d[6]), "+f"(d[7]), "+f"(d[8]), "+f"(d[9]), "+f"(d[10]), "+f"(d[11]), "+f"(d[12]), "+f"(d[13]), "+f"(d[14]), "+f"(d[15]), "+f"(d[16]), "+f"(d[17]), "+f"(d[18]), "+f"(d[19]), "+f"(d[20]), "+f"(d[21]), "+f"(d[22]), "+f"(d[23]), "+f"(d[24]), "+f"(d[25]), "+f"(d[26]), "+f"(d[27]), "+f"(d[28]), "+f"(d[29]), "+f"(d[30]), "+f"(d[31])
        : "r"(a[0]), "r"(a[1]), "r"(a[2]), "r"(a[3]), "l"(db), "r"(acc), "n"(TB));
}
template <int TB>
__device__ __forceinline__ void wgmma_rs16(float* d, const uint32_t* a, uint64_t db, uint32_t acc) {
    asm volatile("{\n.reg .pred P;\nsetp.ne.u32 P, %13, 0;\nwgmma.mma_async.sync.aligned.m64n16k16.f32.bf16.bf16 "
        "{%0, %1, %2, %3, %4, %5, %6, %7}, {%8, %9, %10, %11}, %12, P, 1, 1, %14;\n}"
        : "+f"(d[0]), "+f"(d[1]), "+f"(d[2]), "+f"(d[3]), "+f"(d[4]), "+f"(d[5]), "+f"(d[6]), "+f"(d[7])
        : "r"(a[0]), "r"(a[1]), "r"(a[2]), "r"(a[3]), "l"(db), "r"(acc), "n"(TB));
}

__device__ __forceinline__ uint32_t delay_loop(int n, uint32_t x0) {
    uint32_t z;
    asm volatile("{\n.reg .pred P;\n.reg .u32 c, x;\nmov.u32 c, %1;\nmov.u32 x, %2;\nDL: mad.lo.u32 x, x, 1664525, 1013904223;\nadd.u32 c, c, -1;\nsetp.gt.s32 P, c, 0;\n@P bra DL;\n"
                 "setp.eq.u32 P, x, 0x7fffffff;\nselp.u32 %0, 16, 0, P;\n}" : "=r"(z) : "r"(n), "r"(x0) : "memory");
    return z;
}
__device__ __forceinline__ void wait_clocks(uint32_t n) {
    asm volatile("{\n.reg .pred P;\n.reg .u32 a, b;\nmov.u32 a, %%clock;\nW: mov.u32 b, %%clock;\nsub.u32 b, b, a;\nsetp.lt.u32 P, b, %0;\n@P bra W;\n}" ::"r"(n) : "memory");
}
__device__ __forceinline__ uint32_t gtime() { uint32_t t; asm volatile("mov.u32 %0, %%globaltimer_lo;" : "=r"(t)); return t; }
#define COUNT_RETRY(i)
__device__ __forceinline__ uint32_t stamp_word(uint32_t seq) { return (gtime() & ~31u) | (seq & 31u); }
__device__ __forceinline__ void wait_time(uint32_t t, uint32_t sb) { while ((int32_t)(gtime() - t) < 0) {} }
#define NAPMODE 1
__device__ __forceinline__ void nap(uint32_t ns) { if (NAPMODE) wait_clocks(ns * 7 / 4); else __nanosleep(ns); }
template <int STRIDE>
__device__ __forceinline__ uint32_t latest_stamp(const uint32_t* p, uint32_t seq, uint32_t ref, uint32_t sb) {
    int n = 0;
    while (true) {
        uint32_t bad = 0; int32_t m = INT32_MIN;
#pragma unroll
        for (int i = 0; i < 3; i++) { const uint32_t v = ld_relaxed1(p + i * STRIDE); bad |= (v ^ seq) & 31u; m = max(m, (int32_t)((v & ~31u) - ref)); }
        if (__all_sync(0xffffffffu, bad == 0)) return ref + __reduce_max_sync(0xffffffffu, m);
        nap(100);
        if (++n > SPIN_LIMIT) spin_fault();
    }
}
constexpr uint32_t ONES = 0x3C003C00u, FULL = 0x50005000u;
__device__ __forceinline__ void pacer(const Params& P, const uint32_t sb, const int cta, const int lane, const uint32_t epoch) {
    uint8_t* const zp = P.xb + cta * 2048 + xg_lane(lane);
    uint32_t e0 = 0;
#pragma unroll 2
    for (int i = 0; i < 32; i++) { const uint4 u = __ldg((const uint4*)P.mem0 + i * 32 + lane); e0 = amax(amax(e0, amax(u.x, u.y)), amax(u.z, u.w)); }
    e0 = min(max(warp_exp(e0), 31u), 253u) - 14;
    if (cta < 32) {
        const uint32_t* m = (const uint32_t*)(P.mem0 + (lane >> 2) * 1024 + cta * 32 + (lane & 3) * 2);
        const float sc = __uint_as_float((254 - e0) << 23);
        auto cv = [&](uint32_t u) { return pack2h(bf_lo(u) * sc, bf_hi(u) * sc); };
        const uint32_t y = cv(m[12]);
        st_relaxed4(zp, cv(m[0]), cv(m[4]), cv(m[8]), prmt(y, FULL, 0x7610));
        st_relaxed1(P.xb + xg_side(cta) + lane * 4, prmt(y, FULL, 0x3254));
    }
    if (cta < 40) {
#pragma unroll 1
        for (int b = 1; b < 8; b++) st_relaxed4(zp + xg_buf(b), 0, 0, 0, 0);
    }
    __threadfence();
    const uint32_t* ts = (const uint32_t*)(P.xb + XG_T) + lane;
    int32_t d0 = P.dly;
    const uint32_t go = mapa(sb + B_GO, (cta / 3 & 1) * 3 + 1 + (lane & 1));
    auto free_segment = [&]() { if (lane == 0) mbar_expect(sb + B_KVFULL, 16384); __syncwarp(); if (lane < 2) mbar_arrive_cluster(go); };
    wait_count(&g_cnt(C_XCNT), (epoch + 1) * 256);
    const uint32_t ex = max(ld_relaxed1(&g_cnt(C_XMAX)) & 255, 67u);
    mbar_wait(sb + B_READY, 0);
    free_segment();
    if (lane == 0) st_relaxed2(g_hint + cta * 32, stamp_word(epoch + 1), lds32(sb + S_EV) | lds32(sb + S_EO) << 16);
    uint32_t a = gtime();
    for (int n = 0;; n++) {
        uint32_t bad = 0, e = 0; int32_t m = INT32_MIN;
#pragma unroll
        for (int i = 0; i < 3; i++) {
            uint32_t v[2];
            ld_relaxed2(v, g_hint + lane * 32 + i * 1024);
            bad |= (v[0] ^ (epoch + 1)) & 31u; m = max(m, (int32_t)((v[0] & ~31u) - a)); e = __vmaxu2(e, v[1]);
        }
        if (__all_sync(0xffffffffu, bad == 0)) {
            a += __reduce_max_sync(0xffffffffu, m);
            const uint32_t ev = __reduce_max_sync(0xffffffffu, e & 255), eo = __reduce_max_sync(0xffffffffu, e >> 16);
            if (lane == 0) { sts64(sb + S_SC, max(ev, 97u) + max(eo, 97u) - 244, ex); sts32(sb + S_ISC, e0 * 0x800080u); }
            break;
        }
        wait_clocks(100);
        if (n > SPIN_LIMIT) spin_fault();
    }
    wait_time(a, sb);
    if (lane == 0) mbar_arrive(sb + B_RELM);
#pragma unroll 1
    for (int s = 0; s < 63; s++) {
        const uint32_t seq = epoch * 63 + s + 1;
        mbar_wait(sb + B_P1, s & 1);
        const uint32_t tx = gtime();
        if (lane == 0) st_relaxed1(ts + (s & 1) * 256 + cta, (tx & ~31u) | (seq & 31u));
        { const uint32_t t = tx; PROFP(3) }
        if (s > 0) {
            const int32_t e0 = latest_stamp<32>(ts + (~s & 1) * 256 + 128, seq - 1, a, sb) + P.mrg - a;
            d0 += s < 3 ? e0 : min(max(e0, -P.clamp0), P.clampv) / 2;
        }
        while ((int32_t)(gtime() - tx) < P.rd) nap(20);
        a = latest_stamp<32>(ts + (s & 1) * 256, seq, tx, sb) + d0;
        { const uint32_t t = gtime(); PROFP(0) }
        mbar_wait(sb + B_RED, s & 1);
        { const uint32_t t = gtime(); PROFP(1) }
        const uint32_t g = tx + __reduce_max_sync(0xffffffffu, lds32(sb + S_TO + (lane & 7) * 4) - tx);
        if (lane == 0) st_relaxed1(ts + (s & 1) * 256 + 128 + cta, (g & ~31u) | (seq & 31u));
        if (P.kvd < 0 && s < 62) free_segment();
        wait_time((int32_t)(g + P.guard - a) > 0 ? g + P.guard : a, sb);
        if (lane == 0) mbar_arrive(sb + B_RELM);
        { const uint32_t t = a; PROFP(2) }
        if (P.kvd >= 0 && s < 62) { if (P.kvd) nap(P.kvd); free_segment(); }
    }
}
__device__ __forceinline__ void st_async2(uint32_t a, uint32_t x, uint32_t y, uint32_t bar, bool on) {
    asm volatile("{\n.reg .pred P;\nsetp.ne.u32 P, %4, 0;\n@P st.async.weak.shared::cluster.mbarrier::complete_tx::bytes.v2.b32 [%0], {%1,%2}, [%3];\n}" ::"r"(a), "r"(x), "r"(y), "r"(bar), "r"((uint32_t)on) : "memory");
}
__device__ __forceinline__ uint32_t xor_or(uint32_t a, uint32_t b, uint32_t t) { uint32_t d; asm("lop3.b32 %0, %1, %2, %3, 0x7E;" : "=r"(d) : "r"(a), "r"(b), "r"(t)); return d; }
__device__ __forceinline__ uint32_t or3(uint32_t a, uint32_t b, uint32_t c) { uint32_t d; asm("lop3.b32 %0, %1, %2, %3, 0xFE;" : "=r"(d) : "r"(a), "r"(b), "r"(c)); return d; }
__device__ __forceinline__ bool tags_ok(uint32_t bad, uint32_t mask = 1) {
    uint32_t r;
    asm volatile("{\n.reg .pred P;\n.reg .b32 x;\nand.b32 x, %1, %2;\nsetp.ne.b32 P, x, 0;\nvote.sync.any.pred P, P, 0xffffffff;\nselp.u32 %0, 0, 1, P;\n}" : "=r"(r) : "r"(bad), "r"(mask));
    return r;
}
constexpr int SROW = 56;
#define PREA 8
#define PREB 9
#define RING1 6
#define RING2 7
#define RING3 8
#define PRE2 10
#define PRE2A 0
#define PRE3 0
#define EFENCE 0
#define RFENCE 1
#define PROG 16
#define EARLY 0
#define LAG 4
#define PUT1 33
#define DEPS 3
#define ADELAY 120
#define BDELAY 0
#define HOLD 1
#define XDELAY 330
#define FENCEA 0x80
#define FENCEB 0x80
#define FENCE2 0x110
#define OFENCE 1
#define MASK3 0x57
#define MASK4 0x55
#define MASK5 0x25
#define OFF3 0x5320
#define OFF4 0x6420
#define OFF5 0x0520
#define RESA (NRA == 3 ? 15 : NRA == 4 ? 3 : 0)
#define RESB (NRB == 3 ? 0xcc : NRB == 4 ? 0x30 : 0)
#define RESB1 (NRB == 3 ? 0xcc : NRB == 4 ? 0xc : 0)
__host__ __device__ constexpr int smem_mask(int NR) { return NR == 3 ? MASK3 : NR == 4 ? MASK4 : MASK5; }
__host__ __device__ constexpr bool round_smem(int r, int NR) { return smem_mask(NR) >> r & 1; }
__host__ __device__ constexpr int kord(int r, int NR) { int c = 0; for (int i = 0; i < r; i++) c += round_smem(i, NR) == round_smem(r, NR); return round_smem(r, NR) ? NR + c : c; }
__host__ __device__ constexpr int slot_r(int n, int NR) { return n < 32 ? n >> 2 : (((n & 31) >> 2) + ((NR == 3 ? OFF3 : NR == 4 ? OFF4 : OFF5) >> (n & 3) * 4)) & 7; }
__host__ __device__ constexpr int slot_k(int n, int NR) { return kord(slot_r(n, NR), NR); }
__host__ __device__ constexpr int slot_sord(int n, int NR) { int c = 0; for (int i = 0; i < n; i++) c += slot_k(i, NR) >= NR; return c; }
__host__ __device__ constexpr int sfrag_slot(int q, int NR) { for (int n = 0; n < 64; n++) if (slot_k(n, NR) >= NR && slot_sord(n, NR) == q) return n; return -1; }
__host__ __device__ constexpr int w1_loaded(int n, int NR, int PRE) {
    int q = PRE;
    for (int i = 0; i <= n; i++) q += q < (8 - NR) * 8 && q - slot_sord(i + 1, NR) < (i < 32 ? RING1 : RING2);
    return q;
}
template <int Q, int NR>
__device__ __forceinline__ void load_w1(uint32_t* w, const uint32_t* a) {
    constexpr int n = sfrag_slot(Q, NR);
    ldsm4t(w, a[n & 3] + ((slot_k(n, NR) - NR) * 2 + (n >> 5)) * 2048);
}
constexpr int AB = NRA < 5, BB = 3 - AB;
__device__ __forceinline__ bool w2_full(int role, int warp) { return warp < (role == 2 ? 2 : 3); }
__device__ __forceinline__ int w2_nblk(int role, int warp) { return warp < 4 ? BB - !w2_full(role, warp) : AB; }
__host__ __device__ constexpr int w2_step(bool full, int i) { return AB ? (full ? -2 * i : 0) : full ? (i == 0 ? 0 : i == 1 ? 16 - 2 * EARLY : 18 - 2 * EARLY) : i; }
__device__ __forceinline__ int w2_block(int role, int warp) {
    const int f = role * 3 + warp, g = role == 2 ? warp : role;
    if (AB) return warp >= 4 ? 16 + role * 4 + (warp - 4) : w2_full(role, warp) ? 4 * (f >> 1) + (f & 1) + 2 : 28 + g;
    return w2_full(role, warp) ? EARLY + 4 * (f >> 1) + (f & 1) : EARLY + 2 + 4 * g;
}
__device__ __forceinline__ int w2_res(int role, int warp) { return warp >= 4 ? RESA : w2_full(role, warp) ? RESB : RESB1; }
__device__ __forceinline__ int w2_units(int role, int warp) { return w2_nblk(role, warp) * 4 - (5 - (warp < 4 ? NRB : NRA)) * 2; }
constexpr int W2B = (BB * 4 - (5 - NRB) * 2) * 2048, W2A = (AB * 4 - (5 - NRA) * 2) * 2048;
static_assert(S_W2 + 4 * W2B - 8192 + 4 * W2A == S_KV, "weights");
__device__ __forceinline__ int w1_base(int warp) { return S_W1 + (warp < 4 ? warp * (8 - NRB) : 4 * (8 - NRB) + (warp - 4) * (8 - NRA)) * 4096; }
__device__ __forceinline__ int w2_base(int warp) { return S_W2 + (warp < 4 ? warp * W2B : 4 * W2B - 8192 + (warp - 4) * W2A); }
__device__ __forceinline__ void chain_load(const Params& P, uint32_t sb, int cta, int warp, int lane, int round) {
    const int role = cta % 3, h = cta / 3;
    if (lane == 0) {
        mbar_expect(sb + B_INIT, round ? (8 - (warp < 4 ? NRB : NRA)) * 4096 : 20480);
        if (round) mbar_expect(sb + B_INIT2, w2_units(role, warp) * 2048);
        int mask = (warp < 4 ? smem_mask(NRB) : smem_mask(NRA)) ^ (round ? 0 : 255);
        uint32_t dst = sb + (round ? w1_base(warp) : warp * 20480);
#pragma unroll 1
        for (int r = 0; r < 8; r++)
            if (mask >> r & 1) { tma3d(dst, &P.tm[M_C1 + role], 0, warp * 128 + r * 16, h * 2, sb + B_INIT); dst += 4096; }
        if (round) dst = sb + w2_base(warp);
        mask = w2_res(role, warp) ^ (round ? 0xfff : 0);
#pragma unroll 1
        for (int i = 0; i < w2_nblk(role, warp) * 4; i++)
            if (mask >> i & 1) { tma2d(dst, &P.tm[M_CO], (w2_block(role, warp) + w2_step(w2_full(role, warp), i >> 2)) * 32, h * 128 + (i & 3) * 32, sb + (round ? B_INIT2 : B_INIT)); dst += 2048; }
    }
    __syncwarp();
}

__device__ __forceinline__ void put_partials(bool TR, uint32_t a, const float* x, const float* y) {
    if (TR) stsm4t(a, pack2(x[0], x[1]), pack2(x[2], x[3]), pack2(y[0], y[1]), pack2(y[2], y[3]));
    else stsm4(a, pack2(x[0], x[1]), pack2(x[2], x[3]), pack2(y[0], y[1]), pack2(y[2], y[3]));
}
template <int NR, int PRE, int FM, int B, int E>
__device__ __forceinline__ void project(float (*acc)[4], bool TR, const uint32_t (*wr)[4], uint32_t (*as)[4], uint32_t (*v)[4], uint32_t* x, const uint32_t* w1a, uint32_t pp, uint32_t zero) {
    static_for<B, E>([&](auto I) {
        constexpr int n = I.value, kk = slot_k(n, NR), T = (n >> 5) * 4 + (n & 3), so = slot_sord(n, NR), q = w1_loaded(n - 1, NR, PRE);
        constexpr bool sm = kk >= NR;
        const uint32_t* w = sm ? as[so] : wr[sm ? 0 : (kk * 2 + (n >> 5)) * 4 + (n & 3)];
        if constexpr (n == 32 && PUT1 < 32) { put_partials(TR, pp, acc[0], acc[1]); put_partials(TR, pp + 4096, acc[2], acc[3]); }
        if constexpr (n == 0) {
            const uint32_t c = prmt(v[0][3], x[0], 0x3254);
            v[0][0] = h2bf(v[0][0], v[0][0]); v[0][1] = h2bf(v[0][1], v[0][1]); v[0][2] = h2bf(v[0][2], v[0][2]); v[0][3] = h2bf(v[0][3], x[0]);
            x[0] = c;
        }
        if constexpr ((n & 31) < 4) acc[T][0] = acc[T][1] = acc[T][2] = acc[T][3] = 0.f;
        mma16816(acc[T], w[0], w[1], w[2], w[3], v[slot_r(n, NR) >> 1][(slot_r(n, NR) & 1) * 2], v[slot_r(n, NR) >> 1][(slot_r(n, NR) & 1) * 2 + 1]);
        if constexpr (n == DEPS) {
            const uint32_t sel = __float_as_uint(acc[T][0]) * zero + 0x7610;
#pragma unroll
            for (int b = 1; b < 4; b++) cvt_block(v[b], x[b], sel);
        }
        if constexpr (w1_loaded(n, NR, PRE) > q) load_w1<q, NR>(as[q], w1a);
        if constexpr (n == PUT1 && n >= 32) { put_partials(TR, pp, acc[0], acc[1]); put_partials(TR, pp + 4096, acc[2], acc[3]); }
        if constexpr (n % 4 == 3 && (FM >> (n / 4) & 1) && n != E - 1) sched_fence();
    });
    if constexpr (E == 64) { put_partials(TR, pp + 8192, acc[4], acc[5]); put_partials(TR, pp + 12288, acc[6], acc[7]); }
}
__device__ __forceinline__ void reduce8(const uint32_t (*x)[4], const uint32_t* sel, float sc, uint32_t& r0, uint32_t& r1) {
    float d[4][4];
#pragma unroll
    for (int i = 0; i < 4; i++) {
        d[i][0] = d[i][1] = d[i][2] = d[i][3] = 0.f;
        mma16816(d[i], x[i][0], x[i][1], x[i][2], x[i][3], sel[2 * i], sel[2 * i + 1]);
    }
    r0 = pack2(((d[0][0] + d[1][0]) + (d[2][0] + d[3][0])) * sc, ((d[0][1] + d[1][1]) + (d[2][1] + d[3][1])) * sc);
    r1 = pack2(((d[0][2] + d[1][2]) + (d[2][2] + d[3][2])) * sc, ((d[0][3] + d[1][3]) + (d[2][3] + d[3][3])) * sc);
}

#define ISTAMP(i)
__host__ __device__ constexpr int wo_count(int n, int RES, bool res) { int c = 0; for (int i = 0; i < n; i++) c += (RES >> (i >> 2) & 1) == res; return c; }
__host__ __device__ constexpr int wo_loaded(int n, int RES, int PRE, int end) { int q = PRE; for (int i = 0; i <= n; i++) q += q < end && q - wo_count(i + 1, RES, false) < RING3; return q; }
template <int Q>
__device__ __forceinline__ void load_w2(uint32_t* w, const uint32_t* a) { ldsm4t(w, a[Q & 1] + (Q >> 1) * 1024); }
template <int NB, int RES, int PRE, int FM>
__device__ __forceinline__ void wo_blocks(uint32_t (*w)[4], const uint32_t (*wp)[4], uint32_t oa, const uint32_t* wa, const uint8_t* dst, const uint8_t* dsd, bool odd) {
    float a[NB][4][4];
    uint32_t o[4][4];
    bar_sync(3, 256);
#pragma unroll
    for (int i = 0; i < 4; i++) ldsm4(o[i], oa + i * 512);
    if (FM & 1) sched_fence();
    static_for<0, NB * 16>([&](auto I) {
        constexpr int n = I.value, i = n & 15, end = wo_count(NB * 16, RES, false), q = wo_loaded(n - 1, RES, PRE, end);
        constexpr bool res = RES >> (n >> 2) & 1;
        const uint32_t* b = o[i >> 2] + (i & 2);
        const uint32_t* x = res ? wp[wo_count(n, RES, true)] : w[wo_count(n, RES, false)];
        float* d = a[n >> 4][i & 3];
        if constexpr (i < 4) d[0] = d[1] = d[2] = d[3] = 0.f;
        mma16816(d, x[0], x[1], x[2], x[3], b[0], b[1]);
        if constexpr (wo_loaded(n, RES, PRE, end) > q) load_w2<q>(w[q], wa);
        if constexpr (n == NB * 16 - 1 || (n >= 16 && i == LAG - 1)) {
            constexpr int k = n == NB * 16 - 1 ? NB - 1 : (n >> 4) - 1;
            const float (*e)[4] = a[k];
            const uint32_t y = pack2h(e[1][2] + e[3][2], e[1][3] + e[3][3]);
            constexpr int bs = w2_step(NB == BB, k);
            red_add4(dst + bs * 2048, movm(pack2h(e[0][0] + e[2][0], e[0][1] + e[2][1])), movm(pack2h(e[0][2] + e[2][2], e[0][3] + e[2][3])),
                     movm(pack2h(e[1][0] + e[3][0], e[1][1] + e[3][1])), movm(odd ? ONES : y));
            red_add1(dsd + (bs >> 1) * 1024 + (bs & 1) * 256, movm(odd ? y : ONES));
        }
        if constexpr (((FM >> (n / 4 + 1)) & 1) && (n & 3) == 3 && n != NB * 16 - 1) sched_fence();
    });
}
#define FRAG1(ln) ((((ln) & 7) + ((ln) >> 4) * 8) * 128 + ((((((ln) >> 3) & 1) << (ROLE == 1)) ^ ((ln) & 7)) << 4))
#define FRAG2(ln) ((((ln) & 7) + ((ln) >> 4) * 8) * 64 + (((((ln) >> 3) & 1) ^ (((ln) >> 1) & 3)) << 4))
#define TILE_X(i) (ROLE == 1 ? (((i) >> 1) << 6) | (((i) & 1) << 4) : (i) << 5)
__device__ __forceinline__ void chain_init(const Params& P, const uint32_t sb, const int cta, const int warp, const int lane, uint32_t (*wr)[4]) {
    const int ROLE = cta % 3, nr = warp < 4 ? NRB : NRA;
    uint32_t m[6] = {}, u[4];
    mbar_wait(sb + B_INIT, 0);
    ISTAMP(0)
#pragma unroll
    for (int f = 0; f < 40; f++) {
        const bool w1 = f < (NRA < NRB ? NRA : NRB) * 8 || f < nr * 8;
        ldsm4t(wr[f], sb + warp * 20480 + (f >> 2) * 2048 + (w1 ? FRAG1(lane) ^ TILE_X(f & 3) : (f & 2) * 512 + (FRAG2(lane) ^ ((f & 1) << 5))));
    }
    fence_async_smem();
    bar_sync(1, 256);
    chain_load(P, sb, cta, warp, lane, 1);
    ISTAMP(1)
#pragma unroll
    for (int f = 0; f < 40; f++) m[f < 24 ? 0 : f >> 3] = amax4(m[f < 24 ? 0 : f >> 3], wr[f]);
    uint32_t m1 = amax(m[0], amax(nr > 3 ? m[3] : 0, nr > 4 ? m[4] : 0)), m2 = amax(nr > 3 ? 0 : m[3], nr > 4 ? 0 : m[4]);
    ISTAMP(5)
    mbar_wait(sb + B_INIT, 1);
    ISTAMP(3)
    if (ROLE == 2) {
#pragma unroll 4
        for (int i = 0; i < S_W2 / 4096; i++) { lds128(u, sb + S_W1 + warp * (S_W2 / 8) + i * 512 + lane * 16); m1 = amax4(m1, u); }
    }
    mbar_wait(sb + B_INIT2, 0);
    ISTAMP(7)
    const int n = w2_units(ROLE, warp) * 4;
#pragma unroll 4
    for (int i = 0; i < n; i++) { lds128(u, sb + w2_base(warp) + i * 512 + lane * 16); m2 = amax4(m2, u); }
    m1 = warp_exp(m1); m2 = warp_exp(m2);
    if (lane == 0) { if (ROLE == 2) red_max_shared(sb + S_EV, m1); red_max_shared(sb + S_EO, m2); }
}
template <bool ATT>
__device__ __forceinline__ void chain_role(const Params& P, const uint32_t sb, const int cta, const int warp, const int lane, const uint32_t epoch, const uint32_t (*wr)[4]) {
    constexpr int NR = ATT ? NRA : NRB, PRE = ATT ? PREA : PREB;
    const int h = cta / 3, ROLE = cta - h * 3;
    ISTAMP(6)
    uint32_t l8 = opq(sb + lane * 8, lane);
    const uint8_t* persu = (const uint8_t*)((ROLE == 1 ? g_km : g_vmt) + h * 512) - (sb >> 1);
    auto persist = [&](int s, int tile, uint32_t r0, uint32_t r1) {
        uint32_t* pp = (uint32_t*)(persu + s * 65536 + (ROLE == 1 ? (tile >> 1) * 512 + (tile & 1) * 128 : tile * 256) + (l8 >> 1));
        pp[0] = r0; pp[ROLE == 1 ? 64 : 32] = r1;
    };
    const uint32_t rk0 = (h & 1) * 3, rd1 = __shfl_sync(0xffffffffu, mapa(sb, rk0 + (ROLE + 1) % 3) - sb, 0), rd2 = __shfl_sync(0xffffffffu, mapa(sb, rk0 + (ROLE + 2) % 3) - sb, 0);
    const uint32_t xo = (ROLE == 2 ? S_XV : S_X + ROLE * 2048) + warp * 256;
    const bool full = w2_full(ROLE, warp);
    const int blk = w2_block(ROLE, warp);
    const uint32_t om = blk * 2048, os = xg_side(blk);
    const uint32_t w1o = sb + w1_base(warp), w2o = sb + w2_base(warp);
    ISTAMP(2)
    if (lane == 0) mbar_arrive(sb + B_READY);
#pragma unroll 1
    for (int s = 0;; s++) {
        l8 += s & P.zero;
        uint32_t r0, r1;
        {
            uint32_t v[4][4], as[(8 - NR) * 8][4], w1a[4];
            float acc[8][4];
            const uint32_t pst = sb + S_P1 + (l8 - sb) * 16 + ((warp * 16) ^ ((l8 & 56) * 2));
#pragma unroll
            for (int i = 0; i < 4; i++) w1a[i] = w1o + (FRAG1((l8 - sb) >> 3) ^ TILE_X(i));
            auto preload = [&]() { static_for<0, PRE>([&](auto I) { load_w1<I.value, NR>(as[I.value], w1a); }); };
#pragma unroll 1
            while (true) {
                uint32_t x[4];
                preload();
                const uint32_t lm = opq(l8 - sb, (l8 - sb) >> 3);
                const uint8_t* pm = P.xb + xg_buf(s) + warp * 8192 + xg_lane(lm >> 3);
                const uint8_t* ps = P.xb + xg_buf(s) + XG_SIDE + warp * 2048 + (lm >> 1);
                pin_ptr(pm); pin_ptr(ps);
                mbar_wait(sb + B_RELM, s & 1);
                if (ATT ? ADELAY : BDELAY) wait_clocks(ATT ? ADELAY : BDELAY);
                PROF(10)
#pragma unroll
                for (int b = 0; b < 4; b++) { ld_relaxed4(v[b], pm + b * 2048); ld_relaxed1n(x[b], ps + (b >> 1) * 1024 + (b & 1) * 256); }
                project<NR, PRE, ATT ? FENCEA : FENCEB, 0, PROG>(acc, ROLE == 2, wr, as, v, x, w1a, pst, P.zero);
                const uint32_t bad = xor_or(x[0], x[1], FULL) | xor_or(x[2], x[3], FULL);
                if (tags_ok(bad, 0xffffffffu)) break;
                COUNT_RETRY(warp >> 1)
                uint32_t n;
                asm volatile("atom.shared.add.u32 %0, [%1], 1;" : "=r"(n) : "r"(sb + S_RETRY) : "memory");
                if (n > SPIN_LIMIT) spin_fault();
            }
            PROF(0)
            sts32((l8 >> 1) + (sb - (sb >> 1) + S_EM + warp * 128), amax4(amax4(amax4(amax(amax(v[0][0], v[0][1]), amax(v[0][2], v[0][3])), v[1]), v[2]), v[3]));
            project<NR, PRE, ATT ? FENCEA : FENCEB, PROG, 64>(acc, ROLE == 2, wr, as, v, nullptr, w1a, pst, 0);
            PROF(1)
            const uint32_t isc = lds32(sb + S_ISC + (s & 1) * 4);
            const uint32_t lq = l8 + ((s >> 3) & P.zero);
            uint32_t x[4][4], sel[8], xd[6] = {l8 + xo, l8 + xo + rd1, l8 + xo + rd2, sb + B_X + rd1, sb + B_X + rd2, sb + S_P1 + warp * 2048 + (lq & 64) * 16 + (lq & 128) + (lq & 56) * 2};
#pragma unroll
            for (int i = 0; i < 8; i++) sel[i] = (lq & 224) == i * 32 ? 0x3F803F80u : 0u;
            pin<6>(xd); pin<8>(sel);
            if (RFENCE) sched_fence();
            bar_sync(1, 256);
#pragma unroll
            for (int i = 0; i < 4; i++) ldsm4t(x[i], xd[5] + i * 256);
            if (!ATT && l8 == sb + (warp - 3) * 1024) mbar_arrive(sb + B_P1);
            reduce8(x, sel, bf_hi(isc), r0, r1);
            st_async2(xd[1], r0, r1, xd[3], s != 63);
            st_async2(xd[2], r0, r1, xd[4], s != 63);
            sts64(xd[0], r0, r1);
            if (s == 63) { persist(s, warp, r0, r1); break; }
            if (!ATT && warp == 0) {
                uint32_t sc[2], u[2][4];
                lds64(sc, sb + S_SC);
                lds128(u[0], l8 * 2 + (S_EM - sb)); lds128(u[1], l8 * 2 + (S_EM + 512 - sb));
                const int em = warp_exp(amax4(amax(amax(u[0][0], u[0][1]), amax(u[0][2], u[0][3])), u[1]));
                if (l8 == sb) sts32(sb + S_ISC + (~s & 1) * 4, min(max(em + (int)(isc >> 23) - 127, (int)sc[1]) + (int)sc[0], 253) * 0x800080u);
            }
            __syncwarp();
            if (l8 == sb) mbar_arrive(sb + B_X);
            PROF(2)
        }
        uint32_t w[40][4], w2a[2], odd;
        const uint8_t *po, *pd;
        auto wo_addr = [&]() {
            const uint32_t lo = (l8 + ((s >> 2) & P.zero) - sb) >> 3;
            w2a[0] = w2o + FRAG2(lo); w2a[1] = w2o + (FRAG2(lo) ^ 32);
            po = P.xb + xg_buf(s + 1) + om + xg_lane(lo);
            pd = P.xb + xg_buf(s + 1) + os + lo * 4;
            odd = lo & 4;
            pin_ptr(po); pin_ptr(pd); pin<2>(w2a); pin<1>(&odd);
        };
        uint32_t oa = l8 * 2 + (S_OX - sb);
        if constexpr (ATT) {
            const uint32_t ln = (l8 + ((s >> 4) & P.zero) - sb) >> 3;
            const uint32_t va = sb + S_KV + 8192 + ((warp >> 1) & 1) * 4096 + ((ln & 7) + (ln >> 4) * 8) * 128 + ((((warp & 1) * 4 + ((ln >> 3) & 1)) ^ (ln & 7)) << 4);
            const uint32_t ka = sb + S_KV + (warp & 1) * 2048 + (ln & 15) * 128 + (((ln >> 4) ^ (ln & 7)) << 4);
            uint32_t ad[5] = {sb + S_SX + (ln & 3) * (8 * SROW) + (ln >> 2) * 4 + (warp < 6 ? (warp - 4) * 64 : 128 + (warp - 6) * 32), l8 + S_XV + (warp - 4) * 512,
                              l8 + S_SX + (ln >> 2) * (4 * SROW - 32), oa + (warp - 4) * 512, sb + S_ISC + (~s & 1) * 4};
            if constexpr (AB) { wo_addr(); pin<1>(&oa); }
            pin<5>(ad);
            const uint32_t sa = ad[0], sr = ad[2];
            uint32_t vf[4][4], vm[2][2], q[8][2];
            float S[4][4];
#pragma unroll
            for (int n = 0; n < 4; n++) { S[n][0] = S[n][1] = S[n][2] = S[n][3] = 0.f; }
            mbar_wait(sb + B_KVFULL, s & 1);
            if (warp < 6) {
                uint32_t kf[8][4];
#pragma unroll
                for (int k = 0; k < 8; k++) ldsm4(kf[k], (ka ^ ((k & 3) << 5)) + (k >> 2) * 4096);
#pragma unroll
                for (int i = 0; i < 4; i++) ldsm4t(vf[i], (va ^ ((i & 1) << 5)) + (i >> 1) * 2048);
                mbar_wait(sb + B_X, s & 1);
                PROF(11)
#pragma unroll
                for (int k = 0; k < 8; k++) lds64(q[k], l8 + S_X + k * 256);
#pragma unroll
                for (int k = 0; k < 8; k++) mma16816(S[k & 3], kf[k][0], kf[k][1], kf[k][2], kf[k][3], q[k][0], q[k][1]);
                sts32(sa, __float_as_uint((S[0][0] + S[1][0]) + (S[2][0] + S[3][0])));
                sts32(sa + 4 * SROW, __float_as_uint((S[0][1] + S[1][1]) + (S[2][1] + S[3][1])));
                sts32(sa + 32, __float_as_uint((S[0][2] + S[1][2]) + (S[2][2] + S[3][2])));
                sts32(sa + 4 * SROW + 32, __float_as_uint((S[0][3] + S[1][3]) + (S[2][3] + S[3][3])));
            } else {
#pragma unroll
                for (int i = 0; i < 4; i++) ldsm4t(vf[i], (va ^ ((i & 1) << 5)) + (i >> 1) * 2048);
                uint32_t xa = l8 + S_X + (warp - 6) * 1024;
                pin<1>(&xa);
                mbar_wait(sb + B_X, s & 1);
                PROF(11)
#pragma unroll
                for (int k = 0; k < 8; k++) lds64(q[k], xa + (k >> 2) * 2048 + (k & 3) * 256);
#pragma unroll
                for (int k = 0; k < 4; k++) mma16816(S[k], q[4 + (k & 2)][0], q[4 + (k & 2)][1], q[5 + (k & 2)][0], q[5 + (k & 2)][1], q[k][0], q[k][1]);
                sts32(sa, __float_as_uint((S[0][0] + S[2][0]) + (S[1][2] + S[3][2])));
                sts32(sa + 4 * SROW, __float_as_uint((S[0][1] + S[2][1]) + (S[1][3] + S[3][3])));
            }
            const uint32_t isn = lds32(ad[4]);
            lds64(vm[0], ad[1]); lds64(vm[1], ad[1] + 256);
            PROF(7)
            bar_sync(2, 128);
            const float cs = 0.08838834764831845f * 1.4426950408889634f;
            float E[6][2];
#pragma unroll
            for (int i = 0; i < 6; i++) lds64f(E[(i + 4) % 6], sr + ((i + 4) % 6) * 32);
            E[4][0] += E[5][0]; E[4][1] += E[5][1];
            float m = fmaxf(fmaxf(fmaxf(fmaxf(E[0][0], E[0][1]), fmaxf(E[1][0], E[1][1])), fmaxf(fmaxf(E[2][0], E[2][1]), fmaxf(E[3][0], E[3][1]))), fmaxf(E[4][0], E[4][1]));
            m = fmaxf(m, __shfl_xor_sync(0xffffffffu, m, 1));
            m = fmaxf(m, __shfl_xor_sync(0xffffffffu, m, 2));
            m *= cs;
            if constexpr (AB) static_for<0, PRE3>([&](auto I) { load_w2<I.value>(w[I.value], w2a); });
            uint32_t pa[5];
#pragma unroll
            for (int i = 0; i < 5; i++) { const int k = (i + 4) % 5; E[k][0] = ex2(fmaf(E[k][0], cs, -m)); E[k][1] = ex2(fmaf(E[k][1], cs, -m)); pa[k] = pack2(E[k][0], E[k][1]); }
            if (EFENCE) sched_fence();
            float O[2][4], Z[4];
#pragma unroll
            for (int i = 0; i < 4; i++) { O[0][i] = O[1][i] = Z[i] = 0.f; }
#pragma unroll
            for (int i = 0; i < 2; i++) {
                mma1688(O[i], vm[i][0], vm[i][1], pa[4]);
                mma16816(O[i], vf[i][0], vf[i][1], vf[i][2], vf[i][3], pa[0], pa[1]);
                mma16816(O[i], vf[2 + i][0], vf[2 + i][1], vf[2 + i][2], vf[2 + i][3], pa[2], pa[3]);
            }
            const float z = (((E[4][0] + E[4][1]) + (E[0][0] + E[0][1])) + ((E[1][0] + E[1][1]) + (E[2][0] + E[2][1]))) + (E[3][0] + E[3][1]);
            const float zh = __uint_as_float(__float_as_uint(z) & 0xffff0000u);
            mma1688(Z, isn, isn, pack2(zh, z - zh));
            const float i0 = rcp(Z[0]), i1 = rcp(Z[1]);
            stsm4t(ad[3], pack2(O[0][0] * i0, O[0][1] * i1), pack2(O[0][2] * i0, O[0][3] * i1), pack2(O[1][0] * i0, O[1][1] * i1), pack2(O[1][2] * i0, O[1][3] * i1));
            PROF(4)
            if constexpr (AB) wo_blocks<1, RESA, PRE3, OFENCE / 2>(w, wr + NR * 8, oa, w2a, po, pd, odd);
            else bar_arrive(3, 256);
            if (ROLE != 0) persist(s, warp, r0, r1);
            if (warp == 7 && l8 == sb) mbar_expect(sb + B_X, 4096);
        } else {
            if (ROLE != 0) persist(s, warp, r0, r1);
            wo_addr(); pin<1>(&oa);
            static_for<0, PRE2A>([&](auto I) { load_w2<I.value>(w[I.value], w2a); });
            mbar_wait(sb + B_X, s & 1);
            wait_clocks(XDELAY);
            constexpr int PRE1 = (BB - 1) * 16 - (5 - NRB) * 8 < PRE2 ? (BB - 1) * 16 - (5 - NRB) * 8 : PRE2;
            static_for<PRE2A, PRE1>([&](auto I) { load_w2<I.value>(w[I.value], w2a); });
            if (full) {
                static_for<PRE1, PRE2>([&](auto I) { load_w2<I.value>(w[I.value], w2a); });
                wo_blocks<BB, RESB, PRE2, FENCE2 * 2 + OFENCE % 2>(w, wr + NR * 8, oa, w2a, po, pd, odd);
            } else wo_blocks<BB - 1, RESB1, PRE1, FENCE2 * 2 + OFENCE % 2>(w, wr + NR * 8, oa, w2a, po, pd, odd);
        }
        PROF(5)
        if (l8 == sb) { sts32(sb + S_TO + warp * 4, gtime()); mbar_arrive(sb + B_RED); }
        if (HOLD) mbar_wait(sb + B_RED, s & 1);
        if (ROLE != 0 && (s & 3) == 3 && l8 == sb) mbar_arrive(sb + B_PERS);
        if (ROLE == 0 && s == 62) return;
    }
    __syncwarp();
    if (l8 == sb) mbar_arrive(sb + B_PERS);
}
#define IP(i)
struct Pipe { uint32_t stage, phase; };
struct Cons {
    uint32_t sb, rel;
    int wg, wq, lane, rank, pair;
    uint32_t atag, nst;
    Pipe p;
};
__device__ __forceinline__ void pipe_next(Pipe& p) { p.stage = (p.stage + 1) & (NSTAGE - 1); p.phase ^= (p.stage == 0); }
__device__ __forceinline__ void release(const Cons& c, uint32_t stage) { if (c.lane < 2) mbar_arrive_cluster(c.rel + stage * 8); }
__device__ __forceinline__ void wait_full(const Cons& c) { mbar_wait(c.sb + B_FULL + c.p.stage * 8, c.p.phase); }

enum { PEND_NONE = 0, PEND_KVO = 1, PEND_HT = 2, PEND_OUT = 3 };
struct Pend { uint32_t pk[64]; int kind, row, col, cnt; };

__device__ __forceinline__ void staging_wait(const Cons& c) { if (c.nst) mbar_wait(c.sb + B_SFREE + c.wg * 8, (c.nst - 1) & 1); }
__device__ __forceinline__ void staging_post(Cons& c, int kind, int row, int col, int cnt) {
    __syncwarp();
    if (c.lane == 0) {
        if (c.wq == 0) { const uint32_t x[4] = {(uint32_t)kind, (uint32_t)row, (uint32_t)col, (uint32_t)cnt}; sts128(c.sb + S_DESC + c.wg * 16, x); }
        mbar_arrive(c.sb + B_SFULL + c.wg * 8);
    }
    c.nst++;
}
template <bool KVONLY = false>
__device__ __forceinline__ void drain(const Params& P, Cons& c, Pend& d) {
    const uint32_t* pk = d.pk;
    if (!KVONLY && d.kind == PEND_OUT) {
        float* o = P.out + (size_t)(d.row + c.wq * 16 + (c.lane >> 2)) * 2048 + d.col + (c.lane & 3) * 2;
#pragma unroll
        for (int j = 0; j < 16; j++) {
            st_stream2(o + j * 8, bf_lo(pk[j * 2]), bf_hi(pk[j * 2]));
            st_stream2(o + 8 * 2048 + j * 8, bf_lo(pk[j * 2 + 1]), bf_hi(pk[j * 2 + 1]));
        }
    } else {
        const bool ht = !KVONLY && d.kind == PEND_HT;
        const int hi = (c.lane >> 3) & 1;
        const uint32_t base = c.sb + S_STG + c.wg * 16384 + ((ht ? hi * 32 + c.wq * 8 : c.wq * 16 + hi * 8) + (c.lane & 7)) * 128;
        staging_wait(c);
#pragma unroll
        for (int j = 0; j < 8; j++) {
            const int ch = (j & 3) * 2 + (c.lane >> 4);
            stsm4(base + (j >> 2) * 8192 + ((ch ^ (c.lane & 7)) << 4), pk[j * 4], pk[j * 4 + 1], pk[j * 4 + 2], pk[j * 4 + 3]);
        }
        fence_async_smem();
        staging_post(c, d.kind, d.row, d.col, (d.col & 128) ? d.cnt : -1);
    }
    if (d.col & 128) d.kind = PEND_NONE;
    d.col += 128;
#pragma unroll
    for (int i = 0; i < 32; i++) d.pk[i] = d.pk[32 + i];
}

__device__ __forceinline__ void store_warp(const Params& P, uint32_t sb, int wg, int cta) {
    if (cta < 128) {
        const uint32_t e1 = ld_acquire(&g_cnt(C_EPOCH)) + 1;
        const uint4* x = (const uint4*)P.Bx + (cta * 2 + wg) * 1024 + (threadIdx.x & 31);
        uint32_t m = 0;
#pragma unroll 4
        for (int i = 0; i < 32; i++) { const uint4 u = __ldg(x + i * 32); m = amax(amax(m, amax(u.x, u.y)), amax(u.z, u.w)); }
        m = warp_exp(m);
        if (elect_one()) { atomicMax(&g_cnt(C_XMAX), e1 << 8 | m); red_release(&g_cnt(C_XCNT)); }
        __syncwarp();
    }
    const uint32_t stg = sb + S_STG + wg * 16384;
#pragma unroll 1
    for (uint32_t n = 0;; n++) {
        mbar_wait(sb + B_SFULL + wg * 8, n & 1);
        uint32_t x[4];
        lds128(x, sb + S_DESC + wg * 16);
#pragma unroll
        for (int i = 0; i < 4; i++) x[i] = __shfl_sync(0xffffffffu, x[i], 0);
        if (x[0] == PEND_NONE) break;
        const bool ht = x[0] == PEND_HT;
        const CUtensorMap* m = &P.tm[ht ? M_HTS : M_KVO];
        if (elect_one()) {
#pragma unroll
            for (int i = 0; i < 4; i++) tma_store2d(m, x[2] + (i >> 1) * 64, x[1] + (i & 1) * (ht ? 1024 : 32), stg + i * 4096);
            bulk_commit();
            bulk_wait_read();
            mbar_arrive(sb + B_SFREE + wg * 8);
            if ((int)x[3] >= 0) { bulk_wait_all(); fence_async(); red_release(&g_cnt(x[3])); }
        }
        __syncwarp();
    }
}

template <int TA, int TB>
__device__ __forceinline__ void issue_ktile(float* acc, const Cons& c) {
    const uint32_t a = c.sb + c.p.stage * STAGE + c.wg * 8192, b = c.sb + c.p.stage * STAGE + 16384;
    const uint64_t da = mkdesc(a, TA ? 8192 : 16, 1024, 1), db = mkdesc(b, TB ? 8192 : 16, 1024, 1);
    wg_fence();
#pragma unroll
    for (int k = 0; k < 4; k++) wgmma_ss256<TA, TB>(acc, da + (TA ? 128 : 2) * k, db + (TB ? 128 : 2) * k);
    wg_commit();
}
template <bool KVONLY = false>
__device__ __forceinline__ void mainloop(float* acc, const Params& P, Cons& c, Pend& d, int type, int nk) {
    uint32_t prev = 0;
#pragma unroll
    for (int i = 0; i < 128; i++) acc[i] = 0.f;
    pin<128>(acc);
#pragma unroll 1
    for (int kt = 0; kt < nk; kt++) {
        wait_full(c);
        if (!KVONLY && type == T_A1) issue_ktile<0, 0>(acc, c);
        else if (!KVONLY && type == T_A2) issue_ktile<1, 0>(acc, c);
        else issue_ktile<0, 1>(acc, c);
        wg_wait<1>();
        if (kt) release(c, prev);
        else if (!KVONLY) { IP(0) }
        if (!KVONLY && d.kind != PEND_NONE && kt != 1) drain(P, c, d);
        prev = c.p.stage;
        pipe_next(c.p);
    }
    d.kind = PEND_NONE;
    wg_wait<0>();
    pin<128>(acc);
    release(c, prev);
    if (!KVONLY) { IP(1) }
}
__device__ __forceinline__ void pack_half(uint32_t* pk, const float* a) {
#pragma unroll
    for (int i = 0; i < 32; i++) pk[i] = pack2(a[2 * i], a[2 * i + 1]);
}

__device__ __forceinline__ void epi_kv(const float* acc, const Cons& c, Pend& d, int mb, int nb) {
    pack_half(d.pk, acc); pack_half(d.pk + 32, acc + 64);
    d.kind = PEND_KVO; d.row = (nb >> 4) * 2048 + mb * 256 + c.rank * 128 + c.wg * 64; d.col = (nb & 15) * 256; d.cnt = C_KV + mb;
}

__device__ __forceinline__ void qa_scores(float* S, float* Sm, const uint32_t* q, Cons& c) {
    wait_full(c);
    const uint32_t st = c.sb + c.p.stage * STAGE;
    const uint64_t dk = mkdesc(st + c.wg * 8192, 16, 1024, 1), dm = mkdesc(st + 32768 + c.wg * 4096, 128, 2048, 0);
    wg_fence();
#pragma unroll
    for (int i = 0; i < 8; i++) wgmma_rs64<0>(S, q + i * 4, dk + (i >> 2) * 1024 + (i & 3) * 2, i != 0);
#pragma unroll
    for (int i = 0; i < 8; i++) wgmma_rs16<0>(Sm, q + i * 4, dm + i * 16, i != 0);
    wg_commit();
    pipe_next(c.p);
}
__device__ __forceinline__ void qa_softmax(uint32_t (*pa)[4], const float* S, const float* Sm, const Cons& c) {
    const int t = c.lane & 3, i0 = (c.wq & 1) * 16 + (c.lane >> 2) - 2 * t;
    const bool sg = c.wq >= 2;
    const float cs = 0.08838834764831845f * 1.4426950408889634f;
    float x[2][10];
#pragma unroll
    for (int r = 0; r < 2; r++) {
#pragma unroll
        for (int j = 0; j < 4; j++)
#pragma unroll
            for (int e = 0; e < 2; e++) {
                const float v = sg ? S[16 + j * 4 + r * 2 + e] : S[j * 4 + r * 2 + e];
                x[r][j * 2 + e] = (j * 8 + e - r * 8 > i0) ? -1e9f / 0.08838834764831845f : v;
            }
        x[r][8] = sg ? Sm[4 + r * 2] : Sm[r * 2];
        x[r][9] = sg ? Sm[5 + r * 2] : Sm[1 + r * 2];
        float m = fmaxf(fmaxf(fmaxf(fmaxf(x[r][0], x[r][1]), fmaxf(x[r][2], x[r][3])), fmaxf(fmaxf(x[r][4], x[r][5]), fmaxf(x[r][6], x[r][7]))), fmaxf(x[r][8], x[r][9]));
        m = fmaxf(m, __shfl_xor_sync(0xffffffffu, m, 1));
        m = fmaxf(m, __shfl_xor_sync(0xffffffffu, m, 2));
        m *= -cs;
#pragma unroll
        for (int i = 0; i < 10; i++) x[r][i] = ex2(fmaf(x[r][i], cs, m));
        float sum = (((x[r][0] + x[r][1]) + (x[r][2] + x[r][3])) + ((x[r][4] + x[r][5]) + (x[r][6] + x[r][7]))) + (x[r][8] + x[r][9]);
        sum += __shfl_xor_sync(0xffffffffu, sum, 1);
        sum += __shfl_xor_sync(0xffffffffu, sum, 2);
        const float inv = rcp(sum);
#pragma unroll
        for (int i = 0; i < 10; i++) x[r][i] *= inv;
    }
#pragma unroll
    for (int ks = 0; ks < 2; ks++)
#pragma unroll
        for (int i = 0; i < 4; i++) {
            const uint32_t p = pack2(x[i & 1][ks * 4 + (i >> 1) * 2], x[i & 1][ks * 4 + (i >> 1) * 2 + 1]);
            pa[ks][i] = sg ? 0u : p;
            pa[2 + ks][i] = sg ? p : 0u;
        }
#pragma unroll
    for (int r = 0; r < 2; r++) {
        const uint32_t p = pack2(x[r][8], x[r][9]);
        pa[4][r] = sg ? 0u : p;
        pa[4][2 + r] = sg ? p : 0u;
    }
}
__device__ __forceinline__ void qa_values(float* O, uint32_t (*pa)[4], Cons& c) {
    wait_full(c);
    const uint32_t st = c.sb + c.p.stage * STAGE;
    const uint64_t dv = mkdesc(st + c.wg * 8192, 16384, 1024, 1), dm = mkdesc(st + 32768 + c.wg * 4096, 2048, 128, 0);
    pin<20>(&pa[0][0]);
    wg_fence();
#pragma unroll
    for (int ks = 0; ks < 4; ks++) wgmma_rs128<1>(O, pa[ks], dv + ks * 128, ks != 0);
    wgmma_rs128<0>(O, pa[4], dm, 1);
    wg_commit();
    pipe_next(c.p);
}
__device__ __forceinline__ void epi_qa(const float* acc, Cons& c, Pend& d, int mb, int nb) {
    uint32_t q[64], pa[2][5][4];
    float S0[32] = {}, M0[8] = {}, S1[32] = {}, M1[8] = {}, O0[64] = {}, O1[64] = {};
    const uint32_t k0 = c.p.stage;
    pack_half(q, acc);
    pin<32>(q); pin<32>(S0); pin<8>(M0);
    qa_scores(S0, M0, q, c);
    pack_half(q + 32, acc + 64);
    pin<32>(q + 32); pin<32>(S1); pin<8>(M1);
    qa_scores(S1, M1, q + 32, c);
    wg_wait<1>();
    pin<32>(S0); pin<8>(M0);
    release(c, k0);
    qa_softmax(pa[0], S0, M0, c);
    wg_wait<0>();
    pin<32>(S1); pin<8>(M1); pin<64>(q);
    release(c, (k0 + 1) & (NSTAGE - 1));
    pin<64>(O0);
    qa_values(O0, pa[0], c);
    qa_softmax(pa[1], S1, M1, c);
    pin<64>(O1);
    qa_values(O1, pa[1], c);
    wg_wait<1>();
    pin<64>(O0); pin<20>(&pa[0][0][0]);
    release(c, (k0 + 2) & (NSTAGE - 1));
    pack_half(d.pk, O0);
    wg_wait<0>();
    pin<64>(O1); pin<20>(&pa[1][0][0]);
    release(c, (k0 + 3) & (NSTAGE - 1));
    pack_half(d.pk + 32, O1);
    d.kind = PEND_KVO; d.row = 4096 + mb * 256 + c.rank * 128 + c.wg * 64; d.col = nb * 256; d.cnt = C_O + mb;
}

__device__ __forceinline__ void epi_op(const float* acc, const Cons& c, Pend& d, int mb, int nb) {
    pack_half(d.pk, acc); pack_half(d.pk + 32, acc + 64);
    d.kind = PEND_OUT; d.row = mb * 256 + c.rank * 128 + c.wg * 64; d.col = 1024 + nb * 256;
}

__device__ __forceinline__ void epi_a2(float* acc, const Params& P, Cons& c, int mb, int col0) {
    const int g = c.lane >> 2, t = c.lane & 3;
    const int row = mb * 256 + (g >> 1) * 64 + (c.rank * 16 + c.wg * 8 + c.wq * 2) * 2 + (g & 1);
    float* o = P.out + (size_t)row * 2048 + col0 + t * 2;
#pragma unroll 1
    for (int hf = P.zero; hf < 2; hf++) {
    wait_full(c);
    const uint32_t st = c.sb + c.p.stage * STAGE, xa = st + (c.wg * 64 + c.wq * 16 + g) * 128 + t * 4 + (g << 4), da = st + 32768 + t * 4;
#pragma unroll
    for (int j = 0; j < 16; j++) {
        const float* a = acc + j * 4;
        const uint32_t ad = (xa ^ ((j & 7) << 4)) + (j >> 3) * 16384;
        const uint32_t x0 = lds32(ad), x1 = lds32(ad + 1024), dv = lds32(da + j * 16);
        const uint32_t u0 = mul_bf2(x0, dv), u1 = mul_bf2(x1, dv);
        st_stream2(o + j * 8, a[0] + bf_lo(u0), a[1] + bf_hi(u0));
        st_stream2(o + 2 * 2048 + j * 8, a[2] + bf_lo(u1), a[3] + bf_hi(u1));
    }
    __syncwarp();
    release(c, c.p.stage);
    pipe_next(c.p);
    o += 128;
#pragma unroll
    for (int i = 0; i < 64; i++) acc[i] = acc[64 + i];
    }
}

#define TSTAMP(i)
__device__ __forceinline__ float2 cmul(float2 a, float2 b) { return make_float2(fmaf(a.x, b.x, -a.y * b.y), fmaf(a.x, b.y, a.y * b.x)); }
__device__ __forceinline__ float2 cfma(float2 a, float2 b, float2 u) { return make_float2(fmaf(a.x, b.x, fmaf(-a.y, b.y, u.x)), fmaf(a.x, b.y, fmaf(a.y, b.x, u.y))); }
__device__ __forceinline__ float4 ssm_coef(float lre, float lim, float logdt) {
    const float dt = __bfloat162float(__float2bfloat16(expf(logdt)));
    const float ea = expf(dt * lre);
    float sn, cn;
    sincosf(dt * lim, &sn, &cn);
    const float br = ea * cn, bi = ea * sn, nr = br - 1.f;
    float cr, ci;
    if (fabsf(lre) >= fabsf(lim)) { const float r = lim / lre, dn = lre + lim * r; cr = (nr + bi * r) / dn; ci = (bi - nr * r) / dn; }
    else { const float r = lre / lim, dn = lre * r + lim; cr = (nr * r + bi) / dn; ci = (bi * r - nr) / dn; }
    return make_float4(br, bi, cr, ci);
}
__device__ __forceinline__ void epi_a1(const float* acc, const Params& P, const Cons& c, Pend& d, int mb, int nb, uint32_t atag) {
    const int t = c.lane & 3;
    const int p = nb * 128 + c.rank * 64 + c.wg * 32 + c.wq * 8 + (c.lane >> 2);
    const float4 cf = __ldcg(&g_coef[p]);
    const float2 lam = make_float2(cf.x, P.swap_ri ? -cf.y : cf.y);
    const float a0 = P.swap_ri ? -2.f * cf.w : 2.f * cf.z, a1 = P.swap_ri ? 2.f * cf.z : -2.f * cf.w;
    const float b0 = P.swap_ri ? -2.f * cf.z : -2.f * cf.w, b1 = P.swap_ri ? -2.f * cf.w : -2.f * cf.z;
    float2 h = make_float2(0.f, 0.f);
#pragma unroll 1
    for (int round = P.zero; round < 2; round++) {
#pragma unroll
        for (int j = 0; j < 32; j++) {
            h = cfma(lam, h, make_float2(acc[j * 4], acc[j * 4 + 2]));
            const float r0 = fmaf(a0, h.x, a1 * h.y), m0 = fmaf(b0, h.x, b1 * h.y);
            h = cfma(lam, h, make_float2(acc[j * 4 + 1], acc[j * 4 + 3]));
            d.pk[j * 2] = pack2(r0, fmaf(a0, h.x, a1 * h.y));
            d.pk[j * 2 + 1] = pack2(m0, fmaf(b0, h.x, b1 * h.y));
        }
        if (round) continue;
        float2 l64 = lam;
#pragma unroll
        for (int i = 0; i < 6; i++) l64 = cmul(l64, l64);
        const float2 l128 = cmul(l64, l64), l256 = cmul(l128, l128);
        float2 o = make_float2(__shfl_up_sync(0xffffffffu, h.x, 1), __shfl_up_sync(0xffffffffu, h.y, 1));
        if (t >= 1) h = cfma(l64, o, h);
        o = make_float2(__shfl_up_sync(0xffffffffu, h.x, 2), __shfl_up_sync(0xffffffffu, h.y, 2));
        if (t >= 2) h = cfma(l128, o, h);
        IP(2)
        if (t == 3) st_relaxed2(&g_agg[mb * 1024 + p], (__float_as_uint(h.x) & ~1u) | atag, __float_as_uint(h.y));
        h = make_float2(__shfl_up_sync(0xffffffffu, h.x, 1), __shfl_up_sync(0xffffffffu, h.y, 1));
        if (t == 0) h = make_float2(0.f, 0.f);
        uint32_t ax[7], ay[7];
        int n = 0;
        while (true) {
            uint32_t bad = 0;
#pragma unroll
            for (int j = 0; j < 7; j++) { ax[j] = atag; ay[j] = 0; ld_relaxed2_if(ax[j], ay[j], &g_agg[j * 1024 + p], j < mb); }
#pragma unroll
            for (int j = 0; j < 7; j++) bad |= ax[j] ^ atag;
            if (tags_ok(bad)) break;
            __nanosleep(400);
            if (++n > SPIN_LIMIT) spin_fault();
        }
        float2 carry = make_float2(0.f, 0.f);
#pragma unroll
        for (int j = 0; j < 7; j++) if (j < mb) carry = cfma(l256, carry, make_float2(__uint_as_float(ax[j]), __uint_as_float(ay[j])));
        float2 w = (t & 1) ? l64 : make_float2(1.f, 0.f);
        if (t & 2) w = cmul(w, l128);
        h = cfma(w, carry, h);
        IP(3)
    }
    IP(4)
    d.kind = PEND_HT; d.row = nb * 128 + c.rank * 64 + c.wg * 32; d.col = mb * 256; d.cnt = C_HT + mb;
}

__device__ __forceinline__ uint32_t fresh_tid() { uint32_t t; asm volatile("mov.u32 %0, %%tid.x;" : "=r"(t)); return t; }
__device__ __forceinline__ uint32_t acquire_stage(uint32_t sb, Pipe& p, uint32_t bytes) {
    mbar_wait(sb + B_EMPTY + p.stage * 8, p.phase ^ 1);
    mbar_expect_e(sb + B_FULL + p.stage * 8, bytes);
    return p.stage;
}
__device__ __forceinline__ void producer(const Params& P, const uint32_t sb, const int cta, const uint32_t epoch) {
    Pipe p = {0, 0};
    const uint32_t e1 = epoch + 1;
    const int rank = cta & 1;
    const uint16_t both = 3 << (__shfl_sync(0xffffffffu, cluster_rank(), 0) & ~1u);
    for (int it = ITEM_OFF(cta >> 1); it < ITEM_OFF((cta >> 1) + 1); it++) {
        const int item = ITEM(it), kind = (item >> 8) & 7, mb = (item >> 5) & 7;
        const int half = kind >= T_OPH, type = half ? kind * 2 - 10 : kind, nb = item & (half ? 3 : 31), hw = item >> 2 & half;
        if (type == T_CHAIN) {
            const int h = cta / 3, role = cta - h * 3;
            uint32_t* flag = &g_cnt(C_FLAG + (role == 2 ? 32 : 0) + h);
            if (role) { wait_count(&g_cnt(C_KV), e1 * 128); fence_async(); }
#pragma unroll 1
            for (int s = 0; s < 64 && role != 0; s++) {
                if (s < 63) {
                    mbar_wait(sb + B_GO, s & 1);
                    tma3d_mc_e(sb + S_KV + (role - 1) * 8192, &P.tm[M_SEG], 0, (role - 1) * 2048 + s * 32, h * 2, sb + B_KVFULL, 7 << ((h & 1) * 3));
                    if ((s & 7) == 7) { wait_count(&g_cnt(C_KV + 1 + (s >> 3)), e1 * 128); fence_async(); }
                    tma_prefetch3d_e(&P.tm[M_SEG], 0, (role - 1) * 2048 + s * 32 + 32, h * 2);
                }
                if (s > 0 && ((s & 3) == 0 || s == 63)) {
                    const int i = (s - 1) >> 2;
                    mbar_wait(sb + B_PERS, i & 1);
                    asm volatile("{\n.reg .pred E;\nelect.sync _|E, 0xffffffff;\n@E st.release.gpu.global.u32 [%0], %1;\n}" ::"l"(flag), "r"(epoch * 64 + i * 4 + 4) : "memory");
                }
            }
            if (role == 0) {
                const int lane = threadIdx.x & 31;
                if (lane == 0) mbar_arrive(sb + B_RELM);
#pragma unroll 1
                for (int s = 0; s < 63; s++) {
                    mbar_wait(sb + B_P1, s & 1);
                    if (s > 0) {
                        st_relaxed4(P.xb + xg_buf(s - 1) + h * 2048 + xg_lane(lane), 0, 0, 0, 0);
                        st_relaxed1(P.xb + xg_buf(s - 1) + xg_side(h) + lane * 4, 0);
                        __threadfence();
                    }
                    __syncwarp();
                    if (lane == 0) mbar_arrive(sb + B_RELM);
                }
            }
            mbar_wait(sb + B_RESUME, 0);
            continue;
        }
        const int m0 = mb * 256 + rank * 128;
        if (type <= T_OP) {
            const CUtensorMap* ma = &P.tm[half ? M_OAH : type == T_OP ? M_OA : M_BX];
            const CUtensorMap* mw = &P.tm[type == T_OP ? M_WO : type == T_QA ? M_WQ : nb < 16 ? M_WK : M_WV];
            const int nk = type == T_OP ? 64 : 16, nc = (nb & 15) * 4 + rank * 2, ma0 = type == T_OP ? 4096 + m0 + hw * 64 : m0;
            if (type == T_OP) { wait_count(&g_cnt(C_O + mb), e1 * 64); fence_async(); }
            if (type == T_QA) {
                wait_count(&g_cnt(C_KV + mb), e1 * 128);
                fence_async();
            }
            auto arrived = [&]() {
                const uint32_t t = fresh_tid();
                return __all_sync(0xffffffffu, (int32_t)(ld_acquire(&g_cnt(C_FLAG + (t & 2) * 16 + nb * 2 + (t & 1))) - (epoch * 64 + mb * 8 + rank * 4 + 4)) >= 0);
            };
            bool passed = false;
#pragma unroll 1
            for (int kt = 0; kt < nk; kt++) {
                if (type == T_QA && kt == 9) passed = arrived();
                const uint32_t st = acquire_stage(sb, p, STAGE - half * 8192), bar = sb + B_FULL + st * 8;
                tma2d_e(sb + st * STAGE + hw * 8192, ma, kt * 64, ma0, bar);
                tma3d_mc_e(sb + st * STAGE + 16384 + rank * 16384, mw, 0, kt * 64, nc, bar, both);
                if (type == T_QA && kt < 8) tma_prefetch2d_e(&P.tm[M_OA], nb * 256 + (kt & 3) * 64, (kt >> 2) * 2048 + m0);
                pipe_next(p);
            }
            if (type == T_QA) {
                for (int n = 0; !passed; n++) { passed = arrived(); if (!passed) __nanosleep(200); if (n > SPIN_LIMIT) spin_fault(); }
                fence_async();
#pragma unroll 1
                for (int e = 0; e < 4; e++) {
                    const uint32_t st = acquire_stage(sb, p, 40960), bar = sb + B_FULL + st * 8, dst = sb + st * STAGE;
                    tma2d_e(dst, &P.tm[M_OA], nb * 256 + (e & 1) * 128, (e >> 1) * 2048 + m0, bar);
                    tma2d_e(dst + 16384, &P.tm[M_OA], nb * 256 + (e & 1) * 128 + 64, (e >> 1) * 2048 + m0, bar);
                    const uint32_t* src = ((e >> 1) ? g_vmt : g_km) + ((mb * 8 + rank * 4) * 32 + nb * 2 + (e & 1)) * 512;
#pragma unroll 1
                    for (int i = 0; i < 4; i++) bulk_g2s_e(dst + 32768 + i * 2048, src + i * 32 * 512, 2048, bar);
                    pipe_next(p);
                }
            }
        } else if (type == T_A1) {
            wait_count(&g_cnt(C_COEF), e1 * 4);
#pragma unroll 1
            for (int kt = 0; kt < 16; kt++) {
                const uint32_t st = acquire_stage(sb, p, STAGE), bar = sb + B_FULL + st * 8;
                tma4d_e(sb + st * STAGE, &P.tm[M_AB], kt * 64, nb * 16 + rank * 8, bar);
                tma4d_mc_e(sb + st * STAGE + 16384 + rank * 16384, &P.tm[M_AX], kt * 64, mb * 128 + rank * 16, bar, both);
                pipe_next(p);
            }
        } else {
            wait_count(&g_cnt(C_HT + mb), e1 * 32);
            fence_async();
#pragma unroll 1
            for (int kt = 0; kt < 32; kt++) {
                const uint32_t st = acquire_stage(sb, p, STAGE - half * 8192), bar = sb + B_FULL + st * 8;
                tma3d_e(sb + st * STAGE + hw * 8192, &P.tm[half ? M_HTH : M_HT], 0, kt * 64, mb * 4 + rank * 2 + hw, bar);
                tma2d_mc_e(sb + st * STAGE + 16384 + rank * 16384, &P.tm[M_CRE] + (kt >> 4), (kt & 15) * 64, (nb * 2 + rank) * 128, bar, both);
                pipe_next(p);
            }
#pragma unroll 1
            for (int col = nb * 256; col < (nb + 1) * 256; col += 128) {
                const uint32_t st = acquire_stage(sb, p, 32768 + 256), bar = sb + B_FULL + st * 8;
                tma4d_e(sb + st * STAGE, &P.tm[M_AX], col, mb * 128 + rank * 16, bar);
                tma4d_e(sb + st * STAGE + 16384, &P.tm[M_AX], col + 64, mb * 128 + rank * 16, bar);
                bulk_g2s_e(sb + st * STAGE + 32768, P.Dskip + col, 256, bar);
                pipe_next(p);
            }
        }
    }
}

__device__ __forceinline__ uint32_t fresh_ctaid() { uint32_t t; asm volatile("mov.u32 %0, %%ctaid.x;" : "=r"(t)); return t; }
__device__ __forceinline__ void reset_state(const Params& P, Cons& c, Pend& d, uint32_t sb, bool resumed) {
    const uint32_t t = fresh_tid(), b = fresh_ctaid() + P.cta0;
    const int w = __shfl_sync(0xffffffffu, t >> 5, 0);
    c.sb = sb; c.wg = w >> 2; c.wq = w & 3; c.lane = t & 31;
    c.rank = __shfl_sync(0xffffffffu, b & 1, 0); c.pair = __shfl_sync(0xffffffffu, b >> 1, 0);
    c.rel = mapa(sb + B_EMPTY, cluster_rank() ^ (c.lane & 1));
    c.atag = (ld_acquire(&g_cnt(C_EPOCH)) + 1) & 1;
    c.p.stage = 0; c.p.phase = 0;
    c.nst = resumed && c.pair < NCHAIN ? 2 : 0;
    d = Pend{};
}
#define PROF_ITEM(i, item)

__global__ void __launch_bounds__(384, 1) fused_kernel(const __grid_constant__ Params P) {
    extern __shared__ __align__(1024) uint8_t smem[];
    const uint32_t sb = smem_u32(smem);
    asm volatile("griddepcontrol.launch_dependents;");
    declare_fence(P.zero);
    const int tid = threadIdx.x, lane = tid & 31;
    const int warp = __shfl_sync(0xffffffffu, tid >> 5, 0);
    const int cta = __shfl_sync(0xffffffffu, blockIdx.x + P.cta0, 0), pair = cta >> 1, rank = cta & 1;
    if (tid == 0) {
        if (sb & 1023) spin_fault();
        for (int i = 0; i < NSTAGE; i++) { mbar_init(sb + B_FULL + i * 8, 1); mbar_init(sb + B_EMPTY + i * 8, 16); }
        mbar_init(sb + B_RESUME, 2);
        mbar_init(sb + B_KVFULL, 1);
        mbar_init(sb + B_GO, 3); mbar_init(sb + B_RED, 8); mbar_init(sb + B_P1, 1); mbar_init(sb + B_PERS, 8); mbar_init(sb + B_INIT, 8); mbar_init(sb + B_INIT2, 8);
        mbar_init(sb + B_READY, 8);
        for (int i = 0; i < 2; i++) { mbar_init(sb + B_SFULL + i * 8, 4); mbar_init(sb + B_SFREE + i * 8, 1); }
        mbar_init(sb + B_RELM, cta % 3 ? 1 : 2); mbar_init(sb + B_X, 9);
        asm volatile("fence.mbarrier_init.release.cluster;" ::: "memory");
        mbar_expect(sb + B_X, 4096);
        sts64(sb + S_EV, 0, 0); sts32(sb + S_RETRY, 0);
    }
    cluster_sync();
    if (warp >= 8) {
        asm volatile("setmaxnreg.dec.sync.aligned.u32 24;");
        if (warp == 8) {
            producer(P, sb, cta, __shfl_sync(0xffffffffu, ld_acquire(&g_cnt(C_EPOCH)), 0));
            asm volatile("barrier.cluster.arrive.relaxed.aligned;\nbarrier.cluster.wait.aligned;" ::: "memory");
        } else if (warp == 9) {
            if (pair < 64) l2_prefetch((const char*)(rank ? P.Wo : P.Wq) + (size_t)(pair * 32 + lane) * 4096, 4096);
            if (pair < NCHAIN) pacer(P, sb, cta, lane, __shfl_sync(0xffffffffu, ld_acquire(&g_cnt(C_EPOCH)), 0));
        } else {
            store_warp(P, sb, warp - 10, cta);
        }
    } else {
        asm volatile("setmaxnreg.inc.sync.aligned.u32 240;");
        Cons c;
        Pend d;
        if (pair < NCHAIN) {
            reset_state(P, c, d, sb, false);
            {
                const int item = ITEM(ITEM_OFF(pair));
                PROF_ITEM(0, item)
                float acc[128];
                mainloop<true>(acc, P, c, d, T_KV, 16);
                epi_kv(acc, c, d, (item >> 5) & 7, item & 31);
            }
            ISTAMP(4)
            bar_sync(1, 256);
            chain_load(P, sb, cta, warp, lane, 0);
            ISTAMP(9)
#pragma unroll 1
            for (int i = P.zero; i < 2; i++) drain<true>(P, c, d);
            ISTAMP(10)
            staging_wait(c);
            ISTAMP(11)
            PROF_ITEM(1, T_CHAIN << 8)
            const uint32_t epoch = __shfl_sync(0xffffffffu, ld_acquire(&g_cnt(C_EPOCH)), 0);
            uint32_t wr[40][4];
            chain_init(P, sb, cta, warp, lane, wr);
            if (warp < 4) chain_role<false>(P, sb, cta, warp, lane, epoch, wr);
            else chain_role<true>(P, sb, cta, warp, lane, epoch, wr);
            fence_async_smem();
            bar_sync(1, 256);
            const uint32_t t2 = fresh_tid();
            if (t2 < 2) mbar_arrive_cluster(mapa(sb + B_RESUME, cluster_rank() ^ t2));
        } else if (pair >= NPAIR - 2) {
            const int ch = (pair - (NPAIR - 2)) * 512 + rank * 256 + tid;
            g_coef[ch] = ssm_coef(__bfloat162float(P.Lre[ch]), __bfloat162float(P.Lim[ch]), __bfloat162float(P.logdt[ch]));
            bar_sync(1, 256);
            if (tid == 0) red_release(&g_cnt(C_COEF));
        }
        reset_state(P, c, d, sb, true);
        bool urgent = false;
        for (int it = ITEM_OFF(c.pair) + (c.pair < NCHAIN ? 2 : 0);; it++) {
            const bool last = it == ITEM_OFF(c.pair + 1);
            const int item = ITEM(it), kind = (item >> 8) & 7, mb = (item >> 5) & 7;
            const int half = kind >= T_OPH, type = half ? kind * 2 - 10 : kind, nb = item & (half ? 3 : 31);
            const bool idle = half && (item >> 2 & 1) != c.wg;
            if (d.kind != PEND_NONE && (last || urgent || idle || !bar_and(5 + c.wg, mbar_try(sb + B_FULL + c.p.stage * 8, c.p.phase)))) {
#pragma unroll 1
                while (d.kind != PEND_NONE) drain(P, c, d);
            }
            if (last) break;
            const int nk = type == T_OP ? 64 : type == T_A2 ? 32 : 16;
            PROF_ITEM(it - ITEM_OFF(c.pair), item)
            urgent = item & URGENT;
            if (idle) {
#pragma unroll 1
                for (int kt = nk + (type == T_A2 ? 2 : 0); kt > 0; kt--) { wait_full(c); release(c, c.p.stage); pipe_next(c.p); }
                continue;
            }
            float acc[128];
            mainloop(acc, P, c, d, type, nk);
            if (type == T_KV) epi_kv(acc, c, d, mb, nb);
            else if (type == T_QA) epi_qa(acc, c, d, mb, nb);
            else if (type == T_OP) epi_op(acc, c, d, mb, nb);
            else if (type == T_A1) epi_a1(acc, P, c, d, mb, nb, c.atag);
            else epi_a2(acc, P, c, mb, nb * 256);
        }
        staging_wait(c);
        staging_post(c, PEND_NONE, 0, 0, 0);
        cluster_sync();
        if (c.wg == 0 && c.wq == 0 && c.lane == 0 && atomicInc(&g_cnt(C_DONE), NPAIR * 2 - 1) == NPAIR * 2 - 1) { __threadfence(); atomicAdd(&g_cnt(C_EPOCH), 1); }
    }
}

typedef CUresult (*EncodeFn)(CUtensorMap*, CUtensorMapDataType, cuuint32_t, void*, const cuuint64_t*, const cuuint64_t*, const cuuint32_t*, const cuuint32_t*,
                             CUtensorMapInterleave, CUtensorMapSwizzle, CUtensorMapL2promotion, CUtensorMapFloatOOBfill);
void encode(EncodeFn fn, CUtensorMap* m, const void* base, int rank, const uint64_t* dims, const uint64_t* strides, const uint32_t* box, CUtensorMapSwizzle swz = CU_TENSOR_MAP_SWIZZLE_128B) {
    cuuint64_t d[5], s[5]; cuuint32_t b[5], e[5];
    for (int i = 0; i < rank; i++) { d[i] = dims[i]; b[i] = box[i]; e[i] = 1; if (i) s[i - 1] = strides[i - 1]; }
    fn(m, CU_TENSOR_MAP_DATA_TYPE_BFLOAT16, rank, (void*)base, d, s, b, e, CU_TENSOR_MAP_INTERLEAVE_NONE, swz,
       CU_TENSOR_MAP_L2_PROMOTION_L2_256B, CU_TENSOR_MAP_FLOAT_OOB_FILL_NONE);
}
void map_kmajor(EncodeFn fn, CUtensorMap* m, const void* base, uint64_t rows, uint64_t cols, uint32_t box_rows) {
    const uint64_t d[2] = {cols, rows}, s[1] = {cols * 2}; const uint32_t b[2] = {64, box_rows};
    encode(fn, m, base, 2, d, s, b);
}
void map_mnmajor(EncodeFn fn, CUtensorMap* m, const void* base, uint64_t krows, uint64_t cols, uint32_t groups = 2) {
    const uint64_t d[3] = {64, krows, cols / 64}, s[2] = {cols * 2, 128}; const uint32_t b[3] = {64, 64, groups};
    encode(fn, m, base, 3, d, s, b);
}

}

extern "C" void kernel_launch(void* const* d_in, const int* in_sizes, int n_in, void* d_out, int out_size) {
    static Params P;
    static EncodeFn fn = nullptr;
    if (!fn) {
        cudaDriverEntryPointQueryResult q;
        cudaGetDriverEntryPoint("cuTensorMapEncodeTiled", (void**)&fn, cudaEnableDefault, &q);
        cudaFuncSetAttribute(fused_kernel, cudaFuncAttributeMaxDynamicSharedMemorySize, S_TOTAL);
    }
    const bf16* in[15];
    for (int i = 0; i < 15; i++) in[i] = (const bf16*)d_in[i];
    void *kvo, *ht;
    cudaGetSymbolAddress(&kvo, g_kvo);
    cudaGetSymbolAddress(&ht, g_ht);
    map_kmajor(fn, &P.tm[M_BX], in[9], 2048, 1024, 128);
    map_mnmajor(fn, &P.tm[M_WQ], in[11], 1024, 4096);
    map_mnmajor(fn, &P.tm[M_WK], in[12], 1024, 4096);
    map_mnmajor(fn, &P.tm[M_WV], in[13], 1024, 4096);
    map_mnmajor(fn, &P.tm[M_WO], in[14], 4096, 1024);
    map_kmajor(fn, &P.tm[M_OA], kvo, 3 * 2048, 4096, 128);
    P.swap_ri = in[4] < in[3];
    {
        const bf16* lo = P.swap_ri ? in[4] : in[3];
        const uint64_t diff = (uint64_t)((const char*)(P.swap_ri ? in[3] : in[4]) - (const char*)lo);
        const uint64_t d[4] = {1024, 8, 2, 128}, s[3] = {2048, diff, 16384}; const uint32_t b[4] = {64, 8, 2, 8};
        encode(fn, &P.tm[M_AB], lo, 4, d, s, b);
    }
    {
        const uint64_t d[4] = {1024, 2, 4, 1024}, s[3] = {2048, 64 * 2048, 4096}; const uint32_t b[4] = {64, 2, 4, 16};
        encode(fn, &P.tm[M_AX], in[0], 4, d, s, b);
    }
    map_mnmajor(fn, &P.tm[M_HT], ht, 2048, 2048);
    map_kmajor(fn, &P.tm[M_CRE], in[5], 1024, 1024, 128);
    map_kmajor(fn, &P.tm[M_CIM], in[6], 1024, 1024, 128);
    map_kmajor(fn, &P.tm[M_KVO], kvo, 3 * 2048, 4096, 32);
    map_kmajor(fn, &P.tm[M_HTS], ht, 2048, 2048, 32);
    map_kmajor(fn, &P.tm[M_OAH], kvo, 3 * 2048, 4096, 64);
    map_mnmajor(fn, &P.tm[M_HTH], ht, 2048, 2048, 1);
    for (int i = 0; i < 3; i++) {
        const uint64_t d[3] = {64, 1024, 64}, s[2] = {8192, 128}; const uint32_t b[3] = {64, 16, 2};
        encode(fn, &P.tm[M_C1 + i], in[11 + i], 3, d, s, b);
    }
    {
        const uint64_t d[2] = {1024, 4096}, s[1] = {2048}; const uint32_t b[2] = {32, 32};
        encode(fn, &P.tm[M_CO], in[14], 2, d, s, b, CU_TENSOR_MAP_SWIZZLE_64B);
    }
    {
        const uint64_t d[3] = {64, 3 * 2048, 64}, s[2] = {8192, 128}; const uint32_t b[3] = {64, 32, 2};
        encode(fn, &P.tm[M_SEG], kvo, 3, d, s, b);
    }
    void* xs;
    cudaGetSymbolAddress(&xs, g_x);
    P.xb = (uint8_t*)(((uintptr_t)xs + (2u << 20) - 1) & ~(uintptr_t)((2u << 20) - 1));
    P.Wq = in[11]; P.Wk = in[12]; P.Wv = in[13]; P.Wo = in[14]; P.mem0 = in[10]; P.Bx = in[9];
    P.Ax = in[0]; P.Lre = in[1]; P.Lim = in[2]; P.logdt = in[7]; P.Dskip = in[8];
    P.out = (float*)d_out;
    int pv[10] = {1300, 0, 140, 0, 330, 0, 32, 32, 250, 0};
    P.dly = pv[0]; P.mrg = pv[2];
    P.rd = pv[4]; P.guard = pv[5]; P.clampv = pv[6]; P.clamp0 = pv[7]; P.kvd = pv[9]; P.zd = pv[8];
    cudaLaunchConfig_t cfg = {};
    cudaLaunchAttribute at[2];
    cfg.blockDim = dim3(384); cfg.dynamicSmemBytes = S_TOTAL; cfg.stream = cudaStreamPerThread; cfg.attrs = at;
    at[0].id = cudaLaunchAttributeClusterDimension;
    at[0].val.clusterDim.y = at[0].val.clusterDim.z = 1;
    at[1].id = cudaLaunchAttributeProgrammaticStreamSerialization;
    at[1].val.programmaticStreamSerializationAllowed = 1;
    for (int i = 0; i < 2; i++) {
        P.cta0 = i ? 2 * NCHAIN : 0;
        cfg.gridDim = dim3(i ? 2 * (NPAIR - NCHAIN) : 2 * NCHAIN);
        at[0].val.clusterDim.x = i ? 2 : 6;
        cfg.numAttrs = 1 + i;
        cudaLaunchKernelEx(&cfg, fused_kernel, P);
    }
}
```

```cpp
#include <cuda_runtime.h>
#include <cuda_bf16.h>
#include <cuda.h>
#include <stdint.h>
#include <string.h>

typedef __nv_bfloat16 bf16;

namespace {

constexpr int SPIN_LIMIT = 1 << 22;
#define POLLNS 100
constexpr int NPAIR = 66;
constexpr int NCHAIN = 48;
enum { T_KV = 0, T_QA = 1, T_OP = 2, T_A1 = 3, T_A2 = 4, T_CHAIN = 5, T_OPH = 6, T_A2H = 7 };
constexpr int URGENT = 2048;
enum { M_BX = 0, M_WQ, M_WK, M_WV, M_WO, M_OA, M_AB, M_AX, M_HT, M_CRE, M_CIM, M_KVO, M_HTS, M_OAH, M_HTH, M_C1, M_CO = M_C1 + 3, M_SEG, M_COUNT };
enum { C_KV = 0, C_O = 8, C_HT = 16, C_DONE = 24, C_EPOCH = 25, C_COEF = 26, C_XMAX = 27, C_XCNT = 28, C_FLAG = 32 };

struct Params {
    CUtensorMap tm[M_COUNT];
    const bf16 *Wq, *Wk, *Wv, *Wo, *mem0, *Bx, *Ax, *Lre, *Lim, *logdt, *Dskip;
    float* out;
    uint8_t* xb;
    int swap_ri, zero;
    int dly, mrg, rd, guard, clampv, clamp0, kvd, xd, pd;
    uint16_t cta0;
};

__constant__ uint16_t c_off[67] = {0, 5, 10, 15, 20, 25, 30, 35, 40, 45, 50, 55, 60, 65, 70, 75, 80, 85, 90, 95, 100, 105, 110, 115, 120, 125, 130, 135, 140, 145, 150, 155, 160, 165, 170, 175, 180, 185, 190, 195, 200, 205, 210, 214, 218, 222, 226, 230, 234, 253, 272, 291, 310, 329, 348, 367, 386, 405, 424, 443, 462, 481, 500, 519, 537, 556, 574};
__constant__ uint16_t c_items[640] = {
    0, 1280, 2497, 3008, 1728, 16, 1280, 2498, 3009, 1732, 32, 1280, 2499, 3010, 1729, 1, 1280, 2500, 3011, 1733, 17, 1280, 2501, 3012,
    1730, 33, 1280, 2502, 3013, 1734, 2, 1280, 2503, 3014, 1731, 18, 1280, 2504, 3015, 1735, 34, 1280, 2505, 3040, 1760, 3, 1280, 2506,
    3041, 1764, 19, 1280, 2507, 3042, 1761, 35, 1280, 2508, 3043, 1765, 4, 1280, 2509, 3044, 1762, 20, 1280, 2510, 3045, 1766, 36, 1280,
    2511, 3046, 1763, 5, 1280, 2528, 3047, 1767, 21, 1280, 2529, 2886, 1024, 37, 1280, 2530, 2887, 1025, 6, 1280, 2531, 2912, 1026, 22,
    1280, 2532, 2913, 1027, 38, 1280, 2533, 2914, 1056, 7, 1280, 2534, 2915, 1057, 23, 1280, 2535, 2916, 1058, 39, 1280, 2536, 2917, 1059,
    8, 1280, 2537, 2918, 1088, 24, 1280, 2538, 2919, 1089, 40, 1280, 2539, 2944, 1090, 9, 1280, 2540, 2945, 1091, 25, 1280, 2541, 2946,
    1120, 41, 1280, 2542, 2947, 1121, 10, 1280, 2543, 2948, 1122, 26, 1280, 2821, 2949, 1123, 42, 1280, 2822, 2950, 1152, 11, 1280, 2823,
    2951, 1153, 27, 1280, 2848, 2976, 1154, 43, 1280, 2849, 2977, 1155, 12, 1280, 2850, 2978, 1184, 28, 1280, 2851, 2979, 1185, 44, 1280,
    2852, 2980, 1186, 13, 1280, 2853, 2981, 1187, 29, 1280, 2854, 2982, 1216, 45, 1280, 2855, 2983, 1217, 14, 1280, 2885, 642, 30, 1280,
    2884, 643, 46, 1280, 2883, 672, 15, 1280, 2882, 673, 31, 1280, 2881, 674, 47, 1280, 2880, 675, 48, 66, 84, 102, 256, 124,
    142, 160, 175, 191, 207, 224, 239, 298, 332, 366, 416, 2817, 610, 49, 67, 85, 103, 257, 125, 143, 161, 176, 192, 208,
    225, 240, 299, 333, 367, 417, 2818, 611, 50, 68, 86, 104, 258, 126, 144, 162, 177, 193, 209, 226, 241, 300, 334, 384,
    418, 2819, 640, 51, 69, 87, 105, 259, 127, 145, 163, 178, 194, 210, 227, 242, 301, 335, 385, 419, 2820, 641, 52, 70,
    88, 106, 260, 128, 146, 164, 179, 195, 211, 228, 243, 302, 352, 386, 420, 512, 1986, 53, 71, 89, 107, 261, 129, 147,
    165, 180, 196, 212, 229, 244, 303, 353, 387, 421, 513, 1990, 54, 72, 90, 108, 262, 130, 148, 166, 181, 197, 213, 230,
    245, 320, 354, 388, 422, 514, 1987, 55, 73, 91, 109, 263, 131, 149, 167, 182, 198, 214, 231, 246, 321, 355, 389, 423,
    515, 1991, 56, 74, 92, 110, 264, 132, 150, 168, 183, 199, 215, 232, 247, 322, 356, 390, 424, 544, 2016, 57, 75, 93,
    111, 265, 133, 151, 169, 184, 200, 216, 233, 248, 323, 357, 391, 425, 545, 2020, 58, 76, 94, 112, 266, 134, 152, 170,
    185, 201, 217, 234, 249, 324, 358, 392, 426, 546, 2017, 59, 77, 95, 113, 267, 135, 153, 171, 186, 202, 218, 235, 250,
    325, 359, 393, 427, 547, 2021, 60, 78, 96, 114, 268, 136, 154, 172, 187, 203, 219, 236, 251, 326, 360, 394, 428, 576,
    2018, 61, 79, 97, 115, 269, 137, 155, 173, 188, 204, 220, 237, 252, 327, 361, 395, 429, 577, 2022, 62, 80, 98, 116,
    270, 138, 156, 174, 189, 205, 221, 238, 253, 328, 362, 396, 430, 578, 2019, 63, 81, 99, 117, 271, 139, 157, 288, 190,
    292, 293, 296, 297, 331, 365, 399, 2816, 609, 64, 82, 100, 118, 120, 122, 140, 158, 289, 206, 222, 294, 254, 329, 363,
    397, 431, 579, 2023, 65, 83, 101, 119, 121, 123, 141, 159, 290, 291, 223, 295, 255, 330, 364, 398, 2496, 608,
};
#define ITEM_OFF(p) c_off[p]
#define ITEM(i) c_items[i]

__device__ __align__(1024) bf16 g_kvo[3 * 2048 * 4096];
__device__ __align__(1024) bf16 g_ht[2048 * 2048];
__device__ __align__(1024) uint8_t g_x[4 << 20];
__device__ __align__(1024) uint32_t g_km[64 * 32 * 512];
__device__ __align__(1024) uint32_t g_vmt[64 * 32 * 512];
__device__ __align__(1024) float2 g_agg[8 * 1024];
__device__ __align__(1024) float4 g_coef[1024];
__device__ __align__(1024) uint32_t g_cntl[128 * 32];
#define g_cnt(i) g_cntl[(i) * 32]
__device__ __align__(1024) uint32_t g_hint[96 * 32];
#define PROF(i)
#define PROFDUMP()
#define PROFP(i)
constexpr int XG_SIDE = 65536, XG_T = 98304;
__device__ __forceinline__ uint32_t xg_buf(int b) { return (b & 1) * 128 + (b & 2) * 256 + (b & 4) * 32768; }
__device__ __forceinline__ uint32_t xg_lane(uint32_t lane) { return (lane >> 4) * 1024 + (lane & 8) * 32 + (lane & 7) * 16; }
__device__ __forceinline__ uint32_t xg_side(int b) { return XG_SIDE + (b >> 1) * 1024 + (b & 1) * 256; }

constexpr int STAGE = 49152, NSTAGE = 4;
constexpr int S_STG = NSTAGE * STAGE;
constexpr int S_BAR = S_STG + 32768;
constexpr int B_FULL = S_BAR, B_EMPTY = S_BAR + 32, B_RESUME = S_BAR + 64, B_KVFULL = S_BAR + 72, B_GO = S_BAR + 88, B_X = S_BAR + 96, B_PERS = S_BAR + 104,
              B_INIT = S_BAR + 112, B_RELM = S_BAR + 120, B_READY = S_BAR + 136, B_SFULL = S_BAR + 144, B_SFREE = S_BAR + 160, S_DESC = S_BAR + 176, B_RED = S_BAR + 216;
constexpr int S_EV = S_BAR + 80, S_EO = S_BAR + 84, B_INIT2 = S_BAR + 128, S_SC = S_BAR + 208, S_ISC = S_EV;
constexpr int S_XV = S_BAR + 256, S_LOG = S_XV + 2048;
constexpr int S_TOTAL = S_LOG + 768;
#define NRA 5
#define NRB 3
constexpr int S_W1 = 0;
constexpr int S_W2 = 4 * 4096 * (16 - NRA - NRB);
constexpr int S_KV = 188416;
constexpr int S_P1 = S_KV + 16384;
constexpr int S_X = S_P1 + 16384;
constexpr int S_SX = S_P1, S_OX = S_P1 + 2048;
constexpr int S_EM = S_X + 4096, S_TO = S_EM + 1024, S_RETRY = S_BAR + 224, B_P1 = S_BAR + 232;
static_assert(S_TO + 32 <= S_BAR && S_KV % 1024 == 0 && S_TOTAL <= 232448, "chain smem layout");

template <int V> struct IC { static constexpr int value = V; };
template <int B, int E, typename F> __device__ __forceinline__ void static_for(F&& f) { if constexpr (B < E) { f(IC<B>{}); static_for<B + 1, E>(f); } }
__device__ __forceinline__ uint32_t cluster_rank() { uint32_t r; asm volatile("mov.u32 %0, %%cluster_ctarank;" : "=r"(r)); return r; }
__device__ __forceinline__ void spin_fault() { asm volatile("st.global.u32 [%0], 0;" ::"l"(0ull) : "memory"); }
__device__ __forceinline__ uint32_t smem_u32(const void* p) { return (uint32_t)__cvta_generic_to_shared(p); }
__device__ __forceinline__ uint32_t opq(uint32_t x, int lane) { return __shfl_sync(0xffffffffu, x, lane); }
__device__ __forceinline__ uint32_t mapa(uint32_t a, uint32_t r) { uint32_t d; asm volatile("mapa.shared::cluster.u32 %0, %1, %2;" : "=r"(d) : "r"(a), "r"(r)); return d; }
__device__ __forceinline__ void mma16816(float* d, uint32_t a0, uint32_t a1, uint32_t a2, uint32_t a3, uint32_t b0, uint32_t b1) {
    asm("mma.sync.aligned.m16n8k16.row.col.f32.bf16.bf16.f32 {%0,%1,%2,%3}, {%4,%5,%6,%7}, {%8,%9}, {%0,%1,%2,%3};"
        : "+f"(d[0]), "+f"(d[1]), "+f"(d[2]), "+f"(d[3]) : "r"(a0), "r"(a1), "r"(a2), "r"(a3), "r"(b0), "r"(b1));
}
__device__ __forceinline__ void mma1688(float* d, uint32_t a0, uint32_t a1, uint32_t b0) {
    asm("mma.sync.aligned.m16n8k8.row.col.f32.bf16.bf16.f32 {%0,%1,%2,%3}, {%4,%5}, {%6}, {%0,%1,%2,%3};"
        : "+f"(d[0]), "+f"(d[1]), "+f"(d[2]), "+f"(d[3]) : "r"(a0), "r"(a1), "r"(b0));
}
__device__ __forceinline__ void ldsm4(uint32_t* r, uint32_t a) {
    asm volatile("ldmatrix.sync.aligned.m8n8.x4.shared.b16 {%0,%1,%2,%3}, [%4];" : "=r"(r[0]), "=r"(r[1]), "=r"(r[2]), "=r"(r[3]) : "r"(a));
}
__device__ __forceinline__ void ldsm4t(uint32_t* r, uint32_t a) {
    asm volatile("ldmatrix.sync.aligned.m8n8.x4.trans.shared.b16 {%0,%1,%2,%3}, [%4];" : "=r"(r[0]), "=r"(r[1]), "=r"(r[2]), "=r"(r[3]) : "r"(a));
}
__device__ __forceinline__ void stsm4(uint32_t a, uint32_t r0, uint32_t r1, uint32_t r2, uint32_t r3) {
    asm volatile("stmatrix.sync.aligned.m8n8.x4.shared.b16 [%0], {%1,%2,%3,%4};" ::"r"(a), "r"(r0), "r"(r1), "r"(r2), "r"(r3) : "memory");
}
__device__ __forceinline__ void stsm4t(uint32_t a, uint32_t r0, uint32_t r1, uint32_t r2, uint32_t r3) {
    asm volatile("stmatrix.sync.aligned.m8n8.x4.trans.shared.b16 [%0], {%1,%2,%3,%4};" ::"r"(a), "r"(r0), "r"(r1), "r"(r2), "r"(r3) : "memory");
}
__device__ __forceinline__ uint32_t movm(uint32_t a) { uint32_t d; asm volatile("movmatrix.sync.aligned.m8n8.trans.b16 %0, %1;" : "=r"(d) : "r"(a)); return d; }
__device__ __forceinline__ uint32_t pack2(float lo, float hi) { uint32_t d; asm("cvt.rn.bf16x2.f32 %0, %1, %2;" : "=r"(d) : "f"(hi), "f"(lo)); return d; }
__device__ __forceinline__ uint32_t prmt(uint32_t a, uint32_t b, uint32_t s) { uint32_t d; asm("prmt.b32 %0, %1, %2, %3;" : "=r"(d) : "r"(a), "r"(b), "r"(s)); return d; }
__device__ __forceinline__ uint32_t pack2h(float lo, float hi) { uint32_t d; asm("cvt.rn.f16x2.f32 %0, %1, %2;" : "=r"(d) : "f"(hi), "f"(lo)); return d; }
__device__ __forceinline__ uint32_t h2bf(uint32_t a, uint32_t b) {
    uint32_t d;
    asm("{\n.reg .b16 l, h, u;\n.reg .f32 x, y;\nmov.b32 {l, u}, %1;\ncvt.f32.f16 x, l;\nmov.b32 {u, h}, %2;\ncvt.f32.f16 y, h;\ncvt.rn.bf16x2.f32 %0, y, x;\n}" : "=r"(d) : "r"(a), "r"(b));
    return d;
}
__device__ __forceinline__ void cvt_block(uint32_t* u, uint32_t& x, uint32_t sel) {
    const uint32_t a = prmt(u[0], u[0], sel), b = prmt(u[1], u[1], sel), c = prmt(u[2], u[2], sel), d = prmt(u[3], x, sel);
    x ^= u[3] ^ d;
    u[0] = h2bf(a, a); u[1] = h2bf(b, b); u[2] = h2bf(c, c); u[3] = h2bf(d, d);
}
__device__ __forceinline__ uint32_t amax(uint32_t a, uint32_t b) { uint32_t d; asm("max.xorsign.abs.bf16x2 %0, %1, %2;" : "=r"(d) : "r"(a), "r"(b)); return d; }
__device__ __forceinline__ uint32_t amax4(uint32_t m, const uint32_t* v) { return amax(amax(m, amax(v[0], v[1])), amax(v[2], v[3])); }
__device__ __forceinline__ uint32_t warp_exp(uint32_t m) { return __reduce_max_sync(0xffffffffu, max(m & 0x7f80u, (m >> 16) & 0x7f80u)) >> 7; }
__device__ __forceinline__ void red_max_shared(uint32_t a, uint32_t x) { asm volatile("red.shared.max.u32 [%0], %1;" ::"r"(a), "r"(x) : "memory"); }
__device__ __forceinline__ uint32_t mul_bf2(uint32_t a, uint32_t b) { uint32_t d; asm("mul.rn.bf16x2 %0, %1, %2;" : "=r"(d) : "r"(a), "r"(b)); return d; }
__device__ __forceinline__ float bf_lo(uint32_t u) { return __uint_as_float(u << 16); }
__device__ __forceinline__ float bf_hi(uint32_t u) { return __uint_as_float(u & 0xffff0000u); }
__device__ __forceinline__ float ex2(float x) { float y; asm("ex2.approx.ftz.f32 %0, %1;" : "=f"(y) : "f"(x)); return y; }
__device__ __forceinline__ float rcp(float x) { float y; asm("rcp.approx.ftz.f32 %0, %1;" : "=f"(y) : "f"(x)); return y; }
__device__ __forceinline__ void st_relaxed4(const void* p, uint32_t a, uint32_t b, uint32_t c, uint32_t d) {
    asm volatile("{\n.reg .b128 t;\nmov.b128 t, {%1,%2,%3,%4};\nst.relaxed.gpu.global.b128 [%0], t;\n}" ::"l"(p), "r"(a), "r"(b), "r"(c), "r"(d) : "memory");
}
__device__ __forceinline__ void st_relaxed2(const void* p, uint32_t a, uint32_t b) {
    asm volatile("{\n.reg .b64 t;\nmov.b64 t, {%1,%2};\nst.relaxed.gpu.global.b64 [%0], t;\n}" ::"l"(p), "r"(a), "r"(b) : "memory");
}
__device__ __forceinline__ void ld_relaxed2_if(uint32_t& a, uint32_t& b, const void* p, bool on) {
    asm volatile("{\n.reg .pred P;\n.reg .b64 t;\nsetp.ne.u32 P, %3, 0;\nmov.b64 t, {%0,%1};\n@P ld.relaxed.gpu.global.b64 t, [%2];\nmov.b64 {%0,%1}, t;\n}" : "+r"(a), "+r"(b) : "l"(p), "r"((uint32_t)on) : "memory");
}
__device__ __forceinline__ void ld_relaxed4(uint32_t* v, const void* p) {
    asm volatile("ld.relaxed.gpu.global.L1::no_allocate.v4.b32 {%0,%1,%2,%3}, [%4];" : "=r"(v[0]), "=r"(v[1]), "=r"(v[2]), "=r"(v[3]) : "l"(p) : "memory");
}
__device__ __forceinline__ void ld_relaxed1n(uint32_t& v, const void* p) { asm volatile("ld.relaxed.gpu.global.L1::no_allocate.b32 %0, [%1];" : "=r"(v) : "l"(p) : "memory"); }
__device__ __forceinline__ void red_add4(const void* p, uint32_t a, uint32_t b, uint32_t c, uint32_t d) {
    asm volatile("red.relaxed.gpu.global.add.noftz.v4.f16x2 [%0], {%1,%2,%3,%4};" ::"l"(p), "r"(a), "r"(b), "r"(c), "r"(d) : "memory");
}
__device__ __forceinline__ void red_add1(const void* p, uint32_t a) { asm volatile("red.relaxed.gpu.global.add.noftz.f16x2 [%0], %1;" ::"l"(p), "r"(a) : "memory"); }
__device__ __forceinline__ void ld_relaxed2(uint32_t* v, const void* p) {
    asm volatile("{\n.reg .b64 t;\nld.relaxed.gpu.global.L1::no_allocate.b64 t, [%2];\nmov.b64 {%0,%1}, t;\n}" : "=r"(v[0]), "=r"(v[1]) : "l"(p) : "memory");
}
__device__ __forceinline__ uint32_t ld_relaxed1(const void* p) { uint32_t v; asm volatile("ld.relaxed.gpu.global.u32 %0, [%1];" : "=r"(v) : "l"(p) : "memory"); return v; }
__device__ __forceinline__ void st_relaxed1(const void* p, uint32_t v) { asm volatile("st.relaxed.gpu.global.u32 [%0], %1;" ::"l"(p), "r"(v) : "memory"); }
__device__ __forceinline__ uint32_t ld_acquire(const void* p) { uint32_t v; asm volatile("ld.acquire.gpu.global.u32 %0, [%1];" : "=r"(v) : "l"(p) : "memory"); return v; }
__device__ __forceinline__ void red_relaxed(void* p) { asm volatile("red.relaxed.gpu.global.add.u32 [%0], 1;" ::"l"(p) : "memory"); }
__device__ __forceinline__ void red_release(void* p) { asm volatile("red.release.gpu.global.add.u32 [%0], 1;" ::"l"(p) : "memory"); }
__device__ __forceinline__ void st_stream2(float* p, float a, float b) { asm volatile("st.global.cs.v2.f32 [%0], {%1, %2};" ::"l"(p), "f"(a), "f"(b) : "memory"); }
__device__ __forceinline__ void fence_async() { asm volatile("fence.proxy.async.global;" ::: "memory"); }
__device__ __forceinline__ void fence_async_smem() { asm volatile("fence.proxy.async.shared::cta;" ::: "memory"); }
__device__ __forceinline__ void wait_count(const uint32_t* p, uint32_t target) {
    int n = 0;
    while ((int32_t)(ld_acquire(p) - target) < 0) { __nanosleep(POLLNS); if (++n > SPIN_LIMIT) spin_fault(); }
}
__device__ __forceinline__ void bar_sync(int id, int n) { asm volatile("bar.sync %0, %1;" ::"r"(id), "r"(n) : "memory"); }
__device__ __forceinline__ bool bar_and(int id, bool v) {
    uint32_t r;
    asm volatile("{\n.reg .pred P, Q;\nsetp.ne.u32 Q, %2, 0;\nbar.red.and.pred P, %1, 128, Q;\nselp.u32 %0, 1, 0, P;\n}" : "=r"(r) : "r"(id), "r"((uint32_t)v) : "memory");
    return r;
}
__device__ __forceinline__ void bar_arrive(int id, int n) { asm volatile("bar.arrive %0, %1;" ::"r"(id), "r"(n) : "memory"); }
__device__ __forceinline__ void lds128(uint32_t* v, uint32_t a) { asm volatile("ld.shared.v4.b32 {%0,%1,%2,%3}, [%4];" : "=r"(v[0]), "=r"(v[1]), "=r"(v[2]), "=r"(v[3]) : "r"(a) : "memory"); }
__device__ __forceinline__ uint32_t lds32(uint32_t a) { uint32_t v; asm volatile("ld.shared.b32 %0, [%1];" : "=r"(v) : "r"(a) : "memory"); return v; }
__device__ __forceinline__ void lds64(uint32_t* v, uint32_t a) { asm volatile("ld.shared.v2.b32 {%0,%1}, [%2];" : "=r"(v[0]), "=r"(v[1]) : "r"(a) : "memory"); }
__device__ __forceinline__ void lds64f(float* v, uint32_t a) { asm volatile("ld.shared.v2.f32 {%0,%1}, [%2];" : "=f"(v[0]), "=f"(v[1]) : "r"(a) : "memory"); }
__device__ __forceinline__ void sts128(uint32_t a, const uint32_t* v) { asm volatile("st.shared.v4.b32 [%0], {%1,%2,%3,%4};" ::"r"(a), "r"(v[0]), "r"(v[1]), "r"(v[2]), "r"(v[3]) : "memory"); }
__device__ __forceinline__ void sts64(uint32_t a, uint32_t x, uint32_t y) { asm volatile("st.shared.v2.b32 [%0], {%1,%2};" ::"r"(a), "r"(x), "r"(y) : "memory"); }
__device__ __forceinline__ void sts32(uint32_t a, uint32_t x) { asm volatile("st.shared.b32 [%0], %1;" ::"r"(a), "r"(x) : "memory"); }
__device__ __forceinline__ bool mbar_try(uint32_t b, uint32_t par) {
    uint32_t ok;
    asm volatile("{\n.reg .pred P;\nmbarrier.try_wait.parity.shared::cta.b64 P, [%1], %2;\nselp.u32 %0, 1, 0, P;\n}" : "=r"(ok) : "r"(b), "r"(par) : "memory");
    return ok;
}
__device__ __forceinline__ void mbar_wait(uint32_t b, uint32_t par) {
    asm volatile("{\n.reg .pred P, Q;\n.reg .u32 n;\nmov.u32 n, %2;\nW: mbarrier.try_wait.parity.shared::cta.b64 P, [%0], %1;\n"
                 "add.u32 n, n, -1;\nsetp.eq.u32 Q, n, 0;\n@Q st.global.u32 [%3], 0;\n@!P bra W;\n}" ::"r"(b), "r"(par), "n"(SPIN_LIMIT), "l"(0ull) : "memory");
}
__device__ __forceinline__ void mbar_wait_fast(uint32_t b, uint32_t par) {
    asm volatile("{\n.reg .pred P, Q;\n.reg .u32 n;\nmbarrier.try_wait.parity.shared::cta.b64 P, [%0], %1;\n@P bra D;\nmov.u32 n, %2;\nW: mbarrier.try_wait.parity.shared::cta.b64 P, [%0], %1;\n"
                 "add.u32 n, n, -1;\nsetp.eq.u32 Q, n, 0;\n@Q st.global.u32 [%3], 0;\n@!P bra W;\nD:\n}" ::"r"(b), "r"(par), "n"(SPIN_LIMIT), "l"(0ull) : "memory");
}
__device__ __forceinline__ void declare_fence(int zero) { asm volatile(".reg .pred PNEVER;\nsetp.ne.u32 PNEVER, %0, 0;" ::"r"(zero)); }
__device__ __forceinline__ void sched_fence() { asm volatile("{\n.reg .pred Q;\n.reg .u32 x;\n@!PNEVER bra D;\nF: ld.volatile.global.u32 x, [%0];\nsetp.ne.u32 Q, x, 0;\n@Q bra F;\nD:\n}" ::"l"(0ull) : "memory"); }
__device__ __forceinline__ void mbar_init(uint32_t b, uint32_t n) { asm volatile("mbarrier.init.shared::cta.b64 [%0], %1;" ::"r"(b), "r"(n) : "memory"); }
__device__ __forceinline__ void mbar_expect(uint32_t b, uint32_t bytes) { asm volatile("mbarrier.arrive.expect_tx.shared::cta.b64 _, [%0], %1;" ::"r"(b), "r"(bytes) : "memory"); }
__device__ __forceinline__ void mbar_arrive(uint32_t b) { asm volatile("mbarrier.arrive.shared::cta.b64 _, [%0];" ::"r"(b) : "memory"); }
__device__ __forceinline__ void mbar_arrive_cluster(uint32_t b) { asm volatile("mbarrier.arrive.shared::cluster.b64 _, [%0];" ::"r"(b) : "memory"); }
__device__ __forceinline__ void cluster_sync() { asm volatile("barrier.cluster.arrive.aligned;\nbarrier.cluster.wait.aligned;" ::: "memory"); }
__device__ __forceinline__ void tma2d(uint32_t dst, const CUtensorMap* m, int c0, int c1, uint32_t bar) {
    asm volatile("cp.async.bulk.tensor.2d.shared::cluster.global.mbarrier::complete_tx::bytes [%0], [%1, {%2, %3}], [%4];" ::"r"(dst), "l"(m), "r"(c0), "r"(c1), "r"(bar) : "memory");
}
__device__ __forceinline__ void tma2d_mc(uint32_t dst, const CUtensorMap* m, int c0, int c1, uint32_t bar, uint16_t mask) {
    asm volatile("cp.async.bulk.tensor.2d.shared::cluster.global.mbarrier::complete_tx::bytes.multicast::cluster [%0], [%1, {%2, %3}], [%4], %5;" ::"r"(dst), "l"(m), "r"(c0), "r"(c1), "r"(bar), "h"(mask) : "memory");
}
__device__ __forceinline__ void tma3d(uint32_t dst, const CUtensorMap* m, int c0, int c1, int c2, uint32_t bar) {
    asm volatile("cp.async.bulk.tensor.3d.shared::cluster.global.mbarrier::complete_tx::bytes [%0], [%1, {%2, %3, %4}], [%5];" ::"r"(dst), "l"(m), "r"(c0), "r"(c1), "r"(c2), "r"(bar) : "memory");
}
__device__ __forceinline__ void tma3d_mc(uint32_t dst, const CUtensorMap* m, int c0, int c1, int c2, uint32_t bar, uint16_t mask) {
    asm volatile("cp.async.bulk.tensor.3d.shared::cluster.global.mbarrier::complete_tx::bytes.multicast::cluster [%0], [%1, {%2, %3, %4}], [%5], %6;" ::"r"(dst), "l"(m), "r"(c0), "r"(c1), "r"(c2), "r"(bar), "h"(mask) : "memory");
}
__device__ __forceinline__ void tma4d(uint32_t dst, const CUtensorMap* m, int c0, int c3, uint32_t bar) {
    asm volatile("cp.async.bulk.tensor.4d.shared::cluster.global.mbarrier::complete_tx::bytes [%0], [%1, {%2, 0, 0, %3}], [%4];" ::"r"(dst), "l"(m), "r"(c0), "r"(c3), "r"(bar) : "memory");
}
__device__ __forceinline__ void tma4d_mc(uint32_t dst, const CUtensorMap* m, int c0, int c3, uint32_t bar, uint16_t mask) {
    asm volatile("cp.async.bulk.tensor.4d.shared::cluster.global.mbarrier::complete_tx::bytes.multicast::cluster [%0], [%1, {%2, 0, 0, %3}], [%4], %5;" ::"r"(dst), "l"(m), "r"(c0), "r"(c3), "r"(bar), "h"(mask) : "memory");
}
__device__ __forceinline__ void tma_prefetch3d(const CUtensorMap* m, int c0, int c1, int c2) {
    asm volatile("cp.async.bulk.prefetch.tensor.3d.L2.global [%0, {%1, %2, %3}];" ::"l"(m), "r"(c0), "r"(c1), "r"(c2) : "memory");
}
__device__ __forceinline__ void tma_prefetch2d(const CUtensorMap* m, int c0, int c1) {
    asm volatile("cp.async.bulk.prefetch.tensor.2d.L2.global [%0, {%1, %2}];" ::"l"(m), "r"(c0), "r"(c1) : "memory");
}
__device__ __forceinline__ void l2_prefetch(const void* src, uint32_t bytes) { asm volatile("cp.async.bulk.prefetch.L2.global [%0], %1;" ::"l"(src), "r"(bytes) : "memory"); }
__device__ __forceinline__ void bulk_g2s(uint32_t dst, const void* src, uint32_t bytes, uint32_t bar) {
    asm volatile("cp.async.bulk.shared::cluster.global.mbarrier::complete_tx::bytes [%0], [%1], %2, [%3];" ::"r"(dst), "l"(src), "r"(bytes), "r"(bar) : "memory");
}
__device__ __forceinline__ void mbar_expect_e(uint32_t b, uint32_t bytes) {
    asm volatile("{\n.reg .pred E;\nelect.sync _|E, 0xffffffff;\n@E mbarrier.arrive.expect_tx.shared::cta.b64 _, [%0], %1;\n}" ::"r"(b), "r"(bytes) : "memory");
}
__device__ __forceinline__ void tma2d_e(uint32_t dst, const CUtensorMap* m, int c0, int c1, uint32_t bar) {
    asm volatile("{\n.reg .pred E;\nelect.sync _|E, 0xffffffff;\n@E cp.async.bulk.tensor.2d.shared::cluster.global.mbarrier::complete_tx::bytes [%0], [%1, {%2, %3}], [%4];\n}" ::"r"(dst), "l"(m), "r"(c0), "r"(c1), "r"(bar) : "memory");
}
__device__ __forceinline__ void tma2d_mc_e(uint32_t dst, const CUtensorMap* m, int c0, int c1, uint32_t bar, uint16_t mask) {
    asm volatile("{\n.reg .pred E;\nelect.sync _|E, 0xffffffff;\n@E cp.async.bulk.tensor.2d.shared::cluster.global.mbarrier::complete_tx::bytes.multicast::cluster [%0], [%1, {%2, %3}], [%4], %5;\n}" ::"r"(dst), "l"(m), "r"(c0), "r"(c1), "r"(bar), "h"(mask) : "memory");
}
__device__ __forceinline__ void tma3d_e(uint32_t dst, const CUtensorMap* m, int c0, int c1, int c2, uint32_t bar) {
    asm volatile("{\n.reg .pred E;\nelect.sync _|E, 0xffffffff;\n@E cp.async.bulk.tensor.3d.shared::cluster.global.mbarrier::complete_tx::bytes [%0], [%1, {%2, %3, %4}], [%5];\n}" ::"r"(dst), "l"(m), "r"(c0), "r"(c1), "r"(c2), "r"(bar) : "memory");
}
__device__ __forceinline__ void tma3d_mc_e(uint32_t dst, const CUtensorMap* m, int c0, int c1, int c2, uint32_t bar, uint16_t mask) {
    asm volatile("{\n.reg .pred E;\nelect.sync _|E, 0xffffffff;\n@E cp.async.bulk.tensor.3d.shared::cluster.global.mbarrier::complete_tx::bytes.multicast::cluster [%0], [%1, {%2, %3, %4}], [%5], %6;\n}" ::"r"(dst), "l"(m), "r"(c0), "r"(c1), "r"(c2), "r"(bar), "h"(mask) : "memory");
}
__device__ __forceinline__ void tma4d_e(uint32_t dst, const CUtensorMap* m, int c0, int c3, uint32_t bar) {
    asm volatile("{\n.reg .pred E;\nelect.sync _|E, 0xffffffff;\n@E cp.async.bulk.tensor.4d.shared::cluster.global.mbarrier::complete_tx::bytes [%0], [%1, {%2, 0, 0, %3}], [%4];\n}" ::"r"(dst), "l"(m), "r"(c0), "r"(c3), "r"(bar) : "memory");
}
__device__ __forceinline__ void tma4d_mc_e(uint32_t dst, const CUtensorMap* m, int c0, int c3, uint32_t bar, uint16_t mask) {
    asm volatile("{\n.reg .pred E;\nelect.sync _|E, 0xffffffff;\n@E cp.async.bulk.tensor.4d.shared::cluster.global.mbarrier::complete_tx::bytes.multicast::cluster [%0], [%1, {%2, 0, 0, %3}], [%4], %5;\n}" ::"r"(dst), "l"(m), "r"(c0), "r"(c3), "r"(bar), "h"(mask) : "memory");
}
__device__ __forceinline__ void tma_prefetch2d_e(const CUtensorMap* m, int c0, int c1) {
    asm volatile("{\n.reg .pred E;\nelect.sync _|E, 0xffffffff;\n@E cp.async.bulk.prefetch.tensor.2d.L2.global [%0, {%1, %2}];\n}" ::"l"(m), "r"(c0), "r"(c1) : "memory");
}
__device__ __forceinline__ void tma_prefetch3d_e(const CUtensorMap* m, int c0, int c1, int c2) {
    asm volatile("{\n.reg .pred E;\nelect.sync _|E, 0xffffffff;\n@E cp.async.bulk.prefetch.tensor.3d.L2.global [%0, {%1, %2, %3}];\n}" ::"l"(m), "r"(c0), "r"(c1), "r"(c2) : "memory");
}
__device__ __forceinline__ void l2_prefetch_e(const void* src, uint32_t bytes) {
    asm volatile("{\n.reg .pred E;\nelect.sync _|E, 0xffffffff;\n@E cp.async.bulk.prefetch.L2.global [%0], %1;\n}" ::"l"(src), "r"(bytes) : "memory");
}
__device__ __forceinline__ void bulk_g2s_e(uint32_t dst, const void* src, uint32_t bytes, uint32_t bar) {
    asm volatile("{\n.reg .pred E;\nelect.sync _|E, 0xffffffff;\n@E cp.async.bulk.shared::cluster.global.mbarrier::complete_tx::bytes [%0], [%1], %2, [%3];\n}" ::"r"(dst), "l"(src), "r"(bytes), "r"(bar) : "memory");
}
__device__ __forceinline__ bool elect_one() {
    uint32_t r;
    asm volatile("{\n.reg .pred E;\nelect.sync _|E, 0xffffffff;\nselp.u32 %0, 1, 0, E;\n}" : "=r"(r));
    return r;
}
__device__ __forceinline__ void tma_store2d(const CUtensorMap* m, int c0, int c1, uint32_t src) {
    asm volatile("cp.async.bulk.tensor.2d.global.shared::cta.bulk_group [%0, {%1, %2}], [%3];" ::"l"(m), "r"(c0), "r"(c1), "r"(src) : "memory");
}
__device__ __forceinline__ void bulk_commit() { asm volatile("cp.async.bulk.commit_group;" ::: "memory"); }
__device__ __forceinline__ void bulk_wait_read() { asm volatile("cp.async.bulk.wait_group.read 0;" ::: "memory"); }
__device__ __forceinline__ void bulk_wait_all() { asm volatile("cp.async.bulk.wait_group 0;" ::: "memory"); }
__device__ __forceinline__ uint64_t mkdesc(uint32_t addr, uint32_t lbo, uint32_t sbo, uint32_t swz) {
    return (uint64_t)((addr & 0x3FFFF) >> 4) | ((uint64_t)(lbo >> 4) << 16) | ((uint64_t)(sbo >> 4) << 32) | ((uint64_t)swz << 62);
}
__device__ __forceinline__ void wg_fence() { asm volatile("wgmma.fence.sync.aligned;" ::: "memory"); }
__device__ __forceinline__ void wg_commit() { asm volatile("wgmma.commit_group.sync.aligned;" ::: "memory"); }
template <int N> __device__ __forceinline__ void wg_wait() { asm volatile("wgmma.wait_group.sync.aligned %0;" ::"n"(N) : "memory"); }
template <typename T> __device__ __forceinline__ void pin_ptr(T*& p) { asm volatile("" : "+l"(p)); }
template <int N> __device__ __forceinline__ void pin(uint32_t* d) {
#pragma unroll
    for (int i = 0; i < N; i++) asm volatile("" : "+r"(d[i])::"memory");
}
template <int N> __device__ __forceinline__ void pin(float* d) {
#pragma unroll
    for (int i = 0; i < N; i++) asm volatile("" : "+f"(d[i])::"memory");
}

template <int TA, int TB>
__device__ __forceinline__ void wgmma_ss256(float* d, uint64_t da, uint64_t db) {
    asm volatile("wgmma.mma_async.sync.aligned.m64n256k16.f32.bf16.bf16 "
        "{%0, %1, %2, %3, %4, %5, %6, %7, %8, %9, %10, %11, %12, %13, %14, %15, %16, %17, %18, %19, %20, %21, %22, %23, %24, %25, %26, %27, %28, %29, %30, %31, %32, %33, %34, %35, %36, %37, %38, %39, %40, %41, %42, %43, %44, %45, %46, %47, %48, %49, %50, %51, %52, %53, %54, %55, %56, %57, %58, %59, %60, %61, %62, %63, %64, %65, %66, %67, %68, %69, %70, %71, %72, %73, %74, %75, %76, %77, %78, %79, %80, %81, %82, %83, %84, %85, %86, %87, %88, %89, %90, %91, %92, %93, %94, %95, %96, %97, %98, %99, %100, %101, %102, %103, %104, %105, %106, %107, %108, %109, %110, %111, %112, %113, %114, %115, %116, %117, %118, %119, %120, %121, %122, %123, %124, %125, %126, %127}, %128, %129, 1, 1, 1, %130, %131;"
        : "+f"(d[0]), "+f"(d[1]), "+f"(d[2]), "+f"(d[3]), "+f"(d[4]), "+f"(d[5]), "+f"(d[6]), "+f"(d[7]), "+f"(d[8]), "+f"(d[9]), "+f"(d[10]), "+f"(d[11]), "+f"(d[12]), "+f"(d[13]), "+f"(d[14]), "+f"(d[15]), "+f"(d[16]), "+f"(d[17]), "+f"(d[18]), "+f"(d[19]), "+f"(d[20]), "+f"(d[21]), "+f"(d[22]), "+f"(d[23]), "+f"(d[24]), "+f"(d[25]), "+f"(d[26]), "+f"(d[27]), "+f"(d[28]), "+f"(d[29]), "+f"(d[30]), "+f"(d[31]), "+f"(d[32]), "+f"(d[33]), "+f"(d[34]), "+f"(d[35]), "+f"(d[36]), "+f"(d[37]), "+f"(d[38]), "+f"(d[39]), "+f"(d[40]), "+f"(d[41]), "+f"(d[42]), "+f"(d[43]), "+f"(d[44]), "+f"(d[45]), "+f"(d[46]), "+f"(d[47]), "+f"(d[48]), "+f"(d[49]), "+f"(d[50]), "+f"(d[51]), "+f"(d[52]), "+f"(d[53]), "+f"(d[54]), "+f"(d[55]), "+f"(d[56]), "+f"(d[57]), "+f"(d[58]), "+f"(d[59]), "+f"(d[60]), "+f"(d[61]), "+f"(d[62]), "+f"(d[63]), "+f"(d[64]), "+f"(d[65]), "+f"(d[66]), "+f"(d[67]), "+f"(d[68]), "+f"(d[69]), "+f"(d[70]), "+f"(d[71]), "+f"(d[72]), "+f"(d[73]), "+f"(d[74]), "+f"(d[75]), "+f"(d[76]), "+f"(d[77]), "+f"(d[78]), "+f"(d[79]), "+f"(d[80]), "+f"(d[81]), "+f"(d[82]), "+f"(d[83]), "+f"(d[84]), "+f"(d[85]), "+f"(d[86]), "+f"(d[87]), "+f"(d[88]), "+f"(d[89]), "+f"(d[90]), "+f"(d[91]), "+f"(d[92]), "+f"(d[93]), "+f"(d[94]), "+f"(d[95]), "+f"(d[96]), "+f"(d[97]), "+f"(d[98]), "+f"(d[99]), "+f"(d[100]), "+f"(d[101]), "+f"(d[102]), "+f"(d[103]), "+f"(d[104]), "+f"(d[105]), "+f"(d[106]), "+f"(d[107]), "+f"(d[108]), "+f"(d[109]), "+f"(d[110]), "+f"(d[111]), "+f"(d[112]), "+f"(d[113]), "+f"(d[114]), "+f"(d[115]), "+f"(d[116]), "+f"(d[117]), "+f"(d[118]), "+f"(d[119]), "+f"(d[120]), "+f"(d[121]), "+f"(d[122]), "+f"(d[123]), "+f"(d[124]), "+f"(d[125]), "+f"(d[126]), "+f"(d[127])
        : "l"(da), "l"(db), "n"(TA), "n"(TB));
}
template <int TB>
__device__ __forceinline__ void wgmma_rs128(float* d, const uint32_t* a, uint64_t db, uint32_t acc) {
    asm volatile("{\n.reg .pred P;\nsetp.ne.u32 P, %69, 0;\nwgmma.mma_async.sync.aligned.m64n128k16.f32.bf16.bf16 "
        "{%0, %1, %2, %3, %4, %5, %6, %7, %8, %9, %10, %11, %12, %13, %14, %15, %16, %17, %18, %19, %20, %21, %22, %23, %24, %25, %26, %27, %28, %29, %30, %31, %32, %33, %34, %35, %36, %37, %38, %39, %40, %41, %42, %43, %44, %45, %46, %47, %48, %49, %50, %51, %52, %53, %54, %55, %56, %57, %58, %59, %60, %61, %62, %63}, {%64, %65, %66, %67}, %68, P, 1, 1, %70;\n}"
        : "+f"(d[0]), "+f"(d[1]), "+f"(d[2]), "+f"(d[3]), "+f"(d[4]), "+f"(d[5]), "+f"(d[6]), "+f"(d[7]), "+f"(d[8]), "+f"(d[9]), "+f"(d[10]), "+f"(d[11]), "+f"(d[12]), "+f"(d[13]), "+f"(d[14]), "+f"(d[15]), "+f"(d[16]), "+f"(d[17]), "+f"(d[18]), "+f"(d[19]), "+f"(d[20]), "+f"(d[21]), "+f"(d[22]), "+f"(d[23]), "+f"(d[24]), "+f"(d[25]), "+f"(d[26]), "+f"(d[27]), "+f"(d[28]), "+f"(d[29]), "+f"(d[30]), "+f"(d[31]), "+f"(d[32]), "+f"(d[33]), "+f"(d[34]), "+f"(d[35]), "+f"(d[36]), "+f"(d[37]), "+f"(d[38]), "+f"(d[39]), "+f"(d[40]), "+f"(d[41]), "+f"(d[42]), "+f"(d[43]), "+f"(d[44]), "+f"(d[45]), "+f"(d[46]), "+f"(d[47]), "+f"(d[48]), "+f"(d[49]), "+f"(d[50]), "+f"(d[51]), "+f"(d[52]), "+f"(d[53]), "+f"(d[54]), "+f"(d[55]), "+f"(d[56]), "+f"(d[57]), "+f"(d[58]), "+f"(d[59]), "+f"(d[60]), "+f"(d[61]), "+f"(d[62]), "+f"(d[63])
        : "r"(a[0]), "r"(a[1]), "r"(a[2]), "r"(a[3]), "l"(db), "r"(acc), "n"(TB));
}
template <int TB>
__device__ __forceinline__ void wgmma_rs64(float* d, const uint32_t* a, uint64_t db, uint32_t acc) {
    asm volatile("{\n.reg .pred P;\nsetp.ne.u32 P, %37, 0;\nwgmma.mma_async.sync.aligned.m64n64k16.f32.bf16.bf16 "
        "{%0, %1, %2, %3, %4, %5, %6, %7, %8, %9, %10, %11, %12, %13, %14, %15, %16, %17, %18, %19, %20, %21, %22, %23, %24, %25, %26, %27, %28, %29, %30, %31}, {%32, %33, %34, %35}, %36, P, 1, 1, %38;\n}"
        : "+f"(d[0]), "+f"(d[1]), "+f"(d[2]), "+f"(d[3]), "+f"(d[4]), "+f"(d[5]), "+f"(d[6]), "+f"(d[7]), "+f"(d[8]), "+f"(d[9]), "+f"(d[10]), "+f"(d[11]), "+f"(d[12]), "+f"(d[13]), "+f"(d[14]), "+f"(d[15]), "+f"(d[16]), "+f"(d[17]), "+f"(d[18]), "+f"(d[19]), "+f"(d[20]), "+f"(d[21]), "+f"(d[22]), "+f"(d[23]), "+f"(d[24]), "+f"(d[25]), "+f"(d[26]), "+f"(d[27]), "+f"(d[28]), "+f"(d[29]), "+f"(d[30]), "+f"(d[31])
        : "r"(a[0]), "r"(a[1]), "r"(a[2]), "r"(a[3]), "l"(db), "r"(acc), "n"(TB));
}
template <int TB>
__device__ __forceinline__ void wgmma_rs16(float* d, const uint32_t* a, uint64_t db, uint32_t acc) {
    asm volatile("{\n.reg .pred P;\nsetp.ne.u32 P, %13, 0;\nwgmma.mma_async.sync.aligned.m64n16k16.f32.bf16.bf16 "
        "{%0, %1, %2, %3, %4, %5, %6, %7}, {%8, %9, %10, %11}, %12, P, 1, 1, %14;\n}"
        : "+f"(d[0]), "+f"(d[1]), "+f"(d[2]), "+f"(d[3]), "+f"(d[4]), "+f"(d[5]), "+f"(d[6]), "+f"(d[7])
        : "r"(a[0]), "r"(a[1]), "r"(a[2]), "r"(a[3]), "l"(db), "r"(acc), "n"(TB));
}

__device__ __forceinline__ uint32_t delay_loop(int n, uint32_t x0) {
    uint32_t z;
    asm volatile("{\n.reg .pred P;\n.reg .u32 c, x;\nmov.u32 c, %1;\nmov.u32 x, %2;\nDL: mad.lo.u32 x, x, 1664525, 1013904223;\nadd.u32 c, c, -1;\nsetp.gt.s32 P, c, 0;\n@P bra DL;\n"
                 "setp.eq.u32 P, x, 0x7fffffff;\nselp.u32 %0, 16, 0, P;\n}" : "=r"(z) : "r"(n), "r"(x0) : "memory");
    return z;
}
__device__ __forceinline__ void wait_clocks(uint32_t n) {
    asm volatile("{\n.reg .pred P;\n.reg .u32 a, b;\nmov.u32 a, %%clock;\nW: mov.u32 b, %%clock;\nsub.u32 b, b, a;\nsetp.lt.u32 P, b, %0;\n@P bra W;\n}" ::"r"(n) : "memory");
}
__device__ __forceinline__ uint32_t gtime() { uint32_t t; asm volatile("mov.u32 %0, %%globaltimer_lo;" : "=r"(t)); return t; }
#define COUNT_RETRY(i)
__device__ __forceinline__ uint32_t stamp_word(uint32_t seq) { return (gtime() & ~31u) | (seq & 31u); }
__device__ __forceinline__ void wait_time(uint32_t t, uint32_t sb) { while ((int32_t)(gtime() - t) < 0) {} }
#define NAPMODE 1
__device__ __forceinline__ void nap(uint32_t ns) { if (NAPMODE) wait_clocks(ns * 7 / 4); else __nanosleep(ns); }
template <int STRIDE>
__device__ __forceinline__ uint32_t latest_stamp(const uint32_t* p, uint32_t seq, uint32_t ref, uint32_t sb) {
    int n = 0;
    while (true) {
        uint32_t bad = 0; int32_t m = INT32_MIN;
#pragma unroll
        for (int i = 0; i < 3; i++) { const uint32_t v = ld_relaxed1(p + i * STRIDE); bad |= (v ^ seq) & 31u; m = max(m, (int32_t)((v & ~31u) - ref)); }
        if (__all_sync(0xffffffffu, bad == 0)) return ref + __reduce_max_sync(0xffffffffu, m);
        nap(100);
        if (++n > SPIN_LIMIT) spin_fault();
    }
}
constexpr uint32_t ONES = 0x3C003C00u, FULL = 0x50005000u;
__device__ __forceinline__ void pacer(const Params& P, const uint32_t sb, const int cta, const int lane, const uint32_t epoch) {
    uint8_t* const zp = P.xb + cta * 2048 + xg_lane(lane);
    if (lane < 3) asm volatile("prefetch.tensormap [%0];" ::"l"(&P.tm[lane == 0 ? M_C1 + cta % 3 : lane == 1 ? M_CO : M_SEG]) : "memory");
    uint32_t e0 = 0;
#pragma unroll 2
    for (int i = 0; i < 32; i++) { const uint4 u = __ldg((const uint4*)P.mem0 + i * 32 + lane); e0 = amax(amax(e0, amax(u.x, u.y)), amax(u.z, u.w)); }
    e0 = min(max(warp_exp(e0), 31u), 253u) - 14;
    if (cta < 32) {
        const uint32_t* m = (const uint32_t*)(P.mem0 + (lane >> 2) * 1024 + cta * 32 + (lane & 3) * 2);
        const float sc = __uint_as_float((254 - e0) << 23);
        auto cv = [&](uint32_t u) { return pack2h(bf_lo(u) * sc, bf_hi(u) * sc); };
        const uint32_t y = cv(m[12]);
        st_relaxed4(zp, cv(m[0]), cv(m[4]), cv(m[8]), prmt(y, FULL, 0x7610));
        st_relaxed1(P.xb + xg_side(cta) + lane * 4, prmt(y, FULL, 0x3254));
    }
    if (cta < 40) {
#pragma unroll 1
        for (int b = 1; b < 8; b++) st_relaxed4(zp + xg_buf(b), 0, 0, 0, 0);
    }
    __threadfence();
    const uint32_t* ts = (const uint32_t*)(P.xb + XG_T) + lane;
    int32_t d0 = P.dly;
    const uint32_t go = mapa(sb + B_GO, (cta / 3 & 1) * 3 + 1 + (lane & 1));
    auto free_segment = [&]() { if (lane == 0) mbar_expect(sb + B_KVFULL, 16384); __syncwarp(); if (lane < 2) mbar_arrive_cluster(go); };
    wait_count(&g_cnt(C_XCNT), (epoch + 1) * 256);
    const uint32_t ex = max(ld_relaxed1(&g_cnt(C_XMAX)) & 255, 67u);
    mbar_wait(sb + B_READY, 0);
    free_segment();
    if (lane == 0) st_relaxed2(g_hint + cta * 32, stamp_word(epoch + 1), lds32(sb + S_EV) | lds32(sb + S_EO) << 16);
    uint32_t a = gtime();
    for (int n = 0;; n++) {
        uint32_t bad = 0, e = 0; int32_t m = INT32_MIN;
#pragma unroll
        for (int i = 0; i < 3; i++) {
            uint32_t v[2];
            ld_relaxed2(v, g_hint + lane * 32 + i * 1024);
            bad |= (v[0] ^ (epoch + 1)) & 31u; m = max(m, (int32_t)((v[0] & ~31u) - a)); e = __vmaxu2(e, v[1]);
        }
        if (__all_sync(0xffffffffu, bad == 0)) {
            a += __reduce_max_sync(0xffffffffu, m);
            const uint32_t ev = __reduce_max_sync(0xffffffffu, e & 255), eo = __reduce_max_sync(0xffffffffu, e >> 16);
            if (lane == 0) { sts64(sb + S_SC, max(ev, 97u) + max(eo, 97u) - 244, ex); sts32(sb + S_ISC, e0 * 0x800080u); }
            break;
        }
        wait_clocks(100);
        if (n > SPIN_LIMIT) spin_fault();
    }
    wait_time(a, sb);
    if (lane == 0) mbar_arrive(sb + B_RELM);
#pragma unroll 1
    for (int s = 0; s < 63; s++) {
        const uint32_t seq = epoch * 63 + s + 1;
        mbar_wait(sb + B_P1, s & 1);
        const uint32_t tx = gtime();
        if (lane == 0) st_relaxed1(ts + (s & 1) * 256 + cta, (tx & ~31u) | (seq & 31u));
        { const uint32_t t = tx; PROFP(3) }
        if (s > 0) {
            const int32_t e0 = latest_stamp<32>(ts + (~s & 1) * 256 + 128, seq - 1, a, sb) + P.mrg - a;
            d0 += s < 3 ? e0 : min(max(e0, -P.clamp0), P.clampv) / 2;
        }
        while ((int32_t)(gtime() - tx) < P.rd) nap(20);
        a = latest_stamp<32>(ts + (s & 1) * 256, seq, tx, sb) + d0;
        { const uint32_t t = gtime(); PROFP(0) }
        while ((int32_t)(a - gtime()) > 250) nap(40);
        wait_time(a, sb);
        if (lane == 0) mbar_arrive(sb + B_RELM);
        { const uint32_t t = a; PROFP(2) }
        mbar_wait(sb + B_RED, s & 1);
        { const uint32_t t = gtime(); PROFP(1) }
        const uint32_t g = tx + __reduce_max_sync(0xffffffffu, lds32(sb + S_TO + (lane & 7) * 4) - tx);
        if (lane == 0) st_relaxed1(ts + (s & 1) * 256 + 128 + cta, (g & ~31u) | (seq & 31u));
        if (s < 62) { if (P.kvd) nap(P.kvd); free_segment(); }
    }
}
__device__ __forceinline__ void st_async2(uint32_t a, uint32_t x, uint32_t y, uint32_t bar, bool on) {
    asm volatile("{\n.reg .pred P;\nsetp.ne.u32 P, %4, 0;\n@P st.async.weak.shared::cluster.mbarrier::complete_tx::bytes.v2.b32 [%0], {%1,%2}, [%3];\n}" ::"r"(a), "r"(x), "r"(y), "r"(bar), "r"((uint32_t)on) : "memory");
}
__device__ __forceinline__ uint32_t xor_or(uint32_t a, uint32_t b, uint32_t t) { uint32_t d; asm("lop3.b32 %0, %1, %2, %3, 0x7E;" : "=r"(d) : "r"(a), "r"(b), "r"(t)); return d; }
__device__ __forceinline__ uint32_t or3(uint32_t a, uint32_t b, uint32_t c) { uint32_t d; asm("lop3.b32 %0, %1, %2, %3, 0xFE;" : "=r"(d) : "r"(a), "r"(b), "r"(c)); return d; }
__device__ __forceinline__ bool tags_ok(uint32_t bad, uint32_t mask = 1) {
    uint32_t r;
    asm volatile("{\n.reg .pred P;\n.reg .b32 x;\nand.b32 x, %1, %2;\nsetp.ne.b32 P, x, 0;\nvote.sync.any.pred P, P, 0xffffffff;\nselp.u32 %0, 0, 1, P;\n}" : "=r"(r) : "r"(bad), "r"(mask));
    return r;
}
constexpr int SROW = 56;
#define PREA 8
#define PREB 9
#define RING1 6
#define RING2 7
#define RING3 8
#define PRE2 10
#define PRE2A 0
#define PRE3 0
#define EFENCE 0
#define RFENCE 1
#define PROG 16
#define EARLY 0
#define PLATE 1
#define LAG2 8
#define LAG 4
#define PUT1 33
#define DEPS 3
#define ADELAY 120
#define BDELAY 0
#define HOLD 1
#define XDELAY 330
#define FENCEA 0x80
#define FENCEB 0x80
#define FENCE2 0x220
#define OFENCE 0
#define MASK3 0x57
#define MASK4 0x55
#define MASK5 0x25
#define OFF3 0x5320
#define OFF4 0x6420
#define OFF5 0x0520
#define RESA (NRA == 3 ? 15 : NRA == 4 ? 3 : 0)
#define RESB (NRB == 3 ? 0xcc : NRB == 4 ? 0x30 : 0)
#define RESB1 (NRB == 3 ? 0xcc : NRB == 4 ? 0xc : 0)
__host__ __device__ constexpr int smem_mask(int NR) { return NR == 3 ? MASK3 : NR == 4 ? MASK4 : MASK5; }
__host__ __device__ constexpr bool round_smem(int r, int NR) { return smem_mask(NR) >> r & 1; }
__host__ __device__ constexpr int kord(int r, int NR) { int c = 0; for (int i = 0; i < r; i++) c += round_smem(i, NR) == round_smem(r, NR); return round_smem(r, NR) ? NR + c : c; }
__host__ __device__ constexpr int slot_r(int n, int NR) { return n < 32 ? n >> 2 : (((n & 31) >> 2) + ((NR == 3 ? OFF3 : NR == 4 ? OFF4 : OFF5) >> (n & 3) * 4)) & 7; }
__host__ __device__ constexpr int slot_k(int n, int NR) { return kord(slot_r(n, NR), NR); }
__host__ __device__ constexpr int slot_sord(int n, int NR) { int c = 0; for (int i = 0; i < n; i++) c += slot_k(i, NR) >= NR; return c; }
__host__ __device__ constexpr int sfrag_slot(int q, int NR) { for (int n = 0; n < 64; n++) if (slot_k(n, NR) >= NR && slot_sord(n, NR) == q) return n; return -1; }
__host__ __device__ constexpr int w1_loaded(int n, int NR, int PRE) {
    int q = PRE;
    for (int i = 0; i <= n; i++) q += q < (8 - NR) * 8 && q - slot_sord(i + 1, NR) < (i < 32 ? RING1 : RING2);
    return q;
}
template <int Q, int NR>
__device__ __forceinline__ void load_w1(uint32_t* w, const uint32_t* a) {
    constexpr int n = sfrag_slot(Q, NR);
    ldsm4t(w, a[n & 3] + ((slot_k(n, NR) - NR) * 2 + (n >> 5)) * 2048);
}
constexpr int AB = NRA < 5, BB = 3 - AB;
__device__ __forceinline__ bool w2_full(int role, int warp) { return warp < (role == 2 ? 2 : 3); }
__device__ __forceinline__ int w2_nblk(int role, int warp) { return warp < 4 ? BB - !w2_full(role, warp) : AB; }
__host__ __device__ constexpr int w2_step(bool full, int i) { return AB ? (full ? 2 * i : 0) : full ? (i == 0 ? 0 : i == 1 ? 16 - 2 * EARLY : 18 - 2 * EARLY) : i; }
__device__ __forceinline__ int w2_block(int role, int warp) {
    const int f = role * 3 + warp, g = role == 2 ? warp : role;
    if (AB) return (warp >= 4 ? role * 4 + (warp - 4) : w2_full(role, warp) ? 16 + 4 * (f >> 1) + (f & 1) : 12 + g) ^ EARLY;
    return w2_full(role, warp) ? EARLY + 4 * (f >> 1) + (f & 1) : EARLY + 2 + 4 * g;
}
__device__ __forceinline__ int w2_res(int role, int warp) { return warp >= 4 ? RESA : w2_full(role, warp) ? RESB : RESB1; }
__device__ __forceinline__ int w2_units(int role, int warp) { return w2_nblk(role, warp) * 4 - (5 - (warp < 4 ? NRB : NRA)) * 2; }
constexpr int W2B = (BB * 4 - (5 - NRB) * 2) * 2048, W2A = (AB * 4 - (5 - NRA) * 2) * 2048;
static_assert(S_W2 + 4 * W2B - 8192 + 4 * W2A == S_KV, "weights");
__device__ __forceinline__ int w1_base(int warp) { return S_W1 + (warp < 4 ? warp * (8 - NRB) : 4 * (8 - NRB) + (warp - 4) * (8 - NRA)) * 4096; }
__device__ __forceinline__ int w2_base(int warp) { return S_W2 + (warp < 4 ? warp * W2B : 4 * W2B - 8192 + (warp - 4) * W2A); }
__device__ __forceinline__ void chain_load(const Params& P, uint32_t sb, int cta, int warp, int lane, int round) {
    const int role = cta % 3, h = cta / 3;
    mbar_expect_e(sb + B_INIT, round ? (8 - (warp < 4 ? NRB : NRA)) * 4096 : 20480);
    if (round) mbar_expect_e(sb + B_INIT2, w2_units(role, warp) * 2048);
    __syncwarp();
    const int m1 = (warp < 4 ? smem_mask(NRB) : smem_mask(NRA)) ^ (round ? 0 : 255), below = (1 << lane) - 1;
    const int m2 = (w2_res(role, warp) ^ (round ? 0xfff : 0)) & ((1 << w2_nblk(role, warp) * 4) - 1);
    const uint32_t d1 = sb + (round ? w1_base(warp) : warp * 20480), d2 = round ? sb + w2_base(warp) : d1 + __popc(m1) * 4096;
    if (m1 >> lane & 1) tma3d(d1 + __popc(m1 & below) * 4096, &P.tm[M_C1 + role], 0, warp * 128 + lane * 16, h * 2, sb + B_INIT);
    __syncwarp();
    if (m2 >> lane & 1)
        tma2d(d2 + __popc(m2 & below) * 2048, &P.tm[M_CO], (w2_block(role, warp) + w2_step(w2_full(role, warp), lane >> 2)) * 32, h * 128 + (lane & 3) * 32, sb + (round ? B_INIT2 : B_INIT));
    __syncwarp();
}

__device__ __forceinline__ void put_partials(bool TR, uint32_t a, const float* x, const float* y) {
    if (TR) stsm4t(a, pack2(x[0], x[1]), pack2(x[2], x[3]), pack2(y[0], y[1]), pack2(y[2], y[3]));
    else stsm4(a, pack2(x[0], x[1]), pack2(x[2], x[3]), pack2(y[0], y[1]), pack2(y[2], y[3]));
}
template <int NR, int PRE, int FM, int B, int E>
__device__ __forceinline__ void project(float (*acc)[4], bool TR, const uint32_t (*wr)[4], uint32_t (*as)[4], uint32_t (*v)[4], uint32_t* x, const uint32_t* w1a, uint32_t pp, uint32_t zero) {
    static_for<B, E>([&](auto I) {
        constexpr int n = I.value, kk = slot_k(n, NR), T = (n >> 5) * 4 + (n & 3), so = slot_sord(n, NR), q = w1_loaded(n - 1, NR, PRE);
        constexpr bool sm = kk >= NR;
        const uint32_t* w = sm ? as[so] : wr[sm ? 0 : (kk * 2 + (n >> 5)) * 4 + (n & 3)];
        if constexpr (n == 32 && PUT1 < 32) { put_partials(TR, pp, acc[0], acc[1]); put_partials(TR, pp + 4096, acc[2], acc[3]); }
        if constexpr (n == 0) {
            const uint32_t c = prmt(v[0][3], x[0], 0x3254);
            v[0][0] = h2bf(v[0][0], v[0][0]); v[0][1] = h2bf(v[0][1], v[0][1]); v[0][2] = h2bf(v[0][2], v[0][2]); v[0][3] = h2bf(v[0][3], x[0]);
            x[0] = c;
        }
        if constexpr ((n & 31) < 4) acc[T][0] = acc[T][1] = acc[T][2] = acc[T][3] = 0.f;
        mma16816(acc[T], w[0], w[1], w[2], w[3], v[slot_r(n, NR) >> 1][(slot_r(n, NR) & 1) * 2], v[slot_r(n, NR) >> 1][(slot_r(n, NR) & 1) * 2 + 1]);
        if constexpr (n == DEPS) {
            const uint32_t sel = __float_as_uint(acc[T][0]) * zero + 0x7610;
#pragma unroll
            for (int b = 1; b < 4; b++) cvt_block(v[b], x[b], sel);
        }
        if constexpr (w1_loaded(n, NR, PRE) > q) load_w1<q, NR>(as[q], w1a);
        if constexpr (n == PUT1 && n >= 32) { put_partials(TR, pp, acc[0], acc[1]); put_partials(TR, pp + 4096, acc[2], acc[3]); }
        if constexpr (n % 4 == 3 && (FM >> (n / 4) & 1) && n != E - 1) sched_fence();
    });
    if constexpr (E == 64) { put_partials(TR, pp + 8192, acc[4], acc[5]); put_partials(TR, pp + 12288, acc[6], acc[7]); }
}
__device__ __forceinline__ void reduce8(const uint32_t (*x)[4], const uint32_t* sel, float sc, uint32_t& r0, uint32_t& r1) {
    float d[4][4];
#pragma unroll
    for (int i = 0; i < 4; i++) {
        d[i][0] = d[i][1] = d[i][2] = d[i][3] = 0.f;
        mma16816(d[i], x[i][0], x[i][1], x[i][2], x[i][3], sel[2 * i], sel[2 * i + 1]);
    }
    r0 = pack2(((d[0][0] + d[1][0]) + (d[2][0] + d[3][0])) * sc, ((d[0][1] + d[1][1]) + (d[2][1] + d[3][1])) * sc);
    r1 = pack2(((d[0][2] + d[1][2]) + (d[2][2] + d[3][2])) * sc, ((d[0][3] + d[1][3]) + (d[2][3] + d[3][3])) * sc);
}

#define ISTAMP(i)
__host__ __device__ constexpr int wo_count(int n, int RES, bool res) { int c = 0; for (int i = 0; i < n; i++) c += (RES >> (i >> 2) & 1) == res; return c; }
__host__ __device__ constexpr int wo_loaded(int n, int RES, int PRE, int end) { int q = PRE; for (int i = 0; i <= n; i++) q += q < end && q - wo_count(i + 1, RES, false) < RING3; return q; }
template <int Q>
__device__ __forceinline__ void load_w2(uint32_t* w, const uint32_t* a) { ldsm4t(w, a[Q & 1] + (Q >> 1) * 1024); }
template <int NB, int RES, int PRE, int FM>
__device__ __forceinline__ void wo_blocks(uint32_t (*w)[4], const uint32_t (*wp)[4], uint32_t oa, const uint32_t* wa, const uint8_t* dst, const uint8_t* dsd, bool odd) {
    float a[NB][4][4];
    uint32_t o[4][4], r[5];
    bar_sync(3, 256);
#pragma unroll
    for (int i = 0; i < 4; i++) ldsm4(o[i], oa + i * 512);
    if (FM & 1) sched_fence();
    static_for<0, NB * 16>([&](auto I) {
        constexpr int n = I.value, i = n & 15, end = wo_count(NB * 16, RES, false), q = wo_loaded(n - 1, RES, PRE, end);
        constexpr bool res = RES >> (n >> 2) & 1;
        const uint32_t* b = o[i >> 2] + (i & 2);
        const uint32_t* x = res ? wp[wo_count(n, RES, true)] : w[wo_count(n, RES, false)];
        float* d = a[n >> 4][i & 3];
        if constexpr (i < 4) d[0] = d[1] = d[2] = d[3] = 0.f;
        mma16816(d, x[0], x[1], x[2], x[3], b[0], b[1]);
        if constexpr (wo_loaded(n, RES, PRE, end) > q) load_w2<q>(w[q], wa);
        if constexpr (n == NB * 16 - 1 || (n >= 16 && i == LAG - 1)) {
            const float (*e)[4] = a[n == NB * 16 - 1 ? NB - 1 : (n >> 4) - 1];
            const uint32_t y = pack2h(e[1][2] + e[3][2], e[1][3] + e[3][3]);
            r[0] = movm(pack2h(e[0][0] + e[2][0], e[0][1] + e[2][1])); r[1] = movm(pack2h(e[0][2] + e[2][2], e[0][3] + e[2][3]));
            r[2] = movm(pack2h(e[1][0] + e[3][0], e[1][1] + e[3][1])); r[3] = movm(odd ? ONES : y); r[4] = movm(odd ? y : ONES);
        }
        if constexpr (n == NB * 16 - 1 || (n >= 16 && i == LAG2 - 1)) {
            constexpr int bs = w2_step(NB == BB, n == NB * 16 - 1 ? NB - 1 : (n >> 4) - 1);
            red_add4(dst + bs * 2048, r[0], r[1], r[2], r[3]);
            red_add1(dsd + (bs >> 1) * 1024 + (bs & 1) * 256, r[4]);
        }
        if constexpr (((FM >> (n / 4 + 1)) & 1) && (n & 3) == 3 && n != NB * 16 - 1) sched_fence();
    });
}
#define FRAG1(ln) ((((ln) & 7) + ((ln) >> 4) * 8) * 128 + ((((((ln) >> 3) & 1) << (ROLE == 1)) ^ ((ln) & 7)) << 4))
#define FRAG2(ln) ((((ln) & 7) + ((ln) >> 4) * 8) * 64 + (((((ln) >> 3) & 1) ^ (((ln) >> 1) & 3)) << 4))
#define TILE_X(i) (ROLE == 1 ? (((i) >> 1) << 6) | (((i) & 1) << 4) : (i) << 5)
__device__ __forceinline__ void chain_fetch(const Params& P, const uint32_t sb, const int cta, const int warp, const int lane, uint32_t (*wr)[4]) {
    const int ROLE = cta % 3, nr = warp < 4 ? NRB : NRA;
    mbar_wait(sb + B_INIT, 0);
    ISTAMP(0)
#pragma unroll
    for (int f = 0; f < 40; f++) {
        const bool w1 = f < (NRA < NRB ? NRA : NRB) * 8 || f < nr * 8;
        ldsm4t(wr[f], sb + warp * 20480 + (f >> 2) * 2048 + (w1 ? FRAG1(lane) ^ TILE_X(f & 3) : (f & 2) * 512 + (FRAG2(lane) ^ ((f & 1) << 5))));
    }
    fence_async_smem();
    mbar_wait(sb + B_SFREE + (warp >> 2) * 8, 0);
    bar_sync(1, 256);
    chain_load(P, sb, cta, warp, lane, 1);
    ISTAMP(1)
}
__device__ __forceinline__ void chain_bounds(const uint32_t sb, const int cta, const int warp, const int lane, const uint32_t (*wr)[4]) {
    const int ROLE = cta % 3, nr = warp < 4 ? NRB : NRA;
    uint32_t m[6] = {}, u[4];
#pragma unroll
    for (int f = 0; f < 40; f++) m[f < 24 ? 0 : f >> 3] = amax4(m[f < 24 ? 0 : f >> 3], wr[f]);
    uint32_t m1 = amax(m[0], amax(nr > 3 ? m[3] : 0, nr > 4 ? m[4] : 0)), m2 = amax(nr > 3 ? 0 : m[3], nr > 4 ? 0 : m[4]);
    ISTAMP(5)
    mbar_wait(sb + B_INIT, 1);
    ISTAMP(3)
    if (ROLE == 2) {
#pragma unroll 4
        for (int i = 0; i < S_W2 / 4096; i++) { lds128(u, sb + S_W1 + warp * (S_W2 / 8) + i * 512 + lane * 16); m1 = amax4(m1, u); }
    }
    mbar_wait(sb + B_INIT2, 0);
    ISTAMP(7)
    const int n = w2_units(ROLE, warp) * 4;
#pragma unroll 4
    for (int i = 0; i < n; i++) { lds128(u, sb + w2_base(warp) + i * 512 + lane * 16); m2 = amax4(m2, u); }
    m1 = warp_exp(m1); m2 = warp_exp(m2);
    if (lane == 0) { if (ROLE == 2) red_max_shared(sb + S_EV, m1); red_max_shared(sb + S_EO, m2); }
}
template <bool ATT>
__device__ __forceinline__ void chain_role(const Params& P, const uint32_t sb, const int cta, const int warp, const int lane, const uint32_t epoch, const uint32_t (*wr)[4]) {
    constexpr int NR = ATT ? NRA : NRB, PRE = ATT ? PREA : PREB;
    const int h = cta / 3, ROLE = cta - h * 3;
    ISTAMP(6)
    uint32_t l8 = opq(sb + lane * 8, lane);
    const uint8_t* persu = (const uint8_t*)((ROLE == 1 ? g_km : g_vmt) + h * 512) - (sb >> 1);
    auto persist = [&](int s, int tile, uint32_t r0, uint32_t r1) {
        uint32_t* pp = (uint32_t*)(persu + s * 65536 + (ROLE == 1 ? (tile >> 1) * 512 + (tile & 1) * 128 : tile * 256) + (l8 >> 1));
        pp[0] = r0; pp[ROLE == 1 ? 64 : 32] = r1;
    };
    const uint32_t rk0 = (h & 1) * 3, rd1 = __shfl_sync(0xffffffffu, mapa(sb, rk0 + (ROLE + 1) % 3) - sb, 0), rd2 = __shfl_sync(0xffffffffu, mapa(sb, rk0 + (ROLE + 2) % 3) - sb, 0);
    const uint32_t xo = (ROLE == 2 ? S_XV : S_X + ROLE * 2048) + warp * 256;
    const bool full = w2_full(ROLE, warp);
    const int blk = w2_block(ROLE, warp);
    const uint32_t om = blk * 2048, os = xg_side(blk);
    const uint32_t w1o = sb + w1_base(warp), w2o = sb + w2_base(warp);
    ISTAMP(2)
    if (lane == 0) mbar_arrive(sb + B_READY);
#pragma unroll 1
    for (int s = 0;; s++) {
        l8 += s & P.zero;
        uint32_t r0, r1;
        {
            uint32_t v[4][4], as[(8 - NR) * 8][4], w1a[4];
            float acc[8][4];
            const uint32_t pst = sb + S_P1 + (l8 - sb) * 16 + ((warp * 16) ^ ((l8 & 56) * 2));
#pragma unroll
            for (int i = 0; i < 4; i++) w1a[i] = w1o + (FRAG1((l8 - sb) >> 3) ^ TILE_X(i));
            auto preload = [&]() { static_for<0, PRE>([&](auto I) { load_w1<I.value, NR>(as[I.value], w1a); }); };
#pragma unroll 1
            while (true) {
                uint32_t x[4];
                if (!(PLATE >> ATT & 1)) preload();
                const uint32_t lm = opq(l8 - sb, (l8 - sb) >> 3);
                const uint8_t* pm = P.xb + xg_buf(s) + warp * 8192 + xg_lane(lm >> 3);
                const uint8_t* ps = P.xb + xg_buf(s) + XG_SIDE + warp * 2048 + (lm >> 1);
                pin_ptr(pm); pin_ptr(ps);
                mbar_wait(sb + B_RELM, s & 1);
                if (ATT ? ADELAY : BDELAY) wait_clocks(ATT ? ADELAY : BDELAY);
                PROF(10)
#pragma unroll
                for (int b = 0; b < 4; b++) { ld_relaxed4(v[b], pm + b * 2048); ld_relaxed1n(x[b], ps + (b >> 1) * 1024 + (b & 1) * 256); }
                if (PLATE >> ATT & 1) { preload(); if (PLATE >> (ATT + 2) & 1) sched_fence(); }
                project<NR, PRE, ATT ? FENCEA : FENCEB, 0, PROG>(acc, ROLE == 2, wr, as, v, x, w1a, pst, P.zero);
                const uint32_t bad = xor_or(x[0], x[1], FULL) | xor_or(x[2], x[3], FULL);
                if (tags_ok(bad, 0xffffffffu)) break;
                COUNT_RETRY(warp >> 1)
                uint32_t n;
                asm volatile("atom.shared.add.u32 %0, [%1], 1;" : "=r"(n) : "r"(sb + S_RETRY) : "memory");
                if (n > SPIN_LIMIT) spin_fault();
            }
            PROF(0)
            sts32((l8 >> 1) + (sb - (sb >> 1) + S_EM + warp * 128), amax4(amax4(amax4(amax(amax(v[0][0], v[0][1]), amax(v[0][2], v[0][3])), v[1]), v[2]), v[3]));
            project<NR, PRE, ATT ? FENCEA : FENCEB, PROG, 64>(acc, ROLE == 2, wr, as, v, nullptr, w1a, pst, 0);
            PROF(1)
            const uint32_t isc = lds32(sb + S_ISC + (s & 1) * 4);
            const uint32_t lq = l8 + ((s >> 3) & P.zero);
            uint32_t x[4][4], sel[8], xd[6] = {l8 + xo, l8 + xo + rd1, l8 + xo + rd2, sb + B_X + rd1, sb + B_X + rd2, sb + S_P1 + warp * 2048 + (lq & 64) * 16 + (lq & 128) + (lq & 56) * 2};
#pragma unroll
            for (int i = 0; i < 8; i++) sel[i] = (lq & 224) == i * 32 ? 0x3F803F80u : 0u;
            pin<6>(xd); pin<8>(sel);
            if (RFENCE) sched_fence();
            bar_sync(1, 256);
#pragma unroll
            for (int i = 0; i < 4; i++) ldsm4t(x[i], xd[5] + i * 256);
            if (!ATT && l8 == sb + (warp - 3) * 1024) mbar_arrive(sb + B_P1);
            reduce8(x, sel, bf_hi(isc), r0, r1);
            st_async2(xd[1], r0, r1, xd[3], s != 63);
            st_async2(xd[2], r0, r1, xd[4], s != 63);
            sts64(xd[0], r0, r1);
            if (s == 63) { persist(s, warp, r0, r1); break; }
            if (!ATT && warp == 0) {
                uint32_t sc[2], u[2][4];
                lds64(sc, sb + S_SC);
                lds128(u[0], l8 * 2 + (S_EM - sb)); lds128(u[1], l8 * 2 + (S_EM + 512 - sb));
                const int em = warp_exp(amax4(amax(amax(u[0][0], u[0][1]), amax(u[0][2], u[0][3])), u[1]));
                if (l8 == sb) sts32(sb + S_ISC + (~s & 1) * 4, min(max(em + (int)(isc >> 23) - 127, (int)sc[1]) + (int)sc[0], 253) * 0x800080u);
            }
            __syncwarp();
            if (l8 == sb) mbar_arrive(sb + B_X);
            PROF(2)
        }
        uint32_t w[40][4], w2a[2], odd;
        const uint8_t *po, *pd;
        auto wo_addr = [&]() {
            const uint32_t lo = (l8 + ((s >> 2) & P.zero) - sb) >> 3;
            w2a[0] = w2o + FRAG2(lo); w2a[1] = w2o + (FRAG2(lo) ^ 32);
            po = P.xb + xg_buf(s + 1) + om + xg_lane(lo);
            pd = P.xb + xg_buf(s + 1) + os + lo * 4;
            odd = lo & 4;
            pin_ptr(po); pin_ptr(pd); pin<2>(w2a); pin<1>(&odd);
        };
        uint32_t oa = l8 * 2 + (S_OX - sb);
        if constexpr (ATT) {
            const uint32_t ln = (l8 + ((s >> 4) & P.zero) - sb) >> 3;
            const uint32_t va = sb + S_KV + 8192 + ((warp >> 1) & 1) * 4096 + ((ln & 7) + (ln >> 4) * 8) * 128 + ((((warp & 1) * 4 + ((ln >> 3) & 1)) ^ (ln & 7)) << 4);
            const uint32_t ka = sb + S_KV + (warp & 1) * 2048 + (ln & 15) * 128 + (((ln >> 4) ^ (ln & 7)) << 4);
            uint32_t ad[5] = {sb + S_SX + (ln & 3) * (8 * SROW) + (ln >> 2) * 4 + (warp < 6 ? (warp - 4) * 64 : 128 + (warp - 6) * 32), l8 + S_XV + (warp - 4) * 512,
                              l8 + S_SX + (ln >> 2) * (4 * SROW - 32), oa + (warp - 4) * 512, sb + S_ISC + (~s & 1) * 4};
            if constexpr (AB) { wo_addr(); pin<1>(&oa); }
            pin<5>(ad);
            const uint32_t sa = ad[0], sr = ad[2];
            uint32_t vf[4][4], vm[2][2], q[8][2];
            float S[4][4];
#pragma unroll
            for (int n = 0; n < 4; n++) { S[n][0] = S[n][1] = S[n][2] = S[n][3] = 0.f; }
            mbar_wait_fast(sb + B_KVFULL, s & 1);
            if (warp < 6) {
                uint32_t kf[8][4];
#pragma unroll
                for (int k = 0; k < 8; k++) ldsm4(kf[k], (ka ^ ((k & 3) << 5)) + (k >> 2) * 4096);
#pragma unroll
                for (int i = 0; i < 4; i++) ldsm4t(vf[i], (va ^ ((i & 1) << 5)) + (i >> 1) * 2048);
                mbar_wait(sb + B_X, s & 1);
                PROF(11)
#pragma unroll
                for (int k = 0; k < 8; k++) lds64(q[k], l8 + S_X + k * 256);
#pragma unroll
                for (int k = 0; k < 8; k++) mma16816(S[k & 3], kf[k][0], kf[k][1], kf[k][2], kf[k][3], q[k][0], q[k][1]);
                sts32(sa, __float_as_uint((S[0][0] + S[1][0]) + (S[2][0] + S[3][0])));
                sts32(sa + 4 * SROW, __float_as_uint((S[0][1] + S[1][1]) + (S[2][1] + S[3][1])));
                sts32(sa + 32, __float_as_uint((S[0][2] + S[1][2]) + (S[2][2] + S[3][2])));
                sts32(sa + 4 * SROW + 32, __float_as_uint((S[0][3] + S[1][3]) + (S[2][3] + S[3][3])));
            } else {
#pragma unroll
                for (int i = 0; i < 4; i++) ldsm4t(vf[i], (va ^ ((i & 1) << 5)) + (i >> 1) * 2048);
                uint32_t xa = l8 + S_X + (warp - 6) * 1024;
                pin<1>(&xa);
                mbar_wait(sb + B_X, s & 1);
                PROF(11)
#pragma unroll
                for (int k = 0; k < 8; k++) lds64(q[k], xa + (k >> 2) * 2048 + (k & 3) * 256);
#pragma unroll
                for (int k = 0; k < 4; k++) mma16816(S[k], q[4 + (k & 2)][0], q[4 + (k & 2)][1], q[5 + (k & 2)][0], q[5 + (k & 2)][1], q[k][0], q[k][1]);
                sts32(sa, __float_as_uint((S[0][0] + S[2][0]) + (S[1][2] + S[3][2])));
                sts32(sa + 4 * SROW, __float_as_uint((S[0][1] + S[2][1]) + (S[1][3] + S[3][3])));
            }
            const uint32_t isn = lds32(ad[4]);
            lds64(vm[0], ad[1]); lds64(vm[1], ad[1] + 256);
            PROF(7)
            bar_sync(2, 128);
            const float cs = 0.08838834764831845f * 1.4426950408889634f;
            float E[6][2];
#pragma unroll
            for (int i = 0; i < 6; i++) lds64f(E[(i + 4) % 6], sr + ((i + 4) % 6) * 32);
            E[4][0] += E[5][0]; E[4][1] += E[5][1];
            float m = fmaxf(fmaxf(fmaxf(fmaxf(E[0][0], E[0][1]), fmaxf(E[1][0], E[1][1])), fmaxf(fmaxf(E[2][0], E[2][1]), fmaxf(E[3][0], E[3][1]))), fmaxf(E[4][0], E[4][1]));
            m = fmaxf(m, __shfl_xor_sync(0xffffffffu, m, 1));
            m = fmaxf(m, __shfl_xor_sync(0xffffffffu, m, 2));
            m *= cs;
            if constexpr (AB) static_for<0, PRE3>([&](auto I) { load_w2<I.value>(w[I.value], w2a); });
            uint32_t pa[5];
#pragma unroll
            for (int i = 0; i < 5; i++) { const int k = (i + 4) % 5; E[k][0] = ex2(fmaf(E[k][0], cs, -m)); E[k][1] = ex2(fmaf(E[k][1], cs, -m)); pa[k] = pack2(E[k][0], E[k][1]); }
            if (EFENCE) sched_fence();
            float O[2][4], Z[4];
#pragma unroll
            for (int i = 0; i < 4; i++) { O[0][i] = O[1][i] = Z[i] = 0.f; }
#pragma unroll
            for (int i = 0; i < 2; i++) {
                mma1688(O[i], vm[i][0], vm[i][1], pa[4]);
                mma16816(O[i], vf[i][0], vf[i][1], vf[i][2], vf[i][3], pa[0], pa[1]);
                mma16816(O[i], vf[2 + i][0], vf[2 + i][1], vf[2 + i][2], vf[2 + i][3], pa[2], pa[3]);
            }
            const float z = (((E[4][0] + E[4][1]) + (E[0][0] + E[0][1])) + ((E[1][0] + E[1][1]) + (E[2][0] + E[2][1]))) + (E[3][0] + E[3][1]);
            const float zh = __uint_as_float(__float_as_uint(z) & 0xffff0000u);
            mma1688(Z, isn, isn, pack2(zh, z - zh));
            const float i0 = rcp(Z[0]), i1 = rcp(Z[1]);
            stsm4t(ad[3], pack2(O[0][0] * i0, O[0][1] * i1), pack2(O[0][2] * i0, O[0][3] * i1), pack2(O[1][0] * i0, O[1][1] * i1), pack2(O[1][2] * i0, O[1][3] * i1));
            PROF(4)
            if constexpr (AB) wo_blocks<1, RESA, PRE3, OFENCE / 2>(w, wr + NR * 8, oa, w2a, po, pd, odd);
            else bar_arrive(3, 256);
            if (ROLE != 0) persist(s, warp, r0, r1);
            if (warp == 7 && l8 == sb) mbar_expect(sb + B_X, 4096);
        } else {
            if (ROLE != 0) persist(s, warp, r0, r1);
            wo_addr(); pin<1>(&oa);
            static_for<0, PRE2A>([&](auto I) { load_w2<I.value>(w[I.value], w2a); });
            mbar_wait(sb + B_X, s & 1);
            wait_clocks(XDELAY);
            constexpr int PRE1 = (BB - 1) * 16 - (5 - NRB) * 8 < PRE2 ? (BB - 1) * 16 - (5 - NRB) * 8 : PRE2;
            static_for<PRE2A, PRE1>([&](auto I) { load_w2<I.value>(w[I.value], w2a); });
            if (full) {
                static_for<PRE1, PRE2>([&](auto I) { load_w2<I.value>(w[I.value], w2a); });
                wo_blocks<BB, RESB, PRE2, FENCE2 * 2 + OFENCE % 2>(w, wr + NR * 8, oa, w2a, po, pd, odd);
            } else wo_blocks<BB - 1, RESB1, PRE1, FENCE2 * 2 + OFENCE % 2>(w, wr + NR * 8, oa, w2a, po, pd, odd);
        }
        PROF(5)
        if (l8 == sb) { sts32(sb + S_TO + warp * 4, gtime()); mbar_arrive(sb + B_RED); }
        if (HOLD && !(PLATE >> ATT & 1)) mbar_wait(sb + B_RED, s & 1);
        if (ROLE != 0 && (s & 3) == 3 && l8 == sb) mbar_arrive(sb + B_PERS);
        if (ROLE == 0 && s == 62) return;
    }
    __syncwarp();
    if (l8 == sb) mbar_arrive(sb + B_PERS);
}
#define IP(i)
struct Pipe { uint32_t stage, phase; };
struct Cons {
    uint32_t sb, rel;
    int wg, wq, lane, rank, pair;
    uint32_t atag, nst;
    Pipe p;
};
__device__ __forceinline__ void pipe_next(Pipe& p) { p.stage = (p.stage + 1) & (NSTAGE - 1); p.phase ^= (p.stage == 0); }
__device__ __forceinline__ void release(const Cons& c, uint32_t stage) { if (c.lane < 2) mbar_arrive_cluster(c.rel + stage * 8); }
__device__ __forceinline__ void wait_full(const Cons& c) { mbar_wait(c.sb + B_FULL + c.p.stage * 8, c.p.phase); }

enum { PEND_NONE = 0, PEND_KVO = 1, PEND_HT = 2, PEND_OUT = 3 };
struct Pend { uint32_t pk[64]; int kind, row, col, cnt; };

__device__ __forceinline__ void staging_wait(const Cons& c) { if (c.nst) mbar_wait(c.sb + B_SFREE + c.wg * 8, (c.nst - 1) & 1); }
__device__ __forceinline__ void staging_post(Cons& c, int kind, int row, int col, int cnt) {
    __syncwarp();
    if (c.lane == 0) {
        if (c.wq == 0) { const uint32_t x[4] = {(uint32_t)kind, (uint32_t)row, (uint32_t)col, (uint32_t)cnt}; sts128(c.sb + S_DESC + c.wg * 16, x); }
        mbar_arrive(c.sb + B_SFULL + c.wg * 8);
    }
    c.nst++;
}
__device__ __forceinline__ void drain(const Params& P, Cons& c, Pend& d) {
    const uint32_t* pk = d.pk;
    if (d.kind == PEND_OUT) {
        float* o = P.out + (size_t)(d.row + c.wq * 16 + (c.lane >> 2)) * 2048 + d.col + (c.lane & 3) * 2;
#pragma unroll
        for (int j = 0; j < 16; j++) {
            st_stream2(o + j * 8, bf_lo(pk[j * 2]), bf_hi(pk[j * 2]));
            st_stream2(o + 8 * 2048 + j * 8, bf_lo(pk[j * 2 + 1]), bf_hi(pk[j * 2 + 1]));
        }
    } else {
        const bool ht = d.kind == PEND_HT;
        const int hi = (c.lane >> 3) & 1;
        const uint32_t base = c.sb + S_STG + c.wg * 16384 + ((ht ? hi * 32 + c.wq * 8 : c.wq * 16 + hi * 8) + (c.lane & 7)) * 128;
        staging_wait(c);
#pragma unroll
        for (int j = 0; j < 8; j++) {
            const int ch = (j & 3) * 2 + (c.lane >> 4);
            stsm4(base + (j >> 2) * 8192 + ((ch ^ (c.lane & 7)) << 4), pk[j * 4], pk[j * 4 + 1], pk[j * 4 + 2], pk[j * 4 + 3]);
        }
        fence_async_smem();
        staging_post(c, d.kind, d.row, d.col, (d.col & 128) ? d.cnt : -1);
    }
    if (d.col & 128) d.kind = PEND_NONE;
    d.col += 128;
#pragma unroll
    for (int i = 0; i < 32; i++) d.pk[i] = d.pk[32 + i];
}

constexpr int S_STG2 = 8 * 20480, PEND_BOTH = 8;
__device__ __forceinline__ void drain_both(Cons& c, const Pend& d) {
    const uint32_t base = c.sb + c.wg * 16384 + (c.wq * 16 + ((c.lane >> 3) & 1) * 8 + (c.lane & 7)) * 128;
#pragma unroll
    for (int j = 0; j < 16; j++)
        stsm4(base + (j < 8 ? S_STG : S_STG2) + (j >> 2 & 1) * 8192 + ((((j & 3) * 2 + (c.lane >> 4)) ^ (c.lane & 7)) << 4), d.pk[j * 4], d.pk[j * 4 + 1], d.pk[j * 4 + 2], d.pk[j * 4 + 3]);
    fence_async_smem();
    staging_post(c, PEND_KVO | PEND_BOTH, d.row, d.col, d.cnt);
}

__device__ __forceinline__ void store_warp(const Params& P, uint32_t sb, int wg, int cta) {
    if (cta < 128) {
        for (int i = 0; i < P.xd; i++) __nanosleep(1000);
        const uint32_t e1 = ld_acquire(&g_cnt(C_EPOCH)) + 1;
        const uint4* x = (const uint4*)P.Bx + (cta * 2 + wg) * 1024 + (threadIdx.x & 31);
        uint32_t m = 0;
#pragma unroll 4
        for (int i = 0; i < 32; i++) { const uint4 u = __ldg(x + i * 32); m = amax(amax(m, amax(u.x, u.y)), amax(u.z, u.w)); }
        m = warp_exp(m);
        if (elect_one()) { atomicMax(&g_cnt(C_XMAX), e1 << 8 | m); red_release(&g_cnt(C_XCNT)); }
        __syncwarp();
    }
    const uint32_t stg = sb + S_STG + wg * 16384;
#pragma unroll 1
    for (uint32_t n = 0;; n++) {
        mbar_wait(sb + B_SFULL + wg * 8, n & 1);
        uint32_t x[4];
        lds128(x, sb + S_DESC + wg * 16);
#pragma unroll
        for (int i = 0; i < 4; i++) x[i] = __shfl_sync(0xffffffffu, x[i], 0);
        if (x[0] == PEND_NONE) break;
        const bool ht = x[0] == PEND_HT;
        const CUtensorMap* m = &P.tm[ht ? M_HTS : M_KVO];
        if (elect_one()) {
#pragma unroll
            for (int i = 0; i < 4; i++) tma_store2d(m, x[2] + (i >> 1) * 64, x[1] + (i & 1) * (ht ? 1024 : 32), stg + i * 4096);
            if (x[0] & PEND_BOTH) {
#pragma unroll 1
                for (int i = 0; i < 4; i++) tma_store2d(m, x[2] + 128 + (i >> 1) * 64, x[1] + (i & 1) * 32, stg + (S_STG2 - S_STG) + i * 4096);
            }
            bulk_commit();
            bulk_wait_read();
            mbar_arrive(sb + B_SFREE + wg * 8);
            if ((int)x[3] >= 0) { bulk_wait_all(); fence_async(); red_release(&g_cnt(x[3])); }
        }
        __syncwarp();
    }
}

template <int TA, int TB>
__device__ __forceinline__ void issue_ktile(float* acc, const Cons& c) {
    const uint32_t a = c.sb + c.p.stage * STAGE + c.wg * 8192, b = c.sb + c.p.stage * STAGE + 16384;
    const uint64_t da = mkdesc(a, TA ? 8192 : 16, 1024, 1), db = mkdesc(b, TB ? 8192 : 16, 1024, 1);
    wg_fence();
#pragma unroll
    for (int k = 0; k < 4; k++) wgmma_ss256<TA, TB>(acc, da + (TA ? 128 : 2) * k, db + (TB ? 128 : 2) * k);
    wg_commit();
}
template <bool KVONLY = false>
__device__ __forceinline__ void mainloop(float* acc, const Params& P, Cons& c, Pend& d, int type, int nk) {
    uint32_t prev = 0;
#pragma unroll
    for (int i = 0; i < 128; i++) acc[i] = 0.f;
    pin<128>(acc);
#pragma unroll 1
    for (int kt = 0; kt < nk; kt++) {
        wait_full(c);
        if (!KVONLY && type == T_A1) issue_ktile<0, 0>(acc, c);
        else if (!KVONLY && type == T_A2) issue_ktile<1, 0>(acc, c);
        else issue_ktile<0, 1>(acc, c);
        wg_wait<1>();
        if (kt) release(c, prev);
        else if (!KVONLY) { IP(0) }
        if (!KVONLY && d.kind != PEND_NONE && kt != 1) drain(P, c, d);
        prev = c.p.stage;
        pipe_next(c.p);
    }
    d.kind = PEND_NONE;
    wg_wait<0>();
    pin<128>(acc);
    release(c, prev);
    if (!KVONLY) { IP(1) }
}
__device__ __forceinline__ void pack_half(uint32_t* pk, const float* a) {
#pragma unroll
    for (int i = 0; i < 32; i++) pk[i] = pack2(a[2 * i], a[2 * i + 1]);
}

__device__ __forceinline__ void epi_kv(const float* acc, const Cons& c, Pend& d, int mb, int nb) {
    pack_half(d.pk, acc); pack_half(d.pk + 32, acc + 64);
    d.kind = PEND_KVO; d.row = (nb >> 4) * 2048 + mb * 256 + c.rank * 128 + c.wg * 64; d.col = (nb & 15) * 256; d.cnt = C_KV + mb;
}

__device__ __forceinline__ void qa_scores(float* S, float* Sm, const uint32_t* q, Cons& c) {
    wait_full(c);
    const uint32_t st = c.sb + c.p.stage * STAGE;
    const uint64_t dk = mkdesc(st + c.wg * 8192, 16, 1024, 1), dm = mkdesc(st + 32768 + c.wg * 4096, 128, 2048, 0);
    wg_fence();
#pragma unroll
    for (int i = 0; i < 8; i++) wgmma_rs64<0>(S, q + i * 4, dk + (i >> 2) * 1024 + (i & 3) * 2, i != 0);
#pragma unroll
    for (int i = 0; i < 8; i++) wgmma_rs16<0>(Sm, q + i * 4, dm + i * 16, i != 0);
    wg_commit();
    pipe_next(c.p);
}
__device__ __forceinline__ void qa_softmax(uint32_t (*pa)[4], const float* S, const float* Sm, const Cons& c) {
    const int t = c.lane & 3, i0 = (c.wq & 1) * 16 + (c.lane >> 2) - 2 * t;
    const bool sg = c.wq >= 2;
    const float cs = 0.08838834764831845f * 1.4426950408889634f;
    float x[2][10];
#pragma unroll
    for (int r = 0; r < 2; r++) {
#pragma unroll
        for (int j = 0; j < 4; j++)
#pragma unroll
            for (int e = 0; e < 2; e++) {
                const float v = sg ? S[16 + j * 4 + r * 2 + e] : S[j * 4 + r * 2 + e];
                x[r][j * 2 + e] = (j * 8 + e - r * 8 > i0) ? -1e9f / 0.08838834764831845f : v;
            }
        x[r][8] = sg ? Sm[4 + r * 2] : Sm[r * 2];
        x[r][9] = sg ? Sm[5 + r * 2] : Sm[1 + r * 2];
        float m = fmaxf(fmaxf(fmaxf(fmaxf(x[r][0], x[r][1]), fmaxf(x[r][2], x[r][3])), fmaxf(fmaxf(x[r][4], x[r][5]), fmaxf(x[r][6], x[r][7]))), fmaxf(x[r][8], x[r][9]));
        m = fmaxf(m, __shfl_xor_sync(0xffffffffu, m, 1));
        m = fmaxf(m, __shfl_xor_sync(0xffffffffu, m, 2));
        m *= -cs;
#pragma unroll
        for (int i = 0; i < 10; i++) x[r][i] = ex2(fmaf(x[r][i], cs, m));
        float sum = (((x[r][0] + x[r][1]) + (x[r][2] + x[r][3])) + ((x[r][4] + x[r][5]) + (x[r][6] + x[r][7]))) + (x[r][8] + x[r][9]);
        sum += __shfl_xor_sync(0xffffffffu, sum, 1);
        sum += __shfl_xor_sync(0xffffffffu, sum, 2);
        const float inv = rcp(sum);
#pragma unroll
        for (int i = 0; i < 10; i++) x[r][i] *= inv;
    }
#pragma unroll
    for (int ks = 0; ks < 2; ks++)
#pragma unroll
        for (int i = 0; i < 4; i++) {
            const uint32_t p = pack2(x[i & 1][ks * 4 + (i >> 1) * 2], x[i & 1][ks * 4 + (i >> 1) * 2 + 1]);
            pa[ks][i] = sg ? 0u : p;
            pa[2 + ks][i] = sg ? p : 0u;
        }
#pragma unroll
    for (int r = 0; r < 2; r++) {
        const uint32_t p = pack2(x[r][8], x[r][9]);
        pa[4][r] = sg ? 0u : p;
        pa[4][2 + r] = sg ? p : 0u;
    }
}
__device__ __forceinline__ void qa_values(float* O, uint32_t (*pa)[4], Cons& c) {
    wait_full(c);
    const uint32_t st = c.sb + c.p.stage * STAGE;
    const uint64_t dv = mkdesc(st + c.wg * 8192, 16384, 1024, 1), dm = mkdesc(st + 32768 + c.wg * 4096, 2048, 128, 0);
    pin<20>(&pa[0][0]);
    wg_fence();
#pragma unroll
    for (int ks = 0; ks < 4; ks++) wgmma_rs128<1>(O, pa[ks], dv + ks * 128, ks != 0);
    wgmma_rs128<0>(O, pa[4], dm, 1);
    wg_commit();
    pipe_next(c.p);
}
__device__ __forceinline__ void epi_qa(const float* acc, Cons& c, Pend& d, int mb, int nb) {
    uint32_t q[64], pa[2][5][4];
    float S0[32] = {}, M0[8] = {}, S1[32] = {}, M1[8] = {}, O0[64] = {}, O1[64] = {};
    const uint32_t k0 = c.p.stage;
    pack_half(q, acc);
    pin<32>(q); pin<32>(S0); pin<8>(M0);
    qa_scores(S0, M0, q, c);
    pack_half(q + 32, acc + 64);
    pin<32>(q + 32); pin<32>(S1); pin<8>(M1);
    qa_scores(S1, M1, q + 32, c);
    wg_wait<1>();
    pin<32>(S0); pin<8>(M0);
    release(c, k0);
    qa_softmax(pa[0], S0, M0, c);
    wg_wait<0>();
    pin<32>(S1); pin<8>(M1); pin<64>(q);
    release(c, (k0 + 1) & (NSTAGE - 1));
    pin<64>(O0);
    qa_values(O0, pa[0], c);
    qa_softmax(pa[1], S1, M1, c);
    pin<64>(O1);
    qa_values(O1, pa[1], c);
    wg_wait<1>();
    pin<64>(O0); pin<20>(&pa[0][0][0]);
    release(c, (k0 + 2) & (NSTAGE - 1));
    pack_half(d.pk, O0);
    wg_wait<0>();
    pin<64>(O1); pin<20>(&pa[1][0][0]);
    release(c, (k0 + 3) & (NSTAGE - 1));
    pack_half(d.pk + 32, O1);
    d.kind = PEND_KVO; d.row = 4096 + mb * 256 + c.rank * 128 + c.wg * 64; d.col = nb * 256; d.cnt = C_O + mb;
}

__device__ __forceinline__ void epi_op(const float* acc, const Cons& c, Pend& d, int mb, int nb) {
    pack_half(d.pk, acc); pack_half(d.pk + 32, acc + 64);
    d.kind = PEND_OUT; d.row = mb * 256 + c.rank * 128 + c.wg * 64; d.col = 1024 + nb * 256;
}

__device__ __forceinline__ void epi_a2(float* acc, const Params& P, Cons& c, int mb, int col0) {
    const int g = c.lane >> 2, t = c.lane & 3;
    const int row = mb * 256 + (g >> 1) * 64 + (c.rank * 16 + c.wg * 8 + c.wq * 2) * 2 + (g & 1);
    float* o = P.out + (size_t)row * 2048 + col0 + t * 2;
#pragma unroll 1
    for (int hf = P.zero; hf < 2; hf++) {
    wait_full(c);
    const uint32_t st = c.sb + c.p.stage * STAGE, xa = st + (c.wg * 64 + c.wq * 16 + g) * 128 + t * 4 + (g << 4), da = st + 32768 + t * 4;
#pragma unroll
    for (int j = 0; j < 16; j++) {
        const float* a = acc + j * 4;
        const uint32_t ad = (xa ^ ((j & 7) << 4)) + (j >> 3) * 16384;
        const uint32_t x0 = lds32(ad), x1 = lds32(ad + 1024), dv = lds32(da + j * 16);
        const uint32_t u0 = mul_bf2(x0, dv), u1 = mul_bf2(x1, dv);
        st_stream2(o + j * 8, a[0] + bf_lo(u0), a[1] + bf_hi(u0));
        st_stream2(o + 2 * 2048 + j * 8, a[2] + bf_lo(u1), a[3] + bf_hi(u1));
    }
    __syncwarp();
    release(c, c.p.stage);
    pipe_next(c.p);
    o += 128;
#pragma unroll
    for (int i = 0; i < 64; i++) acc[i] = acc[64 + i];
    }
}

#define TSTAMP(i)
__device__ __forceinline__ float2 cmul(float2 a, float2 b) { return make_float2(fmaf(a.x, b.x, -a.y * b.y), fmaf(a.x, b.y, a.y * b.x)); }
__device__ __forceinline__ float2 cfma(float2 a, float2 b, float2 u) { return make_float2(fmaf(a.x, b.x, fmaf(-a.y, b.y, u.x)), fmaf(a.x, b.y, fmaf(a.y, b.x, u.y))); }
__device__ __forceinline__ float4 ssm_coef(float lre, float lim, float logdt) {
    const float dt = __bfloat162float(__float2bfloat16(expf(logdt)));
    const float ea = expf(dt * lre);
    float sn, cn;
    sincosf(dt * lim, &sn, &cn);
    const float br = ea * cn, bi = ea * sn, nr = br - 1.f;
    float cr, ci;
    if (fabsf(lre) >= fabsf(lim)) { const float r = lim / lre, dn = lre + lim * r; cr = (nr + bi * r) / dn; ci = (bi - nr * r) / dn; }
    else { const float r = lre / lim, dn = lre * r + lim; cr = (nr * r + bi) / dn; ci = (bi * r - nr) / dn; }
    return make_float4(br, bi, cr, ci);
}
__device__ __forceinline__ void epi_a1(const float* acc, const Params& P, const Cons& c, Pend& d, int mb, int nb, uint32_t atag) {
    const int t = c.lane & 3;
    const int p = nb * 128 + c.rank * 64 + c.wg * 32 + c.wq * 8 + (c.lane >> 2);
    const float4 cf = __ldcg(&g_coef[p]);
    const float2 lam = make_float2(cf.x, P.swap_ri ? -cf.y : cf.y);
    const float a0 = P.swap_ri ? -2.f * cf.w : 2.f * cf.z, a1 = P.swap_ri ? 2.f * cf.z : -2.f * cf.w;
    const float b0 = P.swap_ri ? -2.f * cf.z : -2.f * cf.w, b1 = P.swap_ri ? -2.f * cf.w : -2.f * cf.z;
    float2 h = make_float2(0.f, 0.f);
#pragma unroll 1
    for (int round = P.zero; round < 2; round++) {
#pragma unroll
        for (int j = 0; j < 32; j++) {
            h = cfma(lam, h, make_float2(acc[j * 4], acc[j * 4 + 2]));
            const float r0 = fmaf(a0, h.x, a1 * h.y), m0 = fmaf(b0, h.x, b1 * h.y);
            h = cfma(lam, h, make_float2(acc[j * 4 + 1], acc[j * 4 + 3]));
            d.pk[j * 2] = pack2(r0, fmaf(a0, h.x, a1 * h.y));
            d.pk[j * 2 + 1] = pack2(m0, fmaf(b0, h.x, b1 * h.y));
        }
        if (round) continue;
        float2 l64 = lam;
#pragma unroll
        for (int i = 0; i < 6; i++) l64 = cmul(l64, l64);
        const float2 l128 = cmul(l64, l64), l256 = cmul(l128, l128);
        float2 o = make_float2(__shfl_up_sync(0xffffffffu, h.x, 1), __shfl_up_sync(0xffffffffu, h.y, 1));
        if (t >= 1) h = cfma(l64, o, h);
        o = make_float2(__shfl_up_sync(0xffffffffu, h.x, 2), __shfl_up_sync(0xffffffffu, h.y, 2));
        if (t >= 2) h = cfma(l128, o, h);
        IP(2)
        if (t == 3) st_relaxed2(&g_agg[mb * 1024 + p], (__float_as_uint(h.x) & ~1u) | atag, __float_as_uint(h.y));
        h = make_float2(__shfl_up_sync(0xffffffffu, h.x, 1), __shfl_up_sync(0xffffffffu, h.y, 1));
        if (t == 0) h = make_float2(0.f, 0.f);
        uint32_t ax[7], ay[7];
        int n = 0;
        while (true) {
            uint32_t bad = 0;
#pragma unroll
            for (int j = 0; j < 7; j++) { ax[j] = atag; ay[j] = 0; ld_relaxed2_if(ax[j], ay[j], &g_agg[j * 1024 + p], j < mb); }
#pragma unroll
            for (int j = 0; j < 7; j++) bad |= ax[j] ^ atag;
            if (tags_ok(bad)) break;
            __nanosleep(2 * POLLNS);
            if (++n > SPIN_LIMIT) spin_fault();
        }
        float2 carry = make_float2(0.f, 0.f);
#pragma unroll
        for (int j = 0; j < 7; j++) if (j < mb) carry = cfma(l256, carry, make_float2(__uint_as_float(ax[j]), __uint_as_float(ay[j])));
        float2 w = (t & 1) ? l64 : make_float2(1.f, 0.f);
        if (t & 2) w = cmul(w, l128);
        h = cfma(w, carry, h);
        IP(3)
    }
    IP(4)
    d.kind = PEND_HT; d.row = nb * 128 + c.rank * 64 + c.wg * 32; d.col = mb * 256; d.cnt = C_HT + mb;
}

__device__ __forceinline__ uint32_t fresh_tid() { uint32_t t; asm volatile("mov.u32 %0, %%tid.x;" : "=r"(t)); return t; }
__device__ __forceinline__ uint32_t acquire_stage(uint32_t sb, Pipe& p, uint32_t bytes) {
    mbar_wait(sb + B_EMPTY + p.stage * 8, p.phase ^ 1);
    mbar_expect_e(sb + B_FULL + p.stage * 8, bytes);
    return p.stage;
}
__device__ __forceinline__ void producer(const Params& P, const uint32_t sb, const int cta, const uint32_t epoch) {
    Pipe p = {0, 0};
    const uint32_t e1 = epoch + 1;
    const int rank = cta & 1;
    const uint16_t both = 3 << (__shfl_sync(0xffffffffu, cluster_rank(), 0) & ~1u);
    for (int it = ITEM_OFF(cta >> 1); it < ITEM_OFF((cta >> 1) + 1); it++) {
        const int item = ITEM(it), kind = (item >> 8) & 7, mb = (item >> 5) & 7;
        const int half = kind >= T_OPH, type = half ? kind * 2 - 10 : kind, nb = item & (half ? 3 : 31), hw = item >> 2 & half;
        if (type == T_CHAIN) {
            const int h = cta / 3, role = cta - h * 3;
            uint32_t* flag = &g_cnt(C_FLAG + (role == 2 ? 32 : 0) + h);
            if (role) { wait_count(&g_cnt(C_KV), e1 * 128); fence_async(); }
#pragma unroll 1
            for (int s = 0; s < 64 && role != 0; s++) {
                if (s < 63) {
                    mbar_wait(sb + B_GO, s & 1);
                    tma3d_mc_e(sb + S_KV + (role - 1) * 8192, &P.tm[M_SEG], 0, (role - 1) * 2048 + s * 32, h * 2, sb + B_KVFULL, 7 << ((h & 1) * 3));
                    if ((s & 7) == 7) { wait_count(&g_cnt(C_KV + 1 + (s >> 3)), e1 * 128); fence_async(); }
                    tma_prefetch3d_e(&P.tm[M_SEG], 0, (role - 1) * 2048 + s * 32 + 32, h * 2);
                }
                if (s > 0 && ((s & 3) == 0 || s == 63)) {
                    const int i = (s - 1) >> 2;
                    mbar_wait(sb + B_PERS, i & 1);
                    asm volatile("{\n.reg .pred E;\nelect.sync _|E, 0xffffffff;\n@E st.release.gpu.global.u32 [%0], %1;\n}" ::"l"(flag), "r"(epoch * 64 + i * 4 + 4) : "memory");
                }
            }
            if (role == 0) {
                const int lane = threadIdx.x & 31;
                if (lane == 0) mbar_arrive(sb + B_RELM);
#pragma unroll 1
                for (int s = 0; s < 63; s++) {
                    mbar_wait(sb + B_P1, s & 1);
                    if (s > 0) {
                        st_relaxed4(P.xb + xg_buf(s - 1) + h * 2048 + xg_lane(lane), 0, 0, 0, 0);
                        st_relaxed1(P.xb + xg_buf(s - 1) + xg_side(h) + lane * 4, 0);
                        __threadfence();
                    }
                    __syncwarp();
                    if (lane == 0) mbar_arrive(sb + B_RELM);
                }
            }
            mbar_wait(sb + B_RESUME, 0);
            continue;
        }
        const int m0 = mb * 256 + rank * 128;
        if (type <= T_OP) {
            const CUtensorMap* ma = &P.tm[half ? M_OAH : type == T_OP ? M_OA : M_BX];
            const CUtensorMap* mw = &P.tm[type == T_OP ? M_WO : type == T_QA ? M_WQ : nb < 16 ? M_WK : M_WV];
            const int nk = type == T_OP ? 64 : 16, nc = (nb & 15) * 4 + rank * 2, ma0 = type == T_OP ? 4096 + m0 + hw * 64 : m0;
            if (type == T_OP) { wait_count(&g_cnt(C_O + mb), e1 * 64); fence_async(); }
            if (type == T_QA) {
                wait_count(&g_cnt(C_KV + mb), e1 * 128);
                fence_async();
            }
            auto arrived = [&]() {
                const uint32_t t = fresh_tid();
                return __all_sync(0xffffffffu, (int32_t)(ld_acquire(&g_cnt(C_FLAG + (t & 2) * 16 + nb * 2 + (t & 1))) - (epoch * 64 + mb * 8 + rank * 4 + 4)) >= 0);
            };
            bool passed = false;
#pragma unroll 1
            for (int kt = 0; kt < nk; kt++) {
                if (type == T_QA && kt == 9) passed = arrived();
                const uint32_t st = acquire_stage(sb, p, STAGE - half * 8192), bar = sb + B_FULL + st * 8;
                tma2d_e(sb + st * STAGE + hw * 8192, ma, kt * 64, ma0, bar);
                tma3d_mc_e(sb + st * STAGE + 16384 + rank * 16384, mw, 0, kt * 64, nc, bar, both);
                if (type == T_QA && kt < 8) tma_prefetch2d_e(&P.tm[M_OA], nb * 256 + (kt & 3) * 64, (kt >> 2) * 2048 + m0);
                pipe_next(p);
            }
            if (type == T_QA) {
                for (int n = 0; !passed; n++) { passed = arrived(); if (!passed) __nanosleep(200); if (n > SPIN_LIMIT) spin_fault(); }
                fence_async();
#pragma unroll 1
                for (int e = 0; e < 4; e++) {
                    const uint32_t st = acquire_stage(sb, p, 40960), bar = sb + B_FULL + st * 8, dst = sb + st * STAGE;
                    tma2d_e(dst, &P.tm[M_OA], nb * 256 + (e & 1) * 128, (e >> 1) * 2048 + m0, bar);
                    tma2d_e(dst + 16384, &P.tm[M_OA], nb * 256 + (e & 1) * 128 + 64, (e >> 1) * 2048 + m0, bar);
                    const uint32_t* src = ((e >> 1) ? g_vmt : g_km) + ((mb * 8 + rank * 4) * 32 + nb * 2 + (e & 1)) * 512;
#pragma unroll 1
                    for (int i = 0; i < 4; i++) bulk_g2s_e(dst + 32768 + i * 2048, src + i * 32 * 512, 2048, bar);
                    pipe_next(p);
                }
            }
        } else if (type == T_A1) {
            wait_count(&g_cnt(C_COEF), e1 * 4);
            l2_prefetch_e(g_coef + nb * 128 + rank * 64, 1024);
#pragma unroll 1
            for (int kt = 0; kt < 16; kt++) {
                const uint32_t st = acquire_stage(sb, p, STAGE), bar = sb + B_FULL + st * 8;
                tma4d_e(sb + st * STAGE, &P.tm[M_AB], kt * 64, nb * 16 + rank * 8, bar);
                tma4d_mc_e(sb + st * STAGE + 16384 + rank * 16384, &P.tm[M_AX], kt * 64, mb * 128 + rank * 16, bar, both);
                pipe_next(p);
            }
        } else {
            wait_count(&g_cnt(C_HT + mb), e1 * 32);
            fence_async();
#pragma unroll 1
            for (int kt = 0; kt < 32; kt++) {
                const uint32_t st = acquire_stage(sb, p, STAGE - half * 8192), bar = sb + B_FULL + st * 8;
                tma3d_e(sb + st * STAGE + hw * 8192, &P.tm[half ? M_HTH : M_HT], 0, kt * 64, mb * 4 + rank * 2 + hw, bar);
                tma2d_mc_e(sb + st * STAGE + 16384 + rank * 16384, &P.tm[M_CRE] + (kt >> 4), (kt & 15) * 64, (nb * 2 + rank) * 128, bar, both);
                pipe_next(p);
            }
#pragma unroll 1
            for (int col = nb * 256; col < (nb + 1) * 256; col += 128) {
                const uint32_t st = acquire_stage(sb, p, 32768 + 256), bar = sb + B_FULL + st * 8;
                tma4d_e(sb + st * STAGE, &P.tm[M_AX], col, mb * 128 + rank * 16, bar);
                tma4d_e(sb + st * STAGE + 16384, &P.tm[M_AX], col + 64, mb * 128 + rank * 16, bar);
                bulk_g2s_e(sb + st * STAGE + 32768, P.Dskip + col, 256, bar);
                pipe_next(p);
            }
        }
    }
}

__device__ __forceinline__ uint32_t fresh_ctaid() { uint32_t t; asm volatile("mov.u32 %0, %%ctaid.x;" : "=r"(t)); return t; }
__device__ __forceinline__ void reset_state(const Params& P, Cons& c, Pend& d, uint32_t sb, bool resumed) {
    const uint32_t t = fresh_tid(), b = fresh_ctaid() + P.cta0;
    const int w = __shfl_sync(0xffffffffu, t >> 5, 0);
    c.sb = sb; c.wg = w >> 2; c.wq = w & 3; c.lane = t & 31;
    c.rank = __shfl_sync(0xffffffffu, b & 1, 0); c.pair = __shfl_sync(0xffffffffu, b >> 1, 0);
    c.rel = mapa(sb + B_EMPTY, cluster_rank() ^ (c.lane & 1));
    c.atag = (ld_acquire(&g_cnt(C_EPOCH)) + 1) & 1;
    c.p.stage = 0; c.p.phase = 0;
    c.nst = resumed && c.pair < NCHAIN;
    d = Pend{};
}
#define PROF_ITEM(i, item)

__global__ void __launch_bounds__(384, 1) fused_kernel(const __grid_constant__ Params P) {
    extern __shared__ __align__(1024) uint8_t smem[];
    const uint32_t sb = smem_u32(smem);
    asm volatile("griddepcontrol.launch_dependents;");
    declare_fence(P.zero);
    const int tid = threadIdx.x, lane = tid & 31;
    const int warp = __shfl_sync(0xffffffffu, tid >> 5, 0);
    const int cta = __shfl_sync(0xffffffffu, blockIdx.x + P.cta0, 0), pair = cta >> 1, rank = cta & 1;
    if (tid == 0) {
        if (sb & 1023) spin_fault();
        for (int i = 0; i < NSTAGE; i++) { mbar_init(sb + B_FULL + i * 8, 1); mbar_init(sb + B_EMPTY + i * 8, 16); }
        mbar_init(sb + B_RESUME, 2);
        mbar_init(sb + B_KVFULL, 1);
        mbar_init(sb + B_GO, 3); mbar_init(sb + B_RED, 8); mbar_init(sb + B_P1, 1); mbar_init(sb + B_PERS, 8); mbar_init(sb + B_INIT, 8); mbar_init(sb + B_INIT2, 8);
        mbar_init(sb + B_READY, 8);
        for (int i = 0; i < 2; i++) { mbar_init(sb + B_SFULL + i * 8, 4); mbar_init(sb + B_SFREE + i * 8, 1); }
        mbar_init(sb + B_RELM, cta % 3 ? 1 : 2); mbar_init(sb + B_X, 9);
        asm volatile("fence.mbarrier_init.release.cluster;" ::: "memory");
        mbar_expect(sb + B_X, 4096);
        sts64(sb + S_EV, 0, 0); sts32(sb + S_RETRY, 0);
    }
    cluster_sync();
    if (warp >= 8) {
        asm volatile("setmaxnreg.dec.sync.aligned.u32 24;");
        if (warp == 8) {
            producer(P, sb, cta, __shfl_sync(0xffffffffu, ld_acquire(&g_cnt(C_EPOCH)), 0));
            asm volatile("barrier.cluster.arrive.relaxed.aligned;\nbarrier.cluster.wait.aligned;" ::: "memory");
        } else if (warp == 9) {
            for (int i = 0; i < P.pd; i++) __nanosleep(1000);
            if (pair < 64) l2_prefetch((const char*)(rank ? P.Wo : P.Wq) + (size_t)(pair * 32 + lane) * 4096, 4096);
            if (pair < NCHAIN) pacer(P, sb, cta, lane, __shfl_sync(0xffffffffu, ld_acquire(&g_cnt(C_EPOCH)), 0));
        } else {
            store_warp(P, sb, warp - 10, cta);
        }
    } else {
        asm volatile("setmaxnreg.inc.sync.aligned.u32 240;");
        Cons c;
        Pend d;
        if (pair < NCHAIN) {
            reset_state(P, c, d, sb, false);
            {
                const int item = ITEM(ITEM_OFF(pair));
                PROF_ITEM(0, item)
                float acc[128];
                mainloop<true>(acc, P, c, d, T_KV, 16);
                ISTAMP(4)
                mbar_wait(sb + B_EMPTY + warp * 20480 / STAGE * 8, 1);
                mbar_wait(sb + B_EMPTY + (warp * 20480 + 20479) / STAGE * 8, 1);
                chain_load(P, sb, cta, warp, lane, 0);
                epi_kv(acc, c, d, (item >> 5) & 7, item & 31);
            }
            ISTAMP(9)
            mbar_wait(sb + B_EMPTY + 3 * 8, 1);
            drain_both(c, d);
            ISTAMP(10)
            uint32_t wr[40][4];
            chain_fetch(P, sb, cta, warp, lane, wr);
            PROF_ITEM(1, T_CHAIN << 8)
            chain_bounds(sb, cta, warp, lane, wr);
            ISTAMP(11)
            const uint32_t epoch = __shfl_sync(0xffffffffu, ld_acquire(&g_cnt(C_EPOCH)), 0);
            if (warp < 4) chain_role<false>(P, sb, cta, warp, lane, epoch, wr);
            else chain_role<true>(P, sb, cta, warp, lane, epoch, wr);
            fence_async_smem();
            bar_sync(1, 256);
            const uint32_t t2 = fresh_tid();
            if (t2 < 2) mbar_arrive_cluster(mapa(sb + B_RESUME, cluster_rank() ^ t2));
        } else if (pair >= NPAIR - 2) {
            const int ch = (pair - (NPAIR - 2)) * 512 + rank * 256 + tid;
            g_coef[ch] = ssm_coef(__bfloat162float(P.Lre[ch]), __bfloat162float(P.Lim[ch]), __bfloat162float(P.logdt[ch]));
            bar_sync(1, 256);
            if (tid == 0) red_release(&g_cnt(C_COEF));
        }
        reset_state(P, c, d, sb, true);
        bool urgent = false;
        for (int it = ITEM_OFF(c.pair) + (c.pair < NCHAIN ? 2 : 0);; it++) {
            const bool last = it == ITEM_OFF(c.pair + 1);
            const int item = ITEM(it), kind = (item >> 8) & 7, mb = (item >> 5) & 7;
            const int half = kind >= T_OPH, type = half ? kind * 2 - 10 : kind, nb = item & (half ? 3 : 31);
            const bool idle = half && (item >> 2 & 1) != c.wg;
            if (d.kind != PEND_NONE && (last || urgent || idle || !bar_and(5 + c.wg, mbar_try(sb + B_FULL + c.p.stage * 8, c.p.phase)))) {
#pragma unroll 1
                while (d.kind != PEND_NONE) drain(P, c, d);
            }
            if (last) break;
            const int nk = type == T_OP ? 64 : type == T_A2 ? 32 : 16;
            PROF_ITEM(it - ITEM_OFF(c.pair), item)
            urgent = item & URGENT;
            if (idle) {
#pragma unroll 1
                for (int kt = nk + (type == T_A2 ? 2 : 0); kt > 0; kt--) { wait_full(c); release(c, c.p.stage); pipe_next(c.p); }
                continue;
            }
            float acc[128];
            mainloop(acc, P, c, d, type, nk);
            if (type == T_KV) epi_kv(acc, c, d, mb, nb);
            else if (type == T_QA) epi_qa(acc, c, d, mb, nb);
            else if (type == T_OP) epi_op(acc, c, d, mb, nb);
            else if (type == T_A1) epi_a1(acc, P, c, d, mb, nb, c.atag);
            else epi_a2(acc, P, c, mb, nb * 256);
        }
        staging_wait(c);
        staging_post(c, PEND_NONE, 0, 0, 0);
        cluster_sync();
        if (c.wg == 0 && c.wq == 0 && c.lane == 0 && atomicInc(&g_cnt(C_DONE), NPAIR * 2 - 1) == NPAIR * 2 - 1) { __threadfence(); atomicAdd(&g_cnt(C_EPOCH), 1); }
    }
}

typedef CUresult (*EncodeFn)(CUtensorMap*, CUtensorMapDataType, cuuint32_t, void*, const cuuint64_t*, const cuuint64_t*, const cuuint32_t*, const cuuint32_t*,
                             CUtensorMapInterleave, CUtensorMapSwizzle, CUtensorMapL2promotion, CUtensorMapFloatOOBfill);
void encode(EncodeFn fn, CUtensorMap* m, const void* base, int rank, const uint64_t* dims, const uint64_t* strides, const uint32_t* box, CUtensorMapSwizzle swz = CU_TENSOR_MAP_SWIZZLE_128B) {
    cuuint64_t d[5], s[5]; cuuint32_t b[5], e[5];
    for (int i = 0; i < rank; i++) { d[i] = dims[i]; b[i] = box[i]; e[i] = 1; if (i) s[i - 1] = strides[i - 1]; }
    fn(m, CU_TENSOR_MAP_DATA_TYPE_BFLOAT16, rank, (void*)base, d, s, b, e, CU_TENSOR_MAP_INTERLEAVE_NONE, swz,
       CU_TENSOR_MAP_L2_PROMOTION_L2_256B, CU_TENSOR_MAP_FLOAT_OOB_FILL_NONE);
}
void map_kmajor(EncodeFn fn, CUtensorMap* m, const void* base, uint64_t rows, uint64_t cols, uint32_t box_rows) {
    const uint64_t d[2] = {cols, rows}, s[1] = {cols * 2}; const uint32_t b[2] = {64, box_rows};
    encode(fn, m, base, 2, d, s, b);
}
void map_mnmajor(EncodeFn fn, CUtensorMap* m, const void* base, uint64_t krows, uint64_t cols, uint32_t groups = 2) {
    const uint64_t d[3] = {64, krows, cols / 64}, s[2] = {cols * 2, 128}; const uint32_t b[3] = {64, 64, groups};
    encode(fn, m, base, 3, d, s, b);
}

}

extern "C" void kernel_launch(void* const* d_in, const int* in_sizes, int n_in, void* d_out, int out_size) {
    static Params P;
    static EncodeFn fn = nullptr;
    if (!fn) {
        cudaDriverEntryPointQueryResult q;
        cudaGetDriverEntryPoint("cuTensorMapEncodeTiled", (void**)&fn, cudaEnableDefault, &q);
        cudaFuncSetAttribute(fused_kernel, cudaFuncAttributeMaxDynamicSharedMemorySize, S_TOTAL);
    }
    const bf16* in[15];
    for (int i = 0; i < 15; i++) in[i] = (const bf16*)d_in[i];
    void *kvo, *ht;
    cudaGetSymbolAddress(&kvo, g_kvo);
    cudaGetSymbolAddress(&ht, g_ht);
    map_kmajor(fn, &P.tm[M_BX], in[9], 2048, 1024, 128);
    map_mnmajor(fn, &P.tm[M_WQ], in[11], 1024, 4096);
    map_mnmajor(fn, &P.tm[M_WK], in[12], 1024, 4096);
    map_mnmajor(fn, &P.tm[M_WV], in[13], 1024, 4096);
    map_mnmajor(fn, &P.tm[M_WO], in[14], 4096, 1024);
    map_kmajor(fn, &P.tm[M_OA], kvo, 3 * 2048, 4096, 128);
    P.swap_ri = in[4] < in[3];
    {
        const bf16* lo = P.swap_ri ? in[4] : in[3];
        const uint64_t diff = (uint64_t)((const char*)(P.swap_ri ? in[3] : in[4]) - (const char*)lo);
        const uint64_t d[4] = {1024, 8, 2, 128}, s[3] = {2048, diff, 16384}; const uint32_t b[4] = {64, 8, 2, 8};
        encode(fn, &P.tm[M_AB], lo, 4, d, s, b);
    }
    {
        const uint64_t d[4] = {1024, 2, 4, 1024}, s[3] = {2048, 64 * 2048, 4096}; const uint32_t b[4] = {64, 2, 4, 16};
        encode(fn, &P.tm[M_AX], in[0], 4, d, s, b);
    }
    map_mnmajor(fn, &P.tm[M_HT], ht, 2048, 2048);
    map_kmajor(fn, &P.tm[M_CRE], in[5], 1024, 1024, 128);
    map_kmajor(fn, &P.tm[M_CIM], in[6], 1024, 1024, 128);
    map_kmajor(fn, &P.tm[M_KVO], kvo, 3 * 2048, 4096, 32);
    map_kmajor(fn, &P.tm[M_HTS], ht, 2048, 2048, 32);
    map_kmajor(fn, &P.tm[M_OAH], kvo, 3 * 2048, 4096, 64);
    map_mnmajor(fn, &P.tm[M_HTH], ht, 2048, 2048, 1);
    for (int i = 0; i < 3; i++) {
        const uint64_t d[3] = {64, 1024, 64}, s[2] = {8192, 128}; const uint32_t b[3] = {64, 16, 2};
        encode(fn, &P.tm[M_C1 + i], in[11 + i], 3, d, s, b);
    }
    {
        const uint64_t d[2] = {1024, 4096}, s[1] = {2048}; const uint32_t b[2] = {32, 32};
        encode(fn, &P.tm[M_CO], in[14], 2, d, s, b, CU_TENSOR_MAP_SWIZZLE_64B);
    }
    {
        const uint64_t d[3] = {64, 3 * 2048, 64}, s[2] = {8192, 128}; const uint32_t b[3] = {64, 32, 2};
        encode(fn, &P.tm[M_SEG], kvo, 3, d, s, b);
    }
    void* xs;
    cudaGetSymbolAddress(&xs, g_x);
    P.xb = (uint8_t*)(((uintptr_t)xs + (2u << 20) - 1) & ~(uintptr_t)((2u << 20) - 1));
    P.Wq = in[11]; P.Wk = in[12]; P.Wv = in[13]; P.Wo = in[14]; P.mem0 = in[10]; P.Bx = in[9];
    P.Ax = in[0]; P.Lre = in[1]; P.Lim = in[2]; P.logdt = in[7]; P.Dskip = in[8];
    P.out = (float*)d_out;
    int pv[10] = {1300, 0, 110, 0, 330, 0, 32, 32, 6, 0};
    P.dly = pv[0]; P.mrg = pv[2];
    P.rd = pv[4]; P.guard = pv[5]; P.clampv = pv[6]; P.clamp0 = pv[7]; P.kvd = pv[9]; P.xd = pv[8]; P.pd = pv[1];
    cudaLaunchConfig_t cfg = {};
    cudaLaunchAttribute at[2];
    cfg.blockDim = dim3(384); cfg.dynamicSmemBytes = S_TOTAL; cfg.stream = cudaStreamPerThread; cfg.attrs = at;
    at[0].id = cudaLaunchAttributeClusterDimension;
    at[0].val.clusterDim.y = at[0].val.clusterDim.z = 1;
    at[1].id = cudaLaunchAttributeProgrammaticStreamSerialization;
    at[1].val.programmaticStreamSerializationAllowed = 1;
    for (int i = 0; i < 2; i++) {
        P.cta0 = i ? 2 * NCHAIN : 0;
        cfg.gridDim = dim3(i ? 2 * (NPAIR - NCHAIN) : 2 * NCHAIN);
        at[0].val.clusterDim.x = i ? 2 : 6;
        cfg.numAttrs = 1 + i;
        cudaLaunchKernelEx(&cfg, fused_kernel, P);
    }
}
```

```cpp
#include <cuda_runtime.h>
#include <cuda_bf16.h>
#include <cuda.h>
#include <stdint.h>
#include <string.h>

typedef __nv_bfloat16 bf16;

namespace {

constexpr int SPIN_LIMIT = 1 << 22;
#define POLLNS 100
constexpr int NPAIR = 66;
constexpr int NCHAIN = 48;
enum { T_KV = 0, T_QA = 1, T_OP = 2, T_A1 = 3, T_A2 = 4, T_CHAIN = 5, T_OPH = 6, T_A2H = 7 };
constexpr int URGENT = 2048;
enum { M_BX = 0, M_WQ, M_WK, M_WV, M_WO, M_OA, M_AB, M_AX, M_HT, M_CRE, M_CIM, M_KVO, M_HTS, M_OAH, M_HTH, M_C1, M_CO = M_C1 + 3, M_SEG, M_COUNT };
enum { C_KV = 0, C_O = 8, C_HT = 16, C_DONE = 24, C_EPOCH = 25, C_COEF = 26, C_XMAX = 27, C_XCNT = 28, C_FLAG = 32 };

struct Params {
    CUtensorMap tm[M_COUNT];
    const bf16 *Wq, *Wk, *Wv, *Wo, *mem0, *Bx, *Ax, *Lre, *Lim, *logdt, *Dskip;
    float* out;
    uint8_t* xb;
    int swap_ri, zero;
    int dly, mrg, rd, guard, clampv, clamp0, kvd, xd, pd;
    uint64_t pol[8];
    uint16_t cta0;
};

__constant__ uint16_t c_off[67] = {0, 5, 10, 15, 20, 25, 30, 35, 40, 45, 50, 55, 60, 65, 70, 75, 80, 85, 90, 95, 100, 105, 110, 115, 120, 125, 130, 135, 140, 145, 150, 155, 160, 165, 170, 175, 180, 185, 190, 195, 200, 205, 210, 214, 218, 222, 226, 230, 234, 253, 272, 291, 310, 329, 348, 367, 386, 405, 424, 443, 462, 481, 500, 519, 537, 556, 574};
__constant__ uint16_t c_items[640] = {
    0, 1280, 2497, 3008, 1728, 16, 1280, 2498, 3009, 1732, 32, 1280, 2499, 3010, 1729, 1, 1280, 2500, 3011, 1733, 17, 1280, 2501, 3012,
    1730, 33, 1280, 2502, 3013, 1734, 2, 1280, 2503, 3014, 1731, 18, 1280, 2504, 3015, 1735, 34, 1280, 2505, 3040, 1760, 3, 1280, 2506,
    3041, 1764, 19, 1280, 2507, 3042, 1761, 35, 1280, 2508, 3043, 1765, 4, 1280, 2509, 3044, 1762, 20, 1280, 2510, 3045, 1766, 36, 1280,
    2511, 3046, 1763, 5, 1280, 2528, 3047, 1767, 21, 1280, 2529, 838, 1024, 37, 1280, 2530, 839, 1025, 6, 1280, 2531, 2912, 1026, 22,
    1280, 2532, 2913, 1027, 38, 1280, 2533, 2914, 1056, 7, 1280, 2534, 2915, 1057, 23, 1280, 2535, 2916, 1058, 39, 1280, 2536, 2917, 1059,
    8, 1280, 2537, 2918, 1088, 24, 1280, 2538, 2919, 1089, 40, 1280, 2539, 2944, 1090, 9, 1280, 2540, 2945, 1091, 25, 1280, 2541, 2946,
    1120, 41, 1280, 2542, 2947, 1121, 10, 1280, 2543, 2948, 1122, 26, 1280, 773, 2949, 1123, 42, 1280, 774, 2950, 1152, 11, 1280, 775,
    2951, 1153, 27, 1280, 800, 2976, 1154, 43, 1280, 801, 2977, 1155, 12, 1280, 802, 2978, 1184, 28, 1280, 803, 2979, 1185, 44, 1280,
    804, 2980, 1186, 13, 1280, 805, 2981, 1187, 29, 1280, 806, 2982, 1216, 45, 1280, 807, 2983, 1217, 14, 1280, 837, 642, 30, 1280,
    836, 643, 46, 1280, 835, 672, 15, 1280, 834, 673, 31, 1280, 833, 674, 47, 1280, 832, 675, 48, 66, 84, 102, 256, 124,
    142, 160, 175, 191, 207, 224, 239, 298, 332, 366, 416, 769, 610, 49, 67, 85, 103, 257, 125, 143, 161, 176, 192, 208,
    225, 240, 299, 333, 367, 417, 770, 611, 50, 68, 86, 104, 258, 126, 144, 162, 177, 193, 209, 226, 241, 300, 334, 384,
    418, 771, 640, 51, 69, 87, 105, 259, 127, 145, 163, 178, 194, 210, 227, 242, 301, 335, 385, 419, 772, 641, 52, 70,
    88, 106, 260, 128, 146, 164, 179, 195, 211, 228, 243, 302, 352, 386, 420, 512, 1986, 53, 71, 89, 107, 261, 129, 147,
    165, 180, 196, 212, 229, 244, 303, 353, 387, 421, 513, 1990, 54, 72, 90, 108, 262, 130, 148, 166, 181, 197, 213, 230,
    245, 320, 354, 388, 422, 514, 1987, 55, 73, 91, 109, 263, 131, 149, 167, 182, 198, 214, 231, 246, 321, 355, 389, 423,
    515, 1991, 56, 74, 92, 110, 264, 132, 150, 168, 183, 199, 215, 232, 247, 322, 356, 390, 424, 544, 2016, 57, 75, 93,
    111, 265, 133, 151, 169, 184, 200, 216, 233, 248, 323, 357, 391, 425, 545, 2020, 58, 76, 94, 112, 266, 134, 152, 170,
    185, 201, 217, 234, 249, 324, 358, 392, 426, 546, 2017, 59, 77, 95, 113, 267, 135, 153, 171, 186, 202, 218, 235, 250,
    325, 359, 393, 427, 547, 2021, 60, 78, 96, 114, 268, 136, 154, 172, 187, 203, 219, 236, 251, 326, 360, 394, 428, 576,
    2018, 61, 79, 97, 115, 269, 137, 155, 173, 188, 204, 220, 237, 252, 327, 361, 395, 429, 577, 2022, 62, 80, 98, 116,
    270, 138, 156, 174, 189, 205, 221, 238, 253, 328, 362, 396, 430, 578, 2019, 63, 81, 99, 117, 271, 139, 157, 288, 190,
    292, 293, 296, 297, 331, 365, 399, 768, 609, 64, 82, 100, 118, 120, 122, 140, 158, 289, 206, 222, 294, 254, 329, 363,
    397, 431, 579, 2023, 65, 83, 101, 119, 121, 123, 141, 159, 290, 291, 223, 295, 255, 330, 364, 398, 2496, 608,
};
#define ITEM_OFF(p) c_off[p]
#define ITEM(i) c_items[i]

__device__ __align__(1024) bf16 g_kvo[3 * 2048 * 4096];
__device__ __align__(1024) bf16 g_ht[2048 * 2048];
__device__ __align__(1024) uint8_t g_x[4 << 20];
__device__ __align__(1024) uint32_t g_km[64 * 32 * 512];
__device__ __align__(1024) uint32_t g_vmt[64 * 32 * 512];
__device__ __align__(1024) float2 g_agg[8 * 1024];
__device__ __align__(1024) float4 g_coef[1024];
__device__ __align__(1024) uint32_t g_cntl[128 * 32];
#define g_cnt(i) g_cntl[(i) * 32]
__device__ __align__(1024) uint32_t g_hint[96 * 32];
#define PROF(i)
#define PROFDUMP()
#define PROFP(i)
constexpr int XG_SIDE = 65536, XG_T = 98304;
__device__ __forceinline__ uint32_t xg_buf(int b) { return (b & 1) * 128 + (b & 2) * 256 + (b & 4) * 32768; }
__device__ __forceinline__ uint32_t xg_lane(uint32_t lane) { return (lane >> 4) * 1024 + (lane & 8) * 32 + (lane & 7) * 16; }
__device__ __forceinline__ uint32_t xg_side(int b) { return XG_SIDE + (b >> 1) * 1024 + (b & 1) * 256; }

constexpr int STAGE = 49152, NSTAGE = 4;
constexpr int S_STG = NSTAGE * STAGE;
constexpr int S_BAR = S_STG + 32768;
constexpr int B_FULL = S_BAR, B_EMPTY = S_BAR + 32, B_RESUME = S_BAR + 64, B_KVFULL = S_BAR + 72, B_GO = S_BAR + 88, B_X = S_BAR + 96, B_PERS = S_BAR + 104,
              B_INIT = S_BAR + 112, B_RELM = S_BAR + 120, B_READY = S_BAR + 136, B_SFULL = S_BAR + 144, B_SFREE = S_BAR + 160, S_DESC = S_BAR + 176, B_RED = S_BAR + 216;
constexpr int S_EV = S_BAR + 80, S_EO = S_BAR + 84, B_INIT2 = S_BAR + 128, S_SC = S_BAR + 208, S_ISC = S_EV;
constexpr int S_XV = S_BAR + 256, S_LOG = S_XV + 2048;
constexpr int S_TOTAL = S_LOG + 768;
#define NRA 5
#define NRB 3
constexpr int S_W1 = 0;
constexpr int S_W2 = 4 * 4096 * (16 - NRA - NRB);
constexpr int S_KV = 188416;
constexpr int S_P1 = S_KV + 16384;
constexpr int S_X = S_P1 + 16384;
constexpr int S_SX = S_P1, S_OX = S_P1 + 2048;
constexpr int S_EM = S_X + 4096, S_TO = S_EM + 1024, S_RETRY = S_BAR + 224, B_P1 = S_BAR + 232;
static_assert(S_TO + 32 <= S_BAR && S_KV % 1024 == 0 && S_TOTAL <= 232448, "chain smem layout");

template <int V> struct IC { static constexpr int value = V; };
template <int B, int E, typename F> __device__ __forceinline__ void static_for(F&& f) { if constexpr (B < E) { f(IC<B>{}); static_for<B + 1, E>(f); } }
__device__ __forceinline__ uint32_t cluster_rank() { uint32_t r; asm volatile("mov.u32 %0, %%cluster_ctarank;" : "=r"(r)); return r; }
__device__ __forceinline__ void spin_fault() { asm volatile("st.global.u32 [%0], 0;" ::"l"(0ull) : "memory"); }
__device__ __forceinline__ uint32_t smem_u32(const void* p) { return (uint32_t)__cvta_generic_to_shared(p); }
__device__ __forceinline__ uint32_t opq(uint32_t x, int lane) { return __shfl_sync(0xffffffffu, x, lane); }
__device__ __forceinline__ uint32_t mapa(uint32_t a, uint32_t r) { uint32_t d; asm volatile("mapa.shared::cluster.u32 %0, %1, %2;" : "=r"(d) : "r"(a), "r"(r)); return d; }
__device__ __forceinline__ void mma16816(float* d, uint32_t a0, uint32_t a1, uint32_t a2, uint32_t a3, uint32_t b0, uint32_t b1) {
    asm("mma.sync.aligned.m16n8k16.row.col.f32.bf16.bf16.f32 {%0,%1,%2,%3}, {%4,%5,%6,%7}, {%8,%9}, {%0,%1,%2,%3};"
        : "+f"(d[0]), "+f"(d[1]), "+f"(d[2]), "+f"(d[3]) : "r"(a0), "r"(a1), "r"(a2), "r"(a3), "r"(b0), "r"(b1));
}
__device__ __forceinline__ void mma1688(float* d, uint32_t a0, uint32_t a1, uint32_t b0) {
    asm("mma.sync.aligned.m16n8k8.row.col.f32.bf16.bf16.f32 {%0,%1,%2,%3}, {%4,%5}, {%6}, {%0,%1,%2,%3};"
        : "+f"(d[0]), "+f"(d[1]), "+f"(d[2]), "+f"(d[3]) : "r"(a0), "r"(a1), "r"(b0));
}
__device__ __forceinline__ void ldsm4(uint32_t* r, uint32_t a) {
    asm volatile("ldmatrix.sync.aligned.m8n8.x4.shared.b16 {%0,%1,%2,%3}, [%4];" : "=r"(r[0]), "=r"(r[1]), "=r"(r[2]), "=r"(r[3]) : "r"(a));
}
__device__ __forceinline__ void ldsm4t(uint32_t* r, uint32_t a) {
    asm volatile("ldmatrix.sync.aligned.m8n8.x4.trans.shared.b16 {%0,%1,%2,%3}, [%4];" : "=r"(r[0]), "=r"(r[1]), "=r"(r[2]), "=r"(r[3]) : "r"(a));
}
__device__ __forceinline__ void stsm4(uint32_t a, uint32_t r0, uint32_t r1, uint32_t r2, uint32_t r3) {
    asm volatile("stmatrix.sync.aligned.m8n8.x4.shared.b16 [%0], {%1,%2,%3,%4};" ::"r"(a), "r"(r0), "r"(r1), "r"(r2), "r"(r3) : "memory");
}
__device__ __forceinline__ void stsm4t(uint32_t a, uint32_t r0, uint32_t r1, uint32_t r2, uint32_t r3) {
    asm volatile("stmatrix.sync.aligned.m8n8.x4.trans.shared.b16 [%0], {%1,%2,%3,%4};" ::"r"(a), "r"(r0), "r"(r1), "r"(r2), "r"(r3) : "memory");
}
__device__ __forceinline__ uint32_t movm(uint32_t a) { uint32_t d; asm volatile("movmatrix.sync.aligned.m8n8.trans.b16 %0, %1;" : "=r"(d) : "r"(a)); return d; }
__device__ __forceinline__ uint32_t pack2(float lo, float hi) { uint32_t d; asm("cvt.rn.bf16x2.f32 %0, %1, %2;" : "=r"(d) : "f"(hi), "f"(lo)); return d; }
__device__ __forceinline__ uint32_t prmt(uint32_t a, uint32_t b, uint32_t s) { uint32_t d; asm("prmt.b32 %0, %1, %2, %3;" : "=r"(d) : "r"(a), "r"(b), "r"(s)); return d; }
__device__ __forceinline__ uint32_t pack2h(float lo, float hi) { uint32_t d; asm("cvt.rn.f16x2.f32 %0, %1, %2;" : "=r"(d) : "f"(hi), "f"(lo)); return d; }
__device__ __forceinline__ uint32_t h2bf(uint32_t a, uint32_t b) {
    uint32_t d;
    asm("{\n.reg .b16 l, h, u;\n.reg .f32 x, y;\nmov.b32 {l, u}, %1;\ncvt.f32.f16 x, l;\nmov.b32 {u, h}, %2;\ncvt.f32.f16 y, h;\ncvt.rn.bf16x2.f32 %0, y, x;\n}" : "=r"(d) : "r"(a), "r"(b));
    return d;
}
__device__ __forceinline__ void cvt_block(uint32_t* u, uint32_t& x, uint32_t sel) {
    const uint32_t a = prmt(u[0], u[0], sel), b = prmt(u[1], u[1], sel), c = prmt(u[2], u[2], sel), d = prmt(u[3], x, sel);
    x ^= u[3] ^ d;
    u[0] = h2bf(a, a); u[1] = h2bf(b, b); u[2] = h2bf(c, c); u[3] = h2bf(d, d);
}
__device__ __forceinline__ uint32_t amax(uint32_t a, uint32_t b) { uint32_t d; asm("max.xorsign.abs.bf16x2 %0, %1, %2;" : "=r"(d) : "r"(a), "r"(b)); return d; }
__device__ __forceinline__ uint32_t amax4(uint32_t m, const uint32_t* v) { return amax(amax(m, amax(v[0], v[1])), amax(v[2], v[3])); }
__device__ __forceinline__ uint32_t warp_exp(uint32_t m) { return __reduce_max_sync(0xffffffffu, max(m & 0x7f80u, (m >> 16) & 0x7f80u)) >> 7; }
__device__ __forceinline__ void red_max_shared(uint32_t a, uint32_t x) { asm volatile("red.shared.max.u32 [%0], %1;" ::"r"(a), "r"(x) : "memory"); }
__device__ __forceinline__ uint32_t mul_bf2(uint32_t a, uint32_t b) { uint32_t d; asm("mul.rn.bf16x2 %0, %1, %2;" : "=r"(d) : "r"(a), "r"(b)); return d; }
__device__ __forceinline__ float bf_lo(uint32_t u) { return __uint_as_float(u << 16); }
__device__ __forceinline__ float bf_hi(uint32_t u) { return __uint_as_float(u & 0xffff0000u); }
__device__ __forceinline__ float ex2(float x) { float y; asm("ex2.approx.ftz.f32 %0, %1;" : "=f"(y) : "f"(x)); return y; }
__device__ __forceinline__ float rcp(float x) { float y; asm("rcp.approx.ftz.f32 %0, %1;" : "=f"(y) : "f"(x)); return y; }
__device__ __forceinline__ void st_relaxed4(const void* p, uint32_t a, uint32_t b, uint32_t c, uint32_t d) {
    asm volatile("{\n.reg .b128 t;\nmov.b128 t, {%1,%2,%3,%4};\nst.relaxed.gpu.global.b128 [%0], t;\n}" ::"l"(p), "r"(a), "r"(b), "r"(c), "r"(d) : "memory");
}
__device__ __forceinline__ void st_relaxed2(const void* p, uint32_t a, uint32_t b) {
    asm volatile("{\n.reg .b64 t;\nmov.b64 t, {%1,%2};\nst.relaxed.gpu.global.b64 [%0], t;\n}" ::"l"(p), "r"(a), "r"(b) : "memory");
}
__device__ __forceinline__ void ld_relaxed2_if(uint32_t& a, uint32_t& b, const void* p, bool on) {
    asm volatile("{\n.reg .pred P;\n.reg .b64 t;\nsetp.ne.u32 P, %3, 0;\nmov.b64 t, {%0,%1};\n@P ld.relaxed.gpu.global.b64 t, [%2];\nmov.b64 {%0,%1}, t;\n}" : "+r"(a), "+r"(b) : "l"(p), "r"((uint32_t)on) : "memory");
}
__device__ __forceinline__ void ld_relaxed4(uint32_t* v, const void* p) {
    asm volatile("ld.relaxed.gpu.global.L1::no_allocate.v4.b32 {%0,%1,%2,%3}, [%4];" : "=r"(v[0]), "=r"(v[1]), "=r"(v[2]), "=r"(v[3]) : "l"(p) : "memory");
}
__device__ __forceinline__ void ld_relaxed1n(uint32_t& v, const void* p) { asm volatile("ld.relaxed.gpu.global.L1::no_allocate.b32 %0, [%1];" : "=r"(v) : "l"(p) : "memory"); }
__device__ __forceinline__ void red_add4(const void* p, uint32_t a, uint32_t b, uint32_t c, uint32_t d) {
    asm volatile("red.relaxed.gpu.global.add.noftz.v4.f16x2 [%0], {%1,%2,%3,%4};" ::"l"(p), "r"(a), "r"(b), "r"(c), "r"(d) : "memory");
}
__device__ __forceinline__ void red_add1(const void* p, uint32_t a) { asm volatile("red.relaxed.gpu.global.add.noftz.f16x2 [%0], %1;" ::"l"(p), "r"(a) : "memory"); }
__device__ __forceinline__ void ld_relaxed2(uint32_t* v, const void* p) {
    asm volatile("{\n.reg .b64 t;\nld.relaxed.gpu.global.L1::no_allocate.b64 t, [%2];\nmov.b64 {%0,%1}, t;\n}" : "=r"(v[0]), "=r"(v[1]) : "l"(p) : "memory");
}
__device__ __forceinline__ uint32_t ld_relaxed1(const void* p) { uint32_t v; asm volatile("ld.relaxed.gpu.global.u32 %0, [%1];" : "=r"(v) : "l"(p) : "memory"); return v; }
__device__ __forceinline__ void st_relaxed1(const void* p, uint32_t v) { asm volatile("st.relaxed.gpu.global.u32 [%0], %1;" ::"l"(p), "r"(v) : "memory"); }
__device__ __forceinline__ uint32_t ld_acquire(const void* p) { uint32_t v; asm volatile("ld.acquire.gpu.global.u32 %0, [%1];" : "=r"(v) : "l"(p) : "memory"); return v; }
__device__ __forceinline__ void red_relaxed(void* p) { asm volatile("red.relaxed.gpu.global.add.u32 [%0], 1;" ::"l"(p) : "memory"); }
__device__ __forceinline__ void red_release(void* p) { asm volatile("red.release.gpu.global.add.u32 [%0], 1;" ::"l"(p) : "memory"); }
__device__ __forceinline__ void st_stream2(float* p, float a, float b) { asm volatile("st.global.cs.v2.f32 [%0], {%1, %2};" ::"l"(p), "f"(a), "f"(b) : "memory"); }
__device__ __forceinline__ void fence_async() { asm volatile("fence.proxy.async.global;" ::: "memory"); }
__device__ __forceinline__ void fence_async_smem() { asm volatile("fence.proxy.async.shared::cta;" ::: "memory"); }
__device__ __forceinline__ void wait_count(const uint32_t* p, uint32_t target) {
    int n = 0;
    while ((int32_t)(ld_acquire(p) - target) < 0) { __nanosleep(POLLNS); if (++n > SPIN_LIMIT) spin_fault(); }
}
__device__ __forceinline__ void bar_sync(int id, int n) { asm volatile("bar.sync %0, %1;" ::"r"(id), "r"(n) : "memory"); }
__device__ __forceinline__ bool bar_and(int id, bool v) {
    uint32_t r;
    asm volatile("{\n.reg .pred P, Q;\nsetp.ne.u32 Q, %2, 0;\nbar.red.and.pred P, %1, 128, Q;\nselp.u32 %0, 1, 0, P;\n}" : "=r"(r) : "r"(id), "r"((uint32_t)v) : "memory");
    return r;
}
__device__ __forceinline__ void bar_arrive(int id, int n) { asm volatile("bar.arrive %0, %1;" ::"r"(id), "r"(n) : "memory"); }
__device__ __forceinline__ void lds128(uint32_t* v, uint32_t a) { asm volatile("ld.shared.v4.b32 {%0,%1,%2,%3}, [%4];" : "=r"(v[0]), "=r"(v[1]), "=r"(v[2]), "=r"(v[3]) : "r"(a) : "memory"); }
__device__ __forceinline__ uint32_t lds32(uint32_t a) { uint32_t v; asm volatile("ld.shared.b32 %0, [%1];" : "=r"(v) : "r"(a) : "memory"); return v; }
__device__ __forceinline__ void lds64(uint32_t* v, uint32_t a) { asm volatile("ld.shared.v2.b32 {%0,%1}, [%2];" : "=r"(v[0]), "=r"(v[1]) : "r"(a) : "memory"); }
__device__ __forceinline__ void lds64f(float* v, uint32_t a) { asm volatile("ld.shared.v2.f32 {%0,%1}, [%2];" : "=f"(v[0]), "=f"(v[1]) : "r"(a) : "memory"); }
__device__ __forceinline__ void sts128(uint32_t a, const uint32_t* v) { asm volatile("st.shared.v4.b32 [%0], {%1,%2,%3,%4};" ::"r"(a), "r"(v[0]), "r"(v[1]), "r"(v[2]), "r"(v[3]) : "memory"); }
__device__ __forceinline__ void sts64(uint32_t a, uint32_t x, uint32_t y) { asm volatile("st.shared.v2.b32 [%0], {%1,%2};" ::"r"(a), "r"(x), "r"(y) : "memory"); }
__device__ __forceinline__ void sts32(uint32_t a, uint32_t x) { asm volatile("st.shared.b32 [%0], %1;" ::"r"(a), "r"(x) : "memory"); }
__device__ __forceinline__ bool mbar_try(uint32_t b, uint32_t par) {
    uint32_t ok;
    asm volatile("{\n.reg .pred P;\nmbarrier.test_wait.parity.shared::cta.b64 P, [%1], %2;\nselp.u32 %0, 1, 0, P;\n}" : "=r"(ok) : "r"(b), "r"(par) : "memory");
    return ok;
}
__device__ __forceinline__ void mbar_wait(uint32_t b, uint32_t par) {
    asm volatile("{\n.reg .pred P, Q;\n.reg .u32 n;\nmov.u32 n, %2;\nW: mbarrier.try_wait.parity.shared::cta.b64 P, [%0], %1;\n"
                 "add.u32 n, n, -1;\nsetp.eq.u32 Q, n, 0;\n@Q st.global.u32 [%3], 0;\n@!P bra W;\n}" ::"r"(b), "r"(par), "n"(SPIN_LIMIT), "l"(0ull) : "memory");
}
__device__ __forceinline__ void mbar_wait_fast(uint32_t b, uint32_t par) {
    asm volatile("{\n.reg .pred P, Q;\n.reg .u32 n;\nmbarrier.try_wait.parity.shared::cta.b64 P, [%0], %1;\n@P bra D;\nmov.u32 n, %2;\nW: mbarrier.try_wait.parity.shared::cta.b64 P, [%0], %1;\n"
                 "add.u32 n, n, -1;\nsetp.eq.u32 Q, n, 0;\n@Q st.global.u32 [%3], 0;\n@!P bra W;\nD:\n}" ::"r"(b), "r"(par), "n"(SPIN_LIMIT), "l"(0ull) : "memory");
}
__device__ __forceinline__ void declare_fence(int zero) { asm volatile(".reg .pred PNEVER;\nsetp.ne.u32 PNEVER, %0, 0;" ::"r"(zero)); }
__device__ __forceinline__ void sched_fence() { asm volatile("{\n.reg .pred Q;\n.reg .u32 x;\n@!PNEVER bra D;\nF: ld.volatile.global.u32 x, [%0];\nsetp.ne.u32 Q, x, 0;\n@Q bra F;\nD:\n}" ::"l"(0ull) : "memory"); }
__device__ __forceinline__ void mbar_init(uint32_t b, uint32_t n) { asm volatile("mbarrier.init.shared::cta.b64 [%0], %1;" ::"r"(b), "r"(n) : "memory"); }
__device__ __forceinline__ void mbar_expect(uint32_t b, uint32_t bytes) { asm volatile("mbarrier.arrive.expect_tx.shared::cta.b64 _, [%0], %1;" ::"r"(b), "r"(bytes) : "memory"); }
__device__ __forceinline__ void mbar_arrive(uint32_t b) { asm volatile("mbarrier.arrive.shared::cta.b64 _, [%0];" ::"r"(b) : "memory"); }
__device__ __forceinline__ void mbar_arrive_cluster(uint32_t b) { asm volatile("mbarrier.arrive.shared::cluster.b64 _, [%0];" ::"r"(b) : "memory"); }
__device__ __forceinline__ void cluster_sync() { asm volatile("barrier.cluster.arrive.aligned;\nbarrier.cluster.wait.aligned;" ::: "memory"); }
__device__ __forceinline__ void tma2d(uint32_t dst, const CUtensorMap* m, int c0, int c1, uint32_t bar) {
    asm volatile("cp.async.bulk.tensor.2d.shared::cluster.global.mbarrier::complete_tx::bytes [%0], [%1, {%2, %3}], [%4];" ::"r"(dst), "l"(m), "r"(c0), "r"(c1), "r"(bar) : "memory");
}
__device__ __forceinline__ void tma2d_mc(uint32_t dst, const CUtensorMap* m, int c0, int c1, uint32_t bar, uint16_t mask) {
    asm volatile("cp.async.bulk.tensor.2d.shared::cluster.global.mbarrier::complete_tx::bytes.multicast::cluster [%0], [%1, {%2, %3}], [%4], %5;" ::"r"(dst), "l"(m), "r"(c0), "r"(c1), "r"(bar), "h"(mask) : "memory");
}
__device__ __forceinline__ void tma3d(uint32_t dst, const CUtensorMap* m, int c0, int c1, int c2, uint32_t bar) {
    asm volatile("cp.async.bulk.tensor.3d.shared::cluster.global.mbarrier::complete_tx::bytes [%0], [%1, {%2, %3, %4}], [%5];" ::"r"(dst), "l"(m), "r"(c0), "r"(c1), "r"(c2), "r"(bar) : "memory");
}
__device__ __forceinline__ void tma3d_mc(uint32_t dst, const CUtensorMap* m, int c0, int c1, int c2, uint32_t bar, uint16_t mask) {
    asm volatile("cp.async.bulk.tensor.3d.shared::cluster.global.mbarrier::complete_tx::bytes.multicast::cluster [%0], [%1, {%2, %3, %4}], [%5], %6;" ::"r"(dst), "l"(m), "r"(c0), "r"(c1), "r"(c2), "r"(bar), "h"(mask) : "memory");
}
__device__ __forceinline__ void tma4d(uint32_t dst, const CUtensorMap* m, int c0, int c3, uint32_t bar) {
    asm volatile("cp.async.bulk.tensor.4d.shared::cluster.global.mbarrier::complete_tx::bytes [%0], [%1, {%2, 0, 0, %3}], [%4];" ::"r"(dst), "l"(m), "r"(c0), "r"(c3), "r"(bar) : "memory");
}
__device__ __forceinline__ void tma4d_mc(uint32_t dst, const CUtensorMap* m, int c0, int c3, uint32_t bar, uint16_t mask) {
    asm volatile("cp.async.bulk.tensor.4d.shared::cluster.global.mbarrier::complete_tx::bytes.multicast::cluster [%0], [%1, {%2, 0, 0, %3}], [%4], %5;" ::"r"(dst), "l"(m), "r"(c0), "r"(c3), "r"(bar), "h"(mask) : "memory");
}
__device__ __forceinline__ void tma_prefetch3d(const CUtensorMap* m, int c0, int c1, int c2) {
    asm volatile("cp.async.bulk.prefetch.tensor.3d.L2.global [%0, {%1, %2, %3}];" ::"l"(m), "r"(c0), "r"(c1), "r"(c2) : "memory");
}
__device__ __forceinline__ void tma_prefetch2d(const CUtensorMap* m, int c0, int c1) {
    asm volatile("cp.async.bulk.prefetch.tensor.2d.L2.global [%0, {%1, %2}];" ::"l"(m), "r"(c0), "r"(c1) : "memory");
}
__device__ __forceinline__ void l2_prefetch(const void* src, uint32_t bytes) { asm volatile("cp.async.bulk.prefetch.L2.global [%0], %1;" ::"l"(src), "r"(bytes) : "memory"); }
__device__ __forceinline__ void bulk_g2s(uint32_t dst, const void* src, uint32_t bytes, uint32_t bar) {
    asm volatile("cp.async.bulk.shared::cluster.global.mbarrier::complete_tx::bytes [%0], [%1], %2, [%3];" ::"r"(dst), "l"(src), "r"(bytes), "r"(bar) : "memory");
}
__device__ __forceinline__ void mbar_expect_e(uint32_t b, uint32_t bytes) {
    asm volatile("{\n.reg .pred E;\nelect.sync _|E, 0xffffffff;\n@E mbarrier.arrive.expect_tx.shared::cta.b64 _, [%0], %1;\n}" ::"r"(b), "r"(bytes) : "memory");
}
__device__ __forceinline__ void tma2d_e(uint32_t dst, const CUtensorMap* m, int c0, int c1, uint32_t bar, uint64_t pol) {
    asm volatile("{\n.reg .pred E;\nelect.sync _|E, 0xffffffff;\n@E cp.async.bulk.tensor.2d.shared::cluster.global.mbarrier::complete_tx::bytes.L2::cache_hint [%0], [%1, {%2, %3}], [%4], %5;\n}" ::"r"(dst), "l"(m), "r"(c0), "r"(c1), "r"(bar), "l"(pol) : "memory");
}
__device__ __forceinline__ void tma2d_mc_e(uint32_t dst, const CUtensorMap* m, int c0, int c1, uint32_t bar, uint16_t mask) {
    asm volatile("{\n.reg .pred E;\nelect.sync _|E, 0xffffffff;\n@E cp.async.bulk.tensor.2d.shared::cluster.global.mbarrier::complete_tx::bytes.multicast::cluster [%0], [%1, {%2, %3}], [%4], %5;\n}" ::"r"(dst), "l"(m), "r"(c0), "r"(c1), "r"(bar), "h"(mask) : "memory");
}
__device__ __forceinline__ void tma3d_e(uint32_t dst, const CUtensorMap* m, int c0, int c1, int c2, uint32_t bar, uint64_t pol) {
    asm volatile("{\n.reg .pred E;\nelect.sync _|E, 0xffffffff;\n@E cp.async.bulk.tensor.3d.shared::cluster.global.mbarrier::complete_tx::bytes.L2::cache_hint [%0], [%1, {%2, %3, %4}], [%5], %6;\n}" ::"r"(dst), "l"(m), "r"(c0), "r"(c1), "r"(c2), "r"(bar), "l"(pol) : "memory");
}
__device__ __forceinline__ void tma3d_mc_e(uint32_t dst, const CUtensorMap* m, int c0, int c1, int c2, uint32_t bar, uint16_t mask) {
    asm volatile("{\n.reg .pred E;\nelect.sync _|E, 0xffffffff;\n@E cp.async.bulk.tensor.3d.shared::cluster.global.mbarrier::complete_tx::bytes.multicast::cluster [%0], [%1, {%2, %3, %4}], [%5], %6;\n}" ::"r"(dst), "l"(m), "r"(c0), "r"(c1), "r"(c2), "r"(bar), "h"(mask) : "memory");
}
__device__ __forceinline__ void tma4d_e(uint32_t dst, const CUtensorMap* m, int c0, int c3, uint32_t bar) {
    asm volatile("{\n.reg .pred E;\nelect.sync _|E, 0xffffffff;\n@E cp.async.bulk.tensor.4d.shared::cluster.global.mbarrier::complete_tx::bytes [%0], [%1, {%2, 0, 0, %3}], [%4];\n}" ::"r"(dst), "l"(m), "r"(c0), "r"(c3), "r"(bar) : "memory");
}
__device__ __forceinline__ void tma4d_mc_e(uint32_t dst, const CUtensorMap* m, int c0, int c3, uint32_t bar, uint16_t mask) {
    asm volatile("{\n.reg .pred E;\nelect.sync _|E, 0xffffffff;\n@E cp.async.bulk.tensor.4d.shared::cluster.global.mbarrier::complete_tx::bytes.multicast::cluster [%0], [%1, {%2, 0, 0, %3}], [%4], %5;\n}" ::"r"(dst), "l"(m), "r"(c0), "r"(c3), "r"(bar), "h"(mask) : "memory");
}
__device__ __forceinline__ void tma_prefetch2d_e(const CUtensorMap* m, int c0, int c1) {
    asm volatile("{\n.reg .pred E;\nelect.sync _|E, 0xffffffff;\n@E cp.async.bulk.prefetch.tensor.2d.L2.global [%0, {%1, %2}];\n}" ::"l"(m), "r"(c0), "r"(c1) : "memory");
}
__device__ __forceinline__ void tma_prefetch3d_e(const CUtensorMap* m, int c0, int c1, int c2) {
    asm volatile("{\n.reg .pred E;\nelect.sync _|E, 0xffffffff;\n@E cp.async.bulk.prefetch.tensor.3d.L2.global [%0, {%1, %2, %3}];\n}" ::"l"(m), "r"(c0), "r"(c1), "r"(c2) : "memory");
}
__device__ __forceinline__ void l2_prefetch_e(const void* src, uint32_t bytes) {
    asm volatile("{\n.reg .pred E;\nelect.sync _|E, 0xffffffff;\n@E cp.async.bulk.prefetch.L2.global [%0], %1;\n}" ::"l"(src), "r"(bytes) : "memory");
}
__device__ __forceinline__ void bulk_g2s_e(uint32_t dst, const void* src, uint32_t bytes, uint32_t bar) {
    asm volatile("{\n.reg .pred E;\nelect.sync _|E, 0xffffffff;\n@E cp.async.bulk.shared::cluster.global.mbarrier::complete_tx::bytes [%0], [%1], %2, [%3];\n}" ::"r"(dst), "l"(src), "r"(bytes), "r"(bar) : "memory");
}
__device__ __forceinline__ bool elect_one() {
    uint32_t r;
    asm volatile("{\n.reg .pred E;\nelect.sync _|E, 0xffffffff;\nselp.u32 %0, 1, 0, E;\n}" : "=r"(r));
    return r;
}
__device__ __forceinline__ void tma_store2d(const CUtensorMap* m, int c0, int c1, uint32_t src, uint64_t pol) {
    asm volatile("cp.async.bulk.tensor.2d.global.shared::cta.bulk_group.L2::cache_hint [%0, {%1, %2}], [%3], %4;" ::"l"(m), "r"(c0), "r"(c1), "r"(src), "l"(pol) : "memory");
}
__device__ __forceinline__ void bulk_commit() { asm volatile("cp.async.bulk.commit_group;" ::: "memory"); }
__device__ __forceinline__ void bulk_wait_read() { asm volatile("cp.async.bulk.wait_group.read 0;" ::: "memory"); }
__device__ __forceinline__ void bulk_wait_all() { asm volatile("cp.async.bulk.wait_group 0;" ::: "memory"); }
__device__ __forceinline__ uint64_t mkdesc(uint32_t addr, uint32_t lbo, uint32_t sbo, uint32_t swz) {
    return (uint64_t)((addr & 0x3FFFF) >> 4) | ((uint64_t)(lbo >> 4) << 16) | ((uint64_t)(sbo >> 4) << 32) | ((uint64_t)swz << 62);
}
__device__ __forceinline__ void wg_fence() { asm volatile("wgmma.fence.sync.aligned;" ::: "memory"); }
__device__ __forceinline__ void wg_commit() { asm volatile("wgmma.commit_group.sync.aligned;" ::: "memory"); }
template <int N> __device__ __forceinline__ void wg_wait() { asm volatile("wgmma.wait_group.sync.aligned %0;" ::"n"(N) : "memory"); }
template <typename T> __device__ __forceinline__ void pin_ptr(T*& p) { asm volatile("" : "+l"(p)); }
template <int N> __device__ __forceinline__ void pin(uint32_t* d) {
#pragma unroll
    for (int i = 0; i < N; i++) asm volatile("" : "+r"(d[i])::"memory");
}
template <int N> __device__ __forceinline__ void pin(float* d) {
#pragma unroll
    for (int i = 0; i < N; i++) asm volatile("" : "+f"(d[i])::"memory");
}

template <int TA, int TB>
__device__ __forceinline__ void wgmma_ss256(float* d, uint64_t da, uint64_t db) {
    asm volatile("wgmma.mma_async.sync.aligned.m64n256k16.f32.bf16.bf16 "
        "{%0, %1, %2, %3, %4, %5, %6, %7, %8, %9, %10, %11, %12, %13, %14, %15, %16, %17, %18, %19, %20, %21, %22, %23, %24, %25, %26, %27, %28, %29, %30, %31, %32, %33, %34, %35, %36, %37, %38, %39, %40, %41, %42, %43, %44, %45, %46, %47, %48, %49, %50, %51, %52, %53, %54, %55, %56, %57, %58, %59, %60, %61, %62, %63, %64, %65, %66, %67, %68, %69, %70, %71, %72, %73, %74, %75, %76, %77, %78, %79, %80, %81, %82, %83, %84, %85, %86, %87, %88, %89, %90, %91, %92, %93, %94, %95, %96, %97, %98, %99, %100, %101, %102, %103, %104, %105, %106, %107, %108, %109, %110, %111, %112, %113, %114, %115, %116, %117, %118, %119, %120, %121, %122, %123, %124, %125, %126, %127}, %128, %129, 1, 1, 1, %130, %131;"
        : "+f"(d[0]), "+f"(d[1]), "+f"(d[2]), "+f"(d[3]), "+f"(d[4]), "+f"(d[5]), "+f"(d[6]), "+f"(d[7]), "+f"(d[8]), "+f"(d[9]), "+f"(d[10]), "+f"(d[11]), "+f"(d[12]), "+f"(d[13]), "+f"(d[14]), "+f"(d[15]), "+f"(d[16]), "+f"(d[17]), "+f"(d[18]), "+f"(d[19]), "+f"(d[20]), "+f"(d[21]), "+f"(d[22]), "+f"(d[23]), "+f"(d[24]), "+f"(d[25]), "+f"(d[26]), "+f"(d[27]), "+f"(d[28]), "+f"(d[29]), "+f"(d[30]), "+f"(d[31]), "+f"(d[32]), "+f"(d[33]), "+f"(d[34]), "+f"(d[35]), "+f"(d[36]), "+f"(d[37]), "+f"(d[38]), "+f"(d[39]), "+f"(d[40]), "+f"(d[41]), "+f"(d[42]), "+f"(d[43]), "+f"(d[44]), "+f"(d[45]), "+f"(d[46]), "+f"(d[47]), "+f"(d[48]), "+f"(d[49]), "+f"(d[50]), "+f"(d[51]), "+f"(d[52]), "+f"(d[53]), "+f"(d[54]), "+f"(d[55]), "+f"(d[56]), "+f"(d[57]), "+f"(d[58]), "+f"(d[59]), "+f"(d[60]), "+f"(d[61]), "+f"(d[62]), "+f"(d[63]), "+f"(d[64]), "+f"(d[65]), "+f"(d[66]), "+f"(d[67]), "+f"(d[68]), "+f"(d[69]), "+f"(d[70]), "+f"(d[71]), "+f"(d[72]), "+f"(d[73]), "+f"(d[74]), "+f"(d[75]), "+f"(d[76]), "+f"(d[77]), "+f"(d[78]), "+f"(d[79]), "+f"(d[80]), "+f"(d[81]), "+f"(d[82]), "+f"(d[83]), "+f"(d[84]), "+f"(d[85]), "+f"(d[86]), "+f"(d[87]), "+f"(d[88]), "+f"(d[89]), "+f"(d[90]), "+f"(d[91]), "+f"(d[92]), "+f"(d[93]), "+f"(d[94]), "+f"(d[95]), "+f"(d[96]), "+f"(d[97]), "+f"(d[98]), "+f"(d[99]), "+f"(d[100]), "+f"(d[101]), "+f"(d[102]), "+f"(d[103]), "+f"(d[104]), "+f"(d[105]), "+f"(d[106]), "+f"(d[107]), "+f"(d[108]), "+f"(d[109]), "+f"(d[110]), "+f"(d[111]), "+f"(d[112]), "+f"(d[113]), "+f"(d[114]), "+f"(d[115]), "+f"(d[116]), "+f"(d[117]), "+f"(d[118]), "+f"(d[119]), "+f"(d[120]), "+f"(d[121]), "+f"(d[122]), "+f"(d[123]), "+f"(d[124]), "+f"(d[125]), "+f"(d[126]), "+f"(d[127])
        : "l"(da), "l"(db), "n"(TA), "n"(TB));
}
template <int TA, int TB>
__device__ __forceinline__ void wgmma_ss256_first(float* d, uint64_t da, uint64_t db) {
    asm volatile("wgmma.mma_async.sync.aligned.m64n256k16.f32.bf16.bf16 "
        "{%0, %1, %2, %3, %4, %5, %6, %7, %8, %9, %10, %11, %12, %13, %14, %15, %16, %17, %18, %19, %20, %21, %22, %23, %24, %25, %26, %27, %28, %29, %30, %31, %32, %33, %34, %35, %36, %37, %38, %39, %40, %41, %42, %43, %44, %45, %46, %47, %48, %49, %50, %51, %52, %53, %54, %55, %56, %57, %58, %59, %60, %61, %62, %63, %64, %65, %66, %67, %68, %69, %70, %71, %72, %73, %74, %75, %76, %77, %78, %79, %80, %81, %82, %83, %84, %85, %86, %87, %88, %89, %90, %91, %92, %93, %94, %95, %96, %97, %98, %99, %100, %101, %102, %103, %104, %105, %106, %107, %108, %109, %110, %111, %112, %113, %114, %115, %116, %117, %118, %119, %120, %121, %122, %123, %124, %125, %126, %127}, %128, %129, 0, 1, 1, %130, %131;"
        : "=f"(d[0]), "=f"(d[1]), "=f"(d[2]), "=f"(d[3]), "=f"(d[4]), "=f"(d[5]), "=f"(d[6]), "=f"(d[7]), "=f"(d[8]), "=f"(d[9]), "=f"(d[10]), "=f"(d[11]), "=f"(d[12]), "=f"(d[13]), "=f"(d[14]), "=f"(d[15]), "=f"(d[16]), "=f"(d[17]), "=f"(d[18]), "=f"(d[19]), "=f"(d[20]), "=f"(d[21]), "=f"(d[22]), "=f"(d[23]), "=f"(d[24]), "=f"(d[25]), "=f"(d[26]), "=f"(d[27]), "=f"(d[28]), "=f"(d[29]), "=f"(d[30]), "=f"(d[31]), "=f"(d[32]), "=f"(d[33]), "=f"(d[34]), "=f"(d[35]), "=f"(d[36]), "=f"(d[37]), "=f"(d[38]), "=f"(d[39]), "=f"(d[40]), "=f"(d[41]), "=f"(d[42]), "=f"(d[43]), "=f"(d[44]), "=f"(d[45]), "=f"(d[46]), "=f"(d[47]), "=f"(d[48]), "=f"(d[49]), "=f"(d[50]), "=f"(d[51]), "=f"(d[52]), "=f"(d[53]), "=f"(d[54]), "=f"(d[55]), "=f"(d[56]), "=f"(d[57]), "=f"(d[58]), "=f"(d[59]), "=f"(d[60]), "=f"(d[61]), "=f"(d[62]), "=f"(d[63]), "=f"(d[64]), "=f"(d[65]), "=f"(d[66]), "=f"(d[67]), "=f"(d[68]), "=f"(d[69]), "=f"(d[70]), "=f"(d[71]), "=f"(d[72]), "=f"(d[73]), "=f"(d[74]), "=f"(d[75]), "=f"(d[76]), "=f"(d[77]), "=f"(d[78]), "=f"(d[79]), "=f"(d[80]), "=f"(d[81]), "=f"(d[82]), "=f"(d[83]), "=f"(d[84]), "=f"(d[85]), "=f"(d[86]), "=f"(d[87]), "=f"(d[88]), "=f"(d[89]), "=f"(d[90]), "=f"(d[91]), "=f"(d[92]), "=f"(d[93]), "=f"(d[94]), "=f"(d[95]), "=f"(d[96]), "=f"(d[97]), "=f"(d[98]), "=f"(d[99]), "=f"(d[100]), "=f"(d[101]), "=f"(d[102]), "=f"(d[103]), "=f"(d[104]), "=f"(d[105]), "=f"(d[106]), "=f"(d[107]), "=f"(d[108]), "=f"(d[109]), "=f"(d[110]), "=f"(d[111]), "=f"(d[112]), "=f"(d[113]), "=f"(d[114]), "=f"(d[115]), "=f"(d[116]), "=f"(d[117]), "=f"(d[118]), "=f"(d[119]), "=f"(d[120]), "=f"(d[121]), "=f"(d[122]), "=f"(d[123]), "=f"(d[124]), "=f"(d[125]), "=f"(d[126]), "=f"(d[127])
        : "l"(da), "l"(db), "n"(TA), "n"(TB));
}
template <int TB>
__device__ __forceinline__ void wgmma_rs128(float* d, const uint32_t* a, uint64_t db, uint32_t acc) {
    asm volatile("{\n.reg .pred P;\nsetp.ne.u32 P, %69, 0;\nwgmma.mma_async.sync.aligned.m64n128k16.f32.bf16.bf16 "
        "{%0, %1, %2, %3, %4, %5, %6, %7, %8, %9, %10, %11, %12, %13, %14, %15, %16, %17, %18, %19, %20, %21, %22, %23, %24, %25, %26, %27, %28, %29, %30, %31, %32, %33, %34, %35, %36, %37, %38, %39, %40, %41, %42, %43, %44, %45, %46, %47, %48, %49, %50, %51, %52, %53, %54, %55, %56, %57, %58, %59, %60, %61, %62, %63}, {%64, %65, %66, %67}, %68, P, 1, 1, %70;\n}"
        : "+f"(d[0]), "+f"(d[1]), "+f"(d[2]), "+f"(d[3]), "+f"(d[4]), "+f"(d[5]), "+f"(d[6]), "+f"(d[7]), "+f"(d[8]), "+f"(d[9]), "+f"(d[10]), "+f"(d[11]), "+f"(d[12]), "+f"(d[13]), "+f"(d[14]), "+f"(d[15]), "+f"(d[16]), "+f"(d[17]), "+f"(d[18]), "+f"(d[19]), "+f"(d[20]), "+f"(d[21]), "+f"(d[22]), "+f"(d[23]), "+f"(d[24]), "+f"(d[25]), "+f"(d[26]), "+f"(d[27]), "+f"(d[28]), "+f"(d[29]), "+f"(d[30]), "+f"(d[31]), "+f"(d[32]), "+f"(d[33]), "+f"(d[34]), "+f"(d[35]), "+f"(d[36]), "+f"(d[37]), "+f"(d[38]), "+f"(d[39]), "+f"(d[40]), "+f"(d[41]), "+f"(d[42]), "+f"(d[43]), "+f"(d[44]), "+f"(d[45]), "+f"(d[46]), "+f"(d[47]), "+f"(d[48]), "+f"(d[49]), "+f"(d[50]), "+f"(d[51]), "+f"(d[52]), "+f"(d[53]), "+f"(d[54]), "+f"(d[55]), "+f"(d[56]), "+f"(d[57]), "+f"(d[58]), "+f"(d[59]), "+f"(d[60]), "+f"(d[61]), "+f"(d[62]), "+f"(d[63])
        : "r"(a[0]), "r"(a[1]), "r"(a[2]), "r"(a[3]), "l"(db), "r"(acc), "n"(TB));
}
template <int TB>
__device__ __forceinline__ void wgmma_rs64(float* d, const uint32_t* a, uint64_t db, uint32_t acc) {
    asm volatile("{\n.reg .pred P;\nsetp.ne.u32 P, %37, 0;\nwgmma.mma_async.sync.aligned.m64n64k16.f32.bf16.bf16 "
        "{%0, %1, %2, %3, %4, %5, %6, %7, %8, %9, %10, %11, %12, %13, %14, %15, %16, %17, %18, %19, %20, %21, %22, %23, %24, %25, %26, %27, %28, %29, %30, %31}, {%32, %33, %34, %35}, %36, P, 1, 1, %38;\n}"
        : "+f"(d[0]), "+f"(d[1]), "+f"(d[2]), "+f"(d[3]), "+f"(d[4]), "+f"(d[5]), "+f"(d[6]), "+f"(d[7]), "+f"(d[8]), "+f"(d[9]), "+f"(d[10]), "+f"(d[11]), "+f"(d[12]), "+f"(d[13]), "+f"(d[14]), "+f"(d[15]), "+f"(d[16]), "+f"(d[17]), "+f"(d[18]), "+f"(d[19]), "+f"(d[20]), "+f"(d[21]), "+f"(d[22]), "+f"(d[23]), "+f"(d[24]), "+f"(d[25]), "+f"(d[26]), "+f"(d[27]), "+f"(d[28]), "+f"(d[29]), "+f"(d[30]), "+f"(d[31])
        : "r"(a[0]), "r"(a[1]), "r"(a[2]), "r"(a[3]), "l"(db), "r"(acc), "n"(TB));
}
template <int TB>
__device__ __forceinline__ void wgmma_rs16(float* d, const uint32_t* a, uint64_t db, uint32_t acc) {
    asm volatile("{\n.reg .pred P;\nsetp.ne.u32 P, %13, 0;\nwgmma.mma_async.sync.aligned.m64n16k16.f32.bf16.bf16 "
        "{%0, %1, %2, %3, %4, %5, %6, %7}, {%8, %9, %10, %11}, %12, P, 1, 1, %14;\n}"
        : "+f"(d[0]), "+f"(d[1]), "+f"(d[2]), "+f"(d[3]), "+f"(d[4]), "+f"(d[5]), "+f"(d[6]), "+f"(d[7])
        : "r"(a[0]), "r"(a[1]), "r"(a[2]), "r"(a[3]), "l"(db), "r"(acc), "n"(TB));
}

__device__ __forceinline__ uint32_t delay_loop(int n, uint32_t x0) {
    uint32_t z;
    asm volatile("{\n.reg .pred P;\n.reg .u32 c, x;\nmov.u32 c, %1;\nmov.u32 x, %2;\nDL: mad.lo.u32 x, x, 1664525, 1013904223;\nadd.u32 c, c, -1;\nsetp.gt.s32 P, c, 0;\n@P bra DL;\n"
                 "setp.eq.u32 P, x, 0x7fffffff;\nselp.u32 %0, 16, 0, P;\n}" : "=r"(z) : "r"(n), "r"(x0) : "memory");
    return z;
}
__device__ __forceinline__ void wait_clocks(uint32_t n) {
    asm volatile("{\n.reg .pred P;\n.reg .u32 a, b;\nmov.u32 a, %%clock;\nW: mov.u32 b, %%clock;\nsub.u32 b, b, a;\nsetp.lt.u32 P, b, %0;\n@P bra W;\n}" ::"r"(n) : "memory");
}
__device__ __forceinline__ uint32_t gtime() { uint32_t t; asm volatile("mov.u32 %0, %%globaltimer_lo;" : "=r"(t)); return t; }
#define COUNT_RETRY(i)
__device__ __forceinline__ uint32_t stamp_word(uint32_t seq) { return (gtime() & ~31u) | (seq & 31u); }
__device__ __forceinline__ void wait_time(uint32_t t, uint32_t sb) { while ((int32_t)(gtime() - t) < 0) {} }
#define NAPMODE 1
__device__ __forceinline__ void nap(uint32_t ns) { if (NAPMODE) wait_clocks(ns * 7 / 4); else __nanosleep(ns); }
template <int STRIDE>
__device__ __forceinline__ uint32_t latest_stamp(const uint32_t* p, uint32_t seq, uint32_t ref, uint32_t sb) {
    int n = 0;
    while (true) {
        uint32_t bad = 0; int32_t m = INT32_MIN;
#pragma unroll
        for (int i = 0; i < 3; i++) { const uint32_t v = ld_relaxed1(p + i * STRIDE); bad |= (v ^ seq) & 31u; m = max(m, (int32_t)((v & ~31u) - ref)); }
        if (__all_sync(0xffffffffu, bad == 0)) return ref + __reduce_max_sync(0xffffffffu, m);
        nap(100);
        if (++n > SPIN_LIMIT) spin_fault();
    }
}
constexpr uint32_t ONES = 0x3C003C00u, FULL = 0x50005000u;
__device__ __forceinline__ void pacer(const Params& P, const uint32_t sb, const int cta, const int lane, const uint32_t epoch) {
    uint8_t* const zp = P.xb + cta * 2048 + xg_lane(lane);
    if (lane < 3) asm volatile("prefetch.tensormap [%0];" ::"l"(&P.tm[lane == 0 ? M_C1 + cta % 3 : lane == 1 ? M_CO : M_SEG]) : "memory");
    uint32_t e0 = 0;
#pragma unroll 2
    for (int i = 0; i < 32; i++) { const uint4 u = __ldg((const uint4*)P.mem0 + i * 32 + lane); e0 = amax(amax(e0, amax(u.x, u.y)), amax(u.z, u.w)); }
    e0 = min(max(warp_exp(e0), 31u), 253u) - 14;
    if (cta < 32) {
        const uint32_t* m = (const uint32_t*)(P.mem0 + (lane >> 2) * 1024 + cta * 32 + (lane & 3) * 2);
        const float sc = __uint_as_float((254 - e0) << 23);
        auto cv = [&](uint32_t u) { return pack2h(bf_lo(u) * sc, bf_hi(u) * sc); };
        const uint32_t y = cv(m[12]);
        st_relaxed4(zp, cv(m[0]), cv(m[4]), cv(m[8]), prmt(y, FULL, 0x7610));
        st_relaxed1(P.xb + xg_side(cta) + lane * 4, prmt(y, FULL, 0x3254));
    }
    if (cta < 40) {
#pragma unroll 1
        for (int b = 1; b < 8; b++) st_relaxed4(zp + xg_buf(b), 0, 0, 0, 0);
    }
    __threadfence();
    const uint32_t* ts = (const uint32_t*)(P.xb + XG_T) + lane;
    int32_t d0 = P.dly;
    const uint32_t go = mapa(sb + B_GO, (cta / 3 & 1) * 3 + 1 + (lane & 1));
    auto free_segment = [&]() { if (lane == 0) mbar_expect(sb + B_KVFULL, 16384); __syncwarp(); if (lane < 2) mbar_arrive_cluster(go); };
    wait_count(&g_cnt(C_XCNT), (epoch + 1) * 256);
    const uint32_t ex = max(ld_relaxed1(&g_cnt(C_XMAX)) & 255, 67u);
    mbar_wait(sb + B_READY, 0);
    free_segment();
    if (lane == 0) st_relaxed2(g_hint + cta * 32, stamp_word(epoch + 1), lds32(sb + S_EV) | lds32(sb + S_EO) << 16);
    uint32_t a = gtime();
    for (int n = 0;; n++) {
        uint32_t bad = 0, e = 0; int32_t m = INT32_MIN;
#pragma unroll
        for (int i = 0; i < 3; i++) {
            uint32_t v[2];
            ld_relaxed2(v, g_hint + lane * 32 + i * 1024);
            bad |= (v[0] ^ (epoch + 1)) & 31u; m = max(m, (int32_t)((v[0] & ~31u) - a)); e = __vmaxu2(e, v[1]);
        }
        if (__all_sync(0xffffffffu, bad == 0)) {
            a += __reduce_max_sync(0xffffffffu, m);
            const uint32_t ev = __reduce_max_sync(0xffffffffu, e & 255), eo = __reduce_max_sync(0xffffffffu, e >> 16);
            if (lane == 0) { sts64(sb + S_SC, max(ev, 97u) + max(eo, 97u) - 244, ex); sts32(sb + S_ISC, e0 * 0x800080u); }
            break;
        }
        wait_clocks(100);
        if (n > SPIN_LIMIT) spin_fault();
    }
    wait_time(a, sb);
    if (lane == 0) mbar_arrive(sb + B_RELM);
#pragma unroll 1
    for (int s = 0; s < 63; s++) {
        const uint32_t seq = epoch * 63 + s + 1;
        mbar_wait(sb + B_P1, s & 1);
        const uint32_t tx = gtime();
        if (lane == 0) st_relaxed1(ts + (s & 1) * 256 + cta, (tx & ~31u) | (seq & 31u));
        { const uint32_t t = tx; PROFP(3) }
        if (s > 0) {
            const int32_t e0 = latest_stamp<32>(ts + (~s & 1) * 256 + 128, seq - 1, a, sb) + P.mrg - a;
            d0 += s < 3 ? e0 : min(max(e0, -P.clamp0), P.clampv) / 2;
        }
        while ((int32_t)(gtime() - tx) < P.rd) nap(20);
        a = latest_stamp<32>(ts + (s & 1) * 256, seq, tx, sb) + d0;
        { const uint32_t t = gtime(); PROFP(0) }
        while ((int32_t)(a - gtime()) > 250) nap(40);
        wait_time(a, sb);
        if (lane == 0) mbar_arrive(sb + B_RELM);
        { const uint32_t t = a; PROFP(2) }
        mbar_wait(sb + B_RED, s & 1);
        { const uint32_t t = gtime(); PROFP(1) }
        const uint32_t g = tx + __reduce_max_sync(0xffffffffu, lds32(sb + S_TO + (lane & 7) * 4) - tx);
        if (lane == 0) st_relaxed1(ts + (s & 1) * 256 + 128 + cta, (g & ~31u) | (seq & 31u));
        if (s < 62) { if (P.kvd) nap(P.kvd); free_segment(); }
    }
}
__device__ __forceinline__ void st_async2(uint32_t a, uint32_t x, uint32_t y, uint32_t bar, bool on) {
    asm volatile("{\n.reg .pred P;\nsetp.ne.u32 P, %4, 0;\n@P st.async.weak.shared::cluster.mbarrier::complete_tx::bytes.v2.b32 [%0], {%1,%2}, [%3];\n}" ::"r"(a), "r"(x), "r"(y), "r"(bar), "r"((uint32_t)on) : "memory");
}
__device__ __forceinline__ uint32_t xor_or(uint32_t a, uint32_t b, uint32_t t) { uint32_t d; asm("lop3.b32 %0, %1, %2, %3, 0x7E;" : "=r"(d) : "r"(a), "r"(b), "r"(t)); return d; }
__device__ __forceinline__ uint32_t or3(uint32_t a, uint32_t b, uint32_t c) { uint32_t d; asm("lop3.b32 %0, %1, %2, %3, 0xFE;" : "=r"(d) : "r"(a), "r"(b), "r"(c)); return d; }
__device__ __forceinline__ bool tags_ok(uint32_t bad, uint32_t mask = 1) {
    uint32_t r;
    asm volatile("{\n.reg .pred P;\n.reg .b32 x;\nand.b32 x, %1, %2;\nsetp.ne.b32 P, x, 0;\nvote.sync.any.pred P, P, 0xffffffff;\nselp.u32 %0, 0, 1, P;\n}" : "=r"(r) : "r"(bad), "r"(mask));
    return r;
}
constexpr int SROW = 56;
#define PREA 8
#define PREB 9
#define RING1 6
#define RING2 7
#define RING3 8
#define PRE2 10
#define PRE2A 0
#define PRE3 0
#define EFENCE 0
#define RFENCE 1
#define PROG 16
#define EARLY 0
#define PLATE 1
#define LAG2 8
#define LAG 4
#define PUT1 33
#define DEPS 3
#define ADELAY 120
#define BDELAY 0
#define HOLD 1
#define XDELAY 330
#define FENCEA 0x80
#define FENCEB 0x80
#define FENCE2 0x220
#define OFENCE 0
#define MASK3 0x57
#define MASK4 0x55
#define MASK5 0x25
#define OFF3 0x5320
#define OFF4 0x6420
#define OFF5 0x0520
#define RESA (NRA == 3 ? 15 : NRA == 4 ? 3 : 0)
#define RESB (NRB == 3 ? 0xcc : NRB == 4 ? 0x30 : 0)
#define RESB1 (NRB == 3 ? 0xcc : NRB == 4 ? 0xc : 0)
__host__ __device__ constexpr int smem_mask(int NR) { return NR == 3 ? MASK3 : NR == 4 ? MASK4 : MASK5; }
__host__ __device__ constexpr bool round_smem(int r, int NR) { return smem_mask(NR) >> r & 1; }
__host__ __device__ constexpr int kord(int r, int NR) { int c = 0; for (int i = 0; i < r; i++) c += round_smem(i, NR) == round_smem(r, NR); return round_smem(r, NR) ? NR + c : c; }
__host__ __device__ constexpr int slot_r(int n, int NR) { return n < 32 ? n >> 2 : (((n & 31) >> 2) + ((NR == 3 ? OFF3 : NR == 4 ? OFF4 : OFF5) >> (n & 3) * 4)) & 7; }
__host__ __device__ constexpr int slot_k(int n, int NR) { return kord(slot_r(n, NR), NR); }
__host__ __device__ constexpr int slot_sord(int n, int NR) { int c = 0; for (int i = 0; i < n; i++) c += slot_k(i, NR) >= NR; return c; }
__host__ __device__ constexpr int sfrag_slot(int q, int NR) { for (int n = 0; n < 64; n++) if (slot_k(n, NR) >= NR && slot_sord(n, NR) == q) return n; return -1; }
__host__ __device__ constexpr int w1_loaded(int n, int NR, int PRE) {
    int q = PRE;
    for (int i = 0; i <= n; i++) q += q < (8 - NR) * 8 && q - slot_sord(i + 1, NR) < (i < 32 ? RING1 : RING2);
    return q;
}
template <int Q, int NR>
__device__ __forceinline__ void load_w1(uint32_t* w, const uint32_t* a) {
    constexpr int n = sfrag_slot(Q, NR);
    ldsm4t(w, a[n & 3] + ((slot_k(n, NR) - NR) * 2 + (n >> 5)) * 2048);
}
constexpr int AB = NRA < 5, BB = 3 - AB;
__device__ __forceinline__ bool w2_full(int role, int warp) { return warp < (role == 2 ? 2 : 3); }
__device__ __forceinline__ int w2_nblk(int role, int warp) { return warp < 4 ? BB - !w2_full(role, warp) : AB; }
__host__ __device__ constexpr int w2_step(bool full, int i) { return AB ? (full ? 2 * i : 0) : full ? (i == 0 ? 0 : i == 1 ? 16 - 2 * EARLY : 18 - 2 * EARLY) : i; }
__device__ __forceinline__ int w2_block(int role, int warp) {
    const int f = role * 3 + warp, g = role == 2 ? warp : role;
    if (AB) return (warp >= 4 ? role * 4 + (warp - 4) : w2_full(role, warp) ? 16 + 4 * (f >> 1) + (f & 1) : 12 + g) ^ EARLY;
    return w2_full(role, warp) ? EARLY + 4 * (f >> 1) + (f & 1) : EARLY + 2 + 4 * g;
}
__device__ __forceinline__ int w2_res(int role, int warp) { return warp >= 4 ? RESA : w2_full(role, warp) ? RESB : RESB1; }
__device__ __forceinline__ int w2_units(int role, int warp) { return w2_nblk(role, warp) * 4 - (5 - (warp < 4 ? NRB : NRA)) * 2; }
constexpr int W2B = (BB * 4 - (5 - NRB) * 2) * 2048, W2A = (AB * 4 - (5 - NRA) * 2) * 2048;
static_assert(S_W2 + 4 * W2B - 8192 + 4 * W2A == S_KV, "weights");
__device__ __forceinline__ int w1_base(int warp) { return S_W1 + (warp < 4 ? warp * (8 - NRB) : 4 * (8 - NRB) + (warp - 4) * (8 - NRA)) * 4096; }
__device__ __forceinline__ int w2_base(int warp) { return S_W2 + (warp < 4 ? warp * W2B : 4 * W2B - 8192 + (warp - 4) * W2A); }
__device__ __forceinline__ void chain_load(const Params& P, uint32_t sb, int cta, int warp, int lane, int round) {
    const int role = cta % 3, h = cta / 3;
    mbar_expect_e(sb + B_INIT, round ? (8 - (warp < 4 ? NRB : NRA)) * 4096 : 20480);
    if (round) mbar_expect_e(sb + B_INIT2, w2_units(role, warp) * 2048);
    __syncwarp();
    const int m1 = (warp < 4 ? smem_mask(NRB) : smem_mask(NRA)) ^ (round ? 0 : 255), below = (1 << lane) - 1;
    const int m2 = (w2_res(role, warp) ^ (round ? 0xfff : 0)) & ((1 << w2_nblk(role, warp) * 4) - 1);
    const uint32_t d1 = sb + (round ? w1_base(warp) : warp * 20480), d2 = round ? sb + w2_base(warp) : d1 + __popc(m1) * 4096;
    if (m1 >> lane & 1) tma3d(d1 + __popc(m1 & below) * 4096, &P.tm[M_C1 + role], 0, warp * 128 + lane * 16, h * 2, sb + B_INIT);
    __syncwarp();
    if (m2 >> lane & 1)
        tma2d(d2 + __popc(m2 & below) * 2048, &P.tm[M_CO], (w2_block(role, warp) + w2_step(w2_full(role, warp), lane >> 2)) * 32, h * 128 + (lane & 3) * 32, sb + (round ? B_INIT2 : B_INIT));
    __syncwarp();
}

__device__ __forceinline__ void put_partials(bool TR, uint32_t a, const float* x, const float* y) {
    if (TR) stsm4t(a, pack2(x[0], x[1]), pack2(x[2], x[3]), pack2(y[0], y[1]), pack2(y[2], y[3]));
    else stsm4(a, pack2(x[0], x[1]), pack2(x[2], x[3]), pack2(y[0], y[1]), pack2(y[2], y[3]));
}
template <int NR, int PRE, int FM, int B, int E>
__device__ __forceinline__ void project(float (*acc)[4], bool TR, const uint32_t (*wr)[4], uint32_t (*as)[4], uint32_t (*v)[4], uint32_t* x, const uint32_t* w1a, uint32_t pp, uint32_t zero) {
    static_for<B, E>([&](auto I) {
        constexpr int n = I.value, kk = slot_k(n, NR), T = (n >> 5) * 4 + (n & 3), so = slot_sord(n, NR), q = w1_loaded(n - 1, NR, PRE);
        constexpr bool sm = kk >= NR;
        const uint32_t* w = sm ? as[so] : wr[sm ? 0 : (kk * 2 + (n >> 5)) * 4 + (n & 3)];
        if constexpr (n == 32 && PUT1 < 32) { put_partials(TR, pp, acc[0], acc[1]); put_partials(TR, pp + 4096, acc[2], acc[3]); }
        if constexpr (n == 0) {
            const uint32_t c = prmt(v[0][3], x[0], 0x3254);
            v[0][0] = h2bf(v[0][0], v[0][0]); v[0][1] = h2bf(v[0][1], v[0][1]); v[0][2] = h2bf(v[0][2], v[0][2]); v[0][3] = h2bf(v[0][3], x[0]);
            x[0] = c;
        }
        if constexpr ((n & 31) < 4) acc[T][0] = acc[T][1] = acc[T][2] = acc[T][3] = 0.f;
        mma16816(acc[T], w[0], w[1], w[2], w[3], v[slot_r(n, NR) >> 1][(slot_r(n, NR) & 1) * 2], v[slot_r(n, NR) >> 1][(slot_r(n, NR) & 1) * 2 + 1]);
        if constexpr (n == DEPS) {
            const uint32_t sel = __float_as_uint(acc[T][0]) * zero + 0x7610;
#pragma unroll
            for (int b = 1; b < 4; b++) cvt_block(v[b], x[b], sel);
        }
        if constexpr (w1_loaded(n, NR, PRE) > q) load_w1<q, NR>(as[q], w1a);
        if constexpr (n == PUT1 && n >= 32) { put_partials(TR, pp, acc[0], acc[1]); put_partials(TR, pp + 4096, acc[2], acc[3]); }
        if constexpr (n % 4 == 3 && (FM >> (n / 4) & 1) && n != E - 1) sched_fence();
    });
    if constexpr (E == 64) { put_partials(TR, pp + 8192, acc[4], acc[5]); put_partials(TR, pp + 12288, acc[6], acc[7]); }
}
__device__ __forceinline__ void reduce8(const uint32_t (*x)[4], const uint32_t* sel, float sc, uint32_t& r0, uint32_t& r1) {
    float d[4][4];
#pragma unroll
    for (int i = 0; i < 4; i++) {
        d[i][0] = d[i][1] = d[i][2] = d[i][3] = 0.f;
        mma16816(d[i], x[i][0], x[i][1], x[i][2], x[i][3], sel[2 * i], sel[2 * i + 1]);
    }
    r0 = pack2(((d[0][0] + d[1][0]) + (d[2][0] + d[3][0])) * sc, ((d[0][1] + d[1][1]) + (d[2][1] + d[3][1])) * sc);
    r1 = pack2(((d[0][2] + d[1][2]) + (d[2][2] + d[3][2])) * sc, ((d[0][3] + d[1][3]) + (d[2][3] + d[3][3])) * sc);
}

#define ISTAMP(i)
__host__ __device__ constexpr int wo_count(int n, int RES, bool res) { int c = 0; for (int i = 0; i < n; i++) c += (RES >> (i >> 2) & 1) == res; return c; }
__host__ __device__ constexpr int wo_loaded(int n, int RES, int PRE, int end) { int q = PRE; for (int i = 0; i <= n; i++) q += q < end && q - wo_count(i + 1, RES, false) < RING3; return q; }
template <int Q>
__device__ __forceinline__ void load_w2(uint32_t* w, const uint32_t* a) { ldsm4t(w, a[Q & 1] + (Q >> 1) * 1024); }
template <int NB, int RES, int PRE, int FM>
__device__ __forceinline__ void wo_blocks(uint32_t (*w)[4], const uint32_t (*wp)[4], uint32_t oa, const uint32_t* wa, const uint8_t* dst, const uint8_t* dsd, bool odd) {
    float a[NB][4][4];
    uint32_t o[4][4], r[5];
    bar_sync(3, 256);
#pragma unroll
    for (int i = 0; i < 4; i++) ldsm4(o[i], oa + i * 512);
    if (FM & 1) sched_fence();
    static_for<0, NB * 16>([&](auto I) {
        constexpr int n = I.value, i = n & 15, end = wo_count(NB * 16, RES, false), q = wo_loaded(n - 1, RES, PRE, end);
        constexpr bool res = RES >> (n >> 2) & 1;
        const uint32_t* b = o[i >> 2] + (i & 2);
        const uint32_t* x = res ? wp[wo_count(n, RES, true)] : w[wo_count(n, RES, false)];
        float* d = a[n >> 4][i & 3];
        if constexpr (i < 4) d[0] = d[1] = d[2] = d[3] = 0.f;
        mma16816(d, x[0], x[1], x[2], x[3], b[0], b[1]);
        if constexpr (wo_loaded(n, RES, PRE, end) > q) load_w2<q>(w[q], wa);
        if constexpr (n == NB * 16 - 1 || (n >= 16 && i == LAG - 1)) {
            const float (*e)[4] = a[n == NB * 16 - 1 ? NB - 1 : (n >> 4) - 1];
            const uint32_t y = pack2h(e[1][2] + e[3][2], e[1][3] + e[3][3]);
            r[0] = movm(pack2h(e[0][0] + e[2][0], e[0][1] + e[2][1])); r[1] = movm(pack2h(e[0][2] + e[2][2], e[0][3] + e[2][3]));
            r[2] = movm(pack2h(e[1][0] + e[3][0], e[1][1] + e[3][1])); r[3] = movm(odd ? ONES : y); r[4] = movm(odd ? y : ONES);
        }
        if constexpr (n == NB * 16 - 1 || (n >= 16 && i == LAG2 - 1)) {
            constexpr int bs = w2_step(NB == BB, n == NB * 16 - 1 ? NB - 1 : (n >> 4) - 1);
            red_add4(dst + bs * 2048, r[0], r[1], r[2], r[3]);
            red_add1(dsd + (bs >> 1) * 1024 + (bs & 1) * 256, r[4]);
        }
        if constexpr (((FM >> (n / 4 + 1)) & 1) && (n & 3) == 3 && n != NB * 16 - 1) sched_fence();
    });
}
#define FRAG1(ln) ((((ln) & 7) + ((ln) >> 4) * 8) * 128 + ((((((ln) >> 3) & 1) << (ROLE == 1)) ^ ((ln) & 7)) << 4))
#define FRAG2(ln) ((((ln) & 7) + ((ln) >> 4) * 8) * 64 + (((((ln) >> 3) & 1) ^ (((ln) >> 1) & 3)) << 4))
#define TILE_X(i) (ROLE == 1 ? (((i) >> 1) << 6) | (((i) & 1) << 4) : (i) << 5)
__device__ __forceinline__ void chain_fetch(const Params& P, const uint32_t sb, const int cta, const int warp, const int lane, uint32_t (*wr)[4]) {
    const int ROLE = cta % 3, nr = warp < 4 ? NRB : NRA;
    mbar_wait(sb + B_INIT, 0);
    ISTAMP(0)
#pragma unroll
    for (int f = 0; f < 40; f++) {
        const bool w1 = f < (NRA < NRB ? NRA : NRB) * 8 || f < nr * 8;
        ldsm4t(wr[f], sb + warp * 20480 + (f >> 2) * 2048 + (w1 ? FRAG1(lane) ^ TILE_X(f & 3) : (f & 2) * 512 + (FRAG2(lane) ^ ((f & 1) << 5))));
    }
    fence_async_smem();
    mbar_wait(sb + B_SFREE + (warp >> 2) * 8, 0);
    bar_sync(1, 256);
    chain_load(P, sb, cta, warp, lane, 1);
    ISTAMP(1)
}
__device__ __forceinline__ void chain_bounds(const uint32_t sb, const int cta, const int warp, const int lane, const uint32_t (*wr)[4]) {
    const int ROLE = cta % 3, nr = warp < 4 ? NRB : NRA;
    uint32_t m[6] = {}, u[4];
#pragma unroll
    for (int f = 0; f < 40; f++) m[f < 24 ? 0 : f >> 3] = amax4(m[f < 24 ? 0 : f >> 3], wr[f]);
    uint32_t m1 = amax(m[0], amax(nr > 3 ? m[3] : 0, nr > 4 ? m[4] : 0)), m2 = amax(nr > 3 ? 0 : m[3], nr > 4 ? 0 : m[4]);
    ISTAMP(5)
    mbar_wait(sb + B_INIT, 1);
    ISTAMP(3)
    if (ROLE == 2) {
#pragma unroll 4
        for (int i = 0; i < S_W2 / 4096; i++) { lds128(u, sb + S_W1 + warp * (S_W2 / 8) + i * 512 + lane * 16); m1 = amax4(m1, u); }
    }
    mbar_wait(sb + B_INIT2, 0);
    ISTAMP(7)
    const int n = w2_units(ROLE, warp) * 4;
#pragma unroll 4
    for (int i = 0; i < n; i++) { lds128(u, sb + w2_base(warp) + i * 512 + lane * 16); m2 = amax4(m2, u); }
    m1 = warp_exp(m1); m2 = warp_exp(m2);
    if (lane == 0) { if (ROLE == 2) red_max_shared(sb + S_EV, m1); red_max_shared(sb + S_EO, m2); }
}
template <bool ATT>
__device__ __forceinline__ void chain_role(const Params& P, const uint32_t sb, const int cta, const int warp, const int lane, const uint32_t epoch, const uint32_t (*wr)[4]) {
    constexpr int NR = ATT ? NRA : NRB, PRE = ATT ? PREA : PREB;
    const int h = cta / 3, ROLE = cta - h * 3;
    ISTAMP(6)
    uint32_t l8 = opq(sb + lane * 8, lane);
    const uint8_t* persu = (const uint8_t*)((ROLE == 1 ? g_km : g_vmt) + h * 512) - (sb >> 1);
    auto persist = [&](int s, int tile, uint32_t r0, uint32_t r1) {
        uint32_t* pp = (uint32_t*)(persu + s * 65536 + (ROLE == 1 ? (tile >> 1) * 512 + (tile & 1) * 128 : tile * 256) + (l8 >> 1));
        pp[0] = r0; pp[ROLE == 1 ? 64 : 32] = r1;
    };
    const uint32_t rk0 = (h & 1) * 3, rd1 = __shfl_sync(0xffffffffu, mapa(sb, rk0 + (ROLE + 1) % 3) - sb, 0), rd2 = __shfl_sync(0xffffffffu, mapa(sb, rk0 + (ROLE + 2) % 3) - sb, 0);
    const uint32_t xo = (ROLE == 2 ? S_XV : S_X + ROLE * 2048) + warp * 256;
    const bool full = w2_full(ROLE, warp);
    const int blk = w2_block(ROLE, warp);
    const uint32_t om = blk * 2048, os = xg_side(blk);
    const uint32_t w1o = sb + w1_base(warp), w2o = sb + w2_base(warp);
    ISTAMP(2)
    if (lane == 0) mbar_arrive(sb + B_READY);
#pragma unroll 1
    for (int s = 0;; s++) {
        l8 += s & P.zero;
        uint32_t r0, r1;
        {
            uint32_t v[4][4], as[(8 - NR) * 8][4], w1a[4];
            float acc[8][4];
            const uint32_t pst = sb + S_P1 + (l8 - sb) * 16 + ((warp * 16) ^ ((l8 & 56) * 2));
#pragma unroll
            for (int i = 0; i < 4; i++) w1a[i] = w1o + (FRAG1((l8 - sb) >> 3) ^ TILE_X(i));
            auto preload = [&]() { static_for<0, PRE>([&](auto I) { load_w1<I.value, NR>(as[I.value], w1a); }); };
#pragma unroll 1
            while (true) {
                uint32_t x[4];
                if (!(PLATE >> ATT & 1)) preload();
                const uint32_t lm = opq(l8 - sb, (l8 - sb) >> 3);
                const uint8_t* pm = P.xb + xg_buf(s) + warp * 8192 + xg_lane(lm >> 3);
                const uint8_t* ps = P.xb + xg_buf(s) + XG_SIDE + warp * 2048 + (lm >> 1);
                pin_ptr(pm); pin_ptr(ps);
                mbar_wait(sb + B_RELM, s & 1);
                if (ATT ? ADELAY : BDELAY) wait_clocks(ATT ? ADELAY : BDELAY);
                PROF(10)
#pragma unroll
                for (int b = 0; b < 4; b++) { ld_relaxed4(v[b], pm + b * 2048); ld_relaxed1n(x[b], ps + (b >> 1) * 1024 + (b & 1) * 256); }
                if (PLATE >> ATT & 1) { preload(); if (PLATE >> (ATT + 2) & 1) sched_fence(); }
                project<NR, PRE, ATT ? FENCEA : FENCEB, 0, PROG>(acc, ROLE == 2, wr, as, v, x, w1a, pst, P.zero);
                const uint32_t bad = xor_or(x[0], x[1], FULL) | xor_or(x[2], x[3], FULL);
                if (tags_ok(bad, 0xffffffffu)) break;
                COUNT_RETRY(warp >> 1)
                uint32_t n;
                asm volatile("atom.shared.add.u32 %0, [%1], 1;" : "=r"(n) : "r"(sb + S_RETRY) : "memory");
                if (n > SPIN_LIMIT) spin_fault();
            }
            PROF(0)
            sts32((l8 >> 1) + (sb - (sb >> 1) + S_EM + warp * 128), amax4(amax4(amax4(amax(amax(v[0][0], v[0][1]), amax(v[0][2], v[0][3])), v[1]), v[2]), v[3]));
            project<NR, PRE, ATT ? FENCEA : FENCEB, PROG, 64>(acc, ROLE == 2, wr, as, v, nullptr, w1a, pst, 0);
            PROF(1)
            const uint32_t isc = lds32(sb + S_ISC + (s & 1) * 4);
            const uint32_t lq = l8 + ((s >> 3) & P.zero);
            uint32_t x[4][4], sel[8], xd[6] = {l8 + xo, l8 + xo + rd1, l8 + xo + rd2, sb + B_X + rd1, sb + B_X + rd2, sb + S_P1 + warp * 2048 + (lq & 64) * 16 + (lq & 128) + (lq & 56) * 2};
#pragma unroll
            for (int i = 0; i < 8; i++) sel[i] = (lq & 224) == i * 32 ? 0x3F803F80u : 0u;
            pin<6>(xd); pin<8>(sel);
            if (RFENCE) sched_fence();
            bar_sync(1, 256);
#pragma unroll
            for (int i = 0; i < 4; i++) ldsm4t(x[i], xd[5] + i * 256);
            if (!ATT && l8 == sb + (warp - 3) * 1024) mbar_arrive(sb + B_P1);
            reduce8(x, sel, bf_hi(isc), r0, r1);
            st_async2(xd[1], r0, r1, xd[3], s != 63);
            st_async2(xd[2], r0, r1, xd[4], s != 63);
            sts64(xd[0], r0, r1);
            if (s == 63) { persist(s, warp, r0, r1); break; }
            if (!ATT && warp == 0) {
                uint32_t sc[2], u[2][4];
                lds64(sc, sb + S_SC);
                lds128(u[0], l8 * 2 + (S_EM - sb)); lds128(u[1], l8 * 2 + (S_EM + 512 - sb));
                const int em = warp_exp(amax4(amax(amax(u[0][0], u[0][1]), amax(u[0][2], u[0][3])), u[1]));
                if (l8 == sb) sts32(sb + S_ISC + (~s & 1) * 4, min(max(em + (int)(isc >> 23) - 127, (int)sc[1]) + (int)sc[0], 253) * 0x800080u);
            }
            __syncwarp();
            if (l8 == sb) mbar_arrive(sb + B_X);
            PROF(2)
        }
        uint32_t w[40][4], w2a[2], odd;
        const uint8_t *po, *pd;
        auto wo_addr = [&]() {
            const uint32_t lo = (l8 + ((s >> 2) & P.zero) - sb) >> 3;
            w2a[0] = w2o + FRAG2(lo); w2a[1] = w2o + (FRAG2(lo) ^ 32);
            po = P.xb + xg_buf(s + 1) + om + xg_lane(lo);
            pd = P.xb + xg_buf(s + 1) + os + lo * 4;
            odd = lo & 4;
            pin_ptr(po); pin_ptr(pd); pin<2>(w2a); pin<1>(&odd);
        };
        uint32_t oa = l8 * 2 + (S_OX - sb);
        if constexpr (ATT) {
            const uint32_t ln = (l8 + ((s >> 4) & P.zero) - sb) >> 3;
            const uint32_t va = sb + S_KV + 8192 + ((warp >> 1) & 1) * 4096 + ((ln & 7) + (ln >> 4) * 8) * 128 + ((((warp & 1) * 4 + ((ln >> 3) & 1)) ^ (ln & 7)) << 4);
            const uint32_t ka = sb + S_KV + (warp & 1) * 2048 + (ln & 15) * 128 + (((ln >> 4) ^ (ln & 7)) << 4);
            uint32_t ad[5] = {sb + S_SX + (ln & 3) * (8 * SROW) + (ln >> 2) * 4 + (warp < 6 ? (warp - 4) * 64 : 128 + (warp - 6) * 32), l8 + S_XV + (warp - 4) * 512,
                              l8 + S_SX + (ln >> 2) * (4 * SROW - 32), oa + (warp - 4) * 512, sb + S_ISC + (~s & 1) * 4};
            if constexpr (AB) { wo_addr(); pin<1>(&oa); }
            pin<5>(ad);
            const uint32_t sa = ad[0], sr = ad[2];
            uint32_t vf[4][4], vm[2][2], q[8][2];
            float S[4][4];
#pragma unroll
            for (int n = 0; n < 4; n++) { S[n][0] = S[n][1] = S[n][2] = S[n][3] = 0.f; }
            mbar_wait_fast(sb + B_KVFULL, s & 1);
            if (warp < 6) {
                uint32_t kf[8][4];
#pragma unroll
                for (int k = 0; k < 8; k++) ldsm4(kf[k], (ka ^ ((k & 3) << 5)) + (k >> 2) * 4096);
#pragma unroll
                for (int i = 0; i < 4; i++) ldsm4t(vf[i], (va ^ ((i & 1) << 5)) + (i >> 1) * 2048);
                mbar_wait(sb + B_X, s & 1);
                PROF(11)
#pragma unroll
                for (int k = 0; k < 8; k++) lds64(q[k], l8 + S_X + k * 256);
#pragma unroll
                for (int k = 0; k < 8; k++) mma16816(S[k & 3], kf[k][0], kf[k][1], kf[k][2], kf[k][3], q[k][0], q[k][1]);
                sts32(sa, __float_as_uint((S[0][0] + S[1][0]) + (S[2][0] + S[3][0])));
                sts32(sa + 4 * SROW, __float_as_uint((S[0][1] + S[1][1]) + (S[2][1] + S[3][1])));
                sts32(sa + 32, __float_as_uint((S[0][2] + S[1][2]) + (S[2][2] + S[3][2])));
                sts32(sa + 4 * SROW + 32, __float_as_uint((S[0][3] + S[1][3]) + (S[2][3] + S[3][3])));
            } else {
#pragma unroll
                for (int i = 0; i < 4; i++) ldsm4t(vf[i], (va ^ ((i & 1) << 5)) + (i >> 1) * 2048);
                uint32_t xa = l8 + S_X + (warp - 6) * 1024;
                pin<1>(&xa);
                mbar_wait(sb + B_X, s & 1);
                PROF(11)
#pragma unroll
                for (int k = 0; k < 8; k++) lds64(q[k], xa + (k >> 2) * 2048 + (k & 3) * 256);
#pragma unroll
                for (int k = 0; k < 4; k++) mma16816(S[k], q[4 + (k & 2)][0], q[4 + (k & 2)][1], q[5 + (k & 2)][0], q[5 + (k & 2)][1], q[k][0], q[k][1]);
                sts32(sa, __float_as_uint((S[0][0] + S[2][0]) + (S[1][2] + S[3][2])));
                sts32(sa + 4 * SROW, __float_as_uint((S[0][1] + S[2][1]) + (S[1][3] + S[3][3])));
            }
            const uint32_t isn = lds32(ad[4]);
            lds64(vm[0], ad[1]); lds64(vm[1], ad[1] + 256);
            PROF(7)
            bar_sync(2, 128);
            const float cs = 0.08838834764831845f * 1.4426950408889634f;
            float E[6][2];
#pragma unroll
            for (int i = 0; i < 6; i++) lds64f(E[(i + 4) % 6], sr + ((i + 4) % 6) * 32);
            E[4][0] += E[5][0]; E[4][1] += E[5][1];
            float m = fmaxf(fmaxf(fmaxf(fmaxf(E[0][0], E[0][1]), fmaxf(E[1][0], E[1][1])), fmaxf(fmaxf(E[2][0], E[2][1]), fmaxf(E[3][0], E[3][1]))), fmaxf(E[4][0], E[4][1]));
            m = fmaxf(m, __shfl_xor_sync(0xffffffffu, m, 1));
            m = fmaxf(m, __shfl_xor_sync(0xffffffffu, m, 2));
            m *= cs;
            if constexpr (AB) static_for<0, PRE3>([&](auto I) { load_w2<I.value>(w[I.value], w2a); });
            uint32_t pa[5];
#pragma unroll
            for (int i = 0; i < 5; i++) { const int k = (i + 4) % 5; E[k][0] = ex2(fmaf(E[k][0], cs, -m)); E[k][1] = ex2(fmaf(E[k][1], cs, -m)); pa[k] = pack2(E[k][0], E[k][1]); }
            if (EFENCE) sched_fence();
            float O[2][4], Z[4];
#pragma unroll
            for (int i = 0; i < 4; i++) { O[0][i] = O[1][i] = Z[i] = 0.f; }
#pragma unroll
            for (int i = 0; i < 2; i++) {
                mma1688(O[i], vm[i][0], vm[i][1], pa[4]);
                mma16816(O[i], vf[i][0], vf[i][1], vf[i][2], vf[i][3], pa[0], pa[1]);
                mma16816(O[i], vf[2 + i][0], vf[2 + i][1], vf[2 + i][2], vf[2 + i][3], pa[2], pa[3]);
            }
            const float z = (((E[4][0] + E[4][1]) + (E[0][0] + E[0][1])) + ((E[1][0] + E[1][1]) + (E[2][0] + E[2][1]))) + (E[3][0] + E[3][1]);
            const float zh = __uint_as_float(__float_as_uint(z) & 0xffff0000u);
            mma1688(Z, isn, isn, pack2(zh, z - zh));
            const float i0 = rcp(Z[0]), i1 = rcp(Z[1]);
            stsm4t(ad[3], pack2(O[0][0] * i0, O[0][1] * i1), pack2(O[0][2] * i0, O[0][3] * i1), pack2(O[1][0] * i0, O[1][1] * i1), pack2(O[1][2] * i0, O[1][3] * i1));
            PROF(4)
            if constexpr (AB) wo_blocks<1, RESA, PRE3, OFENCE / 2>(w, wr + NR * 8, oa, w2a, po, pd, odd);
            else bar_arrive(3, 256);
            if (ROLE != 0) persist(s, warp, r0, r1);
            if (warp == 7 && l8 == sb) mbar_expect(sb + B_X, 4096);
        } else {
            if (ROLE != 0) persist(s, warp, r0, r1);
            wo_addr(); pin<1>(&oa);
            static_for<0, PRE2A>([&](auto I) { load_w2<I.value>(w[I.value], w2a); });
            mbar_wait(sb + B_X, s & 1);
            wait_clocks(XDELAY);
            constexpr int PRE1 = (BB - 1) * 16 - (5 - NRB) * 8 < PRE2 ? (BB - 1) * 16 - (5 - NRB) * 8 : PRE2;
            static_for<PRE2A, PRE1>([&](auto I) { load_w2<I.value>(w[I.value], w2a); });
            if (full) {
                static_for<PRE1, PRE2>([&](auto I) { load_w2<I.value>(w[I.value], w2a); });
                wo_blocks<BB, RESB, PRE2, FENCE2 * 2 + OFENCE % 2>(w, wr + NR * 8, oa, w2a, po, pd, odd);
            } else wo_blocks<BB - 1, RESB1, PRE1, FENCE2 * 2 + OFENCE % 2>(w, wr + NR * 8, oa, w2a, po, pd, odd);
        }
        PROF(5)
        if (l8 == sb) { sts32(sb + S_TO + warp * 4, gtime()); mbar_arrive(sb + B_RED); }
        if (HOLD && !(PLATE >> ATT & 1)) mbar_wait(sb + B_RED, s & 1);
        if (ROLE != 0 && (s & 3) == 3 && l8 == sb) mbar_arrive(sb + B_PERS);
        if (ROLE == 0 && s == 62) return;
    }
    __syncwarp();
    if (l8 == sb) mbar_arrive(sb + B_PERS);
}
#define IP(i)
struct Pipe { uint32_t stage, phase; };
struct Cons {
    uint32_t sb, rel;
    int wg, wq, lane, rank, pair;
    uint32_t atag, nst;
    Pipe p;
};
__device__ __forceinline__ void pipe_next(Pipe& p) { p.stage = (p.stage + 1) & (NSTAGE - 1); p.phase ^= (p.stage == 0); }
__device__ __forceinline__ void release(const Cons& c, uint32_t stage) { if (c.lane < 2) mbar_arrive_cluster(c.rel + stage * 8); }
__device__ __forceinline__ void wait_full(const Cons& c) { mbar_wait(c.sb + B_FULL + c.p.stage * 8, c.p.phase); }

enum { PEND_NONE = 0, PEND_KVO = 1, PEND_HT = 2, PEND_OUT = 3 };
struct Pend { uint32_t pk[64]; int kind, row, col, cnt; };

__device__ __forceinline__ void staging_wait(const Cons& c) { if (c.nst) mbar_wait(c.sb + B_SFREE + c.wg * 8, (c.nst - 1) & 1); }
__device__ __forceinline__ void staging_post(Cons& c, int kind, int row, int col, int cnt) {
    __syncwarp();
    if (c.lane == 0) {
        if (c.wq == 0) { const uint32_t x[4] = {(uint32_t)kind, (uint32_t)row, (uint32_t)col, (uint32_t)cnt}; sts128(c.sb + S_DESC + c.wg * 16, x); }
        mbar_arrive(c.sb + B_SFULL + c.wg * 8);
    }
    c.nst++;
}
__device__ __forceinline__ void drain(const Params& P, Cons& c, Pend& d) {
    const uint32_t* pk = d.pk;
    if (d.kind == PEND_OUT) {
        float* o = P.out + (size_t)(d.row + c.wq * 16 + (c.lane >> 2)) * 2048 + d.col + (c.lane & 3) * 2;
#pragma unroll
        for (int j = 0; j < 16; j++) {
            st_stream2(o + j * 8, bf_lo(pk[j * 2]), bf_hi(pk[j * 2]));
            st_stream2(o + 8 * 2048 + j * 8, bf_lo(pk[j * 2 + 1]), bf_hi(pk[j * 2 + 1]));
        }
    } else {
        const bool ht = d.kind == PEND_HT;
        const int hi = (c.lane >> 3) & 1;
        const uint32_t base = c.sb + S_STG + c.wg * 16384 + ((ht ? hi * 32 + c.wq * 8 : c.wq * 16 + hi * 8) + (c.lane & 7)) * 128;
        staging_wait(c);
#pragma unroll
        for (int j = 0; j < 8; j++) {
            const int ch = (j & 3) * 2 + (c.lane >> 4);
            stsm4(base + (j >> 2) * 8192 + ((ch ^ (c.lane & 7)) << 4), pk[j * 4], pk[j * 4 + 1], pk[j * 4 + 2], pk[j * 4 + 3]);
        }
        fence_async_smem();
        staging_post(c, d.kind, d.row, d.col, (d.col & 128) ? d.cnt : -1);
    }
    if (d.col & 128) d.kind = PEND_NONE;
    d.col += 128;
#pragma unroll
    for (int i = 0; i < 32; i++) d.pk[i] = d.pk[32 + i];
}

constexpr int S_STG2 = 8 * 20480, PEND_BOTH = 8;
__device__ __forceinline__ void drain_both(Cons& c, const Pend& d) {
    const uint32_t base = c.sb + c.wg * 16384 + (c.wq * 16 + ((c.lane >> 3) & 1) * 8 + (c.lane & 7)) * 128;
#pragma unroll
    for (int j = 0; j < 16; j++)
        stsm4(base + (j < 8 ? S_STG : S_STG2) + (j >> 2 & 1) * 8192 + ((((j & 3) * 2 + (c.lane >> 4)) ^ (c.lane & 7)) << 4), d.pk[j * 4], d.pk[j * 4 + 1], d.pk[j * 4 + 2], d.pk[j * 4 + 3]);
    fence_async_smem();
    staging_post(c, PEND_KVO | PEND_BOTH, d.row, d.col, d.cnt);
}

__device__ __forceinline__ void store_warp(const Params& P, uint32_t sb, int wg, int cta) {
    if (cta < 128) {
        for (int i = 0; i < P.xd; i++) __nanosleep(1000);
        const uint32_t e1 = ld_acquire(&g_cnt(C_EPOCH)) + 1;
        const uint4* x = (const uint4*)P.Bx + (cta * 2 + wg) * 1024 + (threadIdx.x & 31);
        uint32_t m = 0;
#pragma unroll 4
        for (int i = 0; i < 32; i++) { const uint4 u = __ldg(x + i * 32); m = amax(amax(m, amax(u.x, u.y)), amax(u.z, u.w)); }
        m = warp_exp(m);
        if (elect_one()) { atomicMax(&g_cnt(C_XMAX), e1 << 8 | m); red_release(&g_cnt(C_XCNT)); }
        __syncwarp();
    }
    const uint32_t stg = sb + S_STG + wg * 16384;
#pragma unroll 1
    for (uint32_t n = 0;; n++) {
        mbar_wait(sb + B_SFULL + wg * 8, n & 1);
        uint32_t x[4];
        lds128(x, sb + S_DESC + wg * 16);
#pragma unroll
        for (int i = 0; i < 4; i++) x[i] = __shfl_sync(0xffffffffu, x[i], 0);
        if (x[0] == PEND_NONE) break;
        const bool ht = x[0] == PEND_HT;
        const CUtensorMap* m = &P.tm[ht ? M_HTS : M_KVO];
        const uint64_t pol = P.pol[ht ? 2 : x[1] >> 12];
        if (elect_one()) {
#pragma unroll
            for (int i = 0; i < 4; i++) tma_store2d(m, x[2] + (i >> 1) * 64, x[1] + (i & 1) * (ht ? 1024 : 32), stg + i * 4096, pol);
            if (x[0] & PEND_BOTH) {
#pragma unroll 1
                for (int i = 0; i < 4; i++) tma_store2d(m, x[2] + 128 + (i >> 1) * 64, x[1] + (i & 1) * 32, stg + (S_STG2 - S_STG) + i * 4096, pol);
            }
            bulk_commit();
            bulk_wait_read();
            mbar_arrive(sb + B_SFREE + wg * 8);
            if ((int)x[3] >= 0) { bulk_wait_all(); fence_async(); red_release(&g_cnt(x[3])); }
        }
        __syncwarp();
    }
}

template <int TA, int TB, bool FIRST>
__device__ __forceinline__ void issue_ktile(float* acc, const Cons& c) {
    const uint32_t a = c.sb + c.p.stage * STAGE + c.wg * 8192, b = c.sb + c.p.stage * STAGE + 16384;
    const uint64_t da = mkdesc(a, TA ? 8192 : 16, 1024, 1), db = mkdesc(b, TB ? 8192 : 16, 1024, 1);
    wg_fence();
#pragma unroll
    for (int k = 0; k < 4; k++) {
        if (FIRST && k == 0) wgmma_ss256_first<TA, TB>(acc, da, db);
        else wgmma_ss256<TA, TB>(acc, da + (TA ? 128 : 2) * k, db + (TB ? 128 : 2) * k);
    }
    wg_commit();
}
template <bool KVONLY, bool FIRST>
__device__ __forceinline__ void issue_any(float* acc, const Cons& c, int type) {
    if (FIRST) mbar_wait_fast(c.sb + B_FULL + c.p.stage * 8, c.p.phase); else wait_full(c);
    if (!KVONLY && type == T_A1) issue_ktile<0, 0, FIRST>(acc, c);
    else if (!KVONLY && type == T_A2) issue_ktile<1, 0, FIRST>(acc, c);
    else issue_ktile<0, 1, FIRST>(acc, c);
}
template <bool KVONLY = false>
__device__ __forceinline__ void mainloop(float* acc, const Params& P, Cons& c, Pend& d, int type, int nk) {
    issue_any<KVONLY, true>(acc, c, type);
    if (!KVONLY) { IP(0) }
    uint32_t prev = c.p.stage;
    pipe_next(c.p);
#pragma unroll 1
    for (int kt = 1; kt < nk; kt++) {
        if (!KVONLY && d.kind != PEND_NONE && kt != 2) drain(P, c, d);
        issue_any<KVONLY, false>(acc, c, type);
        wg_wait<1>();
        release(c, prev);
        prev = c.p.stage;
        pipe_next(c.p);
    }
    d.kind = PEND_NONE;
    wg_wait<0>();
    pin<128>(acc);
    release(c, prev);
    if (!KVONLY) { IP(1) }
}
__device__ __forceinline__ void pack_half(uint32_t* pk, const float* a) {
#pragma unroll
    for (int i = 0; i < 32; i++) pk[i] = pack2(a[2 * i], a[2 * i + 1]);
}

__device__ __forceinline__ void epi_kv(const float* acc, const Cons& c, Pend& d, int mb, int nb) {
    pack_half(d.pk, acc); pack_half(d.pk + 32, acc + 64);
    d.kind = PEND_KVO; d.row = (nb >> 4) * 2048 + mb * 256 + c.rank * 128 + c.wg * 64; d.col = (nb & 15) * 256; d.cnt = C_KV + mb;
}

__device__ __forceinline__ void qa_scores(float* S, float* Sm, const uint32_t* q, Cons& c) {
    wait_full(c);
    const uint32_t st = c.sb + c.p.stage * STAGE;
    const uint64_t dk = mkdesc(st + c.wg * 8192, 16, 1024, 1), dm = mkdesc(st + 32768 + c.wg * 4096, 128, 2048, 0);
    wg_fence();
#pragma unroll
    for (int i = 0; i < 8; i++) wgmma_rs64<0>(S, q + i * 4, dk + (i >> 2) * 1024 + (i & 3) * 2, i != 0);
#pragma unroll
    for (int i = 0; i < 8; i++) wgmma_rs16<0>(Sm, q + i * 4, dm + i * 16, i != 0);
    wg_commit();
    pipe_next(c.p);
}
__device__ __forceinline__ void qa_softmax(uint32_t (*pa)[4], const float* S, const float* Sm, const Cons& c) {
    const int t = c.lane & 3, i0 = (c.wq & 1) * 16 + (c.lane >> 2) - 2 * t;
    const bool sg = c.wq >= 2;
    const float cs = 0.08838834764831845f * 1.4426950408889634f;
    float x[2][10];
#pragma unroll
    for (int r = 0; r < 2; r++) {
#pragma unroll
        for (int j = 0; j < 4; j++)
#pragma unroll
            for (int e = 0; e < 2; e++) {
                const float v = sg ? S[16 + j * 4 + r * 2 + e] : S[j * 4 + r * 2 + e];
                x[r][j * 2 + e] = (j * 8 + e - r * 8 > i0) ? -1e9f / 0.08838834764831845f : v;
            }
        x[r][8] = sg ? Sm[4 + r * 2] : Sm[r * 2];
        x[r][9] = sg ? Sm[5 + r * 2] : Sm[1 + r * 2];
        float m = fmaxf(fmaxf(fmaxf(fmaxf(x[r][0], x[r][1]), fmaxf(x[r][2], x[r][3])), fmaxf(fmaxf(x[r][4], x[r][5]), fmaxf(x[r][6], x[r][7]))), fmaxf(x[r][8], x[r][9]));
        m = fmaxf(m, __shfl_xor_sync(0xffffffffu, m, 1));
        m = fmaxf(m, __shfl_xor_sync(0xffffffffu, m, 2));
        m *= -cs;
#pragma unroll
        for (int i = 0; i < 10; i++) x[r][i] = ex2(fmaf(x[r][i], cs, m));
        float sum = (((x[r][0] + x[r][1]) + (x[r][2] + x[r][3])) + ((x[r][4] + x[r][5]) + (x[r][6] + x[r][7]))) + (x[r][8] + x[r][9]);
        sum += __shfl_xor_sync(0xffffffffu, sum, 1);
        sum += __shfl_xor_sync(0xffffffffu, sum, 2);
        const float inv = rcp(sum);
#pragma unroll
        for (int i = 0; i < 10; i++) x[r][i] *= inv;
    }
#pragma unroll
    for (int ks = 0; ks < 2; ks++)
#pragma unroll
        for (int i = 0; i < 4; i++) {
            const uint32_t p = pack2(x[i & 1][ks * 4 + (i >> 1) * 2], x[i & 1][ks * 4 + (i >> 1) * 2 + 1]);
            pa[ks][i] = sg ? 0u : p;
            pa[2 + ks][i] = sg ? p : 0u;
        }
#pragma unroll
    for (int r = 0; r < 2; r++) {
        const uint32_t p = pack2(x[r][8], x[r][9]);
        pa[4][r] = sg ? 0u : p;
        pa[4][2 + r] = sg ? p : 0u;
    }
}
__device__ __forceinline__ void qa_values(float* O, uint32_t (*pa)[4], Cons& c) {
    wait_full(c);
    const uint32_t st = c.sb + c.p.stage * STAGE;
    const uint64_t dv = mkdesc(st + c.wg * 8192, 16384, 1024, 1), dm = mkdesc(st + 32768 + c.wg * 4096, 2048, 128, 0);
    pin<20>(&pa[0][0]);
    wg_fence();
#pragma unroll
    for (int ks = 0; ks < 4; ks++) wgmma_rs128<1>(O, pa[ks], dv + ks * 128, ks != 0);
    wgmma_rs128<0>(O, pa[4], dm, 1);
    wg_commit();
    pipe_next(c.p);
}
__device__ __forceinline__ void epi_qa(const float* acc, Cons& c, Pend& d, int mb, int nb) {
    uint32_t q[64], pa[2][5][4];
    float S0[32] = {}, M0[8] = {}, S1[32] = {}, M1[8] = {}, O0[64] = {}, O1[64] = {};
    const uint32_t k0 = c.p.stage;
    pack_half(q, acc);
    pin<32>(q); pin<32>(S0); pin<8>(M0);
    qa_scores(S0, M0, q, c);
    pack_half(q + 32, acc + 64);
    pin<32>(q + 32); pin<32>(S1); pin<8>(M1);
    qa_scores(S1, M1, q + 32, c);
    wg_wait<1>();
    pin<32>(S0); pin<8>(M0);
    release(c, k0);
    qa_softmax(pa[0], S0, M0, c);
    wg_wait<0>();
    pin<32>(S1); pin<8>(M1); pin<64>(q);
    release(c, (k0 + 1) & (NSTAGE - 1));
    pin<64>(O0);
    qa_values(O0, pa[0], c);
    qa_softmax(pa[1], S1, M1, c);
    pin<64>(O1);
    qa_values(O1, pa[1], c);
    wg_wait<1>();
    pin<64>(O0); pin<20>(&pa[0][0][0]);
    release(c, (k0 + 2) & (NSTAGE - 1));
    pack_half(d.pk, O0);
    wg_wait<0>();
    pin<64>(O1); pin<20>(&pa[1][0][0]);
    release(c, (k0 + 3) & (NSTAGE - 1));
    pack_half(d.pk + 32, O1);
    d.kind = PEND_KVO; d.row = 4096 + mb * 256 + c.rank * 128 + c.wg * 64; d.col = nb * 256; d.cnt = C_O + mb;
}

__device__ __forceinline__ void epi_op(const float* acc, const Cons& c, Pend& d, int mb, int nb) {
    pack_half(d.pk, acc); pack_half(d.pk + 32, acc + 64);
    d.kind = PEND_OUT; d.row = mb * 256 + c.rank * 128 + c.wg * 64; d.col = 1024 + nb * 256;
}

__device__ __forceinline__ void epi_a2(float* acc, const Params& P, Cons& c, int mb, int col0) {
    const int g = c.lane >> 2, t = c.lane & 3;
    const int row = mb * 256 + (g >> 1) * 64 + (c.rank * 16 + c.wg * 8 + c.wq * 2) * 2 + (g & 1);
    float* o = P.out + (size_t)row * 2048 + col0 + t * 2;
#pragma unroll 1
    for (int hf = P.zero; hf < 2; hf++) {
    wait_full(c);
    const uint32_t st = c.sb + c.p.stage * STAGE, xa = st + (c.wg * 64 + c.wq * 16 + g) * 128 + t * 4 + (g << 4), da = st + 32768 + t * 4;
#pragma unroll
    for (int j = 0; j < 16; j++) {
        const float* a = acc + j * 4;
        const uint32_t ad = (xa ^ ((j & 7) << 4)) + (j >> 3) * 16384;
        const uint32_t x0 = lds32(ad), x1 = lds32(ad + 1024), dv = lds32(da + j * 16);
        const uint32_t u0 = mul_bf2(x0, dv), u1 = mul_bf2(x1, dv);
        st_stream2(o + j * 8, a[0] + bf_lo(u0), a[1] + bf_hi(u0));
        st_stream2(o + 2 * 2048 + j * 8, a[2] + bf_lo(u1), a[3] + bf_hi(u1));
    }
    __syncwarp();
    release(c, c.p.stage);
    pipe_next(c.p);
    o += 128;
#pragma unroll
    for (int i = 0; i < 64; i++) acc[i] = acc[64 + i];
    }
}

#define TSTAMP(i)
__device__ __forceinline__ float2 cmul(float2 a, float2 b) { return make_float2(fmaf(a.x, b.x, -a.y * b.y), fmaf(a.x, b.y, a.y * b.x)); }
__device__ __forceinline__ float2 cfma(float2 a, float2 b, float2 u) { return make_float2(fmaf(a.x, b.x, fmaf(-a.y, b.y, u.x)), fmaf(a.x, b.y, fmaf(a.y, b.x, u.y))); }
__device__ __forceinline__ float4 ssm_coef(float lre, float lim, float logdt) {
    const float dt = __bfloat162float(__float2bfloat16(expf(logdt)));
    const float ea = expf(dt * lre);
    float sn, cn;
    sincosf(dt * lim, &sn, &cn);
    const float br = ea * cn, bi = ea * sn, nr = br - 1.f;
    float cr, ci;
    if (fabsf(lre) >= fabsf(lim)) { const float r = lim / lre, dn = lre + lim * r; cr = (nr + bi * r) / dn; ci = (bi - nr * r) / dn; }
    else { const float r = lre / lim, dn = lre * r + lim; cr = (nr * r + bi) / dn; ci = (bi * r - nr) / dn; }
    return make_float4(br, bi, cr, ci);
}
__device__ __forceinline__ void epi_a1(const float* acc, const Params& P, const Cons& c, Pend& d, int mb, int nb, uint32_t atag) {
    const int t = c.lane & 3;
    const int p = nb * 128 + c.rank * 64 + c.wg * 32 + c.wq * 8 + (c.lane >> 2);
    const float4 cf = __ldcg(&g_coef[p]);
    const float2 lam = make_float2(cf.x, P.swap_ri ? -cf.y : cf.y);
    const float a0 = P.swap_ri ? -2.f * cf.w : 2.f * cf.z, a1 = P.swap_ri ? 2.f * cf.z : -2.f * cf.w;
    const float b0 = P.swap_ri ? -2.f * cf.z : -2.f * cf.w, b1 = P.swap_ri ? -2.f * cf.w : -2.f * cf.z;
    float2 h = make_float2(0.f, 0.f);
#pragma unroll 1
    for (int round = P.zero; round < 2; round++) {
#pragma unroll
        for (int j = 0; j < 32; j++) {
            h = cfma(lam, h, make_float2(acc[j * 4], acc[j * 4 + 2]));
            const float r0 = fmaf(a0, h.x, a1 * h.y), m0 = fmaf(b0, h.x, b1 * h.y);
            h = cfma(lam, h, make_float2(acc[j * 4 + 1], acc[j * 4 + 3]));
            d.pk[j * 2] = pack2(r0, fmaf(a0, h.x, a1 * h.y));
            d.pk[j * 2 + 1] = pack2(m0, fmaf(b0, h.x, b1 * h.y));
        }
        if (round) continue;
        float2 l64 = lam;
#pragma unroll
        for (int i = 0; i < 6; i++) l64 = cmul(l64, l64);
        const float2 l128 = cmul(l64, l64), l256 = cmul(l128, l128);
        float2 o = make_float2(__shfl_up_sync(0xffffffffu, h.x, 1), __shfl_up_sync(0xffffffffu, h.y, 1));
        if (t >= 1) h = cfma(l64, o, h);
        o = make_float2(__shfl_up_sync(0xffffffffu, h.x, 2), __shfl_up_sync(0xffffffffu, h.y, 2));
        if (t >= 2) h = cfma(l128, o, h);
        IP(2)
        if (t == 3) st_relaxed2(&g_agg[mb * 1024 + p], (__float_as_uint(h.x) & ~1u) | atag, __float_as_uint(h.y));
        h = make_float2(__shfl_up_sync(0xffffffffu, h.x, 1), __shfl_up_sync(0xffffffffu, h.y, 1));
        if (t == 0) h = make_float2(0.f, 0.f);
        uint32_t ax[7], ay[7];
        int n = 0;
        while (true) {
            uint32_t bad = 0;
#pragma unroll
            for (int j = 0; j < 7; j++) { ax[j] = atag; ay[j] = 0; ld_relaxed2_if(ax[j], ay[j], &g_agg[j * 1024 + p], j < mb); }
#pragma unroll
            for (int j = 0; j < 7; j++) bad |= ax[j] ^ atag;
            if (tags_ok(bad)) break;
            __nanosleep(2 * POLLNS);
            if (++n > SPIN_LIMIT) spin_fault();
        }
        float2 carry = make_float2(0.f, 0.f);
#pragma unroll
        for (int j = 0; j < 7; j++) if (j < mb) carry = cfma(l256, carry, make_float2(__uint_as_float(ax[j]), __uint_as_float(ay[j])));
        float2 w = (t & 1) ? l64 : make_float2(1.f, 0.f);
        if (t & 2) w = cmul(w, l128);
        h = cfma(w, carry, h);
        IP(3)
    }
    IP(4)
    d.kind = PEND_HT; d.row = nb * 128 + c.rank * 64 + c.wg * 32; d.col = mb * 256; d.cnt = C_HT + mb;
}

__device__ __forceinline__ uint32_t fresh_tid() { uint32_t t; asm volatile("mov.u32 %0, %%tid.x;" : "=r"(t)); return t; }
__device__ __forceinline__ uint32_t acquire_stage(uint32_t sb, Pipe& p, uint32_t bytes) {
    mbar_wait(sb + B_EMPTY + p.stage * 8, p.phase ^ 1);
    mbar_expect_e(sb + B_FULL + p.stage * 8, bytes);
    return p.stage;
}
__device__ __forceinline__ void producer(const Params& P, const uint32_t sb, const int cta, const uint32_t epoch) {
    Pipe p = {0, 0};
    const uint32_t e1 = epoch + 1;
    const int rank = cta & 1;
    const uint16_t both = 3 << (__shfl_sync(0xffffffffu, cluster_rank(), 0) & ~1u);
    for (int it = ITEM_OFF(cta >> 1); it < ITEM_OFF((cta >> 1) + 1); it++) {
        const int item = ITEM(it), kind = (item >> 8) & 7, mb = (item >> 5) & 7;
        const int half = kind >= T_OPH, type = half ? kind * 2 - 10 : kind, nb = item & (half ? 3 : 31), hw = item >> 2 & half;
        if (type == T_CHAIN) {
            const int h = cta / 3, role = cta - h * 3;
            uint32_t* flag = &g_cnt(C_FLAG + (role == 2 ? 32 : 0) + h);
            if (role) { wait_count(&g_cnt(C_KV), e1 * 128); fence_async(); }
#pragma unroll 1
            for (int s = 0; s < 64 && role != 0; s++) {
                if (s < 63) {
                    mbar_wait(sb + B_GO, s & 1);
                    tma3d_mc_e(sb + S_KV + (role - 1) * 8192, &P.tm[M_SEG], 0, (role - 1) * 2048 + s * 32, h * 2, sb + B_KVFULL, 7 << ((h & 1) * 3));
                    if ((s & 7) == 7) { wait_count(&g_cnt(C_KV + 1 + (s >> 3)), e1 * 128); fence_async(); }
                    tma_prefetch3d_e(&P.tm[M_SEG], 0, (role - 1) * 2048 + s * 32 + 32, h * 2);
                }
                if (s > 0 && ((s & 3) == 0 || s == 63)) {
                    const int i = (s - 1) >> 2;
                    mbar_wait(sb + B_PERS, i & 1);
                    asm volatile("{\n.reg .pred E;\nelect.sync _|E, 0xffffffff;\n@E st.release.gpu.global.u32 [%0], %1;\n}" ::"l"(flag), "r"(epoch * 64 + i * 4 + 4) : "memory");
                }
            }
            if (role == 0) {
                const int lane = threadIdx.x & 31;
                if (lane == 0) mbar_arrive(sb + B_RELM);
#pragma unroll 1
                for (int s = 0; s < 63; s++) {
                    mbar_wait(sb + B_P1, s & 1);
                    if (s > 0) {
                        st_relaxed4(P.xb + xg_buf(s - 1) + h * 2048 + xg_lane(lane), 0, 0, 0, 0);
                        st_relaxed1(P.xb + xg_buf(s - 1) + xg_side(h) + lane * 4, 0);
                        __threadfence();
                    }
                    __syncwarp();
                    if (lane == 0) mbar_arrive(sb + B_RELM);
                }
            }
            mbar_wait(sb + B_RESUME, 0);
            continue;
        }
        const int m0 = mb * 256 + rank * 128;
        if (type <= T_OP) {
            const CUtensorMap* ma = &P.tm[half ? M_OAH : type == T_OP ? M_OA : M_BX];
            const CUtensorMap* mw = &P.tm[type == T_OP ? M_WO : type == T_QA ? M_WQ : nb < 16 ? M_WK : M_WV];
            const int nk = type == T_OP ? 64 : 16, nc = (nb & 15) * 4 + rank * 2, ma0 = type == T_OP ? 4096 + m0 + hw * 64 : m0;
            if (type == T_OP) { wait_count(&g_cnt(C_O + mb), e1 * 64); fence_async(); }
            if (type == T_QA) {
                wait_count(&g_cnt(C_KV + mb), e1 * 128);
                fence_async();
            }
            auto arrived = [&]() {
                const uint32_t t = fresh_tid();
                return __all_sync(0xffffffffu, (int32_t)(ld_acquire(&g_cnt(C_FLAG + (t & 2) * 16 + nb * 2 + (t & 1))) - (epoch * 64 + mb * 8 + rank * 4 + 4)) >= 0);
            };
            bool passed = false;
#pragma unroll 1
            for (int kt = 0; kt < nk; kt++) {
                if (type == T_QA && kt == 9) passed = arrived();
                const uint32_t st = acquire_stage(sb, p, STAGE - half * 8192), bar = sb + B_FULL + st * 8;
                tma2d_e(sb + st * STAGE + hw * 8192, ma, kt * 64, ma0, bar, P.pol[4 + type]);
                tma3d_mc_e(sb + st * STAGE + 16384 + rank * 16384, mw, 0, kt * 64, nc, bar, both);
                if (type == T_QA && kt < 8) tma_prefetch2d_e(&P.tm[M_OA], nb * 256 + (kt & 3) * 64, (kt >> 2) * 2048 + m0);
                pipe_next(p);
            }
            if (type == T_QA) {
                for (int n = 0; !passed; n++) { passed = arrived(); if (!passed) __nanosleep(200); if (n > SPIN_LIMIT) spin_fault(); }
                fence_async();
#pragma unroll 1
                for (int e = 0; e < 4; e++) {
                    const uint32_t st = acquire_stage(sb, p, 40960), bar = sb + B_FULL + st * 8, dst = sb + st * STAGE;
                    tma2d_e(dst, &P.tm[M_OA], nb * 256 + (e & 1) * 128, (e >> 1) * 2048 + m0, bar, P.pol[3]);
                    tma2d_e(dst + 16384, &P.tm[M_OA], nb * 256 + (e & 1) * 128 + 64, (e >> 1) * 2048 + m0, bar, P.pol[3]);
                    const uint32_t* src = ((e >> 1) ? g_vmt : g_km) + ((mb * 8 + rank * 4) * 32 + nb * 2 + (e & 1)) * 512;
#pragma unroll 1
                    for (int i = 0; i < 4; i++) bulk_g2s_e(dst + 32768 + i * 2048, src + i * 32 * 512, 2048, bar);
                    pipe_next(p);
                }
            }
        } else if (type == T_A1) {
            wait_count(&g_cnt(C_COEF), e1 * 4);
            l2_prefetch_e(g_coef + nb * 128 + rank * 64, 1024);
#pragma unroll 1
            for (int kt = 0; kt < 16; kt++) {
                const uint32_t st = acquire_stage(sb, p, STAGE), bar = sb + B_FULL + st * 8;
                tma4d_e(sb + st * STAGE, &P.tm[M_AB], kt * 64, nb * 16 + rank * 8, bar);
                tma4d_mc_e(sb + st * STAGE + 16384 + rank * 16384, &P.tm[M_AX], kt * 64, mb * 128 + rank * 16, bar, both);
                pipe_next(p);
            }
        } else {
            wait_count(&g_cnt(C_HT + mb), e1 * 32);
            fence_async();
#pragma unroll 1
            for (int kt = 0; kt < 32; kt++) {
                const uint32_t st = acquire_stage(sb, p, STAGE - half * 8192), bar = sb + B_FULL + st * 8;
                tma3d_e(sb + st * STAGE + hw * 8192, &P.tm[half ? M_HTH : M_HT], 0, kt * 64, mb * 4 + rank * 2 + hw, bar, P.pol[7]);
                tma2d_mc_e(sb + st * STAGE + 16384 + rank * 16384, &P.tm[M_CRE] + (kt >> 4), (kt & 15) * 64, (nb * 2 + rank) * 128, bar, both);
                pipe_next(p);
            }
#pragma unroll 1
            for (int col = nb * 256; col < (nb + 1) * 256; col += 128) {
                const uint32_t st = acquire_stage(sb, p, 32768 + 256), bar = sb + B_FULL + st * 8;
                tma4d_e(sb + st * STAGE, &P.tm[M_AX], col, mb * 128 + rank * 16, bar);
                tma4d_e(sb + st * STAGE + 16384, &P.tm[M_AX], col + 64, mb * 128 + rank * 16, bar);
                bulk_g2s_e(sb + st * STAGE + 32768, P.Dskip + col, 256, bar);
                pipe_next(p);
            }
        }
    }
}

__device__ __forceinline__ uint32_t fresh_ctaid() { uint32_t t; asm volatile("mov.u32 %0, %%ctaid.x;" : "=r"(t)); return t; }
__device__ __forceinline__ void reset_state(const Params& P, Cons& c, Pend& d, uint32_t sb, bool resumed) {
    const uint32_t t = fresh_tid(), b = fresh_ctaid() + P.cta0;
    const int w = __shfl_sync(0xffffffffu, t >> 5, 0);
    c.sb = sb; c.wg = w >> 2; c.wq = w & 3; c.lane = t & 31;
    c.rank = __shfl_sync(0xffffffffu, b & 1, 0); c.pair = __shfl_sync(0xffffffffu, b >> 1, 0);
    c.rel = mapa(sb + B_EMPTY, cluster_rank() ^ (c.lane & 1));
    c.atag = (ld_acquire(&g_cnt(C_EPOCH)) + 1) & 1;
    c.p.stage = 0; c.p.phase = 0;
    c.nst = resumed && c.pair < NCHAIN;
    d = Pend{};
}
#define PROF_ITEM(i, item)

__global__ void __launch_bounds__(384, 1) fused_kernel(const __grid_constant__ Params P) {
    extern __shared__ __align__(1024) uint8_t smem[];
    const uint32_t sb = smem_u32(smem);
    asm volatile("griddepcontrol.launch_dependents;");
    declare_fence(P.zero);
    const int tid = threadIdx.x, lane = tid & 31;
    const int warp = __shfl_sync(0xffffffffu, tid >> 5, 0);
    const int cta = __shfl_sync(0xffffffffu, blockIdx.x + P.cta0, 0), pair = cta >> 1, rank = cta & 1;
    if (tid == 0) {
        if (sb & 1023) spin_fault();
        for (int i = 0; i < NSTAGE; i++) { mbar_init(sb + B_FULL + i * 8, 1); mbar_init(sb + B_EMPTY + i * 8, 16); }
        mbar_init(sb + B_RESUME, 2);
        mbar_init(sb + B_KVFULL, 1);
        mbar_init(sb + B_GO, 3); mbar_init(sb + B_RED, 8); mbar_init(sb + B_P1, 1); mbar_init(sb + B_PERS, 8); mbar_init(sb + B_INIT, 8); mbar_init(sb + B_INIT2, 8);
        mbar_init(sb + B_READY, 8);
        for (int i = 0; i < 2; i++) { mbar_init(sb + B_SFULL + i * 8, 4); mbar_init(sb + B_SFREE + i * 8, 1); }
        mbar_init(sb + B_RELM, cta % 3 ? 1 : 2); mbar_init(sb + B_X, 9);
        asm volatile("fence.mbarrier_init.release.cluster;" ::: "memory");
        mbar_expect(sb + B_X, 4096);
        sts64(sb + S_EV, 0, 0); sts32(sb + S_RETRY, 0);
    }
    cluster_sync();
    if (warp >= 8) {
        asm volatile("setmaxnreg.dec.sync.aligned.u32 24;");
        if (warp == 8) {
            producer(P, sb, cta, __shfl_sync(0xffffffffu, ld_acquire(&g_cnt(C_EPOCH)), 0));
            asm volatile("barrier.cluster.arrive.relaxed.aligned;\nbarrier.cluster.wait.aligned;" ::: "memory");
        } else if (warp == 9) {
            for (int i = 0; i < P.pd; i++) __nanosleep(1000);
            if (pair < 64) l2_prefetch((const char*)(rank ? P.Wo : P.Wq) + (size_t)(pair * 32 + lane) * 4096, 4096);
            if (pair < NCHAIN) pacer(P, sb, cta, lane, __shfl_sync(0xffffffffu, ld_acquire(&g_cnt(C_EPOCH)), 0));
        } else {
            store_warp(P, sb, warp - 10, cta);
        }
    } else {
        asm volatile("setmaxnreg.inc.sync.aligned.u32 240;");
        Cons c;
        Pend d;
        if (pair < NCHAIN) {
            reset_state(P, c, d, sb, false);
            {
                const int item = ITEM(ITEM_OFF(pair));
                PROF_ITEM(0, item)
                float acc[128];
                mainloop<true>(acc, P, c, d, T_KV, 16);
                ISTAMP(4)
                mbar_wait(sb + B_EMPTY + warp * 20480 / STAGE * 8, 1);
                mbar_wait(sb + B_EMPTY + (warp * 20480 + 20479) / STAGE * 8, 1);
                chain_load(P, sb, cta, warp, lane, 0);
                epi_kv(acc, c, d, (item >> 5) & 7, item & 31);
            }
            ISTAMP(9)
            mbar_wait(sb + B_EMPTY + 3 * 8, 1);
            drain_both(c, d);
            ISTAMP(10)
            uint32_t wr[40][4];
            chain_fetch(P, sb, cta, warp, lane, wr);
            PROF_ITEM(1, T_CHAIN << 8)
            chain_bounds(sb, cta, warp, lane, wr);
            ISTAMP(11)
            const uint32_t epoch = __shfl_sync(0xffffffffu, ld_acquire(&g_cnt(C_EPOCH)), 0);
            if (warp < 4) chain_role<false>(P, sb, cta, warp, lane, epoch, wr);
            else chain_role<true>(P, sb, cta, warp, lane, epoch, wr);
            fence_async_smem();
            bar_sync(1, 256);
            const uint32_t t2 = fresh_tid();
            if (t2 < 2) mbar_arrive_cluster(mapa(sb + B_RESUME, cluster_rank() ^ t2));
        } else if (pair >= NPAIR - 2) {
            const int ch = (pair - (NPAIR - 2)) * 512 + rank * 256 + tid;
            g_coef[ch] = ssm_coef(__bfloat162float(P.Lre[ch]), __bfloat162float(P.Lim[ch]), __bfloat162float(P.logdt[ch]));
            bar_sync(1, 256);
            if (tid == 0) red_release(&g_cnt(C_COEF));
        }
        reset_state(P, c, d, sb, true);
        int it = ITEM_OFF(c.pair) + (c.pair < NCHAIN ? 2 : 0), next = ITEM(it);
        const int end = ITEM_OFF(c.pair + 1);
        for (;; it++) {
            const bool last = it == end;
            const int item = next, kind = (item >> 8) & 7, mb = (item >> 5) & 7;
            const int half = kind >= T_OPH, type = half ? kind * 2 - 10 : kind, nb = item & (half ? 3 : 31);
            const bool idle = half && (item >> 2 & 1) != c.wg;
            if (d.kind != PEND_NONE && (last || idle || (ITEM(it - 1) & URGENT) || !bar_and(5 + c.wg, mbar_try(sb + B_FULL + c.p.stage * 8, c.p.phase)))) {
#pragma unroll 1
                while (d.kind != PEND_NONE) drain(P, c, d);
            }
            if (last) break;
            next = ITEM(it + 1);
            const int nk = type == T_OP ? 64 : type == T_A2 ? 32 : 16;
            PROF_ITEM(it - ITEM_OFF(c.pair), item)
            if (idle) {
#pragma unroll 1
                for (int kt = nk + (type == T_A2 ? 2 : 0); kt > 0; kt--) { wait_full(c); release(c, c.p.stage); pipe_next(c.p); }
                continue;
            }
            float acc[128];
            mainloop(acc, P, c, d, type, nk);
            if (type == T_KV) epi_kv(acc, c, d, mb, nb);
            else if (type == T_QA) epi_qa(acc, c, d, mb, nb);
            else if (type == T_OP) epi_op(acc, c, d, mb, nb);
            else if (type == T_A1) epi_a1(acc, P, c, d, mb, nb, c.atag);
            else epi_a2(acc, P, c, mb, nb * 256);
        }
        staging_wait(c);
        staging_post(c, PEND_NONE, 0, 0, 0);
        cluster_sync();
        if (c.wg == 0 && c.wq == 0 && c.lane == 0 && atomicInc(&g_cnt(C_DONE), NPAIR * 2 - 1) == NPAIR * 2 - 1) { __threadfence(); atomicAdd(&g_cnt(C_EPOCH), 1); }
    }
}

typedef CUresult (*EncodeFn)(CUtensorMap*, CUtensorMapDataType, cuuint32_t, void*, const cuuint64_t*, const cuuint64_t*, const cuuint32_t*, const cuuint32_t*,
                             CUtensorMapInterleave, CUtensorMapSwizzle, CUtensorMapL2promotion, CUtensorMapFloatOOBfill);
void encode(EncodeFn fn, CUtensorMap* m, const void* base, int rank, const uint64_t* dims, const uint64_t* strides, const uint32_t* box, CUtensorMapSwizzle swz = CU_TENSOR_MAP_SWIZZLE_128B) {
    cuuint64_t d[5], s[5]; cuuint32_t b[5], e[5];
    for (int i = 0; i < rank; i++) { d[i] = dims[i]; b[i] = box[i]; e[i] = 1; if (i) s[i - 1] = strides[i - 1]; }
    fn(m, CU_TENSOR_MAP_DATA_TYPE_BFLOAT16, rank, (void*)base, d, s, b, e, CU_TENSOR_MAP_INTERLEAVE_NONE, swz,
       CU_TENSOR_MAP_L2_PROMOTION_L2_256B, CU_TENSOR_MAP_FLOAT_OOB_FILL_NONE);
}
void map_kmajor(EncodeFn fn, CUtensorMap* m, const void* base, uint64_t rows, uint64_t cols, uint32_t box_rows) {
    const uint64_t d[2] = {cols, rows}, s[1] = {cols * 2}; const uint32_t b[2] = {64, box_rows};
    encode(fn, m, base, 2, d, s, b);
}
void map_mnmajor(EncodeFn fn, CUtensorMap* m, const void* base, uint64_t krows, uint64_t cols, uint32_t groups = 2) {
    const uint64_t d[3] = {64, krows, cols / 64}, s[2] = {cols * 2, 128}; const uint32_t b[3] = {64, 64, groups};
    encode(fn, m, base, 3, d, s, b);
}

}

extern "C" void kernel_launch(void* const* d_in, const int* in_sizes, int n_in, void* d_out, int out_size) {
    static Params P;
    static EncodeFn fn = nullptr;
    if (!fn) {
        cudaDriverEntryPointQueryResult q;
        cudaGetDriverEntryPoint("cuTensorMapEncodeTiled", (void**)&fn, cudaEnableDefault, &q);
        cudaFuncSetAttribute(fused_kernel, cudaFuncAttributeMaxDynamicSharedMemorySize, S_TOTAL);
    }
    const bf16* in[15];
    for (int i = 0; i < 15; i++) in[i] = (const bf16*)d_in[i];
    void *kvo, *ht;
    cudaGetSymbolAddress(&kvo, g_kvo);
    cudaGetSymbolAddress(&ht, g_ht);
    map_kmajor(fn, &P.tm[M_BX], in[9], 2048, 1024, 128);
    map_mnmajor(fn, &P.tm[M_WQ], in[11], 1024, 4096);
    map_mnmajor(fn, &P.tm[M_WK], in[12], 1024, 4096);
    map_mnmajor(fn, &P.tm[M_WV], in[13], 1024, 4096);
    map_mnmajor(fn, &P.tm[M_WO], in[14], 4096, 1024);
    map_kmajor(fn, &P.tm[M_OA], kvo, 3 * 2048, 4096, 128);
    P.swap_ri = in[4] < in[3];
    {
        const bf16* lo = P.swap_ri ? in[4] : in[3];
        const uint64_t diff = (uint64_t)((const char*)(P.swap_ri ? in[3] : in[4]) - (const char*)lo);
        const uint64_t d[4] = {1024, 8, 2, 128}, s[3] = {2048, diff, 16384}; const uint32_t b[4] = {64, 8, 2, 8};
        encode(fn, &P.tm[M_AB], lo, 4, d, s, b);
    }
    {
        const uint64_t d[4] = {1024, 2, 4, 1024}, s[3] = {2048, 64 * 2048, 4096}; const uint32_t b[4] = {64, 2, 4, 16};
        encode(fn, &P.tm[M_AX], in[0], 4, d, s, b);
    }
    map_mnmajor(fn, &P.tm[M_HT], ht, 2048, 2048);
    map_kmajor(fn, &P.tm[M_CRE], in[5], 1024, 1024, 128);
    map_kmajor(fn, &P.tm[M_CIM], in[6], 1024, 1024, 128);
    map_kmajor(fn, &P.tm[M_KVO], kvo, 3 * 2048, 4096, 32);
    map_kmajor(fn, &P.tm[M_HTS], ht, 2048, 2048, 32);
    map_kmajor(fn, &P.tm[M_OAH], kvo, 3 * 2048, 4096, 64);
    map_mnmajor(fn, &P.tm[M_HTH], ht, 2048, 2048, 1);
    for (int i = 0; i < 3; i++) {
        const uint64_t d[3] = {64, 1024, 64}, s[2] = {8192, 128}; const uint32_t b[3] = {64, 16, 2};
        encode(fn, &P.tm[M_C1 + i], in[11 + i], 3, d, s, b);
    }
    {
        const uint64_t d[2] = {1024, 4096}, s[1] = {2048}; const uint32_t b[2] = {32, 32};
        encode(fn, &P.tm[M_CO], in[14], 2, d, s, b, CU_TENSOR_MAP_SWIZZLE_64B);
    }
    {
        const uint64_t d[3] = {64, 3 * 2048, 64}, s[2] = {8192, 128}; const uint32_t b[3] = {64, 32, 2};
        encode(fn, &P.tm[M_SEG], kvo, 3, d, s, b);
    }
    void* xs;
    cudaGetSymbolAddress(&xs, g_x);
    P.xb = (uint8_t*)(((uintptr_t)xs + (2u << 20) - 1) & ~(uintptr_t)((2u << 20) - 1));
    P.Wq = in[11]; P.Wk = in[12]; P.Wv = in[13]; P.Wo = in[14]; P.mem0 = in[10]; P.Bx = in[9];
    P.Ax = in[0]; P.Lre = in[1]; P.Lim = in[2]; P.logdt = in[7]; P.Dskip = in[8];
    P.out = (float*)d_out;
    int pv[10] = {1300, 0, 110, 0, 330, 0, 32, 32, 6, 0};
    int ef = 11;
    for (int i = 0; i < 8; i++) P.pol[i] = (ef >> i & 1) ? 0x12F0000000000000ull : 0x1000000000000000ull;
    P.dly = pv[0]; P.mrg = pv[2];
    P.rd = pv[4]; P.guard = pv[5]; P.clampv = pv[6]; P.clamp0 = pv[7]; P.kvd = pv[9]; P.xd = pv[8]; P.pd = pv[1];
    cudaLaunchConfig_t cfg = {};
    cudaLaunchAttribute at[2];
    cfg.blockDim = dim3(384); cfg.dynamicSmemBytes = S_TOTAL; cfg.stream = cudaStreamPerThread; cfg.attrs = at;
    at[0].id = cudaLaunchAttributeClusterDimension;
    at[0].val.clusterDim.y = at[0].val.clusterDim.z = 1;
    at[1].id = cudaLaunchAttributeProgrammaticStreamSerialization;
    at[1].val.programmaticStreamSerializationAllowed = 1;
    for (int i = 0; i < 2; i++) {
        P.cta0 = i ? 2 * NCHAIN : 0;
        cfg.gridDim = dim3(i ? 2 * (NPAIR - NCHAIN) : 2 * NCHAIN);
        at[0].val.clusterDim.x = i ? 2 : 6;
        cfg.numAttrs = 1 + i;
        cudaLaunchKernelEx(&cfg, fused_kernel, P);
    }
}
```

```cpp
#include <cuda_runtime.h>
#include <cuda_bf16.h>
#include <cuda.h>
#include <stdint.h>
#include <string.h>

typedef __nv_bfloat16 bf16;

namespace {

constexpr int SPIN_LIMIT = 1 << 22;
#define POLLNS 100
constexpr int NPAIR = 66;
constexpr int NCHAIN = 48;
enum { T_KV = 0, T_QA = 1, T_OP = 2, T_A1 = 3, T_A2 = 4, T_CHAIN = 5, T_OPH = 6, T_A2H = 7 };
constexpr int URGENT = 2048;
enum { M_BX = 0, M_WQ, M_WK, M_WV, M_WO, M_OA, M_AB, M_AX, M_HT, M_CRE, M_CIM, M_KVO, M_HTS, M_OAH, M_HTH, M_C1, M_CO = M_C1 + 3, M_SEG, M_COUNT };
enum { C_KV = 0, C_O = 8, C_HT = 16, C_DONE = 24, C_EPOCH = 25, C_COEF = 26, C_XMAX = 27, C_XCNT = 28, C_FLAG = 32 };

struct Params {
    CUtensorMap tm[M_COUNT];
    const bf16 *Wq, *Wk, *Wv, *Wo, *mem0, *Bx, *Ax, *Lre, *Lim, *logdt, *Dskip;
    float* out;
    uint8_t* xb;
    int swap_ri, zero;
    int dly, mrg, rd, guard, clampv, clamp0, kvd, xd, pd;
    uint64_t pol[12];
    uint16_t cta0;
};

__constant__ uint16_t c_off[67] = {0, 5, 10, 15, 20, 25, 30, 35, 40, 45, 50, 55, 60, 65, 70, 75, 80, 85, 90, 95, 100, 105, 110, 115, 120, 125, 130, 135, 140, 145, 150, 155, 160, 165, 170, 175, 180, 185, 190, 195, 200, 205, 210, 214, 218, 222, 226, 230, 234, 253, 272, 291, 310, 329, 348, 367, 386, 405, 424, 443, 462, 481, 500, 519, 537, 556, 574};
__constant__ uint16_t c_items[640] = {
    0, 1280, 2497, 3008, 1728, 16, 1280, 2498, 3009, 1732, 32, 1280, 2499, 3010, 1729, 1, 1280, 2500, 3011, 1733, 17, 1280, 2501, 3012,
    1730, 33, 1280, 2502, 3013, 1734, 2, 1280, 2503, 3014, 1731, 18, 1280, 2504, 3015, 1735, 34, 1280, 2505, 3040, 1760, 3, 1280, 2506,
    3041, 1764, 19, 1280, 2507, 3042, 1761, 35, 1280, 2508, 3043, 1765, 4, 1280, 2509, 3044, 1762, 20, 1280, 2510, 3045, 1766, 36, 1280,
    2511, 3046, 1763, 5, 1280, 2528, 3047, 1767, 21, 1280, 2529, 838, 1024, 37, 1280, 2530, 839, 1025, 6, 1280, 2531, 2912, 1026, 22,
    1280, 2532, 2913, 1027, 38, 1280, 2533, 2914, 1056, 7, 1280, 2534, 2915, 1057, 23, 1280, 2535, 2916, 1058, 39, 1280, 2536, 2917, 1059,
    8, 1280, 2537, 2918, 1088, 24, 1280, 2538, 2919, 1089, 40, 1280, 2539, 2944, 1090, 9, 1280, 2540, 2945, 1091, 25, 1280, 2541, 2946,
    1120, 41, 1280, 2542, 2947, 1121, 10, 1280, 2543, 2948, 1122, 26, 1280, 773, 2949, 1123, 42, 1280, 774, 2950, 1152, 11, 1280, 775,
    2951, 1153, 27, 1280, 800, 2976, 1154, 43, 1280, 801, 2977, 1155, 12, 1280, 802, 2978, 1184, 28, 1280, 803, 2979, 1185, 44, 1280,
    804, 2980, 1186, 13, 1280, 805, 2981, 1187, 29, 1280, 806, 2982, 1216, 45, 1280, 807, 2983, 1217, 14, 1280, 837, 642, 30, 1280,
    836, 643, 46, 1280, 835, 672, 15, 1280, 834, 673, 31, 1280, 833, 674, 47, 1280, 832, 675, 48, 66, 84, 102, 256, 124,
    142, 160, 175, 191, 207, 224, 239, 298, 332, 366, 416, 769, 610, 49, 67, 85, 103, 257, 125, 143, 161, 176, 192, 208,
    225, 240, 299, 333, 367, 417, 770, 611, 50, 68, 86, 104, 258, 126, 144, 162, 177, 193, 209, 226, 241, 300, 334, 384,
    418, 771, 640, 51, 69, 87, 105, 259, 127, 145, 163, 178, 194, 210, 227, 242, 301, 335, 385, 419, 772, 641, 52, 70,
    88, 106, 260, 128, 146, 164, 179, 195, 211, 228, 243, 302, 352, 386, 420, 512, 1986, 53, 71, 89, 107, 261, 129, 147,
    165, 180, 196, 212, 229, 244, 303, 353, 387, 421, 513, 1990, 54, 72, 90, 108, 262, 130, 148, 166, 181, 197, 213, 230,
    245, 320, 354, 388, 422, 514, 1987, 55, 73, 91, 109, 263, 131, 149, 167, 182, 198, 214, 231, 246, 321, 355, 389, 423,
    515, 1991, 56, 74, 92, 110, 264, 132, 150, 168, 183, 199, 215, 232, 247, 322, 356, 390, 424, 544, 2016, 57, 75, 93,
    111, 265, 133, 151, 169, 184, 200, 216, 233, 248, 323, 357, 391, 425, 545, 2020, 58, 76, 94, 112, 266, 134, 152, 170,
    185, 201, 217, 234, 249, 324, 358, 392, 426, 546, 2017, 59, 77, 95, 113, 267, 135, 153, 171, 186, 202, 218, 235, 250,
    325, 359, 393, 427, 547, 2021, 60, 78, 96, 114, 268, 136, 154, 172, 187, 203, 219, 236, 251, 326, 360, 394, 428, 576,
    2018, 61, 79, 97, 115, 269, 137, 155, 173, 188, 204, 220, 237, 252, 327, 361, 395, 429, 577, 2022, 62, 80, 98, 116,
    270, 138, 156, 174, 189, 205, 221, 238, 253, 328, 362, 396, 430, 578, 2019, 63, 81, 99, 117, 271, 139, 157, 288, 190,
    292, 293, 296, 297, 331, 365, 399, 768, 609, 64, 82, 100, 118, 120, 122, 140, 158, 289, 206, 222, 294, 254, 329, 363,
    397, 431, 579, 2023, 65, 83, 101, 119, 121, 123, 141, 159, 290, 291, 223, 295, 255, 330, 364, 398, 2496, 608,
};
#define ITEM_OFF(p) c_off[p]
#define ITEM(i) c_items[i]

__device__ __align__(1024) bf16 g_kvo[3 * 2048 * 4096];
__device__ __align__(1024) bf16 g_ht[2048 * 2048];
__device__ __align__(1024) uint8_t g_x[4 << 20];
__device__ __align__(1024) uint32_t g_km[64 * 32 * 512];
__device__ __align__(1024) uint32_t g_vmt[64 * 32 * 512];
__device__ __align__(1024) float2 g_agg[8 * 1024];
__device__ __align__(1024) float4 g_coef[1024];
__device__ __align__(1024) uint32_t g_cntl[128 * 32];
#define g_cnt(i) g_cntl[(i) * 32]
__device__ __align__(1024) uint32_t g_hint[96 * 32];
#define PROF(i)
#define PROFDUMP()
#define PROFP(i)
constexpr int XG_SIDE = 65536, XG_T = 98304;
__device__ __forceinline__ uint32_t xg_buf(int b) { return (b & 1) * 128 + (b & 2) * 256 + (b & 4) * 32768; }
__device__ __forceinline__ uint32_t xg_lane(uint32_t lane) { return (lane >> 4) * 1024 + (lane & 8) * 32 + (lane & 7) * 16; }
__device__ __forceinline__ uint32_t xg_side(int b) { return XG_SIDE + (b >> 1) * 1024 + (b & 1) * 256; }

constexpr int STAGE = 49152, NSTAGE = 4;
constexpr int S_STG = NSTAGE * STAGE;
constexpr int S_BAR = S_STG + 32768;
constexpr int B_FULL = S_BAR, B_EMPTY = S_BAR + 32, B_RESUME = S_BAR + 64, B_KVFULL = S_BAR + 72, B_GO = S_BAR + 88, B_X = S_BAR + 96, B_PERS = S_BAR + 104,
              B_INIT = S_BAR + 112, B_RELM = S_BAR + 120, B_READY = S_BAR + 136, B_SFULL = S_BAR + 144, B_SFREE = S_BAR + 160, S_DESC = S_BAR + 176, B_RED = S_BAR + 216;
constexpr int S_EV = S_BAR + 80, S_EO = S_BAR + 84, B_INIT2 = S_BAR + 128, S_SC = S_BAR + 208, S_ISC = S_EV;
constexpr int S_XV = S_BAR + 256, S_LOG = S_XV + 2048;
constexpr int S_TOTAL = S_LOG + 768;
#define NRA 5
#define NRB 3
constexpr int S_W1 = 0;
constexpr int S_W2 = 4 * 4096 * (16 - NRA - NRB);
constexpr int S_KV = 188416;
constexpr int S_P1 = S_KV + 16384;
constexpr int S_X = S_P1 + 16384;
constexpr int S_SX = S_P1, S_OX = S_P1 + 2048;
constexpr int S_EM = S_X + 4096, S_TO = S_EM + 32, S_RETRY = S_BAR + 224, B_P1 = S_BAR + 232;
static_assert(S_TO + 32 <= S_BAR && S_KV % 1024 == 0 && S_TOTAL <= 232448, "chain smem layout");

template <int V> struct IC { static constexpr int value = V; };
template <int B, int E, typename F> __device__ __forceinline__ void static_for(F&& f) { if constexpr (B < E) { f(IC<B>{}); static_for<B + 1, E>(f); } }
__device__ __forceinline__ uint32_t cluster_rank() { uint32_t r; asm volatile("mov.u32 %0, %%cluster_ctarank;" : "=r"(r)); return r; }
__device__ __forceinline__ void spin_fault() { asm volatile("st.global.u32 [%0], 0;" ::"l"(0ull) : "memory"); }
__device__ __forceinline__ uint32_t smem_u32(const void* p) { return (uint32_t)__cvta_generic_to_shared(p); }
__device__ __forceinline__ uint32_t opq(uint32_t x, int lane) { return __shfl_sync(0xffffffffu, x, lane); }
__device__ __forceinline__ uint32_t mapa(uint32_t a, uint32_t r) { uint32_t d; asm volatile("mapa.shared::cluster.u32 %0, %1, %2;" : "=r"(d) : "r"(a), "r"(r)); return d; }
__device__ __forceinline__ void mma16816(float* d, uint32_t a0, uint32_t a1, uint32_t a2, uint32_t a3, uint32_t b0, uint32_t b1) {
    asm("mma.sync.aligned.m16n8k16.row.col.f32.bf16.bf16.f32 {%0,%1,%2,%3}, {%4,%5,%6,%7}, {%8,%9}, {%0,%1,%2,%3};"
        : "+f"(d[0]), "+f"(d[1]), "+f"(d[2]), "+f"(d[3]) : "r"(a0), "r"(a1), "r"(a2), "r"(a3), "r"(b0), "r"(b1));
}
__device__ __forceinline__ void mma1688(float* d, uint32_t a0, uint32_t a1, uint32_t b0) {
    asm("mma.sync.aligned.m16n8k8.row.col.f32.bf16.bf16.f32 {%0,%1,%2,%3}, {%4,%5}, {%6}, {%0,%1,%2,%3};"
        : "+f"(d[0]), "+f"(d[1]), "+f"(d[2]), "+f"(d[3]) : "r"(a0), "r"(a1), "r"(b0));
}
__device__ __forceinline__ void ldsm4(uint32_t* r, uint32_t a) {
    asm volatile("ldmatrix.sync.aligned.m8n8.x4.shared.b16 {%0,%1,%2,%3}, [%4];" : "=r"(r[0]), "=r"(r[1]), "=r"(r[2]), "=r"(r[3]) : "r"(a));
}
__device__ __forceinline__ void ldsm4t(uint32_t* r, uint32_t a) {
    asm volatile("ldmatrix.sync.aligned.m8n8.x4.trans.shared.b16 {%0,%1,%2,%3}, [%4];" : "=r"(r[0]), "=r"(r[1]), "=r"(r[2]), "=r"(r[3]) : "r"(a));
}
__device__ __forceinline__ void stsm4(uint32_t a, uint32_t r0, uint32_t r1, uint32_t r2, uint32_t r3) {
    asm volatile("stmatrix.sync.aligned.m8n8.x4.shared.b16 [%0], {%1,%2,%3,%4};" ::"r"(a), "r"(r0), "r"(r1), "r"(r2), "r"(r3) : "memory");
}
__device__ __forceinline__ void stsm4t(uint32_t a, uint32_t r0, uint32_t r1, uint32_t r2, uint32_t r3) {
    asm volatile("stmatrix.sync.aligned.m8n8.x4.trans.shared.b16 [%0], {%1,%2,%3,%4};" ::"r"(a), "r"(r0), "r"(r1), "r"(r2), "r"(r3) : "memory");
}
__device__ __forceinline__ uint32_t movm(uint32_t a) { uint32_t d; asm volatile("movmatrix.sync.aligned.m8n8.trans.b16 %0, %1;" : "=r"(d) : "r"(a)); return d; }
__device__ __forceinline__ uint32_t pack2(float lo, float hi) { uint32_t d; asm("cvt.rn.bf16x2.f32 %0, %1, %2;" : "=r"(d) : "f"(hi), "f"(lo)); return d; }
__device__ __forceinline__ uint32_t prmt(uint32_t a, uint32_t b, uint32_t s) { uint32_t d; asm("prmt.b32 %0, %1, %2, %3;" : "=r"(d) : "r"(a), "r"(b), "r"(s)); return d; }
__device__ __forceinline__ uint32_t pack2h(float lo, float hi) { uint32_t d; asm("cvt.rn.f16x2.f32 %0, %1, %2;" : "=r"(d) : "f"(hi), "f"(lo)); return d; }
__device__ __forceinline__ uint32_t h2bf(uint32_t a, uint32_t b) {
    uint32_t d;
    asm("{\n.reg .b16 l, h, u;\n.reg .f32 x, y;\nmov.b32 {l, u}, %1;\ncvt.f32.f16 x, l;\nmov.b32 {u, h}, %2;\ncvt.f32.f16 y, h;\ncvt.rn.bf16x2.f32 %0, y, x;\n}" : "=r"(d) : "r"(a), "r"(b));
    return d;
}
__device__ __forceinline__ void cvt_block(uint32_t* u, uint32_t& x, uint32_t sel) {
    const uint32_t a = prmt(u[0], u[0], sel), b = prmt(u[1], u[1], sel), c = prmt(u[2], u[2], sel), d = prmt(u[3], x, sel);
    x ^= u[3] ^ d;
    u[0] = h2bf(a, a); u[1] = h2bf(b, b); u[2] = h2bf(c, c); u[3] = h2bf(d, d);
}
__device__ __forceinline__ uint32_t amax(uint32_t a, uint32_t b) { uint32_t d; asm("max.xorsign.abs.bf16x2 %0, %1, %2;" : "=r"(d) : "r"(a), "r"(b)); return d; }
__device__ __forceinline__ uint32_t amax4(uint32_t m, const uint32_t* v) { return amax(amax(m, amax(v[0], v[1])), amax(v[2], v[3])); }
__device__ __forceinline__ uint32_t warp_exp(uint32_t m) { return __reduce_max_sync(0xffffffffu, max(m & 0x7f80u, (m >> 16) & 0x7f80u)) >> 7; }
__device__ __forceinline__ void red_max_shared(uint32_t a, uint32_t x) { asm volatile("red.shared.max.u32 [%0], %1;" ::"r"(a), "r"(x) : "memory"); }
__device__ __forceinline__ uint32_t mul_bf2(uint32_t a, uint32_t b) { uint32_t d; asm("mul.rn.bf16x2 %0, %1, %2;" : "=r"(d) : "r"(a), "r"(b)); return d; }
__device__ __forceinline__ float bf_lo(uint32_t u) { return __uint_as_float(u << 16); }
__device__ __forceinline__ float bf_hi(uint32_t u) { return __uint_as_float(u & 0xffff0000u); }
__device__ __forceinline__ float ex2(float x) { float y; asm("ex2.approx.ftz.f32 %0, %1;" : "=f"(y) : "f"(x)); return y; }
__device__ __forceinline__ float rcp(float x) { float y; asm("rcp.approx.ftz.f32 %0, %1;" : "=f"(y) : "f"(x)); return y; }
__device__ __forceinline__ void st_relaxed4(const void* p, uint32_t a, uint32_t b, uint32_t c, uint32_t d) {
    asm volatile("{\n.reg .b128 t;\nmov.b128 t, {%1,%2,%3,%4};\nst.relaxed.gpu.global.b128 [%0], t;\n}" ::"l"(p), "r"(a), "r"(b), "r"(c), "r"(d) : "memory");
}
__device__ __forceinline__ void st_relaxed2(const void* p, uint32_t a, uint32_t b) {
    asm volatile("{\n.reg .b64 t;\nmov.b64 t, {%1,%2};\nst.relaxed.gpu.global.b64 [%0], t;\n}" ::"l"(p), "r"(a), "r"(b) : "memory");
}
__device__ __forceinline__ void ld_relaxed2_if(uint32_t& a, uint32_t& b, const void* p, bool on) {
    asm volatile("{\n.reg .pred P;\n.reg .b64 t;\nsetp.ne.u32 P, %3, 0;\nmov.b64 t, {%0,%1};\n@P ld.relaxed.gpu.global.b64 t, [%2];\nmov.b64 {%0,%1}, t;\n}" : "+r"(a), "+r"(b) : "l"(p), "r"((uint32_t)on) : "memory");
}
__device__ __forceinline__ void ld_relaxed4(uint32_t* v, const void* p) {
    asm volatile("ld.relaxed.gpu.global.L1::no_allocate.v4.b32 {%0,%1,%2,%3}, [%4];" : "=r"(v[0]), "=r"(v[1]), "=r"(v[2]), "=r"(v[3]) : "l"(p) : "memory");
}
__device__ __forceinline__ void ld_relaxed1n(uint32_t& v, const void* p) { asm volatile("ld.relaxed.gpu.global.L1::no_allocate.b32 %0, [%1];" : "=r"(v) : "l"(p) : "memory"); }
__device__ __forceinline__ void red_add4(const void* p, uint32_t a, uint32_t b, uint32_t c, uint32_t d) {
    asm volatile("red.relaxed.gpu.global.add.noftz.v4.f16x2 [%0], {%1,%2,%3,%4};" ::"l"(p), "r"(a), "r"(b), "r"(c), "r"(d) : "memory");
}
__device__ __forceinline__ void red_add1(const void* p, uint32_t a) { asm volatile("red.relaxed.gpu.global.add.noftz.f16x2 [%0], %1;" ::"l"(p), "r"(a) : "memory"); }
__device__ __forceinline__ void ld_relaxed2(uint32_t* v, const void* p) {
    asm volatile("{\n.reg .b64 t;\nld.relaxed.gpu.global.L1::no_allocate.b64 t, [%2];\nmov.b64 {%0,%1}, t;\n}" : "=r"(v[0]), "=r"(v[1]) : "l"(p) : "memory");
}
__device__ __forceinline__ uint32_t ld_relaxed1(const void* p) { uint32_t v; asm volatile("ld.relaxed.gpu.global.u32 %0, [%1];" : "=r"(v) : "l"(p) : "memory"); return v; }
__device__ __forceinline__ void st_relaxed1(const void* p, uint32_t v) { asm volatile("st.relaxed.gpu.global.u32 [%0], %1;" ::"l"(p), "r"(v) : "memory"); }
__device__ __forceinline__ uint32_t ld_acquire(const void* p) { uint32_t v; asm volatile("ld.acquire.gpu.global.u32 %0, [%1];" : "=r"(v) : "l"(p) : "memory"); return v; }
__device__ __forceinline__ void red_relaxed(void* p) { asm volatile("red.relaxed.gpu.global.add.u32 [%0], 1;" ::"l"(p) : "memory"); }
__device__ __forceinline__ void red_release(void* p) { asm volatile("red.release.gpu.global.add.u32 [%0], 1;" ::"l"(p) : "memory"); }
__device__ __forceinline__ void st_stream2(float* p, float a, float b) { asm volatile("st.global.cs.v2.f32 [%0], {%1, %2};" ::"l"(p), "f"(a), "f"(b) : "memory"); }
__device__ __forceinline__ void fence_async() { asm volatile("fence.proxy.async.global;" ::: "memory"); }
__device__ __forceinline__ void fence_async_smem() { asm volatile("fence.proxy.async.shared::cta;" ::: "memory"); }
__device__ __forceinline__ void wait_count(const uint32_t* p, uint32_t target) {
    int n = 0;
    while ((int32_t)(ld_acquire(p) - target) < 0) { __nanosleep(POLLNS); if (++n > SPIN_LIMIT) spin_fault(); }
}
__device__ __forceinline__ void bar_sync(int id, int n) { asm volatile("bar.sync %0, %1;" ::"r"(id), "r"(n) : "memory"); }
__device__ __forceinline__ bool bar_and(int id, bool v) {
    uint32_t r;
    asm volatile("{\n.reg .pred P, Q;\nsetp.ne.u32 Q, %2, 0;\nbar.red.and.pred P, %1, 128, Q;\nselp.u32 %0, 1, 0, P;\n}" : "=r"(r) : "r"(id), "r"((uint32_t)v) : "memory");
    return r;
}
__device__ __forceinline__ void bar_arrive(int id, int n) { asm volatile("bar.arrive %0, %1;" ::"r"(id), "r"(n) : "memory"); }
__device__ __forceinline__ void lds128(uint32_t* v, uint32_t a) { asm volatile("ld.shared.v4.b32 {%0,%1,%2,%3}, [%4];" : "=r"(v[0]), "=r"(v[1]), "=r"(v[2]), "=r"(v[3]) : "r"(a) : "memory"); }
__device__ __forceinline__ uint32_t lds32(uint32_t a) { uint32_t v; asm volatile("ld.shared.b32 %0, [%1];" : "=r"(v) : "r"(a) : "memory"); return v; }
__device__ __forceinline__ void lds64(uint32_t* v, uint32_t a) { asm volatile("ld.shared.v2.b32 {%0,%1}, [%2];" : "=r"(v[0]), "=r"(v[1]) : "r"(a) : "memory"); }
__device__ __forceinline__ void lds64f(float* v, uint32_t a) { asm volatile("ld.shared.v2.f32 {%0,%1}, [%2];" : "=f"(v[0]), "=f"(v[1]) : "r"(a) : "memory"); }
__device__ __forceinline__ void sts128(uint32_t a, const uint32_t* v) { asm volatile("st.shared.v4.b32 [%0], {%1,%2,%3,%4};" ::"r"(a), "r"(v[0]), "r"(v[1]), "r"(v[2]), "r"(v[3]) : "memory"); }
__device__ __forceinline__ void sts64(uint32_t a, uint32_t x, uint32_t y) { asm volatile("st.shared.v2.b32 [%0], {%1,%2};" ::"r"(a), "r"(x), "r"(y) : "memory"); }
__device__ __forceinline__ void sts32(uint32_t a, uint32_t x) { asm volatile("st.shared.b32 [%0], %1;" ::"r"(a), "r"(x) : "memory"); }
__device__ __forceinline__ bool mbar_try(uint32_t b, uint32_t par) {
    uint32_t ok;
    asm volatile("{\n.reg .pred P;\nmbarrier.test_wait.parity.shared::cta.b64 P, [%1], %2;\nselp.u32 %0, 1, 0, P;\n}" : "=r"(ok) : "r"(b), "r"(par) : "memory");
    return ok;
}
__device__ __forceinline__ void mbar_wait(uint32_t b, uint32_t par) {
    asm volatile("{\n.reg .pred P, Q;\n.reg .u32 n;\nmov.u32 n, %2;\nW: mbarrier.try_wait.parity.shared::cta.b64 P, [%0], %1;\n"
                 "add.u32 n, n, -1;\nsetp.eq.u32 Q, n, 0;\n@Q st.global.u32 [%3], 0;\n@!P bra W;\n}" ::"r"(b), "r"(par), "n"(SPIN_LIMIT), "l"(0ull) : "memory");
}
__device__ __forceinline__ void mbar_wait_fast(uint32_t b, uint32_t par) {
    asm volatile("{\n.reg .pred P, Q;\n.reg .u32 n;\nmbarrier.try_wait.parity.shared::cta.b64 P, [%0], %1;\n@P bra D;\nmov.u32 n, %2;\nW: mbarrier.try_wait.parity.shared::cta.b64 P, [%0], %1;\n"
                 "add.u32 n, n, -1;\nsetp.eq.u32 Q, n, 0;\n@Q st.global.u32 [%3], 0;\n@!P bra W;\nD:\n}" ::"r"(b), "r"(par), "n"(SPIN_LIMIT), "l"(0ull) : "memory");
}
__device__ __forceinline__ void declare_fence(int zero) { asm volatile(".reg .pred PNEVER;\nsetp.ne.u32 PNEVER, %0, 0;" ::"r"(zero)); }
__device__ __forceinline__ void sched_fence() { asm volatile("{\n.reg .pred Q;\n.reg .u32 x;\n@!PNEVER bra D;\nF: ld.volatile.global.u32 x, [%0];\nsetp.ne.u32 Q, x, 0;\n@Q bra F;\nD:\n}" ::"l"(0ull) : "memory"); }
__device__ __forceinline__ void mbar_init(uint32_t b, uint32_t n) { asm volatile("mbarrier.init.shared::cta.b64 [%0], %1;" ::"r"(b), "r"(n) : "memory"); }
__device__ __forceinline__ void mbar_expect(uint32_t b, uint32_t bytes) { asm volatile("mbarrier.arrive.expect_tx.shared::cta.b64 _, [%0], %1;" ::"r"(b), "r"(bytes) : "memory"); }
__device__ __forceinline__ void mbar_arrive(uint32_t b) { asm volatile("mbarrier.arrive.shared::cta.b64 _, [%0];" ::"r"(b) : "memory"); }
__device__ __forceinline__ void mbar_arrive_cluster(uint32_t b) { asm volatile("mbarrier.arrive.shared::cluster.b64 _, [%0];" ::"r"(b) : "memory"); }
__device__ __forceinline__ void cluster_sync() { asm volatile("barrier.cluster.arrive.aligned;\nbarrier.cluster.wait.aligned;" ::: "memory"); }
__device__ __forceinline__ void tma2d(uint32_t dst, const CUtensorMap* m, int c0, int c1, uint32_t bar) {
    asm volatile("cp.async.bulk.tensor.2d.shared::cluster.global.mbarrier::complete_tx::bytes [%0], [%1, {%2, %3}], [%4];" ::"r"(dst), "l"(m), "r"(c0), "r"(c1), "r"(bar) : "memory");
}
__device__ __forceinline__ void tma2d_mc(uint32_t dst, const CUtensorMap* m, int c0, int c1, uint32_t bar, uint16_t mask) {
    asm volatile("cp.async.bulk.tensor.2d.shared::cluster.global.mbarrier::complete_tx::bytes.multicast::cluster [%0], [%1, {%2, %3}], [%4], %5;" ::"r"(dst), "l"(m), "r"(c0), "r"(c1), "r"(bar), "h"(mask) : "memory");
}
__device__ __forceinline__ void tma3d(uint32_t dst, const CUtensorMap* m, int c0, int c1, int c2, uint32_t bar) {
    asm volatile("cp.async.bulk.tensor.3d.shared::cluster.global.mbarrier::complete_tx::bytes [%0], [%1, {%2, %3, %4}], [%5];" ::"r"(dst), "l"(m), "r"(c0), "r"(c1), "r"(c2), "r"(bar) : "memory");
}
__device__ __forceinline__ void tma3d_mc(uint32_t dst, const CUtensorMap* m, int c0, int c1, int c2, uint32_t bar, uint16_t mask) {
    asm volatile("cp.async.bulk.tensor.3d.shared::cluster.global.mbarrier::complete_tx::bytes.multicast::cluster [%0], [%1, {%2, %3, %4}], [%5], %6;" ::"r"(dst), "l"(m), "r"(c0), "r"(c1), "r"(c2), "r"(bar), "h"(mask) : "memory");
}
__device__ __forceinline__ void tma4d(uint32_t dst, const CUtensorMap* m, int c0, int c3, uint32_t bar) {
    asm volatile("cp.async.bulk.tensor.4d.shared::cluster.global.mbarrier::complete_tx::bytes [%0], [%1, {%2, 0, 0, %3}], [%4];" ::"r"(dst), "l"(m), "r"(c0), "r"(c3), "r"(bar) : "memory");
}
__device__ __forceinline__ void tma4d_mc(uint32_t dst, const CUtensorMap* m, int c0, int c3, uint32_t bar, uint16_t mask) {
    asm volatile("cp.async.bulk.tensor.4d.shared::cluster.global.mbarrier::complete_tx::bytes.multicast::cluster [%0], [%1, {%2, 0, 0, %3}], [%4], %5;" ::"r"(dst), "l"(m), "r"(c0), "r"(c3), "r"(bar), "h"(mask) : "memory");
}
__device__ __forceinline__ void tma_prefetch3d(const CUtensorMap* m, int c0, int c1, int c2) {
    asm volatile("cp.async.bulk.prefetch.tensor.3d.L2.global [%0, {%1, %2, %3}];" ::"l"(m), "r"(c0), "r"(c1), "r"(c2) : "memory");
}
__device__ __forceinline__ void tma_prefetch2d(const CUtensorMap* m, int c0, int c1) {
    asm volatile("cp.async.bulk.prefetch.tensor.2d.L2.global [%0, {%1, %2}];" ::"l"(m), "r"(c0), "r"(c1) : "memory");
}
__device__ __forceinline__ void l2_prefetch(const void* src, uint32_t bytes) { asm volatile("cp.async.bulk.prefetch.L2.global [%0], %1;" ::"l"(src), "r"(bytes) : "memory"); }
__device__ __forceinline__ void bulk_g2s(uint32_t dst, const void* src, uint32_t bytes, uint32_t bar) {
    asm volatile("cp.async.bulk.shared::cluster.global.mbarrier::complete_tx::bytes [%0], [%1], %2, [%3];" ::"r"(dst), "l"(src), "r"(bytes), "r"(bar) : "memory");
}
__device__ __forceinline__ void mbar_expect_e(uint32_t b, uint32_t bytes) {
    asm volatile("{\n.reg .pred E;\nelect.sync _|E, 0xffffffff;\n@E mbarrier.arrive.expect_tx.shared::cta.b64 _, [%0], %1;\n}" ::"r"(b), "r"(bytes) : "memory");
}
__device__ __forceinline__ void tma2d_e(uint32_t dst, const CUtensorMap* m, int c0, int c1, uint32_t bar, uint64_t pol) {
    asm volatile("{\n.reg .pred E;\nelect.sync _|E, 0xffffffff;\n@E cp.async.bulk.tensor.2d.shared::cluster.global.mbarrier::complete_tx::bytes.L2::cache_hint [%0], [%1, {%2, %3}], [%4], %5;\n}" ::"r"(dst), "l"(m), "r"(c0), "r"(c1), "r"(bar), "l"(pol) : "memory");
}
__device__ __forceinline__ void tma2d_mc_e(uint32_t dst, const CUtensorMap* m, int c0, int c1, uint32_t bar, uint16_t mask) {
    asm volatile("{\n.reg .pred E;\nelect.sync _|E, 0xffffffff;\n@E cp.async.bulk.tensor.2d.shared::cluster.global.mbarrier::complete_tx::bytes.multicast::cluster [%0], [%1, {%2, %3}], [%4], %5;\n}" ::"r"(dst), "l"(m), "r"(c0), "r"(c1), "r"(bar), "h"(mask) : "memory");
}
__device__ __forceinline__ void tma3d_e(uint32_t dst, const CUtensorMap* m, int c0, int c1, int c2, uint32_t bar, uint64_t pol) {
    asm volatile("{\n.reg .pred E;\nelect.sync _|E, 0xffffffff;\n@E cp.async.bulk.tensor.3d.shared::cluster.global.mbarrier::complete_tx::bytes.L2::cache_hint [%0], [%1, {%2, %3, %4}], [%5], %6;\n}" ::"r"(dst), "l"(m), "r"(c0), "r"(c1), "r"(c2), "r"(bar), "l"(pol) : "memory");
}
__device__ __forceinline__ void tma3d_mc_e(uint32_t dst, const CUtensorMap* m, int c0, int c1, int c2, uint32_t bar, uint16_t mask, uint64_t pol) {
    asm volatile("{\n.reg .pred E;\nelect.sync _|E, 0xffffffff;\n@E cp.async.bulk.tensor.3d.shared::cluster.global.mbarrier::complete_tx::bytes.multicast::cluster.L2::cache_hint [%0], [%1, {%2, %3, %4}], [%5], %6, %7;\n}" ::"r"(dst), "l"(m), "r"(c0), "r"(c1), "r"(c2), "r"(bar), "h"(mask), "l"(pol) : "memory");
}
__device__ __forceinline__ void tma4d_e(uint32_t dst, const CUtensorMap* m, int c0, int c3, uint32_t bar) {
    asm volatile("{\n.reg .pred E;\nelect.sync _|E, 0xffffffff;\n@E cp.async.bulk.tensor.4d.shared::cluster.global.mbarrier::complete_tx::bytes [%0], [%1, {%2, 0, 0, %3}], [%4];\n}" ::"r"(dst), "l"(m), "r"(c0), "r"(c3), "r"(bar) : "memory");
}
__device__ __forceinline__ void tma4d_mc_e(uint32_t dst, const CUtensorMap* m, int c0, int c3, uint32_t bar, uint16_t mask) {
    asm volatile("{\n.reg .pred E;\nelect.sync _|E, 0xffffffff;\n@E cp.async.bulk.tensor.4d.shared::cluster.global.mbarrier::complete_tx::bytes.multicast::cluster [%0], [%1, {%2, 0, 0, %3}], [%4], %5;\n}" ::"r"(dst), "l"(m), "r"(c0), "r"(c3), "r"(bar), "h"(mask) : "memory");
}
__device__ __forceinline__ void tma_prefetch2d_e(const CUtensorMap* m, int c0, int c1) {
    asm volatile("{\n.reg .pred E;\nelect.sync _|E, 0xffffffff;\n@E cp.async.bulk.prefetch.tensor.2d.L2.global [%0, {%1, %2}];\n}" ::"l"(m), "r"(c0), "r"(c1) : "memory");
}
__device__ __forceinline__ void tma_prefetch3d_e(const CUtensorMap* m, int c0, int c1, int c2) {
    asm volatile("{\n.reg .pred E;\nelect.sync _|E, 0xffffffff;\n@E cp.async.bulk.prefetch.tensor.3d.L2.global [%0, {%1, %2, %3}];\n}" ::"l"(m), "r"(c0), "r"(c1), "r"(c2) : "memory");
}
__device__ __forceinline__ void l2_prefetch_e(const void* src, uint32_t bytes) {
    asm volatile("{\n.reg .pred E;\nelect.sync _|E, 0xffffffff;\n@E cp.async.bulk.prefetch.L2.global [%0], %1;\n}" ::"l"(src), "r"(bytes) : "memory");
}
__device__ __forceinline__ void bulk_g2s_e(uint32_t dst, const void* src, uint32_t bytes, uint32_t bar) {
    asm volatile("{\n.reg .pred E;\nelect.sync _|E, 0xffffffff;\n@E cp.async.bulk.shared::cluster.global.mbarrier::complete_tx::bytes [%0], [%1], %2, [%3];\n}" ::"r"(dst), "l"(src), "r"(bytes), "r"(bar) : "memory");
}
__device__ __forceinline__ bool elect_one() {
    uint32_t r;
    asm volatile("{\n.reg .pred E;\nelect.sync _|E, 0xffffffff;\nselp.u32 %0, 1, 0, E;\n}" : "=r"(r));
    return r;
}
__device__ __forceinline__ void tma_store2d(const CUtensorMap* m, int c0, int c1, uint32_t src, uint64_t pol) {
    asm volatile("cp.async.bulk.tensor.2d.global.shared::cta.bulk_group.L2::cache_hint [%0, {%1, %2}], [%3], %4;" ::"l"(m), "r"(c0), "r"(c1), "r"(src), "l"(pol) : "memory");
}
__device__ __forceinline__ void bulk_commit() { asm volatile("cp.async.bulk.commit_group;" ::: "memory"); }
__device__ __forceinline__ void bulk_wait_read() { asm volatile("cp.async.bulk.wait_group.read 0;" ::: "memory"); }
__device__ __forceinline__ void bulk_wait_all() { asm volatile("cp.async.bulk.wait_group 0;" ::: "memory"); }
__device__ __forceinline__ uint64_t mkdesc(uint32_t addr, uint32_t lbo, uint32_t sbo, uint32_t swz) {
    return (uint64_t)((addr & 0x3FFFF) >> 4) | ((uint64_t)(lbo >> 4) << 16) | ((uint64_t)(sbo >> 4) << 32) | ((uint64_t)swz << 62);
}
__device__ __forceinline__ void wg_fence() { asm volatile("wgmma.fence.sync.aligned;" ::: "memory"); }
__device__ __forceinline__ void wg_commit() { asm volatile("wgmma.commit_group.sync.aligned;" ::: "memory"); }
template <int N> __device__ __forceinline__ void wg_wait() { asm volatile("wgmma.wait_group.sync.aligned %0;" ::"n"(N) : "memory"); }
template <typename T> __device__ __forceinline__ void pin_ptr(T*& p) { asm volatile("" : "+l"(p)); }
template <int N> __device__ __forceinline__ void pin(uint32_t* d) {
#pragma unroll
    for (int i = 0; i < N; i++) asm volatile("" : "+r"(d[i])::"memory");
}
template <int N> __device__ __forceinline__ void pin(float* d) {
#pragma unroll
    for (int i = 0; i < N; i++) asm volatile("" : "+f"(d[i])::"memory");
}

template <int TA, int TB>
__device__ __forceinline__ void wgmma_ss256(float* d, uint64_t da, uint64_t db) {
    asm volatile("wgmma.mma_async.sync.aligned.m64n256k16.f32.bf16.bf16 "
        "{%0, %1, %2, %3, %4, %5, %6, %7, %8, %9, %10, %11, %12, %13, %14, %15, %16, %17, %18, %19, %20, %21, %22, %23, %24, %25, %26, %27, %28, %29, %30, %31, %32, %33, %34, %35, %36, %37, %38, %39, %40, %41, %42, %43, %44, %45, %46, %47, %48, %49, %50, %51, %52, %53, %54, %55, %56, %57, %58, %59, %60, %61, %62, %63, %64, %65, %66, %67, %68, %69, %70, %71, %72, %73, %74, %75, %76, %77, %78, %79, %80, %81, %82, %83, %84, %85, %86, %87, %88, %89, %90, %91, %92, %93, %94, %95, %96, %97, %98, %99, %100, %101, %102, %103, %104, %105, %106, %107, %108, %109, %110, %111, %112, %113, %114, %115, %116, %117, %118, %119, %120, %121, %122, %123, %124, %125, %126, %127}, %128, %129, 1, 1, 1, %130, %131;"
        : "+f"(d[0]), "+f"(d[1]), "+f"(d[2]), "+f"(d[3]), "+f"(d[4]), "+f"(d[5]), "+f"(d[6]), "+f"(d[7]), "+f"(d[8]), "+f"(d[9]), "+f"(d[10]), "+f"(d[11]), "+f"(d[12]), "+f"(d[13]), "+f"(d[14]), "+f"(d[15]), "+f"(d[16]), "+f"(d[17]), "+f"(d[18]), "+f"(d[19]), "+f"(d[20]), "+f"(d[21]), "+f"(d[22]), "+f"(d[23]), "+f"(d[24]), "+f"(d[25]), "+f"(d[26]), "+f"(d[27]), "+f"(d[28]), "+f"(d[29]), "+f"(d[30]), "+f"(d[31]), "+f"(d[32]), "+f"(d[33]), "+f"(d[34]), "+f"(d[35]), "+f"(d[36]), "+f"(d[37]), "+f"(d[38]), "+f"(d[39]), "+f"(d[40]), "+f"(d[41]), "+f"(d[42]), "+f"(d[43]), "+f"(d[44]), "+f"(d[45]), "+f"(d[46]), "+f"(d[47]), "+f"(d[48]), "+f"(d[49]), "+f"(d[50]), "+f"(d[51]), "+f"(d[52]), "+f"(d[53]), "+f"(d[54]), "+f"(d[55]), "+f"(d[56]), "+f"(d[57]), "+f"(d[58]), "+f"(d[59]), "+f"(d[60]), "+f"(d[61]), "+f"(d[62]), "+f"(d[63]), "+f"(d[64]), "+f"(d[65]), "+f"(d[66]), "+f"(d[67]), "+f"(d[68]), "+f"(d[69]), "+f"(d[70]), "+f"(d[71]), "+f"(d[72]), "+f"(d[73]), "+f"(d[74]), "+f"(d[75]), "+f"(d[76]), "+f"(d[77]), "+f"(d[78]), "+f"(d[79]), "+f"(d[80]), "+f"(d[81]), "+f"(d[82]), "+f"(d[83]), "+f"(d[84]), "+f"(d[85]), "+f"(d[86]), "+f"(d[87]), "+f"(d[88]), "+f"(d[89]), "+f"(d[90]), "+f"(d[91]), "+f"(d[92]), "+f"(d[93]), "+f"(d[94]), "+f"(d[95]), "+f"(d[96]), "+f"(d[97]), "+f"(d[98]), "+f"(d[99]), "+f"(d[100]), "+f"(d[101]), "+f"(d[102]), "+f"(d[103]), "+f"(d[104]), "+f"(d[105]), "+f"(d[106]), "+f"(d[107]), "+f"(d[108]), "+f"(d[109]), "+f"(d[110]), "+f"(d[111]), "+f"(d[112]), "+f"(d[113]), "+f"(d[114]), "+f"(d[115]), "+f"(d[116]), "+f"(d[117]), "+f"(d[118]), "+f"(d[119]), "+f"(d[120]), "+f"(d[121]), "+f"(d[122]), "+f"(d[123]), "+f"(d[124]), "+f"(d[125]), "+f"(d[126]), "+f"(d[127])
        : "l"(da), "l"(db), "n"(TA), "n"(TB));
}
template <int TA, int TB>
__device__ __forceinline__ void wgmma_ss256_first(float* d, uint64_t da, uint64_t db) {
    asm volatile("wgmma.mma_async.sync.aligned.m64n256k16.f32.bf16.bf16 "
        "{%0, %1, %2, %3, %4, %5, %6, %7, %8, %9, %10, %11, %12, %13, %14, %15, %16, %17, %18, %19, %20, %21, %22, %23, %24, %25, %26, %27, %28, %29, %30, %31, %32, %33, %34, %35, %36, %37, %38, %39, %40, %41, %42, %43, %44, %45, %46, %47, %48, %49, %50, %51, %52, %53, %54, %55, %56, %57, %58, %59, %60, %61, %62, %63, %64, %65, %66, %67, %68, %69, %70, %71, %72, %73, %74, %75, %76, %77, %78, %79, %80, %81, %82, %83, %84, %85, %86, %87, %88, %89, %90, %91, %92, %93, %94, %95, %96, %97, %98, %99, %100, %101, %102, %103, %104, %105, %106, %107, %108, %109, %110, %111, %112, %113, %114, %115, %116, %117, %118, %119, %120, %121, %122, %123, %124, %125, %126, %127}, %128, %129, 0, 1, 1, %130, %131;"
        : "=f"(d[0]), "=f"(d[1]), "=f"(d[2]), "=f"(d[3]), "=f"(d[4]), "=f"(d[5]), "=f"(d[6]), "=f"(d[7]), "=f"(d[8]), "=f"(d[9]), "=f"(d[10]), "=f"(d[11]), "=f"(d[12]), "=f"(d[13]), "=f"(d[14]), "=f"(d[15]), "=f"(d[16]), "=f"(d[17]), "=f"(d[18]), "=f"(d[19]), "=f"(d[20]), "=f"(d[21]), "=f"(d[22]), "=f"(d[23]), "=f"(d[24]), "=f"(d[25]), "=f"(d[26]), "=f"(d[27]), "=f"(d[28]), "=f"(d[29]), "=f"(d[30]), "=f"(d[31]), "=f"(d[32]), "=f"(d[33]), "=f"(d[34]), "=f"(d[35]), "=f"(d[36]), "=f"(d[37]), "=f"(d[38]), "=f"(d[39]), "=f"(d[40]), "=f"(d[41]), "=f"(d[42]), "=f"(d[43]), "=f"(d[44]), "=f"(d[45]), "=f"(d[46]), "=f"(d[47]), "=f"(d[48]), "=f"(d[49]), "=f"(d[50]), "=f"(d[51]), "=f"(d[52]), "=f"(d[53]), "=f"(d[54]), "=f"(d[55]), "=f"(d[56]), "=f"(d[57]), "=f"(d[58]), "=f"(d[59]), "=f"(d[60]), "=f"(d[61]), "=f"(d[62]), "=f"(d[63]), "=f"(d[64]), "=f"(d[65]), "=f"(d[66]), "=f"(d[67]), "=f"(d[68]), "=f"(d[69]), "=f"(d[70]), "=f"(d[71]), "=f"(d[72]), "=f"(d[73]), "=f"(d[74]), "=f"(d[75]), "=f"(d[76]), "=f"(d[77]), "=f"(d[78]), "=f"(d[79]), "=f"(d[80]), "=f"(d[81]), "=f"(d[82]), "=f"(d[83]), "=f"(d[84]), "=f"(d[85]), "=f"(d[86]), "=f"(d[87]), "=f"(d[88]), "=f"(d[89]), "=f"(d[90]), "=f"(d[91]), "=f"(d[92]), "=f"(d[93]), "=f"(d[94]), "=f"(d[95]), "=f"(d[96]), "=f"(d[97]), "=f"(d[98]), "=f"(d[99]), "=f"(d[100]), "=f"(d[101]), "=f"(d[102]), "=f"(d[103]), "=f"(d[104]), "=f"(d[105]), "=f"(d[106]), "=f"(d[107]), "=f"(d[108]), "=f"(d[109]), "=f"(d[110]), "=f"(d[111]), "=f"(d[112]), "=f"(d[113]), "=f"(d[114]), "=f"(d[115]), "=f"(d[116]), "=f"(d[117]), "=f"(d[118]), "=f"(d[119]), "=f"(d[120]), "=f"(d[121]), "=f"(d[122]), "=f"(d[123]), "=f"(d[124]), "=f"(d[125]), "=f"(d[126]), "=f"(d[127])
        : "l"(da), "l"(db), "n"(TA), "n"(TB));
}
template <int TB>
__device__ __forceinline__ void wgmma_rs128(float* d, const uint32_t* a, uint64_t db, uint32_t acc) {
    asm volatile("{\n.reg .pred P;\nsetp.ne.u32 P, %69, 0;\nwgmma.mma_async.sync.aligned.m64n128k16.f32.bf16.bf16 "
        "{%0, %1, %2, %3, %4, %5, %6, %7, %8, %9, %10, %11, %12, %13, %14, %15, %16, %17, %18, %19, %20, %21, %22, %23, %24, %25, %26, %27, %28, %29, %30, %31, %32, %33, %34, %35, %36, %37, %38, %39, %40, %41, %42, %43, %44, %45, %46, %47, %48, %49, %50, %51, %52, %53, %54, %55, %56, %57, %58, %59, %60, %61, %62, %63}, {%64, %65, %66, %67}, %68, P, 1, 1, %70;\n}"
        : "+f"(d[0]), "+f"(d[1]), "+f"(d[2]), "+f"(d[3]), "+f"(d[4]), "+f"(d[5]), "+f"(d[6]), "+f"(d[7]), "+f"(d[8]), "+f"(d[9]), "+f"(d[10]), "+f"(d[11]), "+f"(d[12]), "+f"(d[13]), "+f"(d[14]), "+f"(d[15]), "+f"(d[16]), "+f"(d[17]), "+f"(d[18]), "+f"(d[19]), "+f"(d[20]), "+f"(d[21]), "+f"(d[22]), "+f"(d[23]), "+f"(d[24]), "+f"(d[25]), "+f"(d[26]), "+f"(d[27]), "+f"(d[28]), "+f"(d[29]), "+f"(d[30]), "+f"(d[31]), "+f"(d[32]), "+f"(d[33]), "+f"(d[34]), "+f"(d[35]), "+f"(d[36]), "+f"(d[37]), "+f"(d[38]), "+f"(d[39]), "+f"(d[40]), "+f"(d[41]), "+f"(d[42]), "+f"(d[43]), "+f"(d[44]), "+f"(d[45]), "+f"(d[46]), "+f"(d[47]), "+f"(d[48]), "+f"(d[49]), "+f"(d[50]), "+f"(d[51]), "+f"(d[52]), "+f"(d[53]), "+f"(d[54]), "+f"(d[55]), "+f"(d[56]), "+f"(d[57]), "+f"(d[58]), "+f"(d[59]), "+f"(d[60]), "+f"(d[61]), "+f"(d[62]), "+f"(d[63])
        : "r"(a[0]), "r"(a[1]), "r"(a[2]), "r"(a[3]), "l"(db), "r"(acc), "n"(TB));
}
template <int TB>
__device__ __forceinline__ void wgmma_rs64(float* d, const uint32_t* a, uint64_t db, uint32_t acc) {
    asm volatile("{\n.reg .pred P;\nsetp.ne.u32 P, %37, 0;\nwgmma.mma_async.sync.aligned.m64n64k16.f32.bf16.bf16 "
        "{%0, %1, %2, %3, %4, %5, %6, %7, %8, %9, %10, %11, %12, %13, %14, %15, %16, %17, %18, %19, %20, %21, %22, %23, %24, %25, %26, %27, %28, %29, %30, %31}, {%32, %33, %34, %35}, %36, P, 1, 1, %38;\n}"
        : "+f"(d[0]), "+f"(d[1]), "+f"(d[2]), "+f"(d[3]), "+f"(d[4]), "+f"(d[5]), "+f"(d[6]), "+f"(d[7]), "+f"(d[8]), "+f"(d[9]), "+f"(d[10]), "+f"(d[11]), "+f"(d[12]), "+f"(d[13]), "+f"(d[14]), "+f"(d[15]), "+f"(d[16]), "+f"(d[17]), "+f"(d[18]), "+f"(d[19]), "+f"(d[20]), "+f"(d[21]), "+f"(d[22]), "+f"(d[23]), "+f"(d[24]), "+f"(d[25]), "+f"(d[26]), "+f"(d[27]), "+f"(d[28]), "+f"(d[29]), "+f"(d[30]), "+f"(d[31])
        : "r"(a[0]), "r"(a[1]), "r"(a[2]), "r"(a[3]), "l"(db), "r"(acc), "n"(TB));
}
template <int TB>
__device__ __forceinline__ void wgmma_rs16(float* d, const uint32_t* a, uint64_t db, uint32_t acc) {
    asm volatile("{\n.reg .pred P;\nsetp.ne.u32 P, %13, 0;\nwgmma.mma_async.sync.aligned.m64n16k16.f32.bf16.bf16 "
        "{%0, %1, %2, %3, %4, %5, %6, %7}, {%8, %9, %10, %11}, %12, P, 1, 1, %14;\n}"
        : "+f"(d[0]), "+f"(d[1]), "+f"(d[2]), "+f"(d[3]), "+f"(d[4]), "+f"(d[5]), "+f"(d[6]), "+f"(d[7])
        : "r"(a[0]), "r"(a[1]), "r"(a[2]), "r"(a[3]), "l"(db), "r"(acc), "n"(TB));
}

__device__ __forceinline__ uint32_t delay_loop(int n, uint32_t x0) {
    uint32_t z;
    asm volatile("{\n.reg .pred P;\n.reg .u32 c, x;\nmov.u32 c, %1;\nmov.u32 x, %2;\nDL: mad.lo.u32 x, x, 1664525, 1013904223;\nadd.u32 c, c, -1;\nsetp.gt.s32 P, c, 0;\n@P bra DL;\n"
                 "setp.eq.u32 P, x, 0x7fffffff;\nselp.u32 %0, 16, 0, P;\n}" : "=r"(z) : "r"(n), "r"(x0) : "memory");
    return z;
}
__device__ __forceinline__ void wait_clocks(uint32_t n) {
    asm volatile("{\n.reg .pred P;\n.reg .u32 a, b;\nmov.u32 a, %%clock;\nW: mov.u32 b, %%clock;\nsub.u32 b, b, a;\nsetp.lt.u32 P, b, %0;\n@P bra W;\n}" ::"r"(n) : "memory");
}
__device__ __forceinline__ uint32_t gtime() { uint32_t t; asm volatile("mov.u32 %0, %%globaltimer_lo;" : "=r"(t)); return t; }
#define COUNT_RETRY(i)
__device__ __forceinline__ uint32_t stamp_word(uint32_t seq) { return (gtime() & ~31u) | (seq & 31u); }
__device__ __forceinline__ void wait_time(uint32_t t, uint32_t sb) { while ((int32_t)(gtime() - t) < 0) {} }
#define NAPMODE 1
__device__ __forceinline__ void nap(uint32_t ns) { if (NAPMODE) wait_clocks(ns * 7 / 4); else __nanosleep(ns); }
template <int STRIDE>
__device__ __forceinline__ uint32_t latest_stamp(const uint32_t* p, uint32_t seq, uint32_t ref, uint32_t sb) {
    int n = 0;
    while (true) {
        uint32_t bad = 0; int32_t m = INT32_MIN;
#pragma unroll
        for (int i = 0; i < 3; i++) { const uint32_t v = ld_relaxed1(p + i * STRIDE); bad |= (v ^ seq) & 31u; m = max(m, (int32_t)((v & ~31u) - ref)); }
        if (__all_sync(0xffffffffu, bad == 0)) return ref + __reduce_max_sync(0xffffffffu, m);
        nap(100);
        if (++n > SPIN_LIMIT) spin_fault();
    }
}
constexpr uint32_t ONES = 0x3C003C00u, FULL = 0x50005000u;
__device__ __forceinline__ void pacer(const Params& P, const uint32_t sb, const int cta, const int lane, const uint32_t epoch) {
    uint8_t* const zp = P.xb + cta * 2048 + xg_lane(lane);
    if (lane < 3) asm volatile("prefetch.tensormap [%0];" ::"l"(&P.tm[lane == 0 ? M_C1 + cta % 3 : lane == 1 ? M_CO : M_SEG]) : "memory");
    uint32_t e0 = 0;
#pragma unroll 2
    for (int i = 0; i < 32; i++) { const uint4 u = __ldg((const uint4*)P.mem0 + i * 32 + lane); e0 = amax(amax(e0, amax(u.x, u.y)), amax(u.z, u.w)); }
    e0 = min(max(warp_exp(e0), 31u), 253u) - 14;
    if (cta < 32) {
        const uint32_t* m = (const uint32_t*)(P.mem0 + (lane >> 2) * 1024 + cta * 32 + (lane & 3) * 2);
        const float sc = __uint_as_float((254 - e0) << 23);
        auto cv = [&](uint32_t u) { return pack2h(bf_lo(u) * sc, bf_hi(u) * sc); };
        const uint32_t y = cv(m[12]);
        st_relaxed4(zp, cv(m[0]), cv(m[4]), cv(m[8]), prmt(y, FULL, 0x7610));
        st_relaxed1(P.xb + xg_side(cta) + lane * 4, prmt(y, FULL, 0x3254));
    }
    if (cta < 40) {
#pragma unroll 1
        for (int b = 1; b < 8; b++) st_relaxed4(zp + xg_buf(b), 0, 0, 0, 0);
    }
    __threadfence();
    const uint32_t* ts = (const uint32_t*)(P.xb + XG_T) + lane;
    int32_t d0 = P.dly;
    const uint32_t go = mapa(sb + B_GO, (cta / 3 & 1) * 3 + 1 + (lane & 1));
    auto free_segment = [&]() { if (lane == 0) mbar_expect(sb + B_KVFULL, 16384); __syncwarp(); if (lane < 2) mbar_arrive_cluster(go); };
    wait_count(&g_cnt(C_XCNT), (epoch + 1) * 256);
    const uint32_t ex = max(ld_relaxed1(&g_cnt(C_XMAX)) & 255, 67u);
    mbar_wait(sb + B_READY, 0);
    free_segment();
    if (lane == 0) st_relaxed2(g_hint + cta * 32, stamp_word(epoch + 1), lds32(sb + S_EV) | lds32(sb + S_EO) << 16);
    uint32_t a = gtime();
    for (int n = 0;; n++) {
        uint32_t bad = 0, e = 0; int32_t m = INT32_MIN;
#pragma unroll
        for (int i = 0; i < 3; i++) {
            uint32_t v[2];
            ld_relaxed2(v, g_hint + lane * 32 + i * 1024);
            bad |= (v[0] ^ (epoch + 1)) & 31u; m = max(m, (int32_t)((v[0] & ~31u) - a)); e = __vmaxu2(e, v[1]);
        }
        if (__all_sync(0xffffffffu, bad == 0)) {
            a += __reduce_max_sync(0xffffffffu, m);
            const uint32_t ev = __reduce_max_sync(0xffffffffu, e & 255), eo = __reduce_max_sync(0xffffffffu, e >> 16);
            if (lane == 0) { sts64(sb + S_SC, max(ev, 97u) + max(eo, 97u) - 244, ex); sts32(sb + S_ISC, e0 * 0x800080u); }
            break;
        }
        wait_clocks(100);
        if (n > SPIN_LIMIT) spin_fault();
    }
    wait_time(a, sb);
    if (lane == 0) mbar_arrive(sb + B_RELM);
#pragma unroll 1
    for (int s = 0; s < 63; s++) {
        const uint32_t seq = epoch * 63 + s + 1;
        mbar_wait(sb + B_P1, s & 1);
        const uint32_t tx = gtime();
        if (lane == 0) st_relaxed1(ts + (s & 1) * 256 + cta, (tx & ~31u) | (seq & 31u));
        { const uint32_t t = tx; PROFP(3) }
        if (s > 0) {
            const int32_t e0 = latest_stamp<32>(ts + (~s & 1) * 256 + 128, seq - 1, a, sb) + P.mrg - a;
            d0 += s < 3 ? e0 : min(max(e0, -P.clamp0), P.clampv) / 2;
        }
        while ((int32_t)(gtime() - tx) < P.rd) nap(20);
        a = latest_stamp<32>(ts + (s & 1) * 256, seq, tx, sb) + d0;
        { const uint32_t t = gtime(); PROFP(0) }
        while ((int32_t)(a - gtime()) > 250) nap(40);
        wait_time(a, sb);
        if (lane == 0) mbar_arrive(sb + B_RELM);
        { const uint32_t t = a; PROFP(2) }
        mbar_wait(sb + B_RED, s & 1);
        { const uint32_t t = gtime(); PROFP(1) }
        const uint32_t g = tx + __reduce_max_sync(0xffffffffu, lds32(sb + S_TO + (lane & 7) * 4) - tx);
        if (lane == 0) st_relaxed1(ts + (s & 1) * 256 + 128 + cta, (g & ~31u) | (seq & 31u));
        if (s < 62) { if (P.kvd) nap(P.kvd); free_segment(); }
    }
}
__device__ __forceinline__ void st_async2(uint32_t a, uint32_t x, uint32_t y, uint32_t bar) {
    asm volatile("st.async.weak.shared::cluster.mbarrier::complete_tx::bytes.v2.b32 [%0], {%1,%2}, [%3];" ::"r"(a), "r"(x), "r"(y), "r"(bar) : "memory");
}
__device__ __forceinline__ uint32_t xor_or(uint32_t a, uint32_t b, uint32_t t) { uint32_t d; asm("lop3.b32 %0, %1, %2, %3, 0x7E;" : "=r"(d) : "r"(a), "r"(b), "r"(t)); return d; }
__device__ __forceinline__ uint32_t or3(uint32_t a, uint32_t b, uint32_t c) { uint32_t d; asm("lop3.b32 %0, %1, %2, %3, 0xFE;" : "=r"(d) : "r"(a), "r"(b), "r"(c)); return d; }
__device__ __forceinline__ bool tags_ok(uint32_t bad, uint32_t mask = 1) {
    uint32_t r;
    asm volatile("{\n.reg .pred P;\n.reg .b32 x;\nand.b32 x, %1, %2;\nsetp.ne.b32 P, x, 0;\nvote.sync.any.pred P, P, 0xffffffff;\nselp.u32 %0, 0, 1, P;\n}" : "=r"(r) : "r"(bad), "r"(mask));
    return r;
}
constexpr int SROW = 56;
#define PREA 8
#define PREB 9
#define RING1 6
#define RING2 7
#define RING3 8
#define PRE2 10
#define PRE2A 0
#define PRE3 0
#define EFENCE 0
#define RFENCE 1
#define PROG 16
#define EARLY 0
#define PLATE 1
#define NDEP 0
#define EFENCE2 0
#define LAG2 8
#define LAG 4
#define PUT1 33
#define DEPS 3
#define ADELAY 120
#define BDELAY 0
#define HOLD 1
#define XDELAY 330
#define FENCEA 0x80
#define FENCEB 0x80
#define FENCE2 0x220
#define OFENCE 0
#define MASK3 0x57
#define MASK4 0x55
#define MASK5 0x25
#define OFF3 0x5320
#define OFF4 0x6420
#define OFF5 0x0520
#define RESA (NRA == 3 ? 15 : NRA == 4 ? 3 : 0)
#define RESB (NRB == 3 ? 0xcc : NRB == 4 ? 0x30 : 0)
#define RESB1 (NRB == 3 ? 0xcc : NRB == 4 ? 0xc : 0)
__host__ __device__ constexpr int smem_mask(int NR) { return NR == 3 ? MASK3 : NR == 4 ? MASK4 : MASK5; }
__host__ __device__ constexpr bool round_smem(int r, int NR) { return smem_mask(NR) >> r & 1; }
__host__ __device__ constexpr int kord(int r, int NR) { int c = 0; for (int i = 0; i < r; i++) c += round_smem(i, NR) == round_smem(r, NR); return round_smem(r, NR) ? NR + c : c; }
__host__ __device__ constexpr int slot_r(int n, int NR) { return n < 32 ? n >> 2 : (((n & 31) >> 2) + ((NR == 3 ? OFF3 : NR == 4 ? OFF4 : OFF5) >> (n & 3) * 4)) & 7; }
__host__ __device__ constexpr int slot_k(int n, int NR) { return kord(slot_r(n, NR), NR); }
__host__ __device__ constexpr int slot_sord(int n, int NR) { int c = 0; for (int i = 0; i < n; i++) c += slot_k(i, NR) >= NR; return c; }
__host__ __device__ constexpr int sfrag_slot(int q, int NR) { for (int n = 0; n < 64; n++) if (slot_k(n, NR) >= NR && slot_sord(n, NR) == q) return n; return -1; }
__host__ __device__ constexpr int w1_loaded(int n, int NR, int PRE) {
    int q = PRE;
    for (int i = 0; i <= n; i++) q += q < (8 - NR) * 8 && q - slot_sord(i + 1, NR) < (i < 32 ? RING1 : RING2);
    return q;
}
template <int Q, int NR>
__device__ __forceinline__ void load_w1(uint32_t* w, const uint32_t* a) {
    constexpr int n = sfrag_slot(Q, NR);
    ldsm4t(w, a[n & 3] + ((slot_k(n, NR) - NR) * 2 + (n >> 5)) * 2048);
}
constexpr int AB = NRA < 5, BB = 3 - AB;
__device__ __forceinline__ bool w2_full(int role, int warp) { return warp < (role == 2 ? 2 : 3); }
__device__ __forceinline__ int w2_nblk(int role, int warp) { return warp < 4 ? BB - !w2_full(role, warp) : AB; }
__host__ __device__ constexpr int w2_step(bool full, int i) { return AB ? (full ? 2 * i : 0) : full ? (i == 0 ? 0 : i == 1 ? 16 - 2 * EARLY : 18 - 2 * EARLY) : i; }
__device__ __forceinline__ int w2_block(int role, int warp) {
    const int f = role * 3 + warp, g = role == 2 ? warp : role;
    if (AB) return (warp >= 4 ? role * 4 + (warp - 4) : w2_full(role, warp) ? 16 + 4 * (f >> 1) + (f & 1) : 12 + g) ^ EARLY;
    return w2_full(role, warp) ? EARLY + 4 * (f >> 1) + (f & 1) : EARLY + 2 + 4 * g;
}
__device__ __forceinline__ int w2_res(int role, int warp) { return warp >= 4 ? RESA : w2_full(role, warp) ? RESB : RESB1; }
__device__ __forceinline__ int w2_units(int role, int warp) { return w2_nblk(role, warp) * 4 - (5 - (warp < 4 ? NRB : NRA)) * 2; }
constexpr int W2B = (BB * 4 - (5 - NRB) * 2) * 2048, W2A = (AB * 4 - (5 - NRA) * 2) * 2048;
static_assert(S_W2 + 4 * W2B - 8192 + 4 * W2A == S_KV, "weights");
__device__ __forceinline__ int w1_base(int warp) { return S_W1 + (warp < 4 ? warp * (8 - NRB) : 4 * (8 - NRB) + (warp - 4) * (8 - NRA)) * 4096; }
__device__ __forceinline__ int w2_base(int warp) { return S_W2 + (warp < 4 ? warp * W2B : 4 * W2B - 8192 + (warp - 4) * W2A); }
__device__ __forceinline__ void chain_load(const Params& P, uint32_t sb, int cta, int warp, int lane, int round) {
    const int role = cta % 3, h = cta / 3;
    mbar_expect_e(sb + B_INIT, round ? (8 - (warp < 4 ? NRB : NRA)) * 4096 : 20480);
    if (round) mbar_expect_e(sb + B_INIT2, w2_units(role, warp) * 2048);
    __syncwarp();
    const int m1 = (warp < 4 ? smem_mask(NRB) : smem_mask(NRA)) ^ (round ? 0 : 255), below = (1 << lane) - 1;
    const int m2 = (w2_res(role, warp) ^ (round ? 0xfff : 0)) & ((1 << w2_nblk(role, warp) * 4) - 1);
    const uint32_t d1 = sb + (round ? w1_base(warp) : warp * 20480), d2 = round ? sb + w2_base(warp) : d1 + __popc(m1) * 4096;
    if (m1 >> lane & 1) tma3d(d1 + __popc(m1 & below) * 4096, &P.tm[M_C1 + role], 0, warp * 128 + lane * 16, h * 2, sb + B_INIT);
    __syncwarp();
    if (m2 >> lane & 1)
        tma2d(d2 + __popc(m2 & below) * 2048, &P.tm[M_CO], (w2_block(role, warp) + w2_step(w2_full(role, warp), lane >> 2)) * 32, h * 128 + (lane & 3) * 32, sb + (round ? B_INIT2 : B_INIT));
    __syncwarp();
}

__device__ __forceinline__ void put_partials(bool TR, uint32_t a, const float* x, const float* y) {
    if (TR) stsm4t(a, pack2(x[0], x[1]), pack2(x[2], x[3]), pack2(y[0], y[1]), pack2(y[2], y[3]));
    else stsm4(a, pack2(x[0], x[1]), pack2(x[2], x[3]), pack2(y[0], y[1]), pack2(y[2], y[3]));
}
template <int NR, int PRE, int FM, int B, int E>
__device__ __forceinline__ void project(float (*acc)[4], bool TR, const uint32_t (*wr)[4], uint32_t (*as)[4], uint32_t (*v)[4], uint32_t* x, const uint32_t* w1a, uint32_t pp, uint32_t zero) {
    static_for<B, E>([&](auto I) {
        constexpr int n = I.value, kk = slot_k(n, NR), T = (n >> 5) * 4 + (n & 3), so = slot_sord(n, NR), q = w1_loaded(n - 1, NR, PRE);
        constexpr bool sm = kk >= NR;
        const uint32_t* w = sm ? as[so] : wr[sm ? 0 : (kk * 2 + (n >> 5)) * 4 + (n & 3)];
        if constexpr (n == 32 && PUT1 < 32) { put_partials(TR, pp, acc[0], acc[1]); put_partials(TR, pp + 4096, acc[2], acc[3]); }
        if constexpr (n == 0) {
            const uint32_t c = prmt(v[0][3], x[0], 0x3254);
            v[0][0] = h2bf(v[0][0], v[0][0]); v[0][1] = h2bf(v[0][1], v[0][1]); v[0][2] = h2bf(v[0][2], v[0][2]); v[0][3] = h2bf(v[0][3], x[0]);
            x[0] = c;
        }
        if constexpr ((n & 31) < 4) acc[T][0] = acc[T][1] = acc[T][2] = acc[T][3] = 0.f;
        mma16816(acc[T], w[0], w[1], w[2], w[3], v[slot_r(n, NR) >> 1][(slot_r(n, NR) & 1) * 2], v[slot_r(n, NR) >> 1][(slot_r(n, NR) & 1) * 2 + 1]);
        if constexpr (n == DEPS) {
            const uint32_t sel = __float_as_uint(acc[T][0]) * zero + 0x7610;
#pragma unroll
            for (int b = 1; b < 4; b++) {
                if (b <= NDEP) cvt_block(v[b], x[b], sel);
                else {
                    const uint32_t c = prmt(v[b][3], x[b], 0x3254);
                    v[b][0] = h2bf(v[b][0], v[b][0]); v[b][1] = h2bf(v[b][1], v[b][1]); v[b][2] = h2bf(v[b][2], v[b][2]); v[b][3] = h2bf(v[b][3], x[b]);
                    x[b] = c;
                }
            }
        }
        if constexpr (w1_loaded(n, NR, PRE) > q) load_w1<q, NR>(as[q], w1a);
        if constexpr (n == PUT1 && n >= 32) { put_partials(TR, pp, acc[0], acc[1]); put_partials(TR, pp + 4096, acc[2], acc[3]); }
        if constexpr (n % 4 == 3 && (FM >> (n / 4) & 1) && n != E - 1) sched_fence();
    });
    if constexpr (E == 64) { put_partials(TR, pp + 8192, acc[4], acc[5]); put_partials(TR, pp + 12288, acc[6], acc[7]); }
}
__device__ __forceinline__ void reduce8(const uint32_t (*x)[4], const uint32_t* sel, float sc, uint32_t& r0, uint32_t& r1) {
    float d[4][4];
#pragma unroll
    for (int i = 0; i < 4; i++) {
        d[i][0] = d[i][1] = d[i][2] = d[i][3] = 0.f;
        mma16816(d[i], x[i][0], x[i][1], x[i][2], x[i][3], sel[2 * i], sel[2 * i + 1]);
    }
    r0 = pack2(((d[0][0] + d[1][0]) + (d[2][0] + d[3][0])) * sc, ((d[0][1] + d[1][1]) + (d[2][1] + d[3][1])) * sc);
    r1 = pack2(((d[0][2] + d[1][2]) + (d[2][2] + d[3][2])) * sc, ((d[0][3] + d[1][3]) + (d[2][3] + d[3][3])) * sc);
}

#define ISTAMP(i)
__host__ __device__ constexpr int wo_count(int n, int RES, bool res) { int c = 0; for (int i = 0; i < n; i++) c += (RES >> (i >> 2) & 1) == res; return c; }
__host__ __device__ constexpr int wo_loaded(int n, int RES, int PRE, int end) { int q = PRE; for (int i = 0; i <= n; i++) q += q < end && q - wo_count(i + 1, RES, false) < RING3; return q; }
template <int Q>
__device__ __forceinline__ void load_w2(uint32_t* w, const uint32_t* a) { ldsm4t(w, a[Q & 1] + (Q >> 1) * 1024); }
template <int NB, int RES, int PRE, int FM>
__device__ __forceinline__ void wo_blocks(uint32_t (*w)[4], const uint32_t (*wp)[4], uint32_t oa, const uint32_t* wa, const uint8_t* dst, const uint8_t* dsd, bool odd) {
    float a[NB][4][4];
    uint32_t o[4][4], r[5];
    bar_sync(3, 256);
#pragma unroll
    for (int i = 0; i < 4; i++) ldsm4(o[i], oa + i * 512);
    if (FM & 1) sched_fence();
    static_for<0, NB * 16>([&](auto I) {
        constexpr int n = I.value, i = n & 15, end = wo_count(NB * 16, RES, false), q = wo_loaded(n - 1, RES, PRE, end);
        constexpr bool res = RES >> (n >> 2) & 1;
        const uint32_t* b = o[i >> 2] + (i & 2);
        const uint32_t* x = res ? wp[wo_count(n, RES, true)] : w[wo_count(n, RES, false)];
        float* d = a[n >> 4][i & 3];
        if constexpr (i < 4) d[0] = d[1] = d[2] = d[3] = 0.f;
        mma16816(d, x[0], x[1], x[2], x[3], b[0], b[1]);
        if constexpr (wo_loaded(n, RES, PRE, end) > q) load_w2<q>(w[q], wa);
        if constexpr (n == NB * 16 - 1 || (n >= 16 && i == LAG - 1)) {
            const float (*e)[4] = a[n == NB * 16 - 1 ? NB - 1 : (n >> 4) - 1];
            const uint32_t y = pack2h(e[1][2] + e[3][2], e[1][3] + e[3][3]);
            r[0] = movm(pack2h(e[0][0] + e[2][0], e[0][1] + e[2][1])); r[1] = movm(pack2h(e[0][2] + e[2][2], e[0][3] + e[2][3]));
            r[2] = movm(pack2h(e[1][0] + e[3][0], e[1][1] + e[3][1])); r[3] = movm(odd ? ONES : y); r[4] = movm(odd ? y : ONES);
        }
        if constexpr (n == NB * 16 - 1 || (n >= 16 && i == LAG2 - 1)) {
            constexpr int bs = w2_step(NB == BB, n == NB * 16 - 1 ? NB - 1 : (n >> 4) - 1);
            red_add4(dst + bs * 2048, r[0], r[1], r[2], r[3]);
            red_add1(dsd + (bs >> 1) * 1024 + (bs & 1) * 256, r[4]);
        }
        if constexpr (((FM >> (n / 4 + 1)) & 1) && (n & 3) == 3 && n != NB * 16 - 1) sched_fence();
    });
}
#define FRAG1(ln) ((((ln) & 7) + ((ln) >> 4) * 8) * 128 + ((((((ln) >> 3) & 1) << (ROLE == 1)) ^ ((ln) & 7)) << 4))
#define FRAG2(ln) ((((ln) & 7) + ((ln) >> 4) * 8) * 64 + (((((ln) >> 3) & 1) ^ (((ln) >> 1) & 3)) << 4))
#define TILE_X(i) (ROLE == 1 ? (((i) >> 1) << 6) | (((i) & 1) << 4) : (i) << 5)
__device__ __forceinline__ void chain_fetch(const Params& P, const uint32_t sb, const int cta, const int warp, const int lane, uint32_t (*wr)[4]) {
    const int ROLE = cta % 3, nr = warp < 4 ? NRB : NRA;
    mbar_wait(sb + B_INIT, 0);
    ISTAMP(0)
#pragma unroll
    for (int f = 0; f < 40; f++) {
        const bool w1 = f < (NRA < NRB ? NRA : NRB) * 8 || f < nr * 8;
        ldsm4t(wr[f], sb + warp * 20480 + (f >> 2) * 2048 + (w1 ? FRAG1(lane) ^ TILE_X(f & 3) : (f & 2) * 512 + (FRAG2(lane) ^ ((f & 1) << 5))));
    }
    fence_async_smem();
    mbar_wait(sb + B_SFREE + (warp >> 2) * 8, 0);
    bar_sync(1, 256);
    chain_load(P, sb, cta, warp, lane, 1);
    ISTAMP(1)
}
__device__ __forceinline__ void chain_bounds(const uint32_t sb, const int cta, const int warp, const int lane, const uint32_t (*wr)[4]) {
    const int ROLE = cta % 3, nr = warp < 4 ? NRB : NRA;
    uint32_t m[6] = {}, u[4];
#pragma unroll
    for (int f = 0; f < 40; f++) m[f < 24 ? 0 : f >> 3] = amax4(m[f < 24 ? 0 : f >> 3], wr[f]);
    uint32_t m1 = amax(m[0], amax(nr > 3 ? m[3] : 0, nr > 4 ? m[4] : 0)), m2 = amax(nr > 3 ? 0 : m[3], nr > 4 ? 0 : m[4]);
    ISTAMP(5)
    mbar_wait(sb + B_INIT, 1);
    ISTAMP(3)
    if (ROLE == 2) {
#pragma unroll 4
        for (int i = 0; i < S_W2 / 4096; i++) { lds128(u, sb + S_W1 + warp * (S_W2 / 8) + i * 512 + lane * 16); m1 = amax4(m1, u); }
    }
    mbar_wait(sb + B_INIT2, 0);
    ISTAMP(7)
    const int n = w2_units(ROLE, warp) * 4;
#pragma unroll 4
    for (int i = 0; i < n; i++) { lds128(u, sb + w2_base(warp) + i * 512 + lane * 16); m2 = amax4(m2, u); }
    m1 = warp_exp(m1); m2 = warp_exp(m2);
    if (lane == 0) { if (ROLE == 2) red_max_shared(sb + S_EV, m1); red_max_shared(sb + S_EO, m2); }
}
template <bool ATT>
__device__ __forceinline__ void chain_role(const Params& P, const uint32_t sb, const int cta, const int warp, const int lane, const uint32_t epoch, const uint32_t (*wr)[4]) {
    constexpr int NR = ATT ? NRA : NRB, PRE = ATT ? PREA : PREB;
    const int h = cta / 3, ROLE = cta - h * 3;
    ISTAMP(6)
    uint32_t l8 = opq(sb + lane * 8, lane);
    const uint8_t* persu = (const uint8_t*)((ROLE == 1 ? g_km : g_vmt) + h * 512) - (sb >> 1);
    auto persist = [&](int s, int tile, uint32_t r0, uint32_t r1) {
        uint32_t* pp = (uint32_t*)(persu + s * 65536 + (ROLE == 1 ? (tile >> 1) * 512 + (tile & 1) * 128 : tile * 256) + (l8 >> 1));
        pp[0] = r0; pp[ROLE == 1 ? 64 : 32] = r1;
    };
    const uint32_t rk0 = (h & 1) * 3, rd1 = __shfl_sync(0xffffffffu, mapa(sb, rk0 + (ROLE + 1) % 3) - sb, 0), rd2 = __shfl_sync(0xffffffffu, mapa(sb, rk0 + (ROLE + 2) % 3) - sb, 0);
    const uint32_t xo = (ROLE == 2 ? S_XV : S_X + ROLE * 2048) + warp * 256;
    const bool full = w2_full(ROLE, warp);
    const int blk = w2_block(ROLE, warp);
    const uint32_t om = blk * 2048, os = xg_side(blk);
    const uint32_t w1o = sb + w1_base(warp), w2o = sb + w2_base(warp);
    ISTAMP(2)
    if (lane == 0) mbar_arrive(sb + B_READY);
#pragma unroll 1
    for (int s = 0;; s++) {
        l8 += s & P.zero;
        uint32_t r0, r1;
        {
            uint32_t v[4][4], as[(8 - NR) * 8][4], w1a[4];
            float acc[8][4];
            const uint32_t pst = sb + S_P1 + (l8 - sb) * 16 + ((warp * 16) ^ ((l8 & 56) * 2));
#pragma unroll
            for (int i = 0; i < 4; i++) w1a[i] = w1o + (FRAG1((l8 - sb) >> 3) ^ TILE_X(i));
            auto preload = [&]() { static_for<0, PRE>([&](auto I) { load_w1<I.value, NR>(as[I.value], w1a); }); };
#pragma unroll 1
            while (true) {
                uint32_t x[4];
                if (!(PLATE >> ATT & 1)) preload();
                const uint32_t lm = opq(l8 - sb, (l8 - sb) >> 3);
                const uint8_t* pm = P.xb + xg_buf(s) + warp * 8192 + xg_lane(lm >> 3);
                const uint8_t* ps = P.xb + xg_buf(s) + XG_SIDE + warp * 2048 + (lm >> 1);
                pin_ptr(pm); pin_ptr(ps);
                mbar_wait(sb + B_RELM, s & 1);
                if (ATT ? ADELAY : BDELAY) wait_clocks(ATT ? ADELAY : BDELAY);
                PROF(10)
#pragma unroll
                for (int b = 0; b < 4; b++) { ld_relaxed4(v[b], pm + b * 2048); ld_relaxed1n(x[b], ps + (b >> 1) * 1024 + (b & 1) * 256); }
                if (PLATE >> ATT & 1) { preload(); if (PLATE >> (ATT + 2) & 1) sched_fence(); }
                project<NR, PRE, ATT ? FENCEA : FENCEB, 0, PROG>(acc, ROLE == 2, wr, as, v, x, w1a, pst, P.zero);
                const uint32_t bad = xor_or(x[0], x[1], FULL) | xor_or(x[2], x[3], FULL);
                if (tags_ok(bad, 0xffffffffu)) break;
                COUNT_RETRY(warp >> 1)
                uint32_t n;
                asm volatile("atom.shared.add.u32 %0, [%1], 1;" : "=r"(n) : "r"(sb + S_RETRY) : "memory");
                if (n > SPIN_LIMIT) spin_fault();
            }
            PROF(0)
            project<NR, PRE, ATT ? FENCEA : FENCEB, PROG, 64>(acc, ROLE == 2, wr, as, v, nullptr, w1a, pst, 0);
            PROF(1)
            const uint32_t isc = lds32(sb + S_ISC + (s & 1) * 4);
            const uint32_t lq = l8 + ((s >> 3) & P.zero), e1 = s == 63 ? 0 : rd1, e2 = s == 63 ? 0 : rd2;
            uint32_t x[4][4], sel[8], xd[6] = {l8 + xo, l8 + xo + e1, l8 + xo + e2, sb + B_X + e1, sb + B_X + e2, sb + S_P1 + warp * 2048 + (lq & 64) * 16 + (lq & 128) + (lq & 56) * 2};
#pragma unroll
            for (int i = 0; i < 8; i++) sel[i] = (lq & 224) == i * 32 ? 0x3F803F80u : 0u;
            pin<6>(xd); pin<8>(sel);
            if (RFENCE) sched_fence();
            bar_sync(1, 256);
#pragma unroll
            for (int i = 0; i < 4; i++) ldsm4t(x[i], xd[5] + i * 256);
            if (!ATT && l8 == sb + (warp - 3) * 1024) mbar_arrive(sb + B_P1);
            uint32_t em = warp_exp(amax(amax4(amax(amax(v[0][0], v[0][1]), amax(v[0][2], v[0][3])), v[1]), amax4(amax(amax(v[2][0], v[2][1]), amax(v[2][2], v[2][3])), v[3])));
            if (EFENCE2) sched_fence();
            reduce8(x, sel, bf_hi(isc), r0, r1);
            st_async2(xd[1], r0, r1, xd[3]);
            st_async2(xd[2], r0, r1, xd[4]);
            sts64(xd[0], r0, r1);
            if (s == 63) { persist(s, warp, r0, r1); break; }
            if (l8 == sb) sts32(sb + S_EM + warp * 4, em + (isc >> 23));
            __syncwarp();
            if (l8 == sb) mbar_arrive(sb + B_X);
            PROF(2)
        }
        uint32_t w[40][4], w2a[2], odd;
        const uint8_t *po, *pd;
        auto wo_addr = [&]() {
            const uint32_t lo = (l8 + ((s >> 2) & P.zero) - sb) >> 3;
            w2a[0] = w2o + FRAG2(lo); w2a[1] = w2o + (FRAG2(lo) ^ 32);
            po = P.xb + xg_buf(s + 1) + om + xg_lane(lo);
            pd = P.xb + xg_buf(s + 1) + os + lo * 4;
            odd = lo & 4;
            pin_ptr(po); pin_ptr(pd); pin<2>(w2a); pin<1>(&odd);
        };
        uint32_t oa = l8 * 2 + (S_OX - sb);
        if constexpr (ATT) {
            const uint32_t ln = (l8 + ((s >> 4) & P.zero) - sb) >> 3;
            const uint32_t va = sb + S_KV + 8192 + ((warp >> 1) & 1) * 4096 + ((ln & 7) + (ln >> 4) * 8) * 128 + ((((warp & 1) * 4 + ((ln >> 3) & 1)) ^ (ln & 7)) << 4);
            const uint32_t ka = sb + S_KV + (warp & 1) * 2048 + (ln & 15) * 128 + (((ln >> 4) ^ (ln & 7)) << 4);
            uint32_t ad[5] = {sb + S_SX + (ln & 3) * (8 * SROW) + (ln >> 2) * 4 + (warp < 6 ? (warp - 4) * 64 : 128 + (warp - 6) * 32), l8 + S_XV + (warp - 4) * 512,
                              l8 + S_SX + (ln >> 2) * (4 * SROW - 32), oa + (warp - 4) * 512, sb + S_ISC + (~s & 1) * 4};
            if constexpr (AB) { wo_addr(); pin<1>(&oa); }
            pin<5>(ad);
            const uint32_t sa = ad[0], sr = ad[2];
            uint32_t vf[4][4], vm[2][2], q[8][2];
            float S[4][4];
#pragma unroll
            for (int n = 0; n < 4; n++) { S[n][0] = S[n][1] = S[n][2] = S[n][3] = 0.f; }
            mbar_wait_fast(sb + B_KVFULL, s & 1);
            if (warp < 6) {
                uint32_t kf[8][4];
#pragma unroll
                for (int k = 0; k < 8; k++) ldsm4(kf[k], (ka ^ ((k & 3) << 5)) + (k >> 2) * 4096);
#pragma unroll
                for (int i = 0; i < 4; i++) ldsm4t(vf[i], (va ^ ((i & 1) << 5)) + (i >> 1) * 2048);
                mbar_wait(sb + B_X, s & 1);
                PROF(11)
#pragma unroll
                for (int k = 0; k < 8; k++) lds64(q[k], l8 + S_X + k * 256);
#pragma unroll
                for (int k = 0; k < 8; k++) mma16816(S[k & 3], kf[k][0], kf[k][1], kf[k][2], kf[k][3], q[k][0], q[k][1]);
                sts32(sa, __float_as_uint((S[0][0] + S[1][0]) + (S[2][0] + S[3][0])));
                sts32(sa + 4 * SROW, __float_as_uint((S[0][1] + S[1][1]) + (S[2][1] + S[3][1])));
                sts32(sa + 32, __float_as_uint((S[0][2] + S[1][2]) + (S[2][2] + S[3][2])));
                sts32(sa + 4 * SROW + 32, __float_as_uint((S[0][3] + S[1][3]) + (S[2][3] + S[3][3])));
            } else {
#pragma unroll
                for (int i = 0; i < 4; i++) ldsm4t(vf[i], (va ^ ((i & 1) << 5)) + (i >> 1) * 2048);
                uint32_t xa = l8 + S_X + (warp - 6) * 1024;
                pin<1>(&xa);
                mbar_wait(sb + B_X, s & 1);
                PROF(11)
#pragma unroll
                for (int k = 0; k < 8; k++) lds64(q[k], xa + (k >> 2) * 2048 + (k & 3) * 256);
#pragma unroll
                for (int k = 0; k < 4; k++) mma16816(S[k], q[4 + (k & 2)][0], q[4 + (k & 2)][1], q[5 + (k & 2)][0], q[5 + (k & 2)][1], q[k][0], q[k][1]);
                sts32(sa, __float_as_uint((S[0][0] + S[2][0]) + (S[1][2] + S[3][2])));
                sts32(sa + 4 * SROW, __float_as_uint((S[0][1] + S[2][1]) + (S[1][3] + S[3][3])));
            }
            lds64(vm[0], ad[1]); lds64(vm[1], ad[1] + 256);
            PROF(7)
            bar_sync(2, 160);
            const float cs = 0.08838834764831845f * 1.4426950408889634f;
            float E[6][2];
#pragma unroll
            for (int i = 0; i < 6; i++) lds64f(E[(i + 4) % 6], sr + ((i + 4) % 6) * 32);
            const uint32_t isn = lds32(ad[4]);
            E[4][0] += E[5][0]; E[4][1] += E[5][1];
            float m = fmaxf(fmaxf(fmaxf(fmaxf(E[0][0], E[0][1]), fmaxf(E[1][0], E[1][1])), fmaxf(fmaxf(E[2][0], E[2][1]), fmaxf(E[3][0], E[3][1]))), fmaxf(E[4][0], E[4][1]));
            m = fmaxf(m, __shfl_xor_sync(0xffffffffu, m, 1));
            m = fmaxf(m, __shfl_xor_sync(0xffffffffu, m, 2));
            m *= cs;
            if constexpr (AB) static_for<0, PRE3>([&](auto I) { load_w2<I.value>(w[I.value], w2a); });
            uint32_t pa[5];
#pragma unroll
            for (int i = 0; i < 5; i++) { const int k = (i + 4) % 5; E[k][0] = ex2(fmaf(E[k][0], cs, -m)); E[k][1] = ex2(fmaf(E[k][1], cs, -m)); pa[k] = pack2(E[k][0], E[k][1]); }
            if (EFENCE) sched_fence();
            float O[2][4], Z[4];
#pragma unroll
            for (int i = 0; i < 4; i++) { O[0][i] = O[1][i] = Z[i] = 0.f; }
#pragma unroll
            for (int i = 0; i < 2; i++) {
                mma1688(O[i], vm[i][0], vm[i][1], pa[4]);
                mma16816(O[i], vf[i][0], vf[i][1], vf[i][2], vf[i][3], pa[0], pa[1]);
                mma16816(O[i], vf[2 + i][0], vf[2 + i][1], vf[2 + i][2], vf[2 + i][3], pa[2], pa[3]);
            }
            const float z = (((E[4][0] + E[4][1]) + (E[0][0] + E[0][1])) + ((E[1][0] + E[1][1]) + (E[2][0] + E[2][1]))) + (E[3][0] + E[3][1]);
            const float zh = __uint_as_float(__float_as_uint(z) & 0xffff0000u);
            mma1688(Z, isn, isn, pack2(zh, z - zh));
            const float i0 = rcp(Z[0]), i1 = rcp(Z[1]);
            stsm4t(ad[3], pack2(O[0][0] * i0, O[0][1] * i1), pack2(O[0][2] * i0, O[0][3] * i1), pack2(O[1][0] * i0, O[1][1] * i1), pack2(O[1][2] * i0, O[1][3] * i1));
            PROF(4)
            if constexpr (AB) wo_blocks<1, RESA, PRE3, OFENCE / 2>(w, wr + NR * 8, oa, w2a, po, pd, odd);
            else bar_arrive(3, 256);
            if (ROLE != 0) persist(s, warp, r0, r1);
            if (warp == 7 && l8 == sb) mbar_expect(sb + B_X, 4096);
        } else {
            if (ROLE != 0) persist(s, warp, r0, r1);
            wo_addr(); pin<1>(&oa);
            static_for<0, PRE2A>([&](auto I) { load_w2<I.value>(w[I.value], w2a); });
            mbar_wait(sb + B_X, s & 1);
            if (warp == 0) {
                uint32_t sc[2];
                lds64(sc, sb + S_SC);
                const int em = __reduce_max_sync(0xffffffffu, lds32(sb + S_EM + ((l8 >> 1) & 28)));
                if (l8 == sb) sts32(sb + S_ISC + (~s & 1) * 4, min(max(em - 127, (int)sc[1]) + (int)sc[0], 253) * 0x800080u);
                bar_arrive(2, 160);
            }
            wait_clocks(XDELAY - (warp == 0) * 100);
            constexpr int PRE1 = (BB - 1) * 16 - (5 - NRB) * 8 < PRE2 ? (BB - 1) * 16 - (5 - NRB) * 8 : PRE2;
            static_for<PRE2A, PRE1>([&](auto I) { load_w2<I.value>(w[I.value], w2a); });
            if (full) {
                static_for<PRE1, PRE2>([&](auto I) { load_w2<I.value>(w[I.value], w2a); });
                wo_blocks<BB, RESB, PRE2, FENCE2 * 2 + OFENCE % 2>(w, wr + NR * 8, oa, w2a, po, pd, odd);
            } else wo_blocks<BB - 1, RESB1, PRE1, FENCE2 * 2 + OFENCE % 2>(w, wr + NR * 8, oa, w2a, po, pd, odd);
        }
        PROF(5)
        if (l8 == sb) { sts32(sb + S_TO + warp * 4, gtime()); mbar_arrive(sb + B_RED); }
        if (HOLD && !(PLATE >> ATT & 1)) mbar_wait(sb + B_RED, s & 1);
        if (ROLE != 0 && (s & 3) == 3 && l8 == sb) mbar_arrive(sb + B_PERS);
        if (ROLE == 0 && s == 62) return;
    }
    __syncwarp();
    if (l8 == sb) mbar_arrive(sb + B_PERS);
}
#define IP(i)
struct Pipe { uint32_t stage, phase; };
struct Cons {
    uint32_t sb, rel;
    int wg, wq, lane, rank, pair;
    uint32_t atag, nst;
    Pipe p;
};
__device__ __forceinline__ void pipe_next(Pipe& p) { p.stage = (p.stage + 1) & (NSTAGE - 1); p.phase ^= (p.stage == 0); }
__device__ __forceinline__ void release(const Cons& c, uint32_t stage) { if (c.lane < 2) mbar_arrive_cluster(c.rel + stage * 8); }
__device__ __forceinline__ void wait_full(const Cons& c) { mbar_wait(c.sb + B_FULL + c.p.stage * 8, c.p.phase); }

enum { PEND_NONE = 0, PEND_KVO = 1, PEND_HT = 2, PEND_OUT = 3 };
struct Pend { uint32_t pk[64]; int kind, row, col, cnt; };

__device__ __forceinline__ void staging_wait(const Cons& c) { if (c.nst) mbar_wait(c.sb + B_SFREE + c.wg * 8, (c.nst - 1) & 1); }
__device__ __forceinline__ void staging_post(Cons& c, int kind, int row, int col, int cnt) {
    __syncwarp();
    if (c.lane == 0) {
        if (c.wq == 0) { const uint32_t x[4] = {(uint32_t)kind, (uint32_t)row, (uint32_t)col, (uint32_t)cnt}; sts128(c.sb + S_DESC + c.wg * 16, x); }
        mbar_arrive(c.sb + B_SFULL + c.wg * 8);
    }
    c.nst++;
}
__device__ __forceinline__ void drain(const Params& P, Cons& c, Pend& d) {
    const uint32_t* pk = d.pk;
    if (d.kind == PEND_OUT) {
        float* o = P.out + (size_t)(d.row + c.wq * 16 + (c.lane >> 2)) * 2048 + d.col + (c.lane & 3) * 2;
#pragma unroll
        for (int j = 0; j < 16; j++) {
            st_stream2(o + j * 8, bf_lo(pk[j * 2]), bf_hi(pk[j * 2]));
            st_stream2(o + 8 * 2048 + j * 8, bf_lo(pk[j * 2 + 1]), bf_hi(pk[j * 2 + 1]));
        }
    } else {
        const bool ht = d.kind == PEND_HT;
        const int hi = (c.lane >> 3) & 1;
        const uint32_t base = c.sb + S_STG + c.wg * 16384 + ((ht ? hi * 32 + c.wq * 8 : c.wq * 16 + hi * 8) + (c.lane & 7)) * 128;
        staging_wait(c);
#pragma unroll
        for (int j = 0; j < 8; j++) {
            const int ch = (j & 3) * 2 + (c.lane >> 4);
            stsm4(base + (j >> 2) * 8192 + ((ch ^ (c.lane & 7)) << 4), pk[j * 4], pk[j * 4 + 1], pk[j * 4 + 2], pk[j * 4 + 3]);
        }
        fence_async_smem();
        staging_post(c, d.kind, d.row, d.col, (d.col & 128) ? d.cnt : -1);
    }
    if (d.col & 128) d.kind = PEND_NONE;
    d.col += 128;
#pragma unroll
    for (int i = 0; i < 32; i++) d.pk[i] = d.pk[32 + i];
}

constexpr int S_STG2 = 8 * 20480, PEND_BOTH = 8;
__device__ __forceinline__ void drain_both(Cons& c, const Pend& d) {
    const uint32_t base = c.sb + c.wg * 16384 + (c.wq * 16 + ((c.lane >> 3) & 1) * 8 + (c.lane & 7)) * 128;
#pragma unroll
    for (int j = 0; j < 16; j++)
        stsm4(base + (j < 8 ? S_STG : S_STG2) + (j >> 2 & 1) * 8192 + ((((j & 3) * 2 + (c.lane >> 4)) ^ (c.lane & 7)) << 4), d.pk[j * 4], d.pk[j * 4 + 1], d.pk[j * 4 + 2], d.pk[j * 4 + 3]);
    fence_async_smem();
    staging_post(c, PEND_KVO | PEND_BOTH, d.row, d.col, d.cnt);
}

__device__ __forceinline__ void store_warp(const Params& P, uint32_t sb, int wg, int cta) {
    if (cta < 128) {
        for (int i = 0; i < P.xd; i++) __nanosleep(1000);
        const uint32_t e1 = ld_acquire(&g_cnt(C_EPOCH)) + 1;
        const uint4* x = (const uint4*)P.Bx + (cta * 2 + wg) * 1024 + (threadIdx.x & 31);
        uint32_t m = 0;
#pragma unroll 4
        for (int i = 0; i < 32; i++) { const uint4 u = __ldg(x + i * 32); m = amax(amax(m, amax(u.x, u.y)), amax(u.z, u.w)); }
        m = warp_exp(m);
        if (elect_one()) { atomicMax(&g_cnt(C_XMAX), e1 << 8 | m); red_release(&g_cnt(C_XCNT)); }
        __syncwarp();
    }
    const uint32_t stg = sb + S_STG + wg * 16384;
#pragma unroll 1
    for (uint32_t n = 0;; n++) {
        mbar_wait(sb + B_SFULL + wg * 8, n & 1);
        uint32_t x[4];
        lds128(x, sb + S_DESC + wg * 16);
#pragma unroll
        for (int i = 0; i < 4; i++) x[i] = __shfl_sync(0xffffffffu, x[i], 0);
        if (x[0] == PEND_NONE) break;
        const bool ht = x[0] == PEND_HT;
        const CUtensorMap* m = &P.tm[ht ? M_HTS : M_KVO];
        const uint64_t pol = P.pol[ht ? 2 : x[1] >= 4096 ? 1 : (x[1] & 2047) < 1536 ? 0 : 10];
        if (elect_one()) {
#pragma unroll
            for (int i = 0; i < 4; i++) tma_store2d(m, x[2] + (i >> 1) * 64, x[1] + (i & 1) * (ht ? 1024 : 32), stg + i * 4096, pol);
            if (x[0] & PEND_BOTH) {
#pragma unroll 1
                for (int i = 0; i < 4; i++) tma_store2d(m, x[2] + 128 + (i >> 1) * 64, x[1] + (i & 1) * 32, stg + (S_STG2 - S_STG) + i * 4096, pol);
            }
            bulk_commit();
            bulk_wait_read();
            mbar_arrive(sb + B_SFREE + wg * 8);
            if ((int)x[3] >= 0) { bulk_wait_all(); fence_async(); red_release(&g_cnt(x[3])); }
        }
        __syncwarp();
    }
}

template <int TA, int TB, bool FIRST>
__device__ __forceinline__ void issue_ktile(float* acc, const Cons& c) {
    const uint32_t a = c.sb + c.p.stage * STAGE + c.wg * 8192, b = c.sb + c.p.stage * STAGE + 16384;
    const uint64_t da = mkdesc(a, TA ? 8192 : 16, 1024, 1), db = mkdesc(b, TB ? 8192 : 16, 1024, 1);
    wg_fence();
#pragma unroll
    for (int k = 0; k < 4; k++) {
        if (FIRST && k == 0) wgmma_ss256_first<TA, TB>(acc, da, db);
        else wgmma_ss256<TA, TB>(acc, da + (TA ? 128 : 2) * k, db + (TB ? 128 : 2) * k);
    }
    wg_commit();
}
template <bool KVONLY, bool FIRST>
__device__ __forceinline__ void issue_any(float* acc, const Cons& c, int type) {
    if (FIRST) mbar_wait_fast(c.sb + B_FULL + c.p.stage * 8, c.p.phase); else wait_full(c);
    if (!KVONLY && type == T_A1) issue_ktile<0, 0, FIRST>(acc, c);
    else if (!KVONLY && type == T_A2) issue_ktile<1, 0, FIRST>(acc, c);
    else issue_ktile<0, 1, FIRST>(acc, c);
}
template <bool KVONLY = false>
__device__ __forceinline__ void mainloop(float* acc, const Params& P, Cons& c, Pend& d, int type, int nk) {
    issue_any<KVONLY, true>(acc, c, type);
    if (!KVONLY) { IP(0) }
    uint32_t prev = c.p.stage;
    pipe_next(c.p);
#pragma unroll 1
    for (int kt = 1; kt < nk; kt++) {
        if (!KVONLY && d.kind != PEND_NONE && kt != 2) drain(P, c, d);
        issue_any<KVONLY, false>(acc, c, type);
        wg_wait<1>();
        release(c, prev);
        prev = c.p.stage;
        pipe_next(c.p);
    }
    d.kind = PEND_NONE;
    wg_wait<0>();
    pin<128>(acc);
    release(c, prev);
    if (!KVONLY) { IP(1) }
}
__device__ __forceinline__ void pack_half(uint32_t* pk, const float* a) {
#pragma unroll
    for (int i = 0; i < 32; i++) pk[i] = pack2(a[2 * i], a[2 * i + 1]);
}

__device__ __forceinline__ void epi_kv(const float* acc, const Cons& c, Pend& d, int mb, int nb) {
    pack_half(d.pk, acc); pack_half(d.pk + 32, acc + 64);
    d.kind = PEND_KVO; d.row = (nb >> 4) * 2048 + mb * 256 + c.rank * 128 + c.wg * 64; d.col = (nb & 15) * 256; d.cnt = C_KV + mb;
}

__device__ __forceinline__ void qa_scores(float* S, float* Sm, const uint32_t* q, Cons& c) {
    wait_full(c);
    const uint32_t st = c.sb + c.p.stage * STAGE;
    const uint64_t dk = mkdesc(st + c.wg * 8192, 16, 1024, 1), dm = mkdesc(st + 32768 + c.wg * 4096, 128, 2048, 0);
    wg_fence();
#pragma unroll
    for (int i = 0; i < 8; i++) wgmma_rs64<0>(S, q + i * 4, dk + (i >> 2) * 1024 + (i & 3) * 2, i != 0);
#pragma unroll
    for (int i = 0; i < 8; i++) wgmma_rs16<0>(Sm, q + i * 4, dm + i * 16, i != 0);
    wg_commit();
    pipe_next(c.p);
}
__device__ __forceinline__ void qa_softmax(uint32_t (*pa)[4], const float* S, const float* Sm, const Cons& c) {
    const int t = c.lane & 3, i0 = (c.wq & 1) * 16 + (c.lane >> 2) - 2 * t;
    const bool sg = c.wq >= 2;
    const float cs = 0.08838834764831845f * 1.4426950408889634f;
    float x[2][10];
#pragma unroll
    for (int r = 0; r < 2; r++) {
#pragma unroll
        for (int j = 0; j < 4; j++)
#pragma unroll
            for (int e = 0; e < 2; e++) {
                const float v = sg ? S[16 + j * 4 + r * 2 + e] : S[j * 4 + r * 2 + e];
                x[r][j * 2 + e] = (j * 8 + e - r * 8 > i0) ? -1e9f / 0.08838834764831845f : v;
            }
        x[r][8] = sg ? Sm[4 + r * 2] : Sm[r * 2];
        x[r][9] = sg ? Sm[5 + r * 2] : Sm[1 + r * 2];
        float m = fmaxf(fmaxf(fmaxf(fmaxf(x[r][0], x[r][1]), fmaxf(x[r][2], x[r][3])), fmaxf(fmaxf(x[r][4], x[r][5]), fmaxf(x[r][6], x[r][7]))), fmaxf(x[r][8], x[r][9]));
        m = fmaxf(m, __shfl_xor_sync(0xffffffffu, m, 1));
        m = fmaxf(m, __shfl_xor_sync(0xffffffffu, m, 2));
        m *= -cs;
#pragma unroll
        for (int i = 0; i < 10; i++) x[r][i] = ex2(fmaf(x[r][i], cs, m));
        float sum = (((x[r][0] + x[r][1]) + (x[r][2] + x[r][3])) + ((x[r][4] + x[r][5]) + (x[r][6] + x[r][7]))) + (x[r][8] + x[r][9]);
        sum += __shfl_xor_sync(0xffffffffu, sum, 1);
        sum += __shfl_xor_sync(0xffffffffu, sum, 2);
        const float inv = rcp(sum);
#pragma unroll
        for (int i = 0; i < 10; i++) x[r][i] *= inv;
    }
#pragma unroll
    for (int ks = 0; ks < 2; ks++)
#pragma unroll
        for (int i = 0; i < 4; i++) {
            const uint32_t p = pack2(x[i & 1][ks * 4 + (i >> 1) * 2], x[i & 1][ks * 4 + (i >> 1) * 2 + 1]);
            pa[ks][i] = sg ? 0u : p;
            pa[2 + ks][i] = sg ? p : 0u;
        }
#pragma unroll
    for (int r = 0; r < 2; r++) {
        const uint32_t p = pack2(x[r][8], x[r][9]);
        pa[4][r] = sg ? 0u : p;
        pa[4][2 + r] = sg ? p : 0u;
    }
}
__device__ __forceinline__ void qa_values(float* O, uint32_t (*pa)[4], Cons& c) {
    wait_full(c);
    const uint32_t st = c.sb + c.p.stage * STAGE;
    const uint64_t dv = mkdesc(st + c.wg * 8192, 16384, 1024, 1), dm = mkdesc(st + 32768 + c.wg * 4096, 2048, 128, 0);
    pin<20>(&pa[0][0]);
    wg_fence();
#pragma unroll
    for (int ks = 0; ks < 4; ks++) wgmma_rs128<1>(O, pa[ks], dv + ks * 128, ks != 0);
    wgmma_rs128<0>(O, pa[4], dm, 1);
    wg_commit();
    pipe_next(c.p);
}
__device__ __forceinline__ void epi_qa(const float* acc, Cons& c, Pend& d, int mb, int nb) {
    uint32_t q[64], pa[2][5][4];
    float S0[32] = {}, M0[8] = {}, S1[32] = {}, M1[8] = {}, O0[64] = {}, O1[64] = {};
    const uint32_t k0 = c.p.stage;
    pack_half(q, acc);
    pin<32>(q); pin<32>(S0); pin<8>(M0);
    qa_scores(S0, M0, q, c);
    pack_half(q + 32, acc + 64);
    pin<32>(q + 32); pin<32>(S1); pin<8>(M1);
    qa_scores(S1, M1, q + 32, c);
    wg_wait<1>();
    pin<32>(S0); pin<8>(M0);
    release(c, k0);
    qa_softmax(pa[0], S0, M0, c);
    wg_wait<0>();
    pin<32>(S1); pin<8>(M1); pin<64>(q);
    release(c, (k0 + 1) & (NSTAGE - 1));
    pin<64>(O0);
    qa_values(O0, pa[0], c);
    qa_softmax(pa[1], S1, M1, c);
    pin<64>(O1);
    qa_values(O1, pa[1], c);
    wg_wait<1>();
    pin<64>(O0); pin<20>(&pa[0][0][0]);
    release(c, (k0 + 2) & (NSTAGE - 1));
    pack_half(d.pk, O0);
    wg_wait<0>();
    pin<64>(O1); pin<20>(&pa[1][0][0]);
    release(c, (k0 + 3) & (NSTAGE - 1));
    pack_half(d.pk + 32, O1);
    d.kind = PEND_KVO; d.row = 4096 + mb * 256 + c.rank * 128 + c.wg * 64; d.col = nb * 256; d.cnt = C_O + mb;
}

__device__ __forceinline__ void epi_op(const float* acc, const Cons& c, Pend& d, int mb, int nb) {
    pack_half(d.pk, acc); pack_half(d.pk + 32, acc + 64);
    d.kind = PEND_OUT; d.row = mb * 256 + c.rank * 128 + c.wg * 64; d.col = 1024 + nb * 256;
}

__device__ __forceinline__ void epi_a2(float* acc, const Params& P, Cons& c, int mb, int col0) {
    const int g = c.lane >> 2, t = c.lane & 3;
    const int row = mb * 256 + (g >> 1) * 64 + (c.rank * 16 + c.wg * 8 + c.wq * 2) * 2 + (g & 1);
    float* o = P.out + (size_t)row * 2048 + col0 + t * 2;
#pragma unroll 1
    for (int hf = P.zero; hf < 2; hf++) {
    wait_full(c);
    const uint32_t st = c.sb + c.p.stage * STAGE, xa = st + (c.wg * 64 + c.wq * 16 + g) * 128 + t * 4 + (g << 4), da = st + 32768 + t * 4;
#pragma unroll
    for (int j = 0; j < 16; j++) {
        const float* a = acc + j * 4;
        const uint32_t ad = (xa ^ ((j & 7) << 4)) + (j >> 3) * 16384;
        const uint32_t x0 = lds32(ad), x1 = lds32(ad + 1024), dv = lds32(da + j * 16);
        const uint32_t u0 = mul_bf2(x0, dv), u1 = mul_bf2(x1, dv);
        st_stream2(o + j * 8, a[0] + bf_lo(u0), a[1] + bf_hi(u0));
        st_stream2(o + 2 * 2048 + j * 8, a[2] + bf_lo(u1), a[3] + bf_hi(u1));
    }
    __syncwarp();
    release(c, c.p.stage);
    pipe_next(c.p);
    o += 128;
#pragma unroll
    for (int i = 0; i < 64; i++) acc[i] = acc[64 + i];
    }
}

#define TSTAMP(i)
__device__ __forceinline__ float2 cmul(float2 a, float2 b) { return make_float2(fmaf(a.x, b.x, -a.y * b.y), fmaf(a.x, b.y, a.y * b.x)); }
__device__ __forceinline__ float2 cfma(float2 a, float2 b, float2 u) { return make_float2(fmaf(a.x, b.x, fmaf(-a.y, b.y, u.x)), fmaf(a.x, b.y, fmaf(a.y, b.x, u.y))); }
__device__ __forceinline__ float4 ssm_coef(float lre, float lim, float logdt) {
    const float dt = __bfloat162float(__float2bfloat16(expf(logdt)));
    const float ea = expf(dt * lre);
    float sn, cn;
    sincosf(dt * lim, &sn, &cn);
    const float br = ea * cn, bi = ea * sn, nr = br - 1.f;
    float cr, ci;
    if (fabsf(lre) >= fabsf(lim)) { const float r = lim / lre, dn = lre + lim * r; cr = (nr + bi * r) / dn; ci = (bi - nr * r) / dn; }
    else { const float r = lre / lim, dn = lre * r + lim; cr = (nr * r + bi) / dn; ci = (bi * r - nr) / dn; }
    return make_float4(br, bi, cr, ci);
}
__device__ __forceinline__ void epi_a1(const float* acc, const Params& P, const Cons& c, Pend& d, int mb, int nb, uint32_t atag) {
    const int t = c.lane & 3;
    const int p = nb * 128 + c.rank * 64 + c.wg * 32 + c.wq * 8 + (c.lane >> 2);
    const float4 cf = __ldcg(&g_coef[p]);
    const float2 lam = make_float2(cf.x, P.swap_ri ? -cf.y : cf.y);
    const float a0 = P.swap_ri ? -2.f * cf.w : 2.f * cf.z, a1 = P.swap_ri ? 2.f * cf.z : -2.f * cf.w;
    const float b0 = P.swap_ri ? -2.f * cf.z : -2.f * cf.w, b1 = P.swap_ri ? -2.f * cf.w : -2.f * cf.z;
    float2 h = make_float2(0.f, 0.f);
#pragma unroll 1
    for (int round = P.zero; round < 2; round++) {
#pragma unroll
        for (int j = 0; j < 32; j++) {
            h = cfma(lam, h, make_float2(acc[j * 4], acc[j * 4 + 2]));
            const float r0 = fmaf(a0, h.x, a1 * h.y), m0 = fmaf(b0, h.x, b1 * h.y);
            h = cfma(lam, h, make_float2(acc[j * 4 + 1], acc[j * 4 + 3]));
            d.pk[j * 2] = pack2(r0, fmaf(a0, h.x, a1 * h.y));
            d.pk[j * 2 + 1] = pack2(m0, fmaf(b0, h.x, b1 * h.y));
        }
        if (round) continue;
        float2 l64 = lam;
#pragma unroll
        for (int i = 0; i < 6; i++) l64 = cmul(l64, l64);
        const float2 l128 = cmul(l64, l64), l256 = cmul(l128, l128);
        float2 o = make_float2(__shfl_up_sync(0xffffffffu, h.x, 1), __shfl_up_sync(0xffffffffu, h.y, 1));
        if (t >= 1) h = cfma(l64, o, h);
        o = make_float2(__shfl_up_sync(0xffffffffu, h.x, 2), __shfl_up_sync(0xffffffffu, h.y, 2));
        if (t >= 2) h = cfma(l128, o, h);
        IP(2)
        if (t == 3) st_relaxed2(&g_agg[mb * 1024 + p], (__float_as_uint(h.x) & ~1u) | atag, __float_as_uint(h.y));
        h = make_float2(__shfl_up_sync(0xffffffffu, h.x, 1), __shfl_up_sync(0xffffffffu, h.y, 1));
        if (t == 0) h = make_float2(0.f, 0.f);
        uint32_t ax[7], ay[7];
        int n = 0;
        while (true) {
            uint32_t bad = 0;
#pragma unroll
            for (int j = 0; j < 7; j++) { ax[j] = atag; ay[j] = 0; ld_relaxed2_if(ax[j], ay[j], &g_agg[j * 1024 + p], j < mb); }
#pragma unroll
            for (int j = 0; j < 7; j++) bad |= ax[j] ^ atag;
            if (tags_ok(bad)) break;
            __nanosleep(2 * POLLNS);
            if (++n > SPIN_LIMIT) spin_fault();
        }
        float2 carry = make_float2(0.f, 0.f);
#pragma unroll
        for (int j = 0; j < 7; j++) if (j < mb) carry = cfma(l256, carry, make_float2(__uint_as_float(ax[j]), __uint_as_float(ay[j])));
        float2 w = (t & 1) ? l64 : make_float2(1.f, 0.f);
        if (t & 2) w = cmul(w, l128);
        h = cfma(w, carry, h);
        IP(3)
    }
    IP(4)
    d.kind = PEND_HT; d.row = nb * 128 + c.rank * 64 + c.wg * 32; d.col = mb * 256; d.cnt = C_HT + mb;
}

__device__ __forceinline__ uint32_t fresh_tid() { uint32_t t; asm volatile("mov.u32 %0, %%tid.x;" : "=r"(t)); return t; }
__device__ __forceinline__ uint32_t acquire_stage(uint32_t sb, Pipe& p, uint32_t bytes) {
    mbar_wait(sb + B_EMPTY + p.stage * 8, p.phase ^ 1);
    mbar_expect_e(sb + B_FULL + p.stage * 8, bytes);
    return p.stage;
}
__device__ __forceinline__ void producer(const Params& P, const uint32_t sb, const int cta, const uint32_t epoch) {
    Pipe p = {0, 0};
    uint32_t resume = 1;
    const uint32_t e1 = epoch + 1;
    const int rank = cta & 1;
    const uint16_t both = 3 << (__shfl_sync(0xffffffffu, cluster_rank(), 0) & ~1u);
    for (int it = ITEM_OFF(cta >> 1); it < ITEM_OFF((cta >> 1) + 1); it++) {
        const int item = ITEM(it), kind = (item >> 8) & 7, mb = (item >> 5) & 7;
        const int half = kind >= T_OPH, type = half ? kind * 2 - 10 : kind, nb = item & (half ? 3 : 31), hw = item >> 2 & half;
        if (type == T_CHAIN) {
            const int h = cta / 3, role = cta - h * 3;
            uint32_t* flag = &g_cnt(C_FLAG + (role == 2 ? 32 : 0) + h);
            if (role) { wait_count(&g_cnt(C_KV), e1 * 128); fence_async(); }
#pragma unroll 1
            for (int s = 0; s < 64 && role != 0; s++) {
                if (s < 63) {
                    mbar_wait(sb + B_GO, s & 1);
                    tma3d_mc_e(sb + S_KV + (role - 1) * 8192, &P.tm[M_SEG], 0, (role - 1) * 2048 + s * 32, h * 2, sb + B_KVFULL, 7 << ((h & 1) * 3), P.pol[s < 48 ? 8 : 11]);
                    if ((s & 7) == 7) { wait_count(&g_cnt(C_KV + 1 + (s >> 3)), e1 * 128); fence_async(); }
                    tma_prefetch3d_e(&P.tm[M_SEG], 0, (role - 1) * 2048 + s * 32 + 32, h * 2);
                }
                if (s > 0 && ((s & 3) == 0 || s == 63)) {
                    const int i = (s - 1) >> 2;
                    mbar_wait(sb + B_PERS, i & 1);
                    asm volatile("{\n.reg .pred E;\nelect.sync _|E, 0xffffffff;\n@E st.release.gpu.global.u32 [%0], %1;\n}" ::"l"(flag), "r"(epoch * 64 + i * 4 + 4) : "memory");
                }
            }
            if (role == 0) {
                const int lane = threadIdx.x & 31;
                if (lane == 0) mbar_arrive(sb + B_RELM);
#pragma unroll 1
                for (int s = 0; s < 63; s++) {
                    mbar_wait(sb + B_P1, s & 1);
                    if (s > 0) {
                        st_relaxed4(P.xb + xg_buf(s - 1) + h * 2048 + xg_lane(lane), 0, 0, 0, 0);
                        st_relaxed1(P.xb + xg_buf(s - 1) + xg_side(h) + lane * 4, 0);
                        __threadfence();
                    }
                    __syncwarp();
                    if (lane == 0) mbar_arrive(sb + B_RELM);
                }
            }
            if ((threadIdx.x & 31) < M_C1) asm volatile("prefetch.tensormap [%0];" ::"l"(&P.tm[threadIdx.x & 31]) : "memory");
            resume = 0;
            continue;
        }
        const int m0 = mb * 256 + rank * 128;
        if (type <= T_OP) {
            const CUtensorMap* ma = &P.tm[half ? M_OAH : type == T_OP ? M_OA : M_BX];
            const CUtensorMap* mw = &P.tm[type == T_OP ? M_WO : type == T_QA ? M_WQ : nb < 16 ? M_WK : M_WV];
            const int nk = type == T_OP ? 64 : 16, nc = (nb & 15) * 4 + rank * 2, ma0 = type == T_OP ? 4096 + m0 + hw * 64 : m0;
            if (type == T_OP) { wait_count(&g_cnt(C_O + mb), e1 * 64); fence_async(); }
            if (type == T_QA) {
                wait_count(&g_cnt(C_KV + mb), e1 * 128);
                fence_async();
            }
            auto arrived = [&]() {
                const uint32_t t = fresh_tid();
                return __all_sync(0xffffffffu, (int32_t)(ld_acquire(&g_cnt(C_FLAG + (t & 2) * 16 + nb * 2 + (t & 1))) - (epoch * 64 + mb * 8 + rank * 4 + 4)) >= 0);
            };
            bool passed = false;
            mbar_wait(sb + B_RESUME, resume);
#pragma unroll 1
            for (int kt = 0; kt < nk; kt++) {
                if (type == T_QA && kt == 9) passed = arrived();
                const uint32_t st = acquire_stage(sb, p, STAGE - half * 8192), bar = sb + B_FULL + st * 8;
                tma2d_e(sb + st * STAGE + hw * 8192, ma, kt * 64, ma0, bar, P.pol[4 + type]);
                tma3d_mc_e(sb + st * STAGE + 16384 + rank * 16384, mw, 0, kt * 64, nc, bar, both, P.pol[type == T_KV && mb == 7 ? 9 : 11]);
                if (type == T_QA && kt < 8) tma_prefetch2d_e(&P.tm[M_OA], nb * 256 + (kt & 3) * 64, (kt >> 2) * 2048 + m0);
                pipe_next(p);
            }
            if (type == T_QA) {
                for (int n = 0; !passed; n++) { passed = arrived(); if (!passed) __nanosleep(200); if (n > SPIN_LIMIT) spin_fault(); }
                fence_async();
#pragma unroll 1
                for (int e = 0; e < 4; e++) {
                    const uint32_t st = acquire_stage(sb, p, 40960), bar = sb + B_FULL + st * 8, dst = sb + st * STAGE;
                    tma2d_e(dst, &P.tm[M_OA], nb * 256 + (e & 1) * 128, (e >> 1) * 2048 + m0, bar, P.pol[3]);
                    tma2d_e(dst + 16384, &P.tm[M_OA], nb * 256 + (e & 1) * 128 + 64, (e >> 1) * 2048 + m0, bar, P.pol[3]);
                    const uint32_t* src = ((e >> 1) ? g_vmt : g_km) + ((mb * 8 + rank * 4) * 32 + nb * 2 + (e & 1)) * 512;
#pragma unroll 1
                    for (int i = 0; i < 4; i++) bulk_g2s_e(dst + 32768 + i * 2048, src + i * 32 * 512, 2048, bar);
                    pipe_next(p);
                }
            }
        } else if (type == T_A1) {
            wait_count(&g_cnt(C_COEF), e1 * 4);
            l2_prefetch_e(g_coef + nb * 128 + rank * 64, 1024);
            mbar_wait(sb + B_RESUME, resume);
#pragma unroll 1
            for (int kt = 0; kt < 16; kt++) {
                const uint32_t st = acquire_stage(sb, p, STAGE), bar = sb + B_FULL + st * 8;
                tma4d_e(sb + st * STAGE, &P.tm[M_AB], kt * 64, nb * 16 + rank * 8, bar);
                tma4d_mc_e(sb + st * STAGE + 16384 + rank * 16384, &P.tm[M_AX], kt * 64, mb * 128 + rank * 16, bar, both);
                pipe_next(p);
            }
        } else {
            wait_count(&g_cnt(C_HT + mb), e1 * 32);
            fence_async();
            mbar_wait(sb + B_RESUME, resume);
#pragma unroll 1
            for (int kt = 0; kt < 32; kt++) {
                const uint32_t st = acquire_stage(sb, p, STAGE - half * 8192), bar = sb + B_FULL + st * 8;
                tma3d_e(sb + st * STAGE + hw * 8192, &P.tm[half ? M_HTH : M_HT], 0, kt * 64, mb * 4 + rank * 2 + hw, bar, P.pol[7]);
                tma2d_mc_e(sb + st * STAGE + 16384 + rank * 16384, &P.tm[M_CRE] + (kt >> 4), (kt & 15) * 64, (nb * 2 + rank) * 128, bar, both);
                pipe_next(p);
            }
#pragma unroll 1
            for (int col = nb * 256; col < (nb + 1) * 256; col += 128) {
                const uint32_t st = acquire_stage(sb, p, 32768 + 256), bar = sb + B_FULL + st * 8;
                tma4d_e(sb + st * STAGE, &P.tm[M_AX], col, mb * 128 + rank * 16, bar);
                tma4d_e(sb + st * STAGE + 16384, &P.tm[M_AX], col + 64, mb * 128 + rank * 16, bar);
                bulk_g2s_e(sb + st * STAGE + 32768, P.Dskip + col, 256, bar);
                pipe_next(p);
            }
        }
    }
}

__device__ __forceinline__ uint32_t fresh_ctaid() { uint32_t t; asm volatile("mov.u32 %0, %%ctaid.x;" : "=r"(t)); return t; }
__device__ __forceinline__ void reset_state(const Params& P, Cons& c, Pend& d, uint32_t sb, bool resumed) {
    const uint32_t t = fresh_tid(), b = fresh_ctaid() + P.cta0;
    const int w = __shfl_sync(0xffffffffu, t >> 5, 0);
    c.sb = sb; c.wg = w >> 2; c.wq = w & 3; c.lane = t & 31;
    c.rank = __shfl_sync(0xffffffffu, b & 1, 0); c.pair = __shfl_sync(0xffffffffu, b >> 1, 0);
    c.rel = mapa(sb + B_EMPTY, cluster_rank() ^ (c.lane & 1));
    c.atag = (ld_acquire(&g_cnt(C_EPOCH)) + 1) & 1;
    c.p.stage = 0; c.p.phase = 0;
    c.nst = resumed && c.pair < NCHAIN;
    d = Pend{};
}
#define PROF_ITEM(i, item)

__global__ void __launch_bounds__(384, 1) fused_kernel(const __grid_constant__ Params P) {
    extern __shared__ __align__(1024) uint8_t smem[];
    const uint32_t sb = smem_u32(smem);
    asm volatile("griddepcontrol.launch_dependents;");
    declare_fence(P.zero);
    const int tid = threadIdx.x, lane = tid & 31;
    const int warp = __shfl_sync(0xffffffffu, tid >> 5, 0);
    const int cta = __shfl_sync(0xffffffffu, blockIdx.x + P.cta0, 0), pair = cta >> 1, rank = cta & 1;
    if (tid == 0) {
        if (sb & 1023) spin_fault();
        for (int i = 0; i < NSTAGE; i++) { mbar_init(sb + B_FULL + i * 8, 1); mbar_init(sb + B_EMPTY + i * 8, 16); }
        mbar_init(sb + B_RESUME, 2);
        mbar_init(sb + B_KVFULL, 1);
        mbar_init(sb + B_GO, 3); mbar_init(sb + B_RED, 8); mbar_init(sb + B_P1, 1); mbar_init(sb + B_PERS, 8); mbar_init(sb + B_INIT, 8); mbar_init(sb + B_INIT2, 8);
        mbar_init(sb + B_READY, 8);
        for (int i = 0; i < 2; i++) { mbar_init(sb + B_SFULL + i * 8, 4); mbar_init(sb + B_SFREE + i * 8, 1); }
        mbar_init(sb + B_RELM, cta % 3 ? 1 : 2); mbar_init(sb + B_X, 9);
        asm volatile("fence.mbarrier_init.release.cluster;" ::: "memory");
        mbar_expect(sb + B_X, 4096);
        sts64(sb + S_EV, 0, 0); sts32(sb + S_RETRY, 0);
    }
    cluster_sync();
    if (warp >= 8) {
        asm volatile("setmaxnreg.dec.sync.aligned.u32 24;");
        if (warp == 8) {
            producer(P, sb, cta, __shfl_sync(0xffffffffu, ld_acquire(&g_cnt(C_EPOCH)), 0));
            asm volatile("barrier.cluster.arrive.relaxed.aligned;\nbarrier.cluster.wait.aligned;" ::: "memory");
        } else if (warp == 9) {
            for (int i = 0; i < P.pd; i++) __nanosleep(1000);
            if (pair < 64) l2_prefetch((const char*)(rank ? P.Wo : P.Wq) + (size_t)(pair * 32 + lane) * 4096, 4096);
            if (pair < NCHAIN) pacer(P, sb, cta, lane, __shfl_sync(0xffffffffu, ld_acquire(&g_cnt(C_EPOCH)), 0));
        } else {
            store_warp(P, sb, warp - 10, cta);
        }
    } else {
        asm volatile("setmaxnreg.inc.sync.aligned.u32 240;");
        Cons c;
        Pend d;
        if (pair < NCHAIN) {
            reset_state(P, c, d, sb, false);
            {
                const int item = ITEM(ITEM_OFF(pair));
                PROF_ITEM(0, item)
                float acc[128];
                mainloop<true>(acc, P, c, d, T_KV, 16);
                ISTAMP(4)
                mbar_wait(sb + B_EMPTY + warp * 20480 / STAGE * 8, 1);
                mbar_wait(sb + B_EMPTY + (warp * 20480 + 20479) / STAGE * 8, 1);
                chain_load(P, sb, cta, warp, lane, 0);
                epi_kv(acc, c, d, (item >> 5) & 7, item & 31);
            }
            ISTAMP(9)
            mbar_wait(sb + B_EMPTY + 3 * 8, 1);
            drain_both(c, d);
            ISTAMP(10)
            uint32_t wr[40][4];
            chain_fetch(P, sb, cta, warp, lane, wr);
            PROF_ITEM(1, T_CHAIN << 8)
            chain_bounds(sb, cta, warp, lane, wr);
            ISTAMP(11)
            const uint32_t epoch = __shfl_sync(0xffffffffu, ld_acquire(&g_cnt(C_EPOCH)), 0);
            if (warp < 4) chain_role<false>(P, sb, cta, warp, lane, epoch, wr);
            else chain_role<true>(P, sb, cta, warp, lane, epoch, wr);
            fence_async_smem();
            bar_sync(1, 256);
            const uint32_t t2 = fresh_tid();
            if (t2 < 2) mbar_arrive_cluster(mapa(sb + B_RESUME, cluster_rank() ^ t2));
        } else if (pair >= NPAIR - 2) {
            const int ch = (pair - (NPAIR - 2)) * 512 + rank * 256 + tid;
            g_coef[ch] = ssm_coef(__bfloat162float(P.Lre[ch]), __bfloat162float(P.Lim[ch]), __bfloat162float(P.logdt[ch]));
            bar_sync(1, 256);
            if (tid == 0) red_release(&g_cnt(C_COEF));
        }
        reset_state(P, c, d, sb, true);
        int it = ITEM_OFF(c.pair) + (c.pair < NCHAIN ? 2 : 0), next = ITEM(it);
        const int end = ITEM_OFF(c.pair + 1);
        for (;; it++) {
            const bool last = it == end;
            const int item = next, kind = (item >> 8) & 7, mb = (item >> 5) & 7;
            const int half = kind >= T_OPH, type = half ? kind * 2 - 10 : kind, nb = item & (half ? 3 : 31);
            const bool idle = half && (item >> 2 & 1) != c.wg;
            if (d.kind != PEND_NONE && (last || idle || (ITEM(it - 1) & URGENT) || !bar_and(5 + c.wg, mbar_try(sb + B_FULL + c.p.stage * 8, c.p.phase)))) {
#pragma unroll 1
                while (d.kind != PEND_NONE) drain(P, c, d);
            }
            if (last) break;
            next = ITEM(it + 1);
            const int nk = type == T_OP ? 64 : type == T_A2 ? 32 : 16;
            PROF_ITEM(it - ITEM_OFF(c.pair), item)
            if (idle) {
#pragma unroll 1
                for (int kt = nk + (type == T_A2 ? 2 : 0); kt > 0; kt--) { wait_full(c); release(c, c.p.stage); pipe_next(c.p); }
                continue;
            }
            float acc[128];
            mainloop(acc, P, c, d, type, nk);
            if (type == T_KV) epi_kv(acc, c, d, mb, nb);
            else if (type == T_QA) epi_qa(acc, c, d, mb, nb);
            else if (type == T_OP) epi_op(acc, c, d, mb, nb);
            else if (type == T_A1) epi_a1(acc, P, c, d, mb, nb, c.atag);
            else epi_a2(acc, P, c, mb, nb * 256);
        }
        staging_wait(c);
        staging_post(c, PEND_NONE, 0, 0, 0);
        cluster_sync();
        if (c.wg == 0 && c.wq == 0 && c.lane == 0 && atomicInc(&g_cnt(C_DONE), NPAIR * 2 - 1) == NPAIR * 2 - 1) { __threadfence(); atomicAdd(&g_cnt(C_EPOCH), 1); }
    }
}

typedef CUresult (*EncodeFn)(CUtensorMap*, CUtensorMapDataType, cuuint32_t, void*, const cuuint64_t*, const cuuint64_t*, const cuuint32_t*, const cuuint32_t*,
                             CUtensorMapInterleave, CUtensorMapSwizzle, CUtensorMapL2promotion, CUtensorMapFloatOOBfill);
void encode(EncodeFn fn, CUtensorMap* m, const void* base, int rank, const uint64_t* dims, const uint64_t* strides, const uint32_t* box, CUtensorMapSwizzle swz = CU_TENSOR_MAP_SWIZZLE_128B) {
    cuuint64_t d[5], s[5]; cuuint32_t b[5], e[5];
    for (int i = 0; i < rank; i++) { d[i] = dims[i]; b[i] = box[i]; e[i] = 1; if (i) s[i - 1] = strides[i - 1]; }
    fn(m, CU_TENSOR_MAP_DATA_TYPE_BFLOAT16, rank, (void*)base, d, s, b, e, CU_TENSOR_MAP_INTERLEAVE_NONE, swz,
       CU_TENSOR_MAP_L2_PROMOTION_L2_256B, CU_TENSOR_MAP_FLOAT_OOB_FILL_NONE);
}
void map_kmajor(EncodeFn fn, CUtensorMap* m, const void* base, uint64_t rows, uint64_t cols, uint32_t box_rows) {
    const uint64_t d[2] = {cols, rows}, s[1] = {cols * 2}; const uint32_t b[2] = {64, box_rows};
    encode(fn, m, base, 2, d, s, b);
}
void map_mnmajor(EncodeFn fn, CUtensorMap* m, const void* base, uint64_t krows, uint64_t cols, uint32_t groups = 2) {
    const uint64_t d[3] = {64, krows, cols / 64}, s[2] = {cols * 2, 128}; const uint32_t b[3] = {64, 64, groups};
    encode(fn, m, base, 3, d, s, b);
}

}

extern "C" void kernel_launch(void* const* d_in, const int* in_sizes, int n_in, void* d_out, int out_size) {
    static Params P;
    static EncodeFn fn = nullptr;
    if (!fn) {
        cudaDriverEntryPointQueryResult q;
        cudaGetDriverEntryPoint("cuTensorMapEncodeTiled", (void**)&fn, cudaEnableDefault, &q);
        cudaFuncSetAttribute(fused_kernel, cudaFuncAttributeMaxDynamicSharedMemorySize, S_TOTAL);
    }
    const bf16* in[15];
    for (int i = 0; i < 15; i++) in[i] = (const bf16*)d_in[i];
    void *kvo, *ht;
    cudaGetSymbolAddress(&kvo, g_kvo);
    cudaGetSymbolAddress(&ht, g_ht);
    map_kmajor(fn, &P.tm[M_BX], in[9], 2048, 1024, 128);
    map_mnmajor(fn, &P.tm[M_WQ], in[11], 1024, 4096);
    map_mnmajor(fn, &P.tm[M_WK], in[12], 1024, 4096);
    map_mnmajor(fn, &P.tm[M_WV], in[13], 1024, 4096);
    map_mnmajor(fn, &P.tm[M_WO], in[14], 4096, 1024);
    map_kmajor(fn, &P.tm[M_OA], kvo, 3 * 2048, 4096, 128);
    P.swap_ri = in[4] < in[3];
    {
        const bf16* lo = P.swap_ri ? in[4] : in[3];
        const uint64_t diff = (uint64_t)((const char*)(P.swap_ri ? in[3] : in[4]) - (const char*)lo);
        const uint64_t d[4] = {1024, 8, 2, 128}, s[3] = {2048, diff, 16384}; const uint32_t b[4] = {64, 8, 2, 8};
        encode(fn, &P.tm[M_AB], lo, 4, d, s, b);
    }
    {
        const uint64_t d[4] = {1024, 2, 4, 1024}, s[3] = {2048, 64 * 2048, 4096}; const uint32_t b[4] = {64, 2, 4, 16};
        encode(fn, &P.tm[M_AX], in[0], 4, d, s, b);
    }
    map_mnmajor(fn, &P.tm[M_HT], ht, 2048, 2048);
    map_kmajor(fn, &P.tm[M_CRE], in[5], 1024, 1024, 128);
    map_kmajor(fn, &P.tm[M_CIM], in[6], 1024, 1024, 128);
    map_kmajor(fn, &P.tm[M_KVO], kvo, 3 * 2048, 4096, 32);
    map_kmajor(fn, &P.tm[M_HTS], ht, 2048, 2048, 32);
    map_kmajor(fn, &P.tm[M_OAH], kvo, 3 * 2048, 4096, 64);
    map_mnmajor(fn, &P.tm[M_HTH], ht, 2048, 2048, 1);
    for (int i = 0; i < 3; i++) {
        const uint64_t d[3] = {64, 1024, 64}, s[2] = {8192, 128}; const uint32_t b[3] = {64, 16, 2};
        encode(fn, &P.tm[M_C1 + i], in[11 + i], 3, d, s, b);
    }
    {
        const uint64_t d[2] = {1024, 4096}, s[1] = {2048}; const uint32_t b[2] = {32, 32};
        encode(fn, &P.tm[M_CO], in[14], 2, d, s, b, CU_TENSOR_MAP_SWIZZLE_64B);
    }
    {
        const uint64_t d[3] = {64, 3 * 2048, 64}, s[2] = {8192, 128}; const uint32_t b[3] = {64, 32, 2};
        encode(fn, &P.tm[M_SEG], kvo, 3, d, s, b);
    }
    void* xs;
    cudaGetSymbolAddress(&xs, g_x);
    P.xb = (uint8_t*)(((uintptr_t)xs + (2u << 20) - 1) & ~(uintptr_t)((2u << 20) - 1));
    P.Wq = in[11]; P.Wk = in[12]; P.Wv = in[13]; P.Wo = in[14]; P.mem0 = in[10]; P.Bx = in[9];
    P.Ax = in[0]; P.Lre = in[1]; P.Lim = in[2]; P.logdt = in[7]; P.Dskip = in[8];
    P.out = (float*)d_out;
    int pv[10] = {1300, 0, 110, 0, 330, 0, 32, 32, 6, 0};
    int ef = 779;
    for (int i = 0; i < 12; i++) P.pol[i] = (ef >> i & 1) ? 0x12F0000000000000ull : 0x1000000000000000ull;
    P.dly = pv[0]; P.mrg = pv[2];
    P.rd = pv[4]; P.guard = pv[5]; P.clampv = pv[6]; P.clamp0 = pv[7]; P.kvd = pv[9]; P.xd = pv[8]; P.pd = pv[1];
    cudaLaunchConfig_t cfg = {};
    cudaLaunchAttribute at[2];
    cfg.blockDim = dim3(384); cfg.dynamicSmemBytes = S_TOTAL; cfg.stream = cudaStreamPerThread; cfg.attrs = at;
    at[0].id = cudaLaunchAttributeClusterDimension;
    at[0].val.clusterDim.y = at[0].val.clusterDim.z = 1;
    at[1].id = cudaLaunchAttributeProgrammaticStreamSerialization;
    at[1].val.programmaticStreamSerializationAllowed = 1;
    for (int i = 0; i < 2; i++) {
        P.cta0 = i ? 2 * NCHAIN : 0;
        cfg.gridDim = dim3(i ? 2 * (NPAIR - NCHAIN) : 2 * NCHAIN);
        at[0].val.clusterDim.x = i ? 2 : 6;
        cfg.numAttrs = 1 + i;
        cudaLaunchKernelEx(&cfg, fused_kernel, P);
    }
}
```

```cpp
#include <cuda_runtime.h>
#include <cuda_bf16.h>
#include <cuda.h>
#include <stdint.h>
#include <string.h>

typedef __nv_bfloat16 bf16;

namespace {

constexpr int SPIN_LIMIT = 1 << 22;
#define POLLNS 100
constexpr int NPAIR = 66;
constexpr int NCHAIN = 48;
enum { T_KV = 0, T_QA = 1, T_OP = 2, T_A1 = 3, T_A2 = 4, T_CHAIN = 5 };
constexpr int URGENT = 2048;
constexpr int HALF = 4096;
enum { M_BX = 0, M_WQ, M_WK, M_WV, M_WO, M_OA, M_AB, M_AX, M_HT, M_CRE, M_CIM, M_KVO, M_HTS, M_BXH, M_OAH, M_ABH, M_HTH, M_C1, M_CO = M_C1 + 3, M_SEG, M_COUNT };
enum { C_KV = 0, C_O = 8, C_HT = 16, C_DONE = 24, C_EPOCH = 25, C_COEF = 26, C_XMAX = 27, C_XCNT = 28, C_FLAG = 32 };

struct Params {
    CUtensorMap tm[M_COUNT];
    const bf16 *Wq, *Wk, *Wv, *Wo, *mem0, *Bx, *Ax, *Lre, *Lim, *logdt, *Dskip;
    float* out;
    uint8_t* xb;
    int swap_ri, zero;
    int dly, mrg, rd, guard, clampv, clamp0, kvd, xd, pd;
    uint64_t pol[12];
    uint16_t cta0;
};

__constant__ uint16_t c_off[67] = {0, 4, 8, 13, 18, 23, 27, 31, 35, 39, 43, 48, 53, 57, 61, 65, 70, 75, 80, 84, 88, 92, 97, 102, 106, 111, 116, 121, 125, 130, 135, 139, 143, 148, 153, 157, 162, 166, 171, 175, 180, 184, 189, 193, 198, 202, 206, 210, 214, 234, 252, 271, 291, 311, 331, 351, 371, 391, 411, 431, 451, 471, 490, 510, 529, 547, 565};
__constant__ uint16_t c_items[640] = {
    0, 1280, 2822, 515, 16, 1280, 865, 704, 32, 1280, 775, 2980, 1251, 1, 1280, 2435, 960, 1123, 17, 1280, 2508, 2944, 1027, 33,
    1280, 483, 578, 2, 1280, 2440, 513, 18, 1280, 2528, 512, 34, 1280, 451, 610, 3, 1280, 2505, 514, 19, 1280, 833, 3009, 1089,
    35, 1280, 2887, 2945, 1090, 4, 1280, 490, 546, 20, 1280, 461, 738, 36, 1280, 2535, 545, 5, 1280, 2502, 3014, 1185, 21, 1280,
    800, 2916, 1122, 37, 1280, 771, 2983, 1025, 6, 1280, 396, 609, 22, 1280, 453, 675, 38, 1280, 2500, 608, 7, 1280, 2445, 870,
    12993, 23, 1280, 2506, 962, 1184, 39, 1280, 2541, 706, 8, 1280, 802, 2886, 1088, 24, 1280, 2816, 2948, 1026, 40, 1280, 2818, 864,
    1056, 9, 1280, 834, 672, 25, 1280, 807, 867, 1216, 41, 1280, 801, 967, 1091, 10, 1280, 385, 643, 26, 1280, 2504, 641, 42,
    1280, 2532, 963, 12867, 11, 1280, 2447, 2979, 4675, 27, 1280, 2536, 544, 43, 1280, 2507, 2949, 1186, 12, 1280, 2540, 736, 28, 1280,
    2919, 2950, 1057, 44, 1280, 769, 737, 13, 1280, 449, 2884, 1121, 29, 1280, 2533, 577, 45, 1280, 2537, 804, 1249, 14, 1280, 2542,
    673, 30, 1280, 2539, 2947, 1155, 46, 1280, 2510, 576, 15, 1280, 486, 707, 31, 1280, 2498, 640, 47, 1280, 2529, 642, 48, 66,
    84, 102, 256, 124, 142, 160, 175, 191, 207, 224, 239, 298, 418, 359, 448, 903, 3042, 1217, 49, 67, 85, 103, 257, 125,
    143, 161, 176, 192, 208, 225, 240, 299, 352, 425, 360, 674, 50, 68, 86, 104, 258, 126, 144, 162, 177, 193, 209, 226,
    241, 300, 2411, 2478, 2439, 934, 1152, 51, 69, 87, 105, 259, 127, 145, 163, 178, 194, 210, 227, 242, 301, 4489, 419, 364,
    832, 2981, 1024, 52, 70, 88, 106, 260, 128, 146, 164, 179, 195, 211, 228, 243, 302, 421, 362, 12715, 805, 3013, 1059, 53,
    71, 89, 107, 261, 129, 147, 165, 180, 196, 212, 229, 244, 303, 333, 365, 361, 806, 3041, 1187, 54, 72, 90, 108, 262,
    130, 148, 166, 181, 197, 213, 230, 245, 320, 366, 331, 431, 869, 3046, 1250, 55, 73, 91, 109, 263, 131, 149, 167, 182,
    198, 214, 231, 246, 321, 356, 429, 398, 4869, 2976, 1154, 56, 74, 92, 110, 264, 132, 150, 168, 183, 199, 215, 232, 247,
    322, 388, 334, 463, 837, 3047, 1219, 57, 75, 93, 111, 265, 133, 151, 169, 184, 200, 216, 233, 248, 323, 394, 424, 482,
    803, 3040, 1153, 58, 76, 94, 112, 266, 134, 152, 170, 185, 201, 217, 234, 249, 324, 358, 455, 426, 898, 3044, 1120, 59,
    77, 95, 113, 267, 135, 153, 171, 186, 202, 218, 235, 250, 325, 4523, 384, 423, 772, 2977, 1058, 60, 78, 96, 114, 268,
    136, 154, 172, 187, 203, 219, 236, 251, 326, 330, 367, 355, 930, 995, 1218, 61, 79, 97, 115, 269, 137, 155, 173, 188,
    204, 220, 237, 252, 327, 332, 416, 389, 13061, 739, 62, 80, 98, 116, 270, 138, 156, 174, 189, 205, 221, 238, 253, 328,
    395, 390, 386, 835, 3045, 1248, 63, 81, 99, 117, 271, 139, 157, 288, 190, 292, 293, 296, 297, 2468, 12681, 428, 866, 3012,
    4801, 64, 82, 100, 118, 120, 122, 140, 158, 289, 206, 222, 294, 254, 329, 417, 2405, 2401, 611, 65, 83, 101, 119, 121,
    123, 141, 159, 290, 291, 223, 295, 255, 354, 335, 422, 495, 547,
};
#define ITEM_OFF(p) c_off[p]
#define ITEM(i) c_items[i]

__device__ __align__(1024) bf16 g_kvo[3 * 2048 * 4096];
__device__ __align__(1024) bf16 g_ht[2048 * 2048];
__device__ __align__(1024) uint8_t g_x[4 << 20];
__device__ __align__(1024) uint32_t g_km[64 * 32 * 512];
__device__ __align__(1024) uint32_t g_vmt[64 * 32 * 512];
__device__ __align__(1024) float2 g_agg[8 * 1024];
__device__ __align__(1024) float4 g_coef[1024];
__device__ __align__(1024) uint32_t g_cntl[128 * 32];
#define g_cnt(i) g_cntl[(i) * 32]
__device__ __align__(1024) uint32_t g_hint[96 * 32];
#define PROF(i)
#define PROFDUMP()
#define PROFP(i)
constexpr int XG_SIDE = 65536, XG_T = 98304;
__device__ __forceinline__ uint32_t xg_buf(int b) { return (b & 1) * 128 + (b & 2) * 256 + (b & 4) * 32768; }
__device__ __forceinline__ uint32_t xg_lane(uint32_t lane) { return (lane >> 4) * 1024 + (lane & 8) * 32 + (lane & 7) * 16; }
__device__ __forceinline__ uint32_t xg_side(int b) { return XG_SIDE + (b >> 1) * 1024 + (b & 1) * 256; }

constexpr int STAGE = 49152, NSTAGE = 4;
constexpr int S_STG = NSTAGE * STAGE;
constexpr int S_BAR = S_STG + 32768;
constexpr int B_FULL = S_BAR, B_EMPTY = S_BAR + 32, B_RESUME = S_BAR + 64, B_KVFULL = S_BAR + 72, B_GO = S_BAR + 88, B_X = S_BAR + 96, B_PERS = S_BAR + 104,
              B_INIT = S_BAR + 112, B_RELM = S_BAR + 120, B_READY = S_BAR + 136, B_SFULL = S_BAR + 144, B_SFREE = S_BAR + 160, S_DESC = S_BAR + 176, B_RED = S_BAR + 216;
constexpr int S_EV = S_BAR + 80, S_EO = S_BAR + 84, B_INIT2 = S_BAR + 128, S_SC = S_BAR + 208, S_ISC = S_EV;
constexpr int S_XV = S_BAR + 256, S_LOG = S_XV + 2048;
constexpr int S_TOTAL = S_LOG + 768;
#define NRA 5
#define NRB 3
constexpr int S_W1 = 0;
constexpr int S_W2 = 4 * 4096 * (16 - NRA - NRB);
constexpr int S_KV = 188416;
constexpr int S_P1 = S_KV + 16384;
constexpr int S_X = S_P1 + 16384;
constexpr int S_SX = S_P1, S_OX = S_P1 + 2048;
constexpr int S_EM = S_X + 4096, S_TO = S_EM + 32, S_RETRY = S_BAR + 224, B_P1 = S_BAR + 232;
static_assert(S_TO + 32 <= S_BAR && S_KV % 1024 == 0 && S_TOTAL <= 232448, "chain smem layout");

template <int V> struct IC { static constexpr int value = V; };
template <int B, int E, typename F> __device__ __forceinline__ void static_for(F&& f) { if constexpr (B < E) { f(IC<B>{}); static_for<B + 1, E>(f); } }
__device__ __forceinline__ uint32_t cluster_rank() { uint32_t r; asm volatile("mov.u32 %0, %%cluster_ctarank;" : "=r"(r)); return r; }
__device__ __forceinline__ void spin_fault() { asm volatile("st.global.u32 [%0], 0;" ::"l"(0ull) : "memory"); }
__device__ __forceinline__ uint32_t smem_u32(const void* p) { return (uint32_t)__cvta_generic_to_shared(p); }
__device__ __forceinline__ uint32_t opq(uint32_t x, int lane) { return __shfl_sync(0xffffffffu, x, lane); }
__device__ __forceinline__ uint32_t mapa(uint32_t a, uint32_t r) { uint32_t d; asm volatile("mapa.shared::cluster.u32 %0, %1, %2;" : "=r"(d) : "r"(a), "r"(r)); return d; }
__device__ __forceinline__ void mma16816(float* d, uint32_t a0, uint32_t a1, uint32_t a2, uint32_t a3, uint32_t b0, uint32_t b1) {
    asm("mma.sync.aligned.m16n8k16.row.col.f32.bf16.bf16.f32 {%0,%1,%2,%3}, {%4,%5,%6,%7}, {%8,%9}, {%0,%1,%2,%3};"
        : "+f"(d[0]), "+f"(d[1]), "+f"(d[2]), "+f"(d[3]) : "r"(a0), "r"(a1), "r"(a2), "r"(a3), "r"(b0), "r"(b1));
}
__device__ __forceinline__ void mma1688(float* d, uint32_t a0, uint32_t a1, uint32_t b0) {
    asm("mma.sync.aligned.m16n8k8.row.col.f32.bf16.bf16.f32 {%0,%1,%2,%3}, {%4,%5}, {%6}, {%0,%1,%2,%3};"
        : "+f"(d[0]), "+f"(d[1]), "+f"(d[2]), "+f"(d[3]) : "r"(a0), "r"(a1), "r"(b0));
}
__device__ __forceinline__ void ldsm4(uint32_t* r, uint32_t a) {
    asm volatile("ldmatrix.sync.aligned.m8n8.x4.shared.b16 {%0,%1,%2,%3}, [%4];" : "=r"(r[0]), "=r"(r[1]), "=r"(r[2]), "=r"(r[3]) : "r"(a));
}
__device__ __forceinline__ void ldsm4t(uint32_t* r, uint32_t a) {
    asm volatile("ldmatrix.sync.aligned.m8n8.x4.trans.shared.b16 {%0,%1,%2,%3}, [%4];" : "=r"(r[0]), "=r"(r[1]), "=r"(r[2]), "=r"(r[3]) : "r"(a));
}
__device__ __forceinline__ void stsm4(uint32_t a, uint32_t r0, uint32_t r1, uint32_t r2, uint32_t r3) {
    asm volatile("stmatrix.sync.aligned.m8n8.x4.shared.b16 [%0], {%1,%2,%3,%4};" ::"r"(a), "r"(r0), "r"(r1), "r"(r2), "r"(r3) : "memory");
}
__device__ __forceinline__ void stsm4t(uint32_t a, uint32_t r0, uint32_t r1, uint32_t r2, uint32_t r3) {
    asm volatile("stmatrix.sync.aligned.m8n8.x4.trans.shared.b16 [%0], {%1,%2,%3,%4};" ::"r"(a), "r"(r0), "r"(r1), "r"(r2), "r"(r3) : "memory");
}
__device__ __forceinline__ uint32_t movm(uint32_t a) { uint32_t d; asm volatile("movmatrix.sync.aligned.m8n8.trans.b16 %0, %1;" : "=r"(d) : "r"(a)); return d; }
__device__ __forceinline__ uint32_t pack2(float lo, float hi) { uint32_t d; asm("cvt.rn.bf16x2.f32 %0, %1, %2;" : "=r"(d) : "f"(hi), "f"(lo)); return d; }
__device__ __forceinline__ uint32_t prmt(uint32_t a, uint32_t b, uint32_t s) { uint32_t d; asm("prmt.b32 %0, %1, %2, %3;" : "=r"(d) : "r"(a), "r"(b), "r"(s)); return d; }
__device__ __forceinline__ uint32_t pack2h(float lo, float hi) { uint32_t d; asm("cvt.rn.f16x2.f32 %0, %1, %2;" : "=r"(d) : "f"(hi), "f"(lo)); return d; }
__device__ __forceinline__ uint32_t h2bf(uint32_t a, uint32_t b) {
    uint32_t d;
    asm("{\n.reg .b16 l, h, u;\n.reg .f32 x, y;\nmov.b32 {l, u}, %1;\ncvt.f32.f16 x, l;\nmov.b32 {u, h}, %2;\ncvt.f32.f16 y, h;\ncvt.rn.bf16x2.f32 %0, y, x;\n}" : "=r"(d) : "r"(a), "r"(b));
    return d;
}
__device__ __forceinline__ void cvt_block(uint32_t* u, uint32_t& x, uint32_t sel) {
    const uint32_t a = prmt(u[0], u[0], sel), b = prmt(u[1], u[1], sel), c = prmt(u[2], u[2], sel), d = prmt(u[3], x, sel);
    x ^= u[3] ^ d;
    u[0] = h2bf(a, a); u[1] = h2bf(b, b); u[2] = h2bf(c, c); u[3] = h2bf(d, d);
}
__device__ __forceinline__ uint32_t amax(uint32_t a, uint32_t b) { uint32_t d; asm("max.xorsign.abs.bf16x2 %0, %1, %2;" : "=r"(d) : "r"(a), "r"(b)); return d; }
__device__ __forceinline__ uint32_t amax4(uint32_t m, const uint32_t* v) { return amax(amax(m, amax(v[0], v[1])), amax(v[2], v[3])); }
__device__ __forceinline__ uint32_t warp_exp(uint32_t m) { return __reduce_max_sync(0xffffffffu, max(m & 0x7f80u, (m >> 16) & 0x7f80u)) >> 7; }
__device__ __forceinline__ void red_max_shared(uint32_t a, uint32_t x) { asm volatile("red.shared.max.u32 [%0], %1;" ::"r"(a), "r"(x) : "memory"); }
__device__ __forceinline__ uint32_t mul_bf2(uint32_t a, uint32_t b) { uint32_t d; asm("mul.rn.bf16x2 %0, %1, %2;" : "=r"(d) : "r"(a), "r"(b)); return d; }
__device__ __forceinline__ float bf_lo(uint32_t u) { return __uint_as_float(u << 16); }
__device__ __forceinline__ float bf_hi(uint32_t u) { return __uint_as_float(u & 0xffff0000u); }
__device__ __forceinline__ float ex2(float x) { float y; asm("ex2.approx.ftz.f32 %0, %1;" : "=f"(y) : "f"(x)); return y; }
__device__ __forceinline__ float rcp(float x) { float y; asm("rcp.approx.ftz.f32 %0, %1;" : "=f"(y) : "f"(x)); return y; }
__device__ __forceinline__ void st_relaxed4(const void* p, uint32_t a, uint32_t b, uint32_t c, uint32_t d) {
    asm volatile("{\n.reg .b128 t;\nmov.b128 t, {%1,%2,%3,%4};\nst.relaxed.gpu.global.b128 [%0], t;\n}" ::"l"(p), "r"(a), "r"(b), "r"(c), "r"(d) : "memory");
}
__device__ __forceinline__ void st_relaxed2(const void* p, uint32_t a, uint32_t b) {
    asm volatile("{\n.reg .b64 t;\nmov.b64 t, {%1,%2};\nst.relaxed.gpu.global.b64 [%0], t;\n}" ::"l"(p), "r"(a), "r"(b) : "memory");
}
__device__ __forceinline__ void ld_relaxed2_if(uint32_t& a, uint32_t& b, const void* p, bool on) {
    asm volatile("{\n.reg .pred P;\n.reg .b64 t;\nsetp.ne.u32 P, %3, 0;\nmov.b64 t, {%0,%1};\n@P ld.relaxed.gpu.global.b64 t, [%2];\nmov.b64 {%0,%1}, t;\n}" : "+r"(a), "+r"(b) : "l"(p), "r"((uint32_t)on) : "memory");
}
__device__ __forceinline__ void ld_relaxed4(uint32_t* v, const void* p) {
    asm volatile("ld.relaxed.gpu.global.L1::no_allocate.v4.b32 {%0,%1,%2,%3}, [%4];" : "=r"(v[0]), "=r"(v[1]), "=r"(v[2]), "=r"(v[3]) : "l"(p) : "memory");
}
__device__ __forceinline__ void ld_relaxed1n(uint32_t& v, const void* p) { asm volatile("ld.relaxed.gpu.global.L1::no_allocate.b32 %0, [%1];" : "=r"(v) : "l"(p) : "memory"); }
__device__ __forceinline__ void red_add4(const void* p, uint32_t a, uint32_t b, uint32_t c, uint32_t d) {
    asm volatile("red.relaxed.gpu.global.add.noftz.v4.f16x2 [%0], {%1,%2,%3,%4};" ::"l"(p), "r"(a), "r"(b), "r"(c), "r"(d) : "memory");
}
__device__ __forceinline__ void red_add1(const void* p, uint32_t a) { asm volatile("red.relaxed.gpu.global.add.noftz.f16x2 [%0], %1;" ::"l"(p), "r"(a) : "memory"); }
__device__ __forceinline__ void ld_relaxed2(uint32_t* v, const void* p) {
    asm volatile("{\n.reg .b64 t;\nld.relaxed.gpu.global.L1::no_allocate.b64 t, [%2];\nmov.b64 {%0,%1}, t;\n}" : "=r"(v[0]), "=r"(v[1]) : "l"(p) : "memory");
}
__device__ __forceinline__ uint32_t ld_relaxed1(const void* p) { uint32_t v; asm volatile("ld.relaxed.gpu.global.u32 %0, [%1];" : "=r"(v) : "l"(p) : "memory"); return v; }
__device__ __forceinline__ void st_relaxed1(const void* p, uint32_t v) { asm volatile("st.relaxed.gpu.global.u32 [%0], %1;" ::"l"(p), "r"(v) : "memory"); }
__device__ __forceinline__ uint32_t ld_acquire(const void* p) { uint32_t v; asm volatile("ld.acquire.gpu.global.u32 %0, [%1];" : "=r"(v) : "l"(p) : "memory"); return v; }
__device__ __forceinline__ void red_relaxed(void* p) { asm volatile("red.relaxed.gpu.global.add.u32 [%0], 1;" ::"l"(p) : "memory"); }
__device__ __forceinline__ void red_release(void* p) { asm volatile("red.release.gpu.global.add.u32 [%0], 1;" ::"l"(p) : "memory"); }
__device__ __forceinline__ void st_stream2(float* p, float a, float b) { asm volatile("st.global.cs.v2.f32 [%0], {%1, %2};" ::"l"(p), "f"(a), "f"(b) : "memory"); }
__device__ __forceinline__ void fence_async() { asm volatile("fence.proxy.async.global;" ::: "memory"); }
__device__ __forceinline__ void fence_async_smem() { asm volatile("fence.proxy.async.shared::cta;" ::: "memory"); }
__device__ __forceinline__ void wait_count(const uint32_t* p, uint32_t target) {
    int n = 0;
    while ((int32_t)(ld_acquire(p) - target) < 0) { __nanosleep(POLLNS); if (++n > SPIN_LIMIT) spin_fault(); }
}
__device__ __forceinline__ void bar_sync(int id, int n) { asm volatile("bar.sync %0, %1;" ::"r"(id), "r"(n) : "memory"); }
__device__ __forceinline__ bool bar_and(int id, bool v) {
    uint32_t r;
    asm volatile("{\n.reg .pred P, Q;\nsetp.ne.u32 Q, %2, 0;\nbar.red.and.pred P, %1, 128, Q;\nselp.u32 %0, 1, 0, P;\n}" : "=r"(r) : "r"(id), "r"((uint32_t)v) : "memory");
    return r;
}
__device__ __forceinline__ void bar_arrive(int id, int n) { asm volatile("bar.arrive %0, %1;" ::"r"(id), "r"(n) : "memory"); }
__device__ __forceinline__ void lds128(uint32_t* v, uint32_t a) { asm volatile("ld.shared.v4.b32 {%0,%1,%2,%3}, [%4];" : "=r"(v[0]), "=r"(v[1]), "=r"(v[2]), "=r"(v[3]) : "r"(a) : "memory"); }
__device__ __forceinline__ uint32_t lds32(uint32_t a) { uint32_t v; asm volatile("ld.shared.b32 %0, [%1];" : "=r"(v) : "r"(a) : "memory"); return v; }
__device__ __forceinline__ void lds64(uint32_t* v, uint32_t a) { asm volatile("ld.shared.v2.b32 {%0,%1}, [%2];" : "=r"(v[0]), "=r"(v[1]) : "r"(a) : "memory"); }
__device__ __forceinline__ void lds64f(float* v, uint32_t a) { asm volatile("ld.shared.v2.f32 {%0,%1}, [%2];" : "=f"(v[0]), "=f"(v[1]) : "r"(a) : "memory"); }
__device__ __forceinline__ void sts128(uint32_t a, const uint32_t* v) { asm volatile("st.shared.v4.b32 [%0], {%1,%2,%3,%4};" ::"r"(a), "r"(v[0]), "r"(v[1]), "r"(v[2]), "r"(v[3]) : "memory"); }
__device__ __forceinline__ void sts64(uint32_t a, uint32_t x, uint32_t y) { asm volatile("st.shared.v2.b32 [%0], {%1,%2};" ::"r"(a), "r"(x), "r"(y) : "memory"); }
__device__ __forceinline__ void sts32(uint32_t a, uint32_t x) { asm volatile("st.shared.b32 [%0], %1;" ::"r"(a), "r"(x) : "memory"); }
__device__ __forceinline__ bool mbar_try(uint32_t b, uint32_t par) {
    uint32_t ok;
    asm volatile("{\n.reg .pred P;\nmbarrier.test_wait.parity.shared::cta.b64 P, [%1], %2;\nselp.u32 %0, 1, 0, P;\n}" : "=r"(ok) : "r"(b), "r"(par) : "memory");
    return ok;
}
__device__ __forceinline__ void mbar_wait(uint32_t b, uint32_t par) {
    asm volatile("{\n.reg .pred P, Q;\n.reg .u32 n;\nmov.u32 n, %2;\nW: mbarrier.try_wait.parity.shared::cta.b64 P, [%0], %1;\n"
                 "add.u32 n, n, -1;\nsetp.eq.u32 Q, n, 0;\n@Q st.global.u32 [%3], 0;\n@!P bra W;\n}" ::"r"(b), "r"(par), "n"(SPIN_LIMIT), "l"(0ull) : "memory");
}
__device__ __forceinline__ void mbar_wait_fast(uint32_t b, uint32_t par) {
    asm volatile("{\n.reg .pred P, Q;\n.reg .u32 n;\nmbarrier.try_wait.parity.shared::cta.b64 P, [%0], %1;\n@P bra D;\nmov.u32 n, %2;\nW: mbarrier.try_wait.parity.shared::cta.b64 P, [%0], %1;\n"
                 "add.u32 n, n, -1;\nsetp.eq.u32 Q, n, 0;\n@Q st.global.u32 [%3], 0;\n@!P bra W;\nD:\n}" ::"r"(b), "r"(par), "n"(SPIN_LIMIT), "l"(0ull) : "memory");
}
__device__ __forceinline__ void declare_fence(int zero) { asm volatile(".reg .pred PNEVER;\nsetp.ne.u32 PNEVER, %0, 0;" ::"r"(zero)); }
__device__ __forceinline__ void sched_fence() { asm volatile("{\n.reg .pred Q;\n.reg .u32 x;\n@!PNEVER bra D;\nF: ld.volatile.global.u32 x, [%0];\nsetp.ne.u32 Q, x, 0;\n@Q bra F;\nD:\n}" ::"l"(0ull) : "memory"); }
__device__ __forceinline__ void mbar_init(uint32_t b, uint32_t n) { asm volatile("mbarrier.init.shared::cta.b64 [%0], %1;" ::"r"(b), "r"(n) : "memory"); }
__device__ __forceinline__ void mbar_expect(uint32_t b, uint32_t bytes) { asm volatile("mbarrier.arrive.expect_tx.shared::cta.b64 _, [%0], %1;" ::"r"(b), "r"(bytes) : "memory"); }
__device__ __forceinline__ void mbar_arrive(uint32_t b) { asm volatile("mbarrier.arrive.shared::cta.b64 _, [%0];" ::"r"(b) : "memory"); }
__device__ __forceinline__ void mbar_arrive_cluster(uint32_t b) { asm volatile("mbarrier.arrive.shared::cluster.b64 _, [%0];" ::"r"(b) : "memory"); }
__device__ __forceinline__ void cluster_sync() { asm volatile("barrier.cluster.arrive.aligned;\nbarrier.cluster.wait.aligned;" ::: "memory"); }
__device__ __forceinline__ void tma2d(uint32_t dst, const CUtensorMap* m, int c0, int c1, uint32_t bar) {
    asm volatile("cp.async.bulk.tensor.2d.shared::cluster.global.mbarrier::complete_tx::bytes [%0], [%1, {%2, %3}], [%4];" ::"r"(dst), "l"(m), "r"(c0), "r"(c1), "r"(bar) : "memory");
}
__device__ __forceinline__ void tma2d_mc(uint32_t dst, const CUtensorMap* m, int c0, int c1, uint32_t bar, uint16_t mask) {
    asm volatile("cp.async.bulk.tensor.2d.shared::cluster.global.mbarrier::complete_tx::bytes.multicast::cluster [%0], [%1, {%2, %3}], [%4], %5;" ::"r"(dst), "l"(m), "r"(c0), "r"(c1), "r"(bar), "h"(mask) : "memory");
}
__device__ __forceinline__ void tma3d(uint32_t dst, const CUtensorMap* m, int c0, int c1, int c2, uint32_t bar) {
    asm volatile("cp.async.bulk.tensor.3d.shared::cluster.global.mbarrier::complete_tx::bytes [%0], [%1, {%2, %3, %4}], [%5];" ::"r"(dst), "l"(m), "r"(c0), "r"(c1), "r"(c2), "r"(bar) : "memory");
}
__device__ __forceinline__ void tma3d_mc(uint32_t dst, const CUtensorMap* m, int c0, int c1, int c2, uint32_t bar, uint16_t mask) {
    asm volatile("cp.async.bulk.tensor.3d.shared::cluster.global.mbarrier::complete_tx::bytes.multicast::cluster [%0], [%1, {%2, %3, %4}], [%5], %6;" ::"r"(dst), "l"(m), "r"(c0), "r"(c1), "r"(c2), "r"(bar), "h"(mask) : "memory");
}
__device__ __forceinline__ void tma4d(uint32_t dst, const CUtensorMap* m, int c0, int c3, uint32_t bar) {
    asm volatile("cp.async.bulk.tensor.4d.shared::cluster.global.mbarrier::complete_tx::bytes [%0], [%1, {%2, 0, 0, %3}], [%4];" ::"r"(dst), "l"(m), "r"(c0), "r"(c3), "r"(bar) : "memory");
}
__device__ __forceinline__ void tma4d_mc(uint32_t dst, const CUtensorMap* m, int c0, int c3, uint32_t bar, uint16_t mask) {
    asm volatile("cp.async.bulk.tensor.4d.shared::cluster.global.mbarrier::complete_tx::bytes.multicast::cluster [%0], [%1, {%2, 0, 0, %3}], [%4], %5;" ::"r"(dst), "l"(m), "r"(c0), "r"(c3), "r"(bar), "h"(mask) : "memory");
}
__device__ __forceinline__ void tma_prefetch3d(const CUtensorMap* m, int c0, int c1, int c2) {
    asm volatile("cp.async.bulk.prefetch.tensor.3d.L2.global [%0, {%1, %2, %3}];" ::"l"(m), "r"(c0), "r"(c1), "r"(c2) : "memory");
}
__device__ __forceinline__ void tma_prefetch2d(const CUtensorMap* m, int c0, int c1) {
    asm volatile("cp.async.bulk.prefetch.tensor.2d.L2.global [%0, {%1, %2}];" ::"l"(m), "r"(c0), "r"(c1) : "memory");
}
__device__ __forceinline__ void l2_prefetch(const void* src, uint32_t bytes) { asm volatile("cp.async.bulk.prefetch.L2.global [%0], %1;" ::"l"(src), "r"(bytes) : "memory"); }
__device__ __forceinline__ void bulk_g2s(uint32_t dst, const void* src, uint32_t bytes, uint32_t bar) {
    asm volatile("cp.async.bulk.shared::cluster.global.mbarrier::complete_tx::bytes [%0], [%1], %2, [%3];" ::"r"(dst), "l"(src), "r"(bytes), "r"(bar) : "memory");
}
__device__ __forceinline__ void mbar_expect_e(uint32_t b, uint32_t bytes) {
    asm volatile("{\n.reg .pred E;\nelect.sync _|E, 0xffffffff;\n@E mbarrier.arrive.expect_tx.shared::cta.b64 _, [%0], %1;\n}" ::"r"(b), "r"(bytes) : "memory");
}
__device__ __forceinline__ void tma2d_e(uint32_t dst, const CUtensorMap* m, int c0, int c1, uint32_t bar, uint64_t pol) {
    asm volatile("{\n.reg .pred E;\nelect.sync _|E, 0xffffffff;\n@E cp.async.bulk.tensor.2d.shared::cluster.global.mbarrier::complete_tx::bytes.L2::cache_hint [%0], [%1, {%2, %3}], [%4], %5;\n}" ::"r"(dst), "l"(m), "r"(c0), "r"(c1), "r"(bar), "l"(pol) : "memory");
}
__device__ __forceinline__ void tma2d_mc_e(uint32_t dst, const CUtensorMap* m, int c0, int c1, uint32_t bar, uint16_t mask) {
    asm volatile("{\n.reg .pred E;\nelect.sync _|E, 0xffffffff;\n@E cp.async.bulk.tensor.2d.shared::cluster.global.mbarrier::complete_tx::bytes.multicast::cluster [%0], [%1, {%2, %3}], [%4], %5;\n}" ::"r"(dst), "l"(m), "r"(c0), "r"(c1), "r"(bar), "h"(mask) : "memory");
}
__device__ __forceinline__ void tma3d_e(uint32_t dst, const CUtensorMap* m, int c0, int c1, int c2, uint32_t bar, uint64_t pol) {
    asm volatile("{\n.reg .pred E;\nelect.sync _|E, 0xffffffff;\n@E cp.async.bulk.tensor.3d.shared::cluster.global.mbarrier::complete_tx::bytes.L2::cache_hint [%0], [%1, {%2, %3, %4}], [%5], %6;\n}" ::"r"(dst), "l"(m), "r"(c0), "r"(c1), "r"(c2), "r"(bar), "l"(pol) : "memory");
}
__device__ __forceinline__ void tma3d_mc_e(uint32_t dst, const CUtensorMap* m, int c0, int c1, int c2, uint32_t bar, uint16_t mask, uint64_t pol) {
    asm volatile("{\n.reg .pred E;\nelect.sync _|E, 0xffffffff;\n@E cp.async.bulk.tensor.3d.shared::cluster.global.mbarrier::complete_tx::bytes.multicast::cluster.L2::cache_hint [%0], [%1, {%2, %3, %4}], [%5], %6, %7;\n}" ::"r"(dst), "l"(m), "r"(c0), "r"(c1), "r"(c2), "r"(bar), "h"(mask), "l"(pol) : "memory");
}
__device__ __forceinline__ void tma4d_e(uint32_t dst, const CUtensorMap* m, int c0, int c3, uint32_t bar) {
    asm volatile("{\n.reg .pred E;\nelect.sync _|E, 0xffffffff;\n@E cp.async.bulk.tensor.4d.shared::cluster.global.mbarrier::complete_tx::bytes [%0], [%1, {%2, 0, 0, %3}], [%4];\n}" ::"r"(dst), "l"(m), "r"(c0), "r"(c3), "r"(bar) : "memory");
}
__device__ __forceinline__ void tma4d_mc_e(uint32_t dst, const CUtensorMap* m, int c0, int c3, uint32_t bar, uint16_t mask) {
    asm volatile("{\n.reg .pred E;\nelect.sync _|E, 0xffffffff;\n@E cp.async.bulk.tensor.4d.shared::cluster.global.mbarrier::complete_tx::bytes.multicast::cluster [%0], [%1, {%2, 0, 0, %3}], [%4], %5;\n}" ::"r"(dst), "l"(m), "r"(c0), "r"(c3), "r"(bar), "h"(mask) : "memory");
}
__device__ __forceinline__ void tma_prefetch2d_e(const CUtensorMap* m, int c0, int c1) {
    asm volatile("{\n.reg .pred E;\nelect.sync _|E, 0xffffffff;\n@E cp.async.bulk.prefetch.tensor.2d.L2.global [%0, {%1, %2}];\n}" ::"l"(m), "r"(c0), "r"(c1) : "memory");
}
__device__ __forceinline__ void tma_prefetch3d_e(const CUtensorMap* m, int c0, int c1, int c2) {
    asm volatile("{\n.reg .pred E;\nelect.sync _|E, 0xffffffff;\n@E cp.async.bulk.prefetch.tensor.3d.L2.global [%0, {%1, %2, %3}];\n}" ::"l"(m), "r"(c0), "r"(c1), "r"(c2) : "memory");
}
__device__ __forceinline__ void l2_prefetch_e(const void* src, uint32_t bytes) {
    asm volatile("{\n.reg .pred E;\nelect.sync _|E, 0xffffffff;\n@E cp.async.bulk.prefetch.L2.global [%0], %1;\n}" ::"l"(src), "r"(bytes) : "memory");
}
__device__ __forceinline__ void bulk_g2s_e(uint32_t dst, const void* src, uint32_t bytes, uint32_t bar) {
    asm volatile("{\n.reg .pred E;\nelect.sync _|E, 0xffffffff;\n@E cp.async.bulk.shared::cluster.global.mbarrier::complete_tx::bytes [%0], [%1], %2, [%3];\n}" ::"r"(dst), "l"(src), "r"(bytes), "r"(bar) : "memory");
}
__device__ __forceinline__ bool elect_one() {
    uint32_t r;
    asm volatile("{\n.reg .pred E;\nelect.sync _|E, 0xffffffff;\nselp.u32 %0, 1, 0, E;\n}" : "=r"(r));
    return r;
}
__device__ __forceinline__ void tma_store2d(const CUtensorMap* m, int c0, int c1, uint32_t src, uint64_t pol) {
    asm volatile("cp.async.bulk.tensor.2d.global.shared::cta.bulk_group.L2::cache_hint [%0, {%1, %2}], [%3], %4;" ::"l"(m), "r"(c0), "r"(c1), "r"(src), "l"(pol) : "memory");
}
__device__ __forceinline__ void bulk_commit() { asm volatile("cp.async.bulk.commit_group;" ::: "memory"); }
__device__ __forceinline__ void bulk_wait_read() { asm volatile("cp.async.bulk.wait_group.read 0;" ::: "memory"); }
__device__ __forceinline__ void bulk_wait_all() { asm volatile("cp.async.bulk.wait_group 0;" ::: "memory"); }
__device__ __forceinline__ uint64_t mkdesc(uint32_t addr, uint32_t lbo, uint32_t sbo, uint32_t swz) {
    return (uint64_t)((addr & 0x3FFFF) >> 4) | ((uint64_t)(lbo >> 4) << 16) | ((uint64_t)(sbo >> 4) << 32) | ((uint64_t)swz << 62);
}
__device__ __forceinline__ void wg_fence() { asm volatile("wgmma.fence.sync.aligned;" ::: "memory"); }
__device__ __forceinline__ void wg_commit() { asm volatile("wgmma.commit_group.sync.aligned;" ::: "memory"); }
template <int N> __device__ __forceinline__ void wg_wait() { asm volatile("wgmma.wait_group.sync.aligned %0;" ::"n"(N) : "memory"); }
template <typename T> __device__ __forceinline__ void pin_ptr(T*& p) { asm volatile("" : "+l"(p)); }
template <int N> __device__ __forceinline__ void pin(uint32_t* d) {
#pragma unroll
    for (int i = 0; i < N; i++) asm volatile("" : "+r"(d[i])::"memory");
}
template <int N> __device__ __forceinline__ void pin(float* d) {
#pragma unroll
    for (int i = 0; i < N; i++) asm volatile("" : "+f"(d[i])::"memory");
}

template <int TA, int TB>
__device__ __forceinline__ void wgmma_ss256(float* d, uint64_t da, uint64_t db) {
    asm volatile("wgmma.mma_async.sync.aligned.m64n256k16.f32.bf16.bf16 "
        "{%0, %1, %2, %3, %4, %5, %6, %7, %8, %9, %10, %11, %12, %13, %14, %15, %16, %17, %18, %19, %20, %21, %22, %23, %24, %25, %26, %27, %28, %29, %30, %31, %32, %33, %34, %35, %36, %37, %38, %39, %40, %41, %42, %43, %44, %45, %46, %47, %48, %49, %50, %51, %52, %53, %54, %55, %56, %57, %58, %59, %60, %61, %62, %63, %64, %65, %66, %67, %68, %69, %70, %71, %72, %73, %74, %75, %76, %77, %78, %79, %80, %81, %82, %83, %84, %85, %86, %87, %88, %89, %90, %91, %92, %93, %94, %95, %96, %97, %98, %99, %100, %101, %102, %103, %104, %105, %106, %107, %108, %109, %110, %111, %112, %113, %114, %115, %116, %117, %118, %119, %120, %121, %122, %123, %124, %125, %126, %127}, %128, %129, 1, 1, 1, %130, %131;"
        : "+f"(d[0]), "+f"(d[1]), "+f"(d[2]), "+f"(d[3]), "+f"(d[4]), "+f"(d[5]), "+f"(d[6]), "+f"(d[7]), "+f"(d[8]), "+f"(d[9]), "+f"(d[10]), "+f"(d[11]), "+f"(d[12]), "+f"(d[13]), "+f"(d[14]), "+f"(d[15]), "+f"(d[16]), "+f"(d[17]), "+f"(d[18]), "+f"(d[19]), "+f"(d[20]), "+f"(d[21]), "+f"(d[22]), "+f"(d[23]), "+f"(d[24]), "+f"(d[25]), "+f"(d[26]), "+f"(d[27]), "+f"(d[28]), "+f"(d[29]), "+f"(d[30]), "+f"(d[31]), "+f"(d[32]), "+f"(d[33]), "+f"(d[34]), "+f"(d[35]), "+f"(d[36]), "+f"(d[37]), "+f"(d[38]), "+f"(d[39]), "+f"(d[40]), "+f"(d[41]), "+f"(d[42]), "+f"(d[43]), "+f"(d[44]), "+f"(d[45]), "+f"(d[46]), "+f"(d[47]), "+f"(d[48]), "+f"(d[49]), "+f"(d[50]), "+f"(d[51]), "+f"(d[52]), "+f"(d[53]), "+f"(d[54]), "+f"(d[55]), "+f"(d[56]), "+f"(d[57]), "+f"(d[58]), "+f"(d[59]), "+f"(d[60]), "+f"(d[61]), "+f"(d[62]), "+f"(d[63]), "+f"(d[64]), "+f"(d[65]), "+f"(d[66]), "+f"(d[67]), "+f"(d[68]), "+f"(d[69]), "+f"(d[70]), "+f"(d[71]), "+f"(d[72]), "+f"(d[73]), "+f"(d[74]), "+f"(d[75]), "+f"(d[76]), "+f"(d[77]), "+f"(d[78]), "+f"(d[79]), "+f"(d[80]), "+f"(d[81]), "+f"(d[82]), "+f"(d[83]), "+f"(d[84]), "+f"(d[85]), "+f"(d[86]), "+f"(d[87]), "+f"(d[88]), "+f"(d[89]), "+f"(d[90]), "+f"(d[91]), "+f"(d[92]), "+f"(d[93]), "+f"(d[94]), "+f"(d[95]), "+f"(d[96]), "+f"(d[97]), "+f"(d[98]), "+f"(d[99]), "+f"(d[100]), "+f"(d[101]), "+f"(d[102]), "+f"(d[103]), "+f"(d[104]), "+f"(d[105]), "+f"(d[106]), "+f"(d[107]), "+f"(d[108]), "+f"(d[109]), "+f"(d[110]), "+f"(d[111]), "+f"(d[112]), "+f"(d[113]), "+f"(d[114]), "+f"(d[115]), "+f"(d[116]), "+f"(d[117]), "+f"(d[118]), "+f"(d[119]), "+f"(d[120]), "+f"(d[121]), "+f"(d[122]), "+f"(d[123]), "+f"(d[124]), "+f"(d[125]), "+f"(d[126]), "+f"(d[127])
        : "l"(da), "l"(db), "n"(TA), "n"(TB));
}
template <int TA, int TB>
__device__ __forceinline__ void wgmma_ss256_first(float* d, uint64_t da, uint64_t db) {
    asm volatile("wgmma.mma_async.sync.aligned.m64n256k16.f32.bf16.bf16 "
        "{%0, %1, %2, %3, %4, %5, %6, %7, %8, %9, %10, %11, %12, %13, %14, %15, %16, %17, %18, %19, %20, %21, %22, %23, %24, %25, %26, %27, %28, %29, %30, %31, %32, %33, %34, %35, %36, %37, %38, %39, %40, %41, %42, %43, %44, %45, %46, %47, %48, %49, %50, %51, %52, %53, %54, %55, %56, %57, %58, %59, %60, %61, %62, %63, %64, %65, %66, %67, %68, %69, %70, %71, %72, %73, %74, %75, %76, %77, %78, %79, %80, %81, %82, %83, %84, %85, %86, %87, %88, %89, %90, %91, %92, %93, %94, %95, %96, %97, %98, %99, %100, %101, %102, %103, %104, %105, %106, %107, %108, %109, %110, %111, %112, %113, %114, %115, %116, %117, %118, %119, %120, %121, %122, %123, %124, %125, %126, %127}, %128, %129, 0, 1, 1, %130, %131;"
        : "=f"(d[0]), "=f"(d[1]), "=f"(d[2]), "=f"(d[3]), "=f"(d[4]), "=f"(d[5]), "=f"(d[6]), "=f"(d[7]), "=f"(d[8]), "=f"(d[9]), "=f"(d[10]), "=f"(d[11]), "=f"(d[12]), "=f"(d[13]), "=f"(d[14]), "=f"(d[15]), "=f"(d[16]), "=f"(d[17]), "=f"(d[18]), "=f"(d[19]), "=f"(d[20]), "=f"(d[21]), "=f"(d[22]), "=f"(d[23]), "=f"(d[24]), "=f"(d[25]), "=f"(d[26]), "=f"(d[27]), "=f"(d[28]), "=f"(d[29]), "=f"(d[30]), "=f"(d[31]), "=f"(d[32]), "=f"(d[33]), "=f"(d[34]), "=f"(d[35]), "=f"(d[36]), "=f"(d[37]), "=f"(d[38]), "=f"(d[39]), "=f"(d[40]), "=f"(d[41]), "=f"(d[42]), "=f"(d[43]), "=f"(d[44]), "=f"(d[45]), "=f"(d[46]), "=f"(d[47]), "=f"(d[48]), "=f"(d[49]), "=f"(d[50]), "=f"(d[51]), "=f"(d[52]), "=f"(d[53]), "=f"(d[54]), "=f"(d[55]), "=f"(d[56]), "=f"(d[57]), "=f"(d[58]), "=f"(d[59]), "=f"(d[60]), "=f"(d[61]), "=f"(d[62]), "=f"(d[63]), "=f"(d[64]), "=f"(d[65]), "=f"(d[66]), "=f"(d[67]), "=f"(d[68]), "=f"(d[69]), "=f"(d[70]), "=f"(d[71]), "=f"(d[72]), "=f"(d[73]), "=f"(d[74]), "=f"(d[75]), "=f"(d[76]), "=f"(d[77]), "=f"(d[78]), "=f"(d[79]), "=f"(d[80]), "=f"(d[81]), "=f"(d[82]), "=f"(d[83]), "=f"(d[84]), "=f"(d[85]), "=f"(d[86]), "=f"(d[87]), "=f"(d[88]), "=f"(d[89]), "=f"(d[90]), "=f"(d[91]), "=f"(d[92]), "=f"(d[93]), "=f"(d[94]), "=f"(d[95]), "=f"(d[96]), "=f"(d[97]), "=f"(d[98]), "=f"(d[99]), "=f"(d[100]), "=f"(d[101]), "=f"(d[102]), "=f"(d[103]), "=f"(d[104]), "=f"(d[105]), "=f"(d[106]), "=f"(d[107]), "=f"(d[108]), "=f"(d[109]), "=f"(d[110]), "=f"(d[111]), "=f"(d[112]), "=f"(d[113]), "=f"(d[114]), "=f"(d[115]), "=f"(d[116]), "=f"(d[117]), "=f"(d[118]), "=f"(d[119]), "=f"(d[120]), "=f"(d[121]), "=f"(d[122]), "=f"(d[123]), "=f"(d[124]), "=f"(d[125]), "=f"(d[126]), "=f"(d[127])
        : "l"(da), "l"(db), "n"(TA), "n"(TB));
}
template <int TB>
__device__ __forceinline__ void wgmma_rs128(float* d, const uint32_t* a, uint64_t db, uint32_t acc) {
    asm volatile("{\n.reg .pred P;\nsetp.ne.u32 P, %69, 0;\nwgmma.mma_async.sync.aligned.m64n128k16.f32.bf16.bf16 "
        "{%0, %1, %2, %3, %4, %5, %6, %7, %8, %9, %10, %11, %12, %13, %14, %15, %16, %17, %18, %19, %20, %21, %22, %23, %24, %25, %26, %27, %28, %29, %30, %31, %32, %33, %34, %35, %36, %37, %38, %39, %40, %41, %42, %43, %44, %45, %46, %47, %48, %49, %50, %51, %52, %53, %54, %55, %56, %57, %58, %59, %60, %61, %62, %63}, {%64, %65, %66, %67}, %68, P, 1, 1, %70;\n}"
        : "+f"(d[0]), "+f"(d[1]), "+f"(d[2]), "+f"(d[3]), "+f"(d[4]), "+f"(d[5]), "+f"(d[6]), "+f"(d[7]), "+f"(d[8]), "+f"(d[9]), "+f"(d[10]), "+f"(d[11]), "+f"(d[12]), "+f"(d[13]), "+f"(d[14]), "+f"(d[15]), "+f"(d[16]), "+f"(d[17]), "+f"(d[18]), "+f"(d[19]), "+f"(d[20]), "+f"(d[21]), "+f"(d[22]), "+f"(d[23]), "+f"(d[24]), "+f"(d[25]), "+f"(d[26]), "+f"(d[27]), "+f"(d[28]), "+f"(d[29]), "+f"(d[30]), "+f"(d[31]), "+f"(d[32]), "+f"(d[33]), "+f"(d[34]), "+f"(d[35]), "+f"(d[36]), "+f"(d[37]), "+f"(d[38]), "+f"(d[39]), "+f"(d[40]), "+f"(d[41]), "+f"(d[42]), "+f"(d[43]), "+f"(d[44]), "+f"(d[45]), "+f"(d[46]), "+f"(d[47]), "+f"(d[48]), "+f"(d[49]), "+f"(d[50]), "+f"(d[51]), "+f"(d[52]), "+f"(d[53]), "+f"(d[54]), "+f"(d[55]), "+f"(d[56]), "+f"(d[57]), "+f"(d[58]), "+f"(d[59]), "+f"(d[60]), "+f"(d[61]), "+f"(d[62]), "+f"(d[63])
        : "r"(a[0]), "r"(a[1]), "r"(a[2]), "r"(a[3]), "l"(db), "r"(acc), "n"(TB));
}
template <int TB>
__device__ __forceinline__ void wgmma_rs64(float* d, const uint32_t* a, uint64_t db, uint32_t acc) {
    asm volatile("{\n.reg .pred P;\nsetp.ne.u32 P, %37, 0;\nwgmma.mma_async.sync.aligned.m64n64k16.f32.bf16.bf16 "
        "{%0, %1, %2, %3, %4, %5, %6, %7, %8, %9, %10, %11, %12, %13, %14, %15, %16, %17, %18, %19, %20, %21, %22, %23, %24, %25, %26, %27, %28, %29, %30, %31}, {%32, %33, %34, %35}, %36, P, 1, 1, %38;\n}"
        : "+f"(d[0]), "+f"(d[1]), "+f"(d[2]), "+f"(d[3]), "+f"(d[4]), "+f"(d[5]), "+f"(d[6]), "+f"(d[7]), "+f"(d[8]), "+f"(d[9]), "+f"(d[10]), "+f"(d[11]), "+f"(d[12]), "+f"(d[13]), "+f"(d[14]), "+f"(d[15]), "+f"(d[16]), "+f"(d[17]), "+f"(d[18]), "+f"(d[19]), "+f"(d[20]), "+f"(d[21]), "+f"(d[22]), "+f"(d[23]), "+f"(d[24]), "+f"(d[25]), "+f"(d[26]), "+f"(d[27]), "+f"(d[28]), "+f"(d[29]), "+f"(d[30]), "+f"(d[31])
        : "r"(a[0]), "r"(a[1]), "r"(a[2]), "r"(a[3]), "l"(db), "r"(acc), "n"(TB));
}
template <int TB>
__device__ __forceinline__ void wgmma_rs16(float* d, const uint32_t* a, uint64_t db, uint32_t acc) {
    asm volatile("{\n.reg .pred P;\nsetp.ne.u32 P, %13, 0;\nwgmma.mma_async.sync.aligned.m64n16k16.f32.bf16.bf16 "
        "{%0, %1, %2, %3, %4, %5, %6, %7}, {%8, %9, %10, %11}, %12, P, 1, 1, %14;\n}"
        : "+f"(d[0]), "+f"(d[1]), "+f"(d[2]), "+f"(d[3]), "+f"(d[4]), "+f"(d[5]), "+f"(d[6]), "+f"(d[7])
        : "r"(a[0]), "r"(a[1]), "r"(a[2]), "r"(a[3]), "l"(db), "r"(acc), "n"(TB));
}

__device__ __forceinline__ uint32_t delay_loop(int n, uint32_t x0) {
    uint32_t z;
    asm volatile("{\n.reg .pred P;\n.reg .u32 c, x;\nmov.u32 c, %1;\nmov.u32 x, %2;\nDL: mad.lo.u32 x, x, 1664525, 1013904223;\nadd.u32 c, c, -1;\nsetp.gt.s32 P, c, 0;\n@P bra DL;\n"
                 "setp.eq.u32 P, x, 0x7fffffff;\nselp.u32 %0, 16, 0, P;\n}" : "=r"(z) : "r"(n), "r"(x0) : "memory");
    return z;
}
__device__ __forceinline__ void wait_clocks(uint32_t n) {
    asm volatile("{\n.reg .pred P;\n.reg .u32 a, b;\nmov.u32 a, %%clock;\nW: mov.u32 b, %%clock;\nsub.u32 b, b, a;\nsetp.lt.u32 P, b, %0;\n@P bra W;\n}" ::"r"(n) : "memory");
}
__device__ __forceinline__ uint32_t gtime() { uint32_t t; asm volatile("mov.u32 %0, %%globaltimer_lo;" : "=r"(t)); return t; }
#define COUNT_RETRY(i)
__device__ __forceinline__ uint32_t stamp_word(uint32_t seq) { return (gtime() & ~31u) | (seq & 31u); }
__device__ __forceinline__ void wait_time(uint32_t t, uint32_t sb) { while ((int32_t)(gtime() - t) < 0) {} }
#define NAPMODE 1
__device__ __forceinline__ void nap(uint32_t ns) { if (NAPMODE) wait_clocks(ns * 7 / 4); else __nanosleep(ns); }
template <int STRIDE>
__device__ __forceinline__ uint32_t latest_stamp(const uint32_t* p, uint32_t seq, uint32_t ref, uint32_t sb) {
    int n = 0;
    while (true) {
        uint32_t bad = 0; int32_t m = INT32_MIN;
#pragma unroll
        for (int i = 0; i < 3; i++) { const uint32_t v = ld_relaxed1(p + i * STRIDE); bad |= (v ^ seq) & 31u; m = max(m, (int32_t)((v & ~31u) - ref)); }
        if (__all_sync(0xffffffffu, bad == 0)) return ref + __reduce_max_sync(0xffffffffu, m);
        nap(100);
        if (++n > SPIN_LIMIT) spin_fault();
    }
}
constexpr uint32_t ONES = 0x3C003C00u, FULL = 0x50005000u;
__device__ __forceinline__ void pacer(const Params& P, const uint32_t sb, const int cta, const int lane, const uint32_t epoch) {
    uint8_t* const zp = P.xb + cta * 2048 + xg_lane(lane);
    if (lane < 3) asm volatile("prefetch.tensormap [%0];" ::"l"(&P.tm[lane == 0 ? M_C1 + cta % 3 : lane == 1 ? M_CO : M_SEG]) : "memory");
    uint32_t e0 = 0;
#pragma unroll 2
    for (int i = 0; i < 32; i++) { const uint4 u = __ldg((const uint4*)P.mem0 + i * 32 + lane); e0 = amax(amax(e0, amax(u.x, u.y)), amax(u.z, u.w)); }
    e0 = min(max(warp_exp(e0), 31u), 253u) - 14;
    if (cta < 32) {
        const uint32_t* m = (const uint32_t*)(P.mem0 + (lane >> 2) * 1024 + cta * 32 + (lane & 3) * 2);
        const float sc = __uint_as_float((254 - e0) << 23);
        auto cv = [&](uint32_t u) { return pack2h(bf_lo(u) * sc, bf_hi(u) * sc); };
        const uint32_t y = cv(m[12]);
        st_relaxed4(zp, cv(m[0]), cv(m[4]), cv(m[8]), prmt(y, FULL, 0x7610));
        st_relaxed1(P.xb + xg_side(cta) + lane * 4, prmt(y, FULL, 0x3254));
    }
    if (cta < 40) {
#pragma unroll 1
        for (int b = 1; b < 8; b++) st_relaxed4(zp + xg_buf(b), 0, 0, 0, 0);
    }
    __threadfence();
    const uint32_t* ts = (const uint32_t*)(P.xb + XG_T) + lane;
    int32_t d0 = P.dly;
    const uint32_t go = mapa(sb + B_GO, (cta / 3 & 1) * 3 + 1 + (lane & 1));
    auto free_segment = [&]() { if (lane == 0) mbar_expect(sb + B_KVFULL, 16384); __syncwarp(); if (lane < 2) mbar_arrive_cluster(go); };
    wait_count(&g_cnt(C_XCNT), (epoch + 1) * 256);
    const uint32_t ex = max(ld_relaxed1(&g_cnt(C_XMAX)) & 255, 67u);
    mbar_wait(sb + B_READY, 0);
    free_segment();
    if (lane == 0) st_relaxed2(g_hint + cta * 32, stamp_word(epoch + 1), lds32(sb + S_EV) | lds32(sb + S_EO) << 16);
    uint32_t a = gtime();
    for (int n = 0;; n++) {
        uint32_t bad = 0, e = 0; int32_t m = INT32_MIN;
#pragma unroll
        for (int i = 0; i < 3; i++) {
            uint32_t v[2];
            ld_relaxed2(v, g_hint + lane * 32 + i * 1024);
            bad |= (v[0] ^ (epoch + 1)) & 31u; m = max(m, (int32_t)((v[0] & ~31u) - a)); e = __vmaxu2(e, v[1]);
        }
        if (__all_sync(0xffffffffu, bad == 0)) {
            a += __reduce_max_sync(0xffffffffu, m);
            const uint32_t ev = __reduce_max_sync(0xffffffffu, e & 255), eo = __reduce_max_sync(0xffffffffu, e >> 16);
            if (lane == 0) { sts64(sb + S_SC, max(ev, 97u) + max(eo, 97u) - 244, ex); sts32(sb + S_ISC, e0 * 0x800080u); }
            break;
        }
        wait_clocks(100);
        if (n > SPIN_LIMIT) spin_fault();
    }
    wait_time(a, sb);
    if (lane == 0) mbar_arrive(sb + B_RELM);
#pragma unroll 1
    for (int s = 0; s < 63; s++) {
        const uint32_t seq = epoch * 63 + s + 1;
        mbar_wait(sb + B_P1, s & 1);
        const uint32_t tx = gtime();
        if (lane == 0) st_relaxed1(ts + (s & 1) * 256 + cta, (tx & ~31u) | (seq & 31u));
        { const uint32_t t = tx; PROFP(3) }
        if (s > 0) {
            const int32_t e0 = latest_stamp<32>(ts + (~s & 1) * 256 + 128, seq - 1, a, sb) + P.mrg - a;
            d0 += s < 3 ? e0 : min(max(e0, -P.clamp0), P.clampv) / 2;
        }
        while ((int32_t)(gtime() - tx) < P.rd) nap(20);
        a = latest_stamp<32>(ts + (s & 1) * 256, seq, tx, sb) + d0;
        { const uint32_t t = gtime(); PROFP(0) }
        while ((int32_t)(a - gtime()) > 250) nap(40);
        wait_time(a, sb);
        if (lane == 0) mbar_arrive(sb + B_RELM);
        { const uint32_t t = a; PROFP(2) }
        mbar_wait(sb + B_RED, s & 1);
        { const uint32_t t = gtime(); PROFP(1) }
        const uint32_t g = tx + __reduce_max_sync(0xffffffffu, lds32(sb + S_TO + (lane & 7) * 4) - tx);
        if (lane == 0) st_relaxed1(ts + (s & 1) * 256 + 128 + cta, (g & ~31u) | (seq & 31u));
        if (s < 62) { if (P.kvd) nap(P.kvd); free_segment(); }
    }
}
__device__ __forceinline__ void st_async2(uint32_t a, uint32_t x, uint32_t y, uint32_t bar) {
    asm volatile("st.async.weak.shared::cluster.mbarrier::complete_tx::bytes.v2.b32 [%0], {%1,%2}, [%3];" ::"r"(a), "r"(x), "r"(y), "r"(bar) : "memory");
}
__device__ __forceinline__ uint32_t xor_or(uint32_t a, uint32_t b, uint32_t t) { uint32_t d; asm("lop3.b32 %0, %1, %2, %3, 0x7E;" : "=r"(d) : "r"(a), "r"(b), "r"(t)); return d; }
__device__ __forceinline__ uint32_t or3(uint32_t a, uint32_t b, uint32_t c) { uint32_t d; asm("lop3.b32 %0, %1, %2, %3, 0xFE;" : "=r"(d) : "r"(a), "r"(b), "r"(c)); return d; }
__device__ __forceinline__ bool tags_ok(uint32_t bad, uint32_t mask = 1) {
    uint32_t r;
    asm volatile("{\n.reg .pred P;\n.reg .b32 x;\nand.b32 x, %1, %2;\nsetp.ne.b32 P, x, 0;\nvote.sync.any.pred P, P, 0xffffffff;\nselp.u32 %0, 0, 1, P;\n}" : "=r"(r) : "r"(bad), "r"(mask));
    return r;
}
constexpr int SROW = 56;
#define PREA 8
#define PREB 9
#define RING1 7
#define RING2 7
#define RING3 8
#define PRE2 10
#define PRE2A 0
#define PRE3 0
#define EFENCE 0
#define RFENCE 1
#define PROG 16
#define EARLY 0
#define PLATE 1
#define NDEP 0
#define EFENCE2 0
#define LAG2 8
#define LAG 4
#define PUT1 33
#define DEPS 3
#define ADELAY 120
#define BDELAY 0
#define HOLD 1
#define XDELAY 330
#define FENCEA 0x80
#define FENCEB 0x80
#define FENCE2 0x220
#define OFENCE 0
#define MASK3 0x57
#define MASK4 0x55
#define MASK5 0x25
#define OFF3 0x5320
#define OFF4 0x6420
#define OFF5 0x0520
#define RESA (NRA == 3 ? 15 : NRA == 4 ? 3 : 0)
#define RESB (NRB == 3 ? 0xcc : NRB == 4 ? 0x30 : 0)
#define RESB1 (NRB == 3 ? 0xcc : NRB == 4 ? 0xc : 0)
__host__ __device__ constexpr int smem_mask(int NR) { return NR == 3 ? MASK3 : NR == 4 ? MASK4 : MASK5; }
__host__ __device__ constexpr bool round_smem(int r, int NR) { return smem_mask(NR) >> r & 1; }
__host__ __device__ constexpr int kord(int r, int NR) { int c = 0; for (int i = 0; i < r; i++) c += round_smem(i, NR) == round_smem(r, NR); return round_smem(r, NR) ? NR + c : c; }
__host__ __device__ constexpr int slot_r(int n, int NR) { return n < 32 ? n >> 2 : (((n & 31) >> 2) + ((NR == 3 ? OFF3 : NR == 4 ? OFF4 : OFF5) >> (n & 3) * 4)) & 7; }
__host__ __device__ constexpr int slot_k(int n, int NR) { return kord(slot_r(n, NR), NR); }
__host__ __device__ constexpr int slot_sord(int n, int NR) { int c = 0; for (int i = 0; i < n; i++) c += slot_k(i, NR) >= NR; return c; }
__host__ __device__ constexpr int sfrag_slot(int q, int NR) { for (int n = 0; n < 64; n++) if (slot_k(n, NR) >= NR && slot_sord(n, NR) == q) return n; return -1; }
__host__ __device__ constexpr int w1_loaded(int n, int NR, int PRE) {
    int q = PRE;
    for (int i = 0; i <= n; i++) q += q < (8 - NR) * 8 && q - slot_sord(i + 1, NR) < (i < 32 ? RING1 : RING2);
    return q;
}
template <int Q, int NR>
__device__ __forceinline__ void load_w1(uint32_t* w, const uint32_t* a) {
    constexpr int n = sfrag_slot(Q, NR);
    ldsm4t(w, a[n & 3] + ((slot_k(n, NR) - NR) * 2 + (n >> 5)) * 2048);
}
constexpr int AB = NRA < 5, BB = 3 - AB;
__device__ __forceinline__ bool w2_full(int role, int warp) { return warp < (role == 2 ? 2 : 3); }
__device__ __forceinline__ int w2_nblk(int role, int warp) { return warp < 4 ? BB - !w2_full(role, warp) : AB; }
__host__ __device__ constexpr int w2_step(bool full, int i) { return AB ? (full ? 2 * i : 0) : full ? (i == 0 ? 0 : i == 1 ? 16 - 2 * EARLY : 18 - 2 * EARLY) : i; }
__device__ __forceinline__ int w2_block(int role, int warp) {
    const int f = role * 3 + warp, g = role == 2 ? warp : role;
    if (AB) return (warp >= 4 ? role * 4 + (warp - 4) : w2_full(role, warp) ? 16 + 4 * (f >> 1) + (f & 1) : 12 + g) ^ EARLY;
    return w2_full(role, warp) ? EARLY + 4 * (f >> 1) + (f & 1) : EARLY + 2 + 4 * g;
}
__device__ __forceinline__ int w2_res(int role, int warp) { return warp >= 4 ? RESA : w2_full(role, warp) ? RESB : RESB1; }
__device__ __forceinline__ int w2_units(int role, int warp) { return w2_nblk(role, warp) * 4 - (5 - (warp < 4 ? NRB : NRA)) * 2; }
constexpr int W2B = (BB * 4 - (5 - NRB) * 2) * 2048, W2A = (AB * 4 - (5 - NRA) * 2) * 2048;
static_assert(S_W2 + 4 * W2B - 8192 + 4 * W2A == S_KV, "weights");
__device__ __forceinline__ int w1_base(int warp) { return S_W1 + (warp < 4 ? warp * (8 - NRB) : 4 * (8 - NRB) + (warp - 4) * (8 - NRA)) * 4096; }
__device__ __forceinline__ int w2_base(int warp) { return S_W2 + (warp < 4 ? warp * W2B : 4 * W2B - 8192 + (warp - 4) * W2A); }
__device__ __forceinline__ void chain_load(const Params& P, uint32_t sb, int cta, int warp, int lane, int round) {
    const int role = cta % 3, h = cta / 3;
    mbar_expect_e(sb + B_INIT, round ? (8 - (warp < 4 ? NRB : NRA)) * 4096 : 20480);
    if (round) mbar_expect_e(sb + B_INIT2, w2_units(role, warp) * 2048);
    __syncwarp();
    const int m1 = (warp < 4 ? smem_mask(NRB) : smem_mask(NRA)) ^ (round ? 0 : 255), below = (1 << lane) - 1;
    const int m2 = (w2_res(role, warp) ^ (round ? 0xfff : 0)) & ((1 << w2_nblk(role, warp) * 4) - 1);
    const uint32_t d1 = sb + (round ? w1_base(warp) : warp * 20480), d2 = round ? sb + w2_base(warp) : d1 + __popc(m1) * 4096;
    if (m1 >> lane & 1) tma3d(d1 + __popc(m1 & below) * 4096, &P.tm[M_C1 + role], 0, warp * 128 + lane * 16, h * 2, sb + B_INIT);
    __syncwarp();
    if (m2 >> lane & 1)
        tma2d(d2 + __popc(m2 & below) * 2048, &P.tm[M_CO], (w2_block(role, warp) + w2_step(w2_full(role, warp), lane >> 2)) * 32, h * 128 + (lane & 3) * 32, sb + (round ? B_INIT2 : B_INIT));
    __syncwarp();
}

__device__ __forceinline__ void put_partials(bool TR, uint32_t a, const float* x, const float* y) {
    if (TR) stsm4t(a, pack2(x[0], x[1]), pack2(x[2], x[3]), pack2(y[0], y[1]), pack2(y[2], y[3]));
    else stsm4(a, pack2(x[0], x[1]), pack2(x[2], x[3]), pack2(y[0], y[1]), pack2(y[2], y[3]));
}
template <int NR, int PRE, int FM, int B, int E>
__device__ __forceinline__ void project(float (*acc)[4], bool TR, const uint32_t (*wr)[4], uint32_t (*as)[4], uint32_t (*v)[4], uint32_t* x, const uint32_t* w1a, uint32_t pp, uint32_t zero) {
    static_for<B, E>([&](auto I) {
        constexpr int n = I.value, kk = slot_k(n, NR), T = (n >> 5) * 4 + (n & 3), so = slot_sord(n, NR), q = w1_loaded(n - 1, NR, PRE);
        constexpr bool sm = kk >= NR;
        const uint32_t* w = sm ? as[so] : wr[sm ? 0 : (kk * 2 + (n >> 5)) * 4 + (n & 3)];
        if constexpr (n == 32 && PUT1 < 32) { put_partials(TR, pp, acc[0], acc[1]); put_partials(TR, pp + 4096, acc[2], acc[3]); }
        if constexpr (n == 0) {
            const uint32_t c = prmt(v[0][3], x[0], 0x3254);
            v[0][0] = h2bf(v[0][0], v[0][0]); v[0][1] = h2bf(v[0][1], v[0][1]); v[0][2] = h2bf(v[0][2], v[0][2]); v[0][3] = h2bf(v[0][3], x[0]);
            x[0] = c;
        }
        if constexpr ((n & 31) < 4) acc[T][0] = acc[T][1] = acc[T][2] = acc[T][3] = 0.f;
        mma16816(acc[T], w[0], w[1], w[2], w[3], v[slot_r(n, NR) >> 1][(slot_r(n, NR) & 1) * 2], v[slot_r(n, NR) >> 1][(slot_r(n, NR) & 1) * 2 + 1]);
        if constexpr (n == DEPS) {
            const uint32_t sel = __float_as_uint(acc[T][0]) * zero + 0x7610;
#pragma unroll
            for (int b = 1; b < 4; b++) {
                if (b <= NDEP) cvt_block(v[b], x[b], sel);
                else {
                    const uint32_t c = prmt(v[b][3], x[b], 0x3254);
                    v[b][0] = h2bf(v[b][0], v[b][0]); v[b][1] = h2bf(v[b][1], v[b][1]); v[b][2] = h2bf(v[b][2], v[b][2]); v[b][3] = h2bf(v[b][3], x[b]);
                    x[b] = c;
                }
            }
        }
        if constexpr (w1_loaded(n, NR, PRE) > q) load_w1<q, NR>(as[q], w1a);
        if constexpr (n == PUT1 && n >= 32) { put_partials(TR, pp, acc[0], acc[1]); put_partials(TR, pp + 4096, acc[2], acc[3]); }
        if constexpr (n % 4 == 3 && (FM >> (n / 4) & 1) && n != E - 1) sched_fence();
    });
    if constexpr (E == 64) { put_partials(TR, pp + 8192, acc[4], acc[5]); put_partials(TR, pp + 12288, acc[6], acc[7]); }
}
__device__ __forceinline__ void reduce8(const uint32_t (*x)[4], const uint32_t* sel, float sc, uint32_t& r0, uint32_t& r1) {
    float d[4][4];
#pragma unroll
    for (int i = 0; i < 4; i++) {
        d[i][0] = d[i][1] = d[i][2] = d[i][3] = 0.f;
        mma16816(d[i], x[i][0], x[i][1], x[i][2], x[i][3], sel[2 * i], sel[2 * i + 1]);
    }
    r0 = pack2(((d[0][0] + d[1][0]) + (d[2][0] + d[3][0])) * sc, ((d[0][1] + d[1][1]) + (d[2][1] + d[3][1])) * sc);
    r1 = pack2(((d[0][2] + d[1][2]) + (d[2][2] + d[3][2])) * sc, ((d[0][3] + d[1][3]) + (d[2][3] + d[3][3])) * sc);
}

#define ISTAMP(i)
__host__ __device__ constexpr int wo_count(int n, int RES, bool res) { int c = 0; for (int i = 0; i < n; i++) c += (RES >> (i >> 2) & 1) == res; return c; }
__host__ __device__ constexpr int wo_loaded(int n, int RES, int PRE, int end) { int q = PRE; for (int i = 0; i <= n; i++) q += q < end && q - wo_count(i + 1, RES, false) < RING3; return q; }
template <int Q>
__device__ __forceinline__ void load_w2(uint32_t* w, const uint32_t* a) { ldsm4t(w, a[Q & 1] + (Q >> 1) * 1024); }
template <int NB, int RES, int PRE, int FM>
__device__ __forceinline__ void wo_blocks(uint32_t (*w)[4], const uint32_t (*wp)[4], uint32_t oa, const uint32_t* wa, const uint8_t* dst, const uint8_t* dsd, bool odd) {
    float a[NB][4][4];
    uint32_t o[4][4], r[5];
    bar_sync(3, 256);
#pragma unroll
    for (int i = 0; i < 4; i++) ldsm4(o[i], oa + i * 512);
    if (FM & 1) sched_fence();
    static_for<0, NB * 16>([&](auto I) {
        constexpr int n = I.value, i = n & 15, end = wo_count(NB * 16, RES, false), q = wo_loaded(n - 1, RES, PRE, end);
        constexpr bool res = RES >> (n >> 2) & 1;
        const uint32_t* b = o[i >> 2] + (i & 2);
        const uint32_t* x = res ? wp[wo_count(n, RES, true)] : w[wo_count(n, RES, false)];
        float* d = a[n >> 4][i & 3];
        if constexpr (i < 4) d[0] = d[1] = d[2] = d[3] = 0.f;
        mma16816(d, x[0], x[1], x[2], x[3], b[0], b[1]);
        if constexpr (wo_loaded(n, RES, PRE, end) > q) load_w2<q>(w[q], wa);
        if constexpr (n == NB * 16 - 1 || (n >= 16 && i == LAG - 1)) {
            const float (*e)[4] = a[n == NB * 16 - 1 ? NB - 1 : (n >> 4) - 1];
            const uint32_t y = pack2h(e[1][2] + e[3][2], e[1][3] + e[3][3]);
            r[0] = movm(pack2h(e[0][0] + e[2][0], e[0][1] + e[2][1])); r[1] = movm(pack2h(e[0][2] + e[2][2], e[0][3] + e[2][3]));
            r[2] = movm(pack2h(e[1][0] + e[3][0], e[1][1] + e[3][1])); r[3] = movm(odd ? ONES : y); r[4] = movm(odd ? y : ONES);
        }
        if constexpr (n == NB * 16 - 1 || (n >= 16 && i == LAG2 - 1)) {
            constexpr int bs = w2_step(NB == BB, n == NB * 16 - 1 ? NB - 1 : (n >> 4) - 1);
            red_add4(dst + bs * 2048, r[0], r[1], r[2], r[3]);
            red_add1(dsd + (bs >> 1) * 1024 + (bs & 1) * 256, r[4]);
        }
        if constexpr (((FM >> (n / 4 + 1)) & 1) && (n & 3) == 3 && n != NB * 16 - 1) sched_fence();
    });
}
#define FRAG1(ln) ((((ln) & 7) + ((ln) >> 4) * 8) * 128 + ((((((ln) >> 3) & 1) << (ROLE == 1)) ^ ((ln) & 7)) << 4))
#define FRAG2(ln) ((((ln) & 7) + ((ln) >> 4) * 8) * 64 + (((((ln) >> 3) & 1) ^ (((ln) >> 1) & 3)) << 4))
#define TILE_X(i) (ROLE == 1 ? (((i) >> 1) << 6) | (((i) & 1) << 4) : (i) << 5)
__device__ __forceinline__ void chain_fetch(const Params& P, const uint32_t sb, const int cta, const int warp, const int lane, uint32_t (*wr)[4]) {
    const int ROLE = cta % 3, nr = warp < 4 ? NRB : NRA;
    mbar_wait(sb + B_INIT, 0);
    ISTAMP(0)
#pragma unroll
    for (int f = 0; f < 40; f++) {
        const bool w1 = f < (NRA < NRB ? NRA : NRB) * 8 || f < nr * 8;
        ldsm4t(wr[f], sb + warp * 20480 + (f >> 2) * 2048 + (w1 ? FRAG1(lane) ^ TILE_X(f & 3) : (f & 2) * 512 + (FRAG2(lane) ^ ((f & 1) << 5))));
    }
    fence_async_smem();
    mbar_wait(sb + B_SFREE + (warp >> 2) * 8, 0);
    bar_sync(1, 256);
    chain_load(P, sb, cta, warp, lane, 1);
    ISTAMP(1)
}
__device__ __forceinline__ void chain_bounds(const uint32_t sb, const int cta, const int warp, const int lane, const uint32_t (*wr)[4]) {
    const int ROLE = cta % 3, nr = warp < 4 ? NRB : NRA;
    uint32_t m[6] = {}, u[4];
#pragma unroll
    for (int f = 0; f < 40; f++) m[f < 24 ? 0 : f >> 3] = amax4(m[f < 24 ? 0 : f >> 3], wr[f]);
    uint32_t m1 = amax(m[0], amax(nr > 3 ? m[3] : 0, nr > 4 ? m[4] : 0)), m2 = amax(nr > 3 ? 0 : m[3], nr > 4 ? 0 : m[4]);
    ISTAMP(5)
    mbar_wait(sb + B_INIT, 1);
    ISTAMP(3)
    if (ROLE == 2) {
#pragma unroll 4
        for (int i = 0; i < S_W2 / 4096; i++) { lds128(u, sb + S_W1 + warp * (S_W2 / 8) + i * 512 + lane * 16); m1 = amax4(m1, u); }
    }
    mbar_wait(sb + B_INIT2, 0);
    ISTAMP(7)
    const int n = w2_units(ROLE, warp) * 4;
#pragma unroll 4
    for (int i = 0; i < n; i++) { lds128(u, sb + w2_base(warp) + i * 512 + lane * 16); m2 = amax4(m2, u); }
    m1 = warp_exp(m1); m2 = warp_exp(m2);
    if (lane == 0) { if (ROLE == 2) red_max_shared(sb + S_EV, m1); red_max_shared(sb + S_EO, m2); }
}
template <bool ATT>
__device__ __forceinline__ void chain_role(const Params& P, const uint32_t sb, const int cta, const int warp, const int lane, const uint32_t epoch, const uint32_t (*wr)[4]) {
    constexpr int NR = ATT ? NRA : NRB, PRE = ATT ? PREA : PREB;
    const int h = cta / 3, ROLE = cta - h * 3;
    ISTAMP(6)
    uint32_t l8 = opq(sb + lane * 8, lane);
    const uint8_t* persu = (const uint8_t*)((ROLE == 1 ? g_km : g_vmt) + h * 512) - (sb >> 1);
    auto persist = [&](int s, int tile, uint32_t r0, uint32_t r1) {
        uint32_t* pp = (uint32_t*)(persu + s * 65536 + (ROLE == 1 ? (tile >> 1) * 512 + (tile & 1) * 128 : tile * 256) + (l8 >> 1));
        pp[0] = r0; pp[ROLE == 1 ? 64 : 32] = r1;
    };
    const uint32_t rk0 = (h & 1) * 3, rd1 = __shfl_sync(0xffffffffu, mapa(sb, rk0 + (ROLE + 1) % 3) - sb, 0), rd2 = __shfl_sync(0xffffffffu, mapa(sb, rk0 + (ROLE + 2) % 3) - sb, 0);
    const uint32_t xo = (ROLE == 2 ? S_XV : S_X + ROLE * 2048) + warp * 256;
    const bool full = w2_full(ROLE, warp);
    const int blk = w2_block(ROLE, warp);
    const uint32_t om = blk * 2048, os = xg_side(blk);
    const uint32_t w1o = sb + w1_base(warp), w2o = sb + w2_base(warp);
    ISTAMP(2)
    if (lane == 0) mbar_arrive(sb + B_READY);
#pragma unroll 1
    for (int s = 0;; s++) {
        l8 += s & P.zero;
        uint32_t r0, r1;
        {
            uint32_t v[4][4], as[(8 - NR) * 8][4], w1a[4];
            float acc[8][4];
            const uint32_t pst = sb + S_P1 + (l8 - sb) * 16 + ((warp * 16) ^ ((l8 & 56) * 2));
#pragma unroll
            for (int i = 0; i < 4; i++) w1a[i] = w1o + (FRAG1((l8 - sb) >> 3) ^ TILE_X(i));
            auto preload = [&]() { static_for<0, PRE>([&](auto I) { load_w1<I.value, NR>(as[I.value], w1a); }); };
#pragma unroll 1
            while (true) {
                uint32_t x[4];
                if (!(PLATE >> ATT & 1)) preload();
                const uint32_t lm = opq(l8 - sb, (l8 - sb) >> 3);
                const uint8_t* pm = P.xb + xg_buf(s) + warp * 8192 + xg_lane(lm >> 3);
                const uint8_t* ps = P.xb + xg_buf(s) + XG_SIDE + warp * 2048 + (lm >> 1);
                pin_ptr(pm); pin_ptr(ps);
                mbar_wait(sb + B_RELM, s & 1);
                if (ATT ? ADELAY : BDELAY) wait_clocks(ATT ? ADELAY : BDELAY);
                PROF(10)
#pragma unroll
                for (int b = 0; b < 4; b++) { ld_relaxed4(v[b], pm + b * 2048); ld_relaxed1n(x[b], ps + (b >> 1) * 1024 + (b & 1) * 256); }
                if (PLATE >> ATT & 1) { preload(); if (PLATE >> (ATT + 2) & 1) sched_fence(); }
                project<NR, PRE, ATT ? FENCEA : FENCEB, 0, PROG>(acc, ROLE == 2, wr, as, v, x, w1a, pst, P.zero);
                const uint32_t bad = xor_or(x[0], x[1], FULL) | xor_or(x[2], x[3], FULL);
                if (tags_ok(bad, 0xffffffffu)) break;
                COUNT_RETRY(warp >> 1)
                uint32_t n;
                asm volatile("atom.shared.add.u32 %0, [%1], 1;" : "=r"(n) : "r"(sb + S_RETRY) : "memory");
                if (n > SPIN_LIMIT) spin_fault();
            }
            PROF(0)
            project<NR, PRE, ATT ? FENCEA : FENCEB, PROG, 64>(acc, ROLE == 2, wr, as, v, nullptr, w1a, pst, 0);
            PROF(1)
            const uint32_t isc = lds32(sb + S_ISC + (s & 1) * 4);
            const uint32_t lq = l8 + ((s >> 3) & P.zero), e1 = s == 63 ? 0 : rd1, e2 = s == 63 ? 0 : rd2;
            uint32_t x[4][4], sel[8], xd[6] = {l8 + xo, l8 + xo + e1, l8 + xo + e2, sb + B_X + e1, sb + B_X + e2, sb + S_P1 + warp * 2048 + (lq & 64) * 16 + (lq & 128) + (lq & 56) * 2};
#pragma unroll
            for (int i = 0; i < 8; i++) sel[i] = (lq & 224) == i * 32 ? 0x3F803F80u : 0u;
            pin<6>(xd); pin<8>(sel);
            if (RFENCE) sched_fence();
            bar_sync(1, 256);
#pragma unroll
            for (int i = 0; i < 4; i++) ldsm4t(x[i], xd[5] + i * 256);
            if (!ATT && l8 == sb + (warp - 3) * 1024) mbar_arrive(sb + B_P1);
            uint32_t em = warp_exp(amax(amax4(amax(amax(v[0][0], v[0][1]), amax(v[0][2], v[0][3])), v[1]), amax4(amax(amax(v[2][0], v[2][1]), amax(v[2][2], v[2][3])), v[3])));
            if (EFENCE2) sched_fence();
            reduce8(x, sel, bf_hi(isc), r0, r1);
            st_async2(xd[1], r0, r1, xd[3]);
            st_async2(xd[2], r0, r1, xd[4]);
            sts64(xd[0], r0, r1);
            if (s == 63) { persist(s, warp, r0, r1); break; }
            if (l8 == sb) sts32(sb + S_EM + warp * 4, em + (isc >> 23));
            __syncwarp();
            if (l8 == sb) mbar_arrive(sb + B_X);
            PROF(2)
        }
        uint32_t w[40][4], w2a[2], odd;
        const uint8_t *po, *pd;
        auto wo_addr = [&]() {
            const uint32_t lo = (l8 + ((s >> 2) & P.zero) - sb) >> 3;
            w2a[0] = w2o + FRAG2(lo); w2a[1] = w2o + (FRAG2(lo) ^ 32);
            po = P.xb + xg_buf(s + 1) + om + xg_lane(lo);
            pd = P.xb + xg_buf(s + 1) + os + lo * 4;
            odd = lo & 4;
            pin_ptr(po); pin_ptr(pd); pin<2>(w2a); pin<1>(&odd);
        };
        uint32_t oa = l8 * 2 + (S_OX - sb);
        if constexpr (ATT) {
            const uint32_t ln = (l8 + ((s >> 4) & P.zero) - sb) >> 3;
            const uint32_t va = sb + S_KV + 8192 + ((warp >> 1) & 1) * 4096 + ((ln & 7) + (ln >> 4) * 8) * 128 + ((((warp & 1) * 4 + ((ln >> 3) & 1)) ^ (ln & 7)) << 4);
            const uint32_t ka = sb + S_KV + (warp & 1) * 2048 + (ln & 15) * 128 + (((ln >> 4) ^ (ln & 7)) << 4);
            uint32_t ad[5] = {sb + S_SX + (ln & 3) * (8 * SROW) + (ln >> 2) * 4 + (warp < 6 ? (warp - 4) * 64 : 128 + (warp - 6) * 32), l8 + S_XV + (warp - 4) * 512,
                              l8 + S_SX + (ln >> 2) * (4 * SROW - 32), oa + (warp - 4) * 512, sb + S_ISC + (~s & 1) * 4};
            if constexpr (AB) { wo_addr(); pin<1>(&oa); }
            pin<5>(ad);
            const uint32_t sa = ad[0], sr = ad[2];
            uint32_t vf[4][4], vm[2][2], q[8][2];
            float S[4][4];
#pragma unroll
            for (int n = 0; n < 4; n++) { S[n][0] = S[n][1] = S[n][2] = S[n][3] = 0.f; }
            mbar_wait_fast(sb + B_KVFULL, s & 1);
            if (warp < 6) {
                uint32_t kf[8][4];
#pragma unroll
                for (int k = 0; k < 8; k++) ldsm4(kf[k], (ka ^ ((k & 3) << 5)) + (k >> 2) * 4096);
#pragma unroll
                for (int i = 0; i < 4; i++) ldsm4t(vf[i], (va ^ ((i & 1) << 5)) + (i >> 1) * 2048);
                mbar_wait(sb + B_X, s & 1);
                PROF(11)
#pragma unroll
                for (int k = 0; k < 8; k++) lds64(q[k], l8 + S_X + k * 256);
#pragma unroll
                for (int k = 0; k < 8; k++) mma16816(S[k & 3], kf[k][0], kf[k][1], kf[k][2], kf[k][3], q[k][0], q[k][1]);
                sts32(sa, __float_as_uint((S[0][0] + S[1][0]) + (S[2][0] + S[3][0])));
                sts32(sa + 4 * SROW, __float_as_uint((S[0][1] + S[1][1]) + (S[2][1] + S[3][1])));
                sts32(sa + 32, __float_as_uint((S[0][2] + S[1][2]) + (S[2][2] + S[3][2])));
                sts32(sa + 4 * SROW + 32, __float_as_uint((S[0][3] + S[1][3]) + (S[2][3] + S[3][3])));
            } else {
#pragma unroll
                for (int i = 0; i < 4; i++) ldsm4t(vf[i], (va ^ ((i & 1) << 5)) + (i >> 1) * 2048);
                uint32_t xa = l8 + S_X + (warp - 6) * 1024;
                pin<1>(&xa);
                mbar_wait(sb + B_X, s & 1);
                PROF(11)
#pragma unroll
                for (int k = 0; k < 8; k++) lds64(q[k], xa + (k >> 2) * 2048 + (k & 3) * 256);
#pragma unroll
                for (int k = 0; k < 4; k++) mma16816(S[k], q[4 + (k & 2)][0], q[4 + (k & 2)][1], q[5 + (k & 2)][0], q[5 + (k & 2)][1], q[k][0], q[k][1]);
                sts32(sa, __float_as_uint((S[0][0] + S[2][0]) + (S[1][2] + S[3][2])));
                sts32(sa + 4 * SROW, __float_as_uint((S[0][1] + S[2][1]) + (S[1][3] + S[3][3])));
            }
            lds64(vm[0], ad[1]); lds64(vm[1], ad[1] + 256);
            PROF(7)
            bar_sync(2, 160);
            const float cs = 0.08838834764831845f * 1.4426950408889634f;
            float E[6][2];
#pragma unroll
            for (int i = 0; i < 6; i++) lds64f(E[(i + 4) % 6], sr + ((i + 4) % 6) * 32);
            const uint32_t isn = lds32(ad[4]);
            E[4][0] += E[5][0]; E[4][1] += E[5][1];
            float m = fmaxf(fmaxf(fmaxf(fmaxf(E[0][0], E[0][1]), fmaxf(E[1][0], E[1][1])), fmaxf(fmaxf(E[2][0], E[2][1]), fmaxf(E[3][0], E[3][1]))), fmaxf(E[4][0], E[4][1]));
            m = fmaxf(m, __shfl_xor_sync(0xffffffffu, m, 1));
            m = fmaxf(m, __shfl_xor_sync(0xffffffffu, m, 2));
            m *= cs;
            if constexpr (AB) static_for<0, PRE3>([&](auto I) { load_w2<I.value>(w[I.value], w2a); });
            uint32_t pa[5];
#pragma unroll
            for (int i = 0; i < 5; i++) { const int k = (i + 4) % 5; E[k][0] = ex2(fmaf(E[k][0], cs, -m)); E[k][1] = ex2(fmaf(E[k][1], cs, -m)); pa[k] = pack2(E[k][0], E[k][1]); }
            if (EFENCE) sched_fence();
            float O[2][4], Z[4];
#pragma unroll
            for (int i = 0; i < 4; i++) { O[0][i] = O[1][i] = Z[i] = 0.f; }
#pragma unroll
            for (int i = 0; i < 2; i++) {
                mma1688(O[i], vm[i][0], vm[i][1], pa[4]);
                mma16816(O[i], vf[i][0], vf[i][1], vf[i][2], vf[i][3], pa[0], pa[1]);
                mma16816(O[i], vf[2 + i][0], vf[2 + i][1], vf[2 + i][2], vf[2 + i][3], pa[2], pa[3]);
            }
            const float z = (((E[4][0] + E[4][1]) + (E[0][0] + E[0][1])) + ((E[1][0] + E[1][1]) + (E[2][0] + E[2][1]))) + (E[3][0] + E[3][1]);
            const float zh = __uint_as_float(__float_as_uint(z) & 0xffff0000u);
            mma1688(Z, isn, isn, pack2(zh, z - zh));
            const float i0 = rcp(Z[0]), i1 = rcp(Z[1]);
            stsm4t(ad[3], pack2(O[0][0] * i0, O[0][1] * i1), pack2(O[0][2] * i0, O[0][3] * i1), pack2(O[1][0] * i0, O[1][1] * i1), pack2(O[1][2] * i0, O[1][3] * i1));
            PROF(4)
            if constexpr (AB) wo_blocks<1, RESA, PRE3, OFENCE / 2>(w, wr + NR * 8, oa, w2a, po, pd, odd);
            else bar_arrive(3, 256);
            if (ROLE != 0) persist(s, warp, r0, r1);
            if (warp == 7 && l8 == sb) mbar_expect(sb + B_X, 4096);
        } else {
            if (ROLE != 0) persist(s, warp, r0, r1);
            wo_addr(); pin<1>(&oa);
            static_for<0, PRE2A>([&](auto I) { load_w2<I.value>(w[I.value], w2a); });
            mbar_wait(sb + B_X, s & 1);
            if (warp == 0) {
                uint32_t sc[2];
                lds64(sc, sb + S_SC);
                const int em = __reduce_max_sync(0xffffffffu, lds32(sb + S_EM + ((l8 >> 1) & 28)));
                if (l8 == sb) sts32(sb + S_ISC + (~s & 1) * 4, min(max(em - 127, (int)sc[1]) + (int)sc[0], 253) * 0x800080u);
                bar_arrive(2, 160);
            }
            wait_clocks(XDELAY - (warp == 0) * 100);
            constexpr int PRE1 = (BB - 1) * 16 - (5 - NRB) * 8 < PRE2 ? (BB - 1) * 16 - (5 - NRB) * 8 : PRE2;
            static_for<PRE2A, PRE1>([&](auto I) { load_w2<I.value>(w[I.value], w2a); });
            if (full) {
                static_for<PRE1, PRE2>([&](auto I) { load_w2<I.value>(w[I.value], w2a); });
                wo_blocks<BB, RESB, PRE2, FENCE2 * 2 + OFENCE % 2>(w, wr + NR * 8, oa, w2a, po, pd, odd);
            } else wo_blocks<BB - 1, RESB1, PRE1, FENCE2 * 2 + OFENCE % 2>(w, wr + NR * 8, oa, w2a, po, pd, odd);
        }
        PROF(5)
        if (l8 == sb) { sts32(sb + S_TO + warp * 4, gtime()); mbar_arrive(sb + B_RED); }
        if (HOLD && !(PLATE >> ATT & 1)) mbar_wait(sb + B_RED, s & 1);
        if (ROLE != 0 && (s & 3) == 3 && l8 == sb) mbar_arrive(sb + B_PERS);
        if (ROLE == 0 && s == 62) return;
    }
    __syncwarp();
    if (l8 == sb) mbar_arrive(sb + B_PERS);
}
#define IP(i)
struct Pipe { uint32_t stage, phase; };
struct Cons {
    uint32_t sb, rel;
    int wg, wq, lane, rank, pair;
    uint32_t atag, nst;
    Pipe p;
};
__device__ __forceinline__ void pipe_next(Pipe& p) { p.stage = (p.stage + 1) & (NSTAGE - 1); p.phase ^= (p.stage == 0); }
__device__ __forceinline__ void release(const Cons& c, uint32_t stage) { if (c.lane < 2) mbar_arrive_cluster(c.rel + stage * 8); }
__device__ __forceinline__ void wait_full(const Cons& c) { mbar_wait(c.sb + B_FULL + c.p.stage * 8, c.p.phase); }

enum { PEND_NONE = 0, PEND_KVO = 1, PEND_HT = 2, PEND_OUT = 3 };
struct Pend { uint32_t pk[64]; int kind, row, col, cnt; };

__device__ __forceinline__ void staging_wait(const Cons& c) { if (c.nst) mbar_wait(c.sb + B_SFREE + c.wg * 8, (c.nst - 1) & 1); }
__device__ __forceinline__ void staging_post(Cons& c, int kind, int row, int col, int cnt) {
    __syncwarp();
    if (c.lane == 0) {
        if (c.wq == 0) { const uint32_t x[4] = {(uint32_t)kind, (uint32_t)row, (uint32_t)col, (uint32_t)cnt}; sts128(c.sb + S_DESC + c.wg * 16, x); }
        mbar_arrive(c.sb + B_SFULL + c.wg * 8);
    }
    c.nst++;
}
__device__ __forceinline__ void drain(const Params& P, Cons& c, Pend& d) {
    const uint32_t* pk = d.pk;
    if (d.kind == PEND_OUT) {
        float* o = P.out + (size_t)(d.row + c.wq * 16 + (c.lane >> 2)) * 2048 + d.col + (c.lane & 3) * 2;
#pragma unroll
        for (int j = 0; j < 16; j++) {
            st_stream2(o + j * 8, bf_lo(pk[j * 2]), bf_hi(pk[j * 2]));
            st_stream2(o + 8 * 2048 + j * 8, bf_lo(pk[j * 2 + 1]), bf_hi(pk[j * 2 + 1]));
        }
    } else {
        const bool ht = d.kind == PEND_HT;
        const int hi = (c.lane >> 3) & 1;
        const uint32_t base = c.sb + S_STG + c.wg * 16384 + ((ht ? hi * 32 + c.wq * 8 : c.wq * 16 + hi * 8) + (c.lane & 7)) * 128;
        staging_wait(c);
#pragma unroll
        for (int j = 0; j < 8; j++) {
            const int ch = (j & 3) * 2 + (c.lane >> 4);
            stsm4(base + (j >> 2) * 8192 + ((ch ^ (c.lane & 7)) << 4), pk[j * 4], pk[j * 4 + 1], pk[j * 4 + 2], pk[j * 4 + 3]);
        }
        fence_async_smem();
        staging_post(c, d.kind, d.row, d.col, (d.col & 128) ? d.cnt : -1);
    }
    if (d.col & 128) d.kind = PEND_NONE;
    d.col += 128;
#pragma unroll
    for (int i = 0; i < 32; i++) d.pk[i] = d.pk[32 + i];
}

constexpr int S_STG2 = 8 * 20480, PEND_BOTH = 8;
__device__ __forceinline__ void drain_both(Cons& c, const Pend& d) {
    const uint32_t base = c.sb + c.wg * 16384 + (c.wq * 16 + ((c.lane >> 3) & 1) * 8 + (c.lane & 7)) * 128;
#pragma unroll
    for (int j = 0; j < 16; j++)
        stsm4(base + (j < 8 ? S_STG : S_STG2) + (j >> 2 & 1) * 8192 + ((((j & 3) * 2 + (c.lane >> 4)) ^ (c.lane & 7)) << 4), d.pk[j * 4], d.pk[j * 4 + 1], d.pk[j * 4 + 2], d.pk[j * 4 + 3]);
    fence_async_smem();
    staging_post(c, PEND_KVO | PEND_BOTH, d.row, d.col, d.cnt);
}

__device__ __forceinline__ void store_warp(const Params& P, uint32_t sb, int wg, int cta) {
    if (cta < 128) {
        for (int i = 0; i < P.xd; i++) __nanosleep(1000);
        const uint32_t e1 = ld_acquire(&g_cnt(C_EPOCH)) + 1;
        const uint4* x = (const uint4*)P.Bx + (cta * 2 + wg) * 1024 + (threadIdx.x & 31);
        uint32_t m = 0;
#pragma unroll 4
        for (int i = 0; i < 32; i++) { const uint4 u = __ldg(x + i * 32); m = amax(amax(m, amax(u.x, u.y)), amax(u.z, u.w)); }
        m = warp_exp(m);
        if (elect_one()) { atomicMax(&g_cnt(C_XMAX), e1 << 8 | m); red_release(&g_cnt(C_XCNT)); }
        __syncwarp();
    }
    const uint32_t stg = sb + S_STG + wg * 16384;
#pragma unroll 1
    for (uint32_t n = 0;; n++) {
        mbar_wait(sb + B_SFULL + wg * 8, n & 1);
        uint32_t x[4];
        lds128(x, sb + S_DESC + wg * 16);
#pragma unroll
        for (int i = 0; i < 4; i++) x[i] = __shfl_sync(0xffffffffu, x[i], 0);
        if (x[0] == PEND_NONE) break;
        const bool ht = x[0] == PEND_HT;
        const CUtensorMap* m = &P.tm[ht ? M_HTS : M_KVO];
        const uint64_t pol = P.pol[ht ? 2 : x[1] >= 4096 ? 1 : (x[1] & 2047) < 1536 ? 0 : 10];
        if (elect_one()) {
#pragma unroll
            for (int i = 0; i < 4; i++) tma_store2d(m, x[2] + (i >> 1) * 64, x[1] + (i & 1) * (ht ? 1024 : 32), stg + i * 4096, pol);
            if (x[0] & PEND_BOTH) {
#pragma unroll 1
                for (int i = 0; i < 4; i++) tma_store2d(m, x[2] + 128 + (i >> 1) * 64, x[1] + (i & 1) * 32, stg + (S_STG2 - S_STG) + i * 4096, pol);
            }
            bulk_commit();
            bulk_wait_read();
            mbar_arrive(sb + B_SFREE + wg * 8);
            if ((int)x[3] >= 0) { bulk_wait_all(); fence_async(); red_release(&g_cnt(x[3])); }
        }
        __syncwarp();
    }
}

template <int TA, int TB, bool FIRST>
__device__ __forceinline__ void issue_ktile(float* acc, const Cons& c) {
    const uint32_t a = c.sb + c.p.stage * STAGE + c.wg * 8192, b = c.sb + c.p.stage * STAGE + 16384;
    const uint64_t da = mkdesc(a, TA ? 8192 : 16, 1024, 1), db = mkdesc(b, TB ? 8192 : 16, 1024, 1);
    wg_fence();
#pragma unroll
    for (int k = 0; k < 4; k++) {
        if (FIRST && k == 0) wgmma_ss256_first<TA, TB>(acc, da, db);
        else wgmma_ss256<TA, TB>(acc, da + (TA ? 128 : 2) * k, db + (TB ? 128 : 2) * k);
    }
    wg_commit();
}
template <bool KVONLY, bool FIRST>
__device__ __forceinline__ void issue_any(float* acc, const Cons& c, int type) {
    if (FIRST) mbar_wait_fast(c.sb + B_FULL + c.p.stage * 8, c.p.phase); else wait_full(c);
    if (!KVONLY && type == T_A1) issue_ktile<0, 0, FIRST>(acc, c);
    else if (!KVONLY && type == T_A2) issue_ktile<1, 0, FIRST>(acc, c);
    else issue_ktile<0, 1, FIRST>(acc, c);
}
template <bool KVONLY = false>
__device__ __forceinline__ void mainloop(float* acc, const Params& P, Cons& c, Pend& d, int type, int nk) {
    issue_any<KVONLY, true>(acc, c, type);
    if (!KVONLY) { IP(0) }
    uint32_t prev = c.p.stage;
    pipe_next(c.p);
#pragma unroll 1
    for (int kt = 1; kt < nk; kt++) {
        if (!KVONLY && d.kind != PEND_NONE && kt != 2) drain(P, c, d);
        issue_any<KVONLY, false>(acc, c, type);
        wg_wait<1>();
        release(c, prev);
        prev = c.p.stage;
        pipe_next(c.p);
    }
    d.kind = PEND_NONE;
    wg_wait<0>();
    pin<128>(acc);
    release(c, prev);
    if (!KVONLY) { IP(1) }
}
__device__ __forceinline__ void pack_half(uint32_t* pk, const float* a) {
#pragma unroll
    for (int i = 0; i < 32; i++) pk[i] = pack2(a[2 * i], a[2 * i + 1]);
}

__device__ __forceinline__ void epi_kv(const float* acc, const Cons& c, Pend& d, int mb, int nb) {
    pack_half(d.pk, acc); pack_half(d.pk + 32, acc + 64);
    d.kind = PEND_KVO; d.row = (nb >> 4) * 2048 + mb * 256 + c.rank * 128 + c.wg * 64; d.col = (nb & 15) * 256; d.cnt = C_KV + mb;
}

__device__ __forceinline__ void qa_scores(float* S, float* Sm, const uint32_t* q, Cons& c) {
    wait_full(c);
    const uint32_t st = c.sb + c.p.stage * STAGE;
    const uint64_t dk = mkdesc(st + c.wg * 8192, 16, 1024, 1), dm = mkdesc(st + 32768 + c.wg * 4096, 128, 2048, 0);
    wg_fence();
#pragma unroll
    for (int i = 0; i < 8; i++) wgmma_rs64<0>(S, q + i * 4, dk + (i >> 2) * 1024 + (i & 3) * 2, i != 0);
#pragma unroll
    for (int i = 0; i < 8; i++) wgmma_rs16<0>(Sm, q + i * 4, dm + i * 16, i != 0);
    wg_commit();
    pipe_next(c.p);
}
__device__ __forceinline__ void qa_softmax(uint32_t (*pa)[4], const float* S, const float* Sm, const Cons& c) {
    const int t = c.lane & 3, i0 = (c.wq & 1) * 16 + (c.lane >> 2) - 2 * t;
    const bool sg = c.wq >= 2;
    const float cs = 0.08838834764831845f * 1.4426950408889634f;
    float x[2][10];
#pragma unroll
    for (int r = 0; r < 2; r++) {
#pragma unroll
        for (int j = 0; j < 4; j++)
#pragma unroll
            for (int e = 0; e < 2; e++) {
                const float v = sg ? S[16 + j * 4 + r * 2 + e] : S[j * 4 + r * 2 + e];
                x[r][j * 2 + e] = (j * 8 + e - r * 8 > i0) ? -1e9f / 0.08838834764831845f : v;
            }
        x[r][8] = sg ? Sm[4 + r * 2] : Sm[r * 2];
        x[r][9] = sg ? Sm[5 + r * 2] : Sm[1 + r * 2];
        float m = fmaxf(fmaxf(fmaxf(fmaxf(x[r][0], x[r][1]), fmaxf(x[r][2], x[r][3])), fmaxf(fmaxf(x[r][4], x[r][5]), fmaxf(x[r][6], x[r][7]))), fmaxf(x[r][8], x[r][9]));
        m = fmaxf(m, __shfl_xor_sync(0xffffffffu, m, 1));
        m = fmaxf(m, __shfl_xor_sync(0xffffffffu, m, 2));
        m *= -cs;
#pragma unroll
        for (int i = 0; i < 10; i++) x[r][i] = ex2(fmaf(x[r][i], cs, m));
        float sum = (((x[r][0] + x[r][1]) + (x[r][2] + x[r][3])) + ((x[r][4] + x[r][5]) + (x[r][6] + x[r][7]))) + (x[r][8] + x[r][9]);
        sum += __shfl_xor_sync(0xffffffffu, sum, 1);
        sum += __shfl_xor_sync(0xffffffffu, sum, 2);
        const float inv = rcp(sum);
#pragma unroll
        for (int i = 0; i < 10; i++) x[r][i] *= inv;
    }
#pragma unroll
    for (int ks = 0; ks < 2; ks++)
#pragma unroll
        for (int i = 0; i < 4; i++) {
            const uint32_t p = pack2(x[i & 1][ks * 4 + (i >> 1) * 2], x[i & 1][ks * 4 + (i >> 1) * 2 + 1]);
            pa[ks][i] = sg ? 0u : p;
            pa[2 + ks][i] = sg ? p : 0u;
        }
#pragma unroll
    for (int r = 0; r < 2; r++) {
        const uint32_t p = pack2(x[r][8], x[r][9]);
        pa[4][r] = sg ? 0u : p;
        pa[4][2 + r] = sg ? p : 0u;
    }
}
__device__ __forceinline__ void qa_values(float* O, uint32_t (*pa)[4], Cons& c) {
    wait_full(c);
    const uint32_t st = c.sb + c.p.stage * STAGE;
    const uint64_t dv = mkdesc(st + c.wg * 8192, 16384, 1024, 1), dm = mkdesc(st + 32768 + c.wg * 4096, 2048, 128, 0);
    pin<20>(&pa[0][0]);
    wg_fence();
#pragma unroll
    for (int ks = 0; ks < 4; ks++) wgmma_rs128<1>(O, pa[ks], dv + ks * 128, ks != 0);
    wgmma_rs128<0>(O, pa[4], dm, 1);
    wg_commit();
    pipe_next(c.p);
}
__device__ __forceinline__ void epi_qa(const float* acc, Cons& c, Pend& d, int mb, int nb) {
    uint32_t q[64], pa[2][5][4];
    float S0[32] = {}, M0[8] = {}, S1[32] = {}, M1[8] = {}, O0[64] = {}, O1[64] = {};
    const uint32_t k0 = c.p.stage;
    pack_half(q, acc);
    pin<32>(q); pin<32>(S0); pin<8>(M0);
    qa_scores(S0, M0, q, c);
    pack_half(q + 32, acc + 64);
    pin<32>(q + 32); pin<32>(S1); pin<8>(M1);
    qa_scores(S1, M1, q + 32, c);
    wg_wait<1>();
    pin<32>(S0); pin<8>(M0);
    release(c, k0);
    qa_softmax(pa[0], S0, M0, c);
    wg_wait<0>();
    pin<32>(S1); pin<8>(M1); pin<64>(q);
    release(c, (k0 + 1) & (NSTAGE - 1));
    pin<64>(O0);
    qa_values(O0, pa[0], c);
    qa_softmax(pa[1], S1, M1, c);
    pin<64>(O1);
    qa_values(O1, pa[1], c);
    wg_wait<1>();
    pin<64>(O0); pin<20>(&pa[0][0][0]);
    release(c, (k0 + 2) & (NSTAGE - 1));
    pack_half(d.pk, O0);
    wg_wait<0>();
    pin<64>(O1); pin<20>(&pa[1][0][0]);
    release(c, (k0 + 3) & (NSTAGE - 1));
    pack_half(d.pk + 32, O1);
    d.kind = PEND_KVO; d.row = 4096 + mb * 256 + c.rank * 128 + c.wg * 64; d.col = nb * 256; d.cnt = C_O + mb;
}

__device__ __forceinline__ void epi_op(const float* acc, const Cons& c, Pend& d, int mb, int nb) {
    pack_half(d.pk, acc); pack_half(d.pk + 32, acc + 64);
    d.kind = PEND_OUT; d.row = mb * 256 + c.rank * 128 + c.wg * 64; d.col = 1024 + nb * 256;
}

__device__ __forceinline__ void epi_a2(float* acc, const Params& P, Cons& c, int mb, int col0) {
    const int g = c.lane >> 2, t = c.lane & 3;
    const int row = mb * 256 + (g >> 1) * 64 + (c.rank * 16 + c.wg * 8 + c.wq * 2) * 2 + (g & 1);
    float* o = P.out + (size_t)row * 2048 + col0 + t * 2;
#pragma unroll 1
    for (int hf = P.zero; hf < 2; hf++) {
    wait_full(c);
    const uint32_t st = c.sb + c.p.stage * STAGE, xa = st + (c.wg * 64 + c.wq * 16 + g) * 128 + t * 4 + (g << 4), da = st + 32768 + t * 4;
#pragma unroll
    for (int j = 0; j < 16; j++) {
        const float* a = acc + j * 4;
        const uint32_t ad = (xa ^ ((j & 7) << 4)) + (j >> 3) * 16384;
        const uint32_t x0 = lds32(ad), x1 = lds32(ad + 1024), dv = lds32(da + j * 16);
        const uint32_t u0 = mul_bf2(x0, dv), u1 = mul_bf2(x1, dv);
        st_stream2(o + j * 8, a[0] + bf_lo(u0), a[1] + bf_hi(u0));
        st_stream2(o + 2 * 2048 + j * 8, a[2] + bf_lo(u1), a[3] + bf_hi(u1));
    }
    __syncwarp();
    release(c, c.p.stage);
    pipe_next(c.p);
    o += 128;
#pragma unroll
    for (int i = 0; i < 64; i++) acc[i] = acc[64 + i];
    }
}

#define TSTAMP(i)
__device__ __forceinline__ float2 cmul(float2 a, float2 b) { return make_float2(fmaf(a.x, b.x, -a.y * b.y), fmaf(a.x, b.y, a.y * b.x)); }
__device__ __forceinline__ float2 cfma(float2 a, float2 b, float2 u) { return make_float2(fmaf(a.x, b.x, fmaf(-a.y, b.y, u.x)), fmaf(a.x, b.y, fmaf(a.y, b.x, u.y))); }
__device__ __forceinline__ float4 ssm_coef(float lre, float lim, float logdt) {
    const float dt = __bfloat162float(__float2bfloat16(expf(logdt)));
    const float ea = expf(dt * lre);
    float sn, cn;
    sincosf(dt * lim, &sn, &cn);
    const float br = ea * cn, bi = ea * sn, nr = br - 1.f;
    float cr, ci;
    if (fabsf(lre) >= fabsf(lim)) { const float r = lim / lre, dn = lre + lim * r; cr = (nr + bi * r) / dn; ci = (bi - nr * r) / dn; }
    else { const float r = lre / lim, dn = lre * r + lim; cr = (nr * r + bi) / dn; ci = (bi * r - nr) / dn; }
    return make_float4(br, bi, cr, ci);
}
__device__ __forceinline__ void epi_a1(const float* acc, const Params& P, const Cons& c, Pend& d, int mb, int nb, uint32_t atag) {
    const int t = c.lane & 3;
    const int p = nb * 128 + c.rank * 64 + c.wg * 32 + c.wq * 8 + (c.lane >> 2);
    const float4 cf = __ldcg(&g_coef[p]);
    const float2 lam = make_float2(cf.x, P.swap_ri ? -cf.y : cf.y);
    const float a0 = P.swap_ri ? -2.f * cf.w : 2.f * cf.z, a1 = P.swap_ri ? 2.f * cf.z : -2.f * cf.w;
    const float b0 = P.swap_ri ? -2.f * cf.z : -2.f * cf.w, b1 = P.swap_ri ? -2.f * cf.w : -2.f * cf.z;
    float2 h = make_float2(0.f, 0.f);
#pragma unroll 1
    for (int round = P.zero; round < 2; round++) {
#pragma unroll
        for (int j = 0; j < 32; j++) {
            h = cfma(lam, h, make_float2(acc[j * 4], acc[j * 4 + 2]));
            const float r0 = fmaf(a0, h.x, a1 * h.y), m0 = fmaf(b0, h.x, b1 * h.y);
            h = cfma(lam, h, make_float2(acc[j * 4 + 1], acc[j * 4 + 3]));
            d.pk[j * 2] = pack2(r0, fmaf(a0, h.x, a1 * h.y));
            d.pk[j * 2 + 1] = pack2(m0, fmaf(b0, h.x, b1 * h.y));
        }
        if (round) continue;
        float2 l64 = lam;
#pragma unroll
        for (int i = 0; i < 6; i++) l64 = cmul(l64, l64);
        const float2 l128 = cmul(l64, l64), l256 = cmul(l128, l128);
        float2 o = make_float2(__shfl_up_sync(0xffffffffu, h.x, 1), __shfl_up_sync(0xffffffffu, h.y, 1));
        if (t >= 1) h = cfma(l64, o, h);
        o = make_float2(__shfl_up_sync(0xffffffffu, h.x, 2), __shfl_up_sync(0xffffffffu, h.y, 2));
        if (t >= 2) h = cfma(l128, o, h);
        IP(2)
        if (t == 3) st_relaxed2(&g_agg[mb * 1024 + p], (__float_as_uint(h.x) & ~1u) | atag, __float_as_uint(h.y));
        h = make_float2(__shfl_up_sync(0xffffffffu, h.x, 1), __shfl_up_sync(0xffffffffu, h.y, 1));
        if (t == 0) h = make_float2(0.f, 0.f);
        uint32_t ax[7], ay[7];
        int n = 0;
        while (true) {
            uint32_t bad = 0;
#pragma unroll
            for (int j = 0; j < 7; j++) { ax[j] = atag; ay[j] = 0; ld_relaxed2_if(ax[j], ay[j], &g_agg[j * 1024 + p], j < mb); }
#pragma unroll
            for (int j = 0; j < 7; j++) bad |= ax[j] ^ atag;
            if (tags_ok(bad)) break;
            __nanosleep(2 * POLLNS);
            if (++n > SPIN_LIMIT) spin_fault();
        }
        float2 carry = make_float2(0.f, 0.f);
#pragma unroll
        for (int j = 0; j < 7; j++) if (j < mb) carry = cfma(l256, carry, make_float2(__uint_as_float(ax[j]), __uint_as_float(ay[j])));
        float2 w = (t & 1) ? l64 : make_float2(1.f, 0.f);
        if (t & 2) w = cmul(w, l128);
        h = cfma(w, carry, h);
        IP(3)
    }
    IP(4)
    d.kind = PEND_HT; d.row = nb * 128 + c.rank * 64 + c.wg * 32; d.col = mb * 256; d.cnt = C_HT + mb;
}

__device__ __forceinline__ uint32_t fresh_tid() { uint32_t t; asm volatile("mov.u32 %0, %%tid.x;" : "=r"(t)); return t; }
__device__ __forceinline__ uint32_t acquire_stage(uint32_t sb, Pipe& p, uint32_t bytes) {
    mbar_wait(sb + B_EMPTY + p.stage * 8, p.phase ^ 1);
    mbar_expect_e(sb + B_FULL + p.stage * 8, bytes);
    return p.stage;
}
__device__ __forceinline__ void producer(const Params& P, const uint32_t sb, const int cta, const uint32_t epoch) {
    Pipe p = {0, 0};
    uint32_t resume = 1;
    const uint32_t e1 = epoch + 1;
    const int rank = cta & 1;
    const uint16_t both = 3 << (__shfl_sync(0xffffffffu, cluster_rank(), 0) & ~1u);
    for (int it = ITEM_OFF(cta >> 1); it < ITEM_OFF((cta >> 1) + 1); it++) {
        const int item = ITEM(it), type = (item >> 8) & 7, mb = (item >> 5) & 7, nb = item & 31, half = item >> 12 & 1, hw = item >> 13;
        if (type == T_CHAIN) {
            const int h = cta / 3, role = cta - h * 3;
            uint32_t* flag = &g_cnt(C_FLAG + (role == 2 ? 32 : 0) + h);
            if (role) { wait_count(&g_cnt(C_KV), e1 * 128); fence_async(); }
#pragma unroll 1
            for (int s = 0; s < 64 && role != 0; s++) {
                if (s < 63) {
                    mbar_wait(sb + B_GO, s & 1);
                    tma3d_mc_e(sb + S_KV + (role - 1) * 8192, &P.tm[M_SEG], 0, (role - 1) * 2048 + s * 32, h * 2, sb + B_KVFULL, 7 << ((h & 1) * 3), P.pol[s < 48 ? 8 : 11]);
                    if ((s & 7) == 7) { wait_count(&g_cnt(C_KV + 1 + (s >> 3)), e1 * 128); fence_async(); }
                    tma_prefetch3d_e(&P.tm[M_SEG], 0, (role - 1) * 2048 + s * 32 + 32, h * 2);
                }
                if (s > 0 && ((s & 3) == 0 || s == 63)) {
                    const int i = (s - 1) >> 2;
                    mbar_wait(sb + B_PERS, i & 1);
                    asm volatile("{\n.reg .pred E;\nelect.sync _|E, 0xffffffff;\n@E st.release.gpu.global.u32 [%0], %1;\n}" ::"l"(flag), "r"(epoch * 64 + i * 4 + 4) : "memory");
                }
            }
            if (role == 0) {
                const int lane = threadIdx.x & 31;
                if (lane == 0) mbar_arrive(sb + B_RELM);
#pragma unroll 1
                for (int s = 0; s < 63; s++) {
                    mbar_wait(sb + B_P1, s & 1);
                    if (s > 0) {
                        st_relaxed4(P.xb + xg_buf(s - 1) + h * 2048 + xg_lane(lane), 0, 0, 0, 0);
                        st_relaxed1(P.xb + xg_buf(s - 1) + xg_side(h) + lane * 4, 0);
                        __threadfence();
                    }
                    __syncwarp();
                    if (lane == 0) mbar_arrive(sb + B_RELM);
                }
            }
            if ((threadIdx.x & 31) < M_C1) asm volatile("prefetch.tensormap [%0];" ::"l"(&P.tm[threadIdx.x & 31]) : "memory");
            resume = 0;
            continue;
        }
        const int m0 = mb * 256 + rank * 128;
        if (type <= T_OP) {
            const CUtensorMap* ma = &P.tm[type == T_OP ? (half ? M_OAH : M_OA) : half ? M_BXH : M_BX];
            const CUtensorMap* mw = &P.tm[type == T_OP ? M_WO : type == T_QA ? M_WQ : nb < 16 ? M_WK : M_WV];
            const int nk = type == T_OP ? 64 : 16, nc = (nb & 15) * 4 + rank * 2, ma0 = (type == T_OP ? 4096 : 0) + m0 + hw * 64;
            if (type == T_OP) { wait_count(&g_cnt(C_O + mb), e1 * 64); fence_async(); }
            if (type == T_QA) {
                wait_count(&g_cnt(C_KV + mb), e1 * 128);
                fence_async();
            }
            auto arrived = [&]() {
                const uint32_t t = fresh_tid();
                return __all_sync(0xffffffffu, (int32_t)(ld_acquire(&g_cnt(C_FLAG + (t & 2) * 16 + nb * 2 + (t & 1))) - (epoch * 64 + mb * 8 + rank * 4 + 4)) >= 0);
            };
            bool passed = false;
            mbar_wait(sb + B_RESUME, resume);
#pragma unroll 1
            for (int kt = 0; kt < nk; kt++) {
                if (type == T_QA && kt == 9) passed = arrived();
                const uint32_t st = acquire_stage(sb, p, STAGE - half * 8192), bar = sb + B_FULL + st * 8;
                tma2d_e(sb + st * STAGE + hw * 8192, ma, kt * 64, ma0, bar, P.pol[4 + type]);
                tma3d_mc_e(sb + st * STAGE + 16384 + rank * 16384, mw, 0, kt * 64, nc, bar, both, P.pol[type == T_KV && mb == 7 ? 9 : 11]);
                if (type == T_QA && kt < 8) tma_prefetch2d_e(&P.tm[M_OA], nb * 256 + (kt & 3) * 64, (kt >> 2) * 2048 + m0);
                pipe_next(p);
            }
            if (type == T_QA) {
                for (int n = 0; !passed; n++) { passed = arrived(); if (!passed) __nanosleep(200); if (n > SPIN_LIMIT) spin_fault(); }
                fence_async();
#pragma unroll 1
                for (int e = 0; e < 4; e++) {
                    const uint32_t st = acquire_stage(sb, p, 40960), bar = sb + B_FULL + st * 8, dst = sb + st * STAGE;
                    tma2d_e(dst, &P.tm[M_OA], nb * 256 + (e & 1) * 128, (e >> 1) * 2048 + m0, bar, P.pol[3]);
                    tma2d_e(dst + 16384, &P.tm[M_OA], nb * 256 + (e & 1) * 128 + 64, (e >> 1) * 2048 + m0, bar, P.pol[3]);
                    const uint32_t* src = ((e >> 1) ? g_vmt : g_km) + ((mb * 8 + rank * 4) * 32 + nb * 2 + (e & 1)) * 512;
#pragma unroll 1
                    for (int i = 0; i < 4; i++) bulk_g2s_e(dst + 32768 + i * 2048, src + i * 32 * 512, 2048, bar);
                    pipe_next(p);
                }
            }
        } else if (type == T_A1) {
            wait_count(&g_cnt(C_COEF), e1 * 4);
            l2_prefetch_e(g_coef + nb * 128 + rank * 64, 1024);
            mbar_wait(sb + B_RESUME, resume);
#pragma unroll 1
            for (int kt = 0; kt < 16; kt++) {
                const uint32_t st = acquire_stage(sb, p, STAGE - half * 8192), bar = sb + B_FULL + st * 8;
                tma4d_e(sb + st * STAGE + hw * 8192, &P.tm[half ? M_ABH : M_AB], kt * 64, nb * 16 + rank * 8 + hw * 4, bar);
                tma4d_mc_e(sb + st * STAGE + 16384 + rank * 16384, &P.tm[M_AX], kt * 64, mb * 128 + rank * 16, bar, both);
                pipe_next(p);
            }
        } else {
            wait_count(&g_cnt(C_HT + mb), e1 * 32);
            fence_async();
            mbar_wait(sb + B_RESUME, resume);
#pragma unroll 1
            for (int kt = 0; kt < 32; kt++) {
                const uint32_t st = acquire_stage(sb, p, STAGE - half * 8192), bar = sb + B_FULL + st * 8;
                tma3d_e(sb + st * STAGE + hw * 8192, &P.tm[half ? M_HTH : M_HT], 0, kt * 64, mb * 4 + rank * 2 + hw, bar, P.pol[7]);
                tma2d_mc_e(sb + st * STAGE + 16384 + rank * 16384, &P.tm[M_CRE] + (kt >> 4), (kt & 15) * 64, (nb * 2 + rank) * 128, bar, both);
                pipe_next(p);
            }
#pragma unroll 1
            for (int col = nb * 256; col < (nb + 1) * 256; col += 128) {
                const uint32_t st = acquire_stage(sb, p, 32768 + 256), bar = sb + B_FULL + st * 8;
                tma4d_e(sb + st * STAGE, &P.tm[M_AX], col, mb * 128 + rank * 16, bar);
                tma4d_e(sb + st * STAGE + 16384, &P.tm[M_AX], col + 64, mb * 128 + rank * 16, bar);
                bulk_g2s_e(sb + st * STAGE + 32768, P.Dskip + col, 256, bar);
                pipe_next(p);
            }
        }
    }
}

__device__ __forceinline__ uint32_t fresh_ctaid() { uint32_t t; asm volatile("mov.u32 %0, %%ctaid.x;" : "=r"(t)); return t; }
__device__ __forceinline__ void reset_state(const Params& P, Cons& c, Pend& d, uint32_t sb, bool resumed) {
    const uint32_t t = fresh_tid(), b = fresh_ctaid() + P.cta0;
    const int w = __shfl_sync(0xffffffffu, t >> 5, 0);
    c.sb = sb; c.wg = w >> 2; c.wq = w & 3; c.lane = t & 31;
    c.rank = __shfl_sync(0xffffffffu, b & 1, 0); c.pair = __shfl_sync(0xffffffffu, b >> 1, 0);
    c.rel = mapa(sb + B_EMPTY, cluster_rank() ^ (c.lane & 1));
    c.atag = (ld_acquire(&g_cnt(C_EPOCH)) + 1) & 1;
    c.p.stage = 0; c.p.phase = 0;
    c.nst = resumed && c.pair < NCHAIN;
    d = Pend{};
}
#define PROF_ITEM(i, item)

__global__ void __launch_bounds__(384, 1) fused_kernel(const __grid_constant__ Params P) {
    extern __shared__ __align__(1024) uint8_t smem[];
    const uint32_t sb = smem_u32(smem);
    asm volatile("griddepcontrol.launch_dependents;");
    declare_fence(P.zero);
    const int tid = threadIdx.x, lane = tid & 31;
    const int warp = __shfl_sync(0xffffffffu, tid >> 5, 0);
    const int cta = __shfl_sync(0xffffffffu, blockIdx.x + P.cta0, 0), pair = cta >> 1, rank = cta & 1;
    if (tid == 0) {
        if (sb & 1023) spin_fault();
        for (int i = 0; i < NSTAGE; i++) { mbar_init(sb + B_FULL + i * 8, 1); mbar_init(sb + B_EMPTY + i * 8, 16); }
        mbar_init(sb + B_RESUME, 2);
        mbar_init(sb + B_KVFULL, 1);
        mbar_init(sb + B_GO, 3); mbar_init(sb + B_RED, 8); mbar_init(sb + B_P1, 1); mbar_init(sb + B_PERS, 8); mbar_init(sb + B_INIT, 8); mbar_init(sb + B_INIT2, 8);
        mbar_init(sb + B_READY, 8);
        for (int i = 0; i < 2; i++) { mbar_init(sb + B_SFULL + i * 8, 4); mbar_init(sb + B_SFREE + i * 8, 1); }
        mbar_init(sb + B_RELM, cta % 3 ? 1 : 2); mbar_init(sb + B_X, 9);
        asm volatile("fence.mbarrier_init.release.cluster;" ::: "memory");
        mbar_expect(sb + B_X, 4096);
        sts64(sb + S_EV, 0, 0); sts32(sb + S_RETRY, 0);
    }
    cluster_sync();
    if (warp >= 8) {
        asm volatile("setmaxnreg.dec.sync.aligned.u32 24;");
        if (warp == 8) {
            producer(P, sb, cta, __shfl_sync(0xffffffffu, ld_acquire(&g_cnt(C_EPOCH)), 0));
            asm volatile("barrier.cluster.arrive.relaxed.aligned;\nbarrier.cluster.wait.aligned;" ::: "memory");
        } else if (warp == 9) {
            for (int i = 0; i < P.pd; i++) __nanosleep(1000);
            if (pair < 64) l2_prefetch((const char*)(rank ? P.Wo : P.Wq) + (size_t)(pair * 32 + lane) * 4096, 4096);
            if (pair < NCHAIN) pacer(P, sb, cta, lane, __shfl_sync(0xffffffffu, ld_acquire(&g_cnt(C_EPOCH)), 0));
        } else {
            store_warp(P, sb, warp - 10, cta);
        }
    } else {
        asm volatile("setmaxnreg.inc.sync.aligned.u32 240;");
        Cons c;
        Pend d;
        if (pair < NCHAIN) {
            reset_state(P, c, d, sb, false);
            {
                const int item = ITEM(ITEM_OFF(pair));
                PROF_ITEM(0, item)
                float acc[128];
                mainloop<true>(acc, P, c, d, T_KV, 16);
                ISTAMP(4)
                mbar_wait(sb + B_EMPTY + warp * 20480 / STAGE * 8, 1);
                mbar_wait(sb + B_EMPTY + (warp * 20480 + 20479) / STAGE * 8, 1);
                chain_load(P, sb, cta, warp, lane, 0);
                epi_kv(acc, c, d, (item >> 5) & 7, item & 31);
            }
            ISTAMP(9)
            mbar_wait(sb + B_EMPTY + 3 * 8, 1);
            drain_both(c, d);
            ISTAMP(10)
            uint32_t wr[40][4];
            chain_fetch(P, sb, cta, warp, lane, wr);
            PROF_ITEM(1, T_CHAIN << 8)
            chain_bounds(sb, cta, warp, lane, wr);
            ISTAMP(11)
            const uint32_t epoch = __shfl_sync(0xffffffffu, ld_acquire(&g_cnt(C_EPOCH)), 0);
            if (warp < 4) chain_role<false>(P, sb, cta, warp, lane, epoch, wr);
            else chain_role<true>(P, sb, cta, warp, lane, epoch, wr);
            fence_async_smem();
            bar_sync(1, 256);
            const uint32_t t2 = fresh_tid();
            if (t2 < 2) mbar_arrive_cluster(mapa(sb + B_RESUME, cluster_rank() ^ t2));
        } else if (pair >= NPAIR - 2) {
            const int ch = (pair - (NPAIR - 2)) * 512 + rank * 256 + tid;
            g_coef[ch] = ssm_coef(__bfloat162float(P.Lre[ch]), __bfloat162float(P.Lim[ch]), __bfloat162float(P.logdt[ch]));
            bar_sync(1, 256);
            if (tid == 0) red_release(&g_cnt(C_COEF));
        }
        reset_state(P, c, d, sb, true);
        int it = ITEM_OFF(c.pair) + (c.pair < NCHAIN ? 2 : 0);
        const int end = ITEM_OFF(c.pair + 1);
        for (;; it++) {
            const bool last = it == end;
            const int item = ITEM(it), type = (item >> 8) & 7, mb = (item >> 5) & 7, nb = item & 31;
            const bool idle = (item >> 12) == 3 - 2 * c.wg;
            if (d.kind != PEND_NONE && (last || idle || (ITEM(it - 1) & URGENT) || !bar_and(5 + c.wg, mbar_try(sb + B_FULL + c.p.stage * 8, c.p.phase)))) {
#pragma unroll 1
                while (d.kind != PEND_NONE) drain(P, c, d);
            }
            if (last) break;
            const int nk = type == T_OP ? 64 : type == T_A2 ? 32 : 16;
            PROF_ITEM(it - ITEM_OFF(c.pair), item)
            if (idle) {
#pragma unroll 1
                for (int kt = nk + (type == T_A2 ? 2 : type == T_QA ? 4 : 0); kt > 0; kt--) { wait_full(c); release(c, c.p.stage); pipe_next(c.p); }
                continue;
            }
            float acc[128];
            mainloop(acc, P, c, d, type, nk);
            if (type == T_KV) epi_kv(acc, c, d, mb, nb);
            else if (type == T_QA) epi_qa(acc, c, d, mb, nb);
            else if (type == T_OP) epi_op(acc, c, d, mb, nb);
            else if (type == T_A1) epi_a1(acc, P, c, d, mb, nb, c.atag);
            else epi_a2(acc, P, c, mb, nb * 256);
        }
        staging_wait(c);
        staging_post(c, PEND_NONE, 0, 0, 0);
        cluster_sync();
        if (c.wg == 0 && c.wq == 0 && c.lane == 0 && atomicInc(&g_cnt(C_DONE), NPAIR * 2 - 1) == NPAIR * 2 - 1) { __threadfence(); atomicAdd(&g_cnt(C_EPOCH), 1); }
    }
}

typedef CUresult (*EncodeFn)(CUtensorMap*, CUtensorMapDataType, cuuint32_t, void*, const cuuint64_t*, const cuuint64_t*, const cuuint32_t*, const cuuint32_t*,
                             CUtensorMapInterleave, CUtensorMapSwizzle, CUtensorMapL2promotion, CUtensorMapFloatOOBfill);
void encode(EncodeFn fn, CUtensorMap* m, const void* base, int rank, const uint64_t* dims, const uint64_t* strides, const uint32_t* box, CUtensorMapSwizzle swz = CU_TENSOR_MAP_SWIZZLE_128B) {
    cuuint64_t d[5], s[5]; cuuint32_t b[5], e[5];
    for (int i = 0; i < rank; i++) { d[i] = dims[i]; b[i] = box[i]; e[i] = 1; if (i) s[i - 1] = strides[i - 1]; }
    fn(m, CU_TENSOR_MAP_DATA_TYPE_BFLOAT16, rank, (void*)base, d, s, b, e, CU_TENSOR_MAP_INTERLEAVE_NONE, swz,
       CU_TENSOR_MAP_L2_PROMOTION_L2_256B, CU_TENSOR_MAP_FLOAT_OOB_FILL_NONE);
}
void map_kmajor(EncodeFn fn, CUtensorMap* m, const void* base, uint64_t rows, uint64_t cols, uint32_t box_rows) {
    const uint64_t d[2] = {cols, rows}, s[1] = {cols * 2}; const uint32_t b[2] = {64, box_rows};
    encode(fn, m, base, 2, d, s, b);
}
void map_mnmajor(EncodeFn fn, CUtensorMap* m, const void* base, uint64_t krows, uint64_t cols, uint32_t groups = 2) {
    const uint64_t d[3] = {64, krows, cols / 64}, s[2] = {cols * 2, 128}; const uint32_t b[3] = {64, 64, groups};
    encode(fn, m, base, 3, d, s, b);
}

}

extern "C" void kernel_launch(void* const* d_in, const int* in_sizes, int n_in, void* d_out, int out_size) {
    static Params P;
    static EncodeFn fn = nullptr;
    if (!fn) {
        cudaDriverEntryPointQueryResult q;
        cudaGetDriverEntryPoint("cuTensorMapEncodeTiled", (void**)&fn, cudaEnableDefault, &q);
        cudaFuncSetAttribute(fused_kernel, cudaFuncAttributeMaxDynamicSharedMemorySize, S_TOTAL);
    }
    const bf16* in[15];
    for (int i = 0; i < 15; i++) in[i] = (const bf16*)d_in[i];
    void *kvo, *ht;
    cudaGetSymbolAddress(&kvo, g_kvo);
    cudaGetSymbolAddress(&ht, g_ht);
    map_kmajor(fn, &P.tm[M_BX], in[9], 2048, 1024, 128);
    map_mnmajor(fn, &P.tm[M_WQ], in[11], 1024, 4096);
    map_mnmajor(fn, &P.tm[M_WK], in[12], 1024, 4096);
    map_mnmajor(fn, &P.tm[M_WV], in[13], 1024, 4096);
    map_mnmajor(fn, &P.tm[M_WO], in[14], 4096, 1024);
    map_kmajor(fn, &P.tm[M_OA], kvo, 3 * 2048, 4096, 128);
    P.swap_ri = in[4] < in[3];
    {
        const bf16* lo = P.swap_ri ? in[4] : in[3];
        const uint64_t diff = (uint64_t)((const char*)(P.swap_ri ? in[3] : in[4]) - (const char*)lo);
        const uint64_t d[4] = {1024, 8, 2, 128}, s[3] = {2048, diff, 16384}; const uint32_t b[4] = {64, 8, 2, 8}, bh[4] = {64, 8, 2, 4};
        encode(fn, &P.tm[M_AB], lo, 4, d, s, b);
        encode(fn, &P.tm[M_ABH], lo, 4, d, s, bh);
    }
    {
        const uint64_t d[4] = {1024, 2, 4, 1024}, s[3] = {2048, 64 * 2048, 4096}; const uint32_t b[4] = {64, 2, 4, 16};
        encode(fn, &P.tm[M_AX], in[0], 4, d, s, b);
    }
    map_mnmajor(fn, &P.tm[M_HT], ht, 2048, 2048);
    map_kmajor(fn, &P.tm[M_CRE], in[5], 1024, 1024, 128);
    map_kmajor(fn, &P.tm[M_CIM], in[6], 1024, 1024, 128);
    map_kmajor(fn, &P.tm[M_KVO], kvo, 3 * 2048, 4096, 32);
    map_kmajor(fn, &P.tm[M_HTS], ht, 2048, 2048, 32);
    map_kmajor(fn, &P.tm[M_BXH], in[9], 2048, 1024, 64);
    map_kmajor(fn, &P.tm[M_OAH], kvo, 3 * 2048, 4096, 64);
    map_mnmajor(fn, &P.tm[M_HTH], ht, 2048, 2048, 1);
    for (int i = 0; i < 3; i++) {
        const uint64_t d[3] = {64, 1024, 64}, s[2] = {8192, 128}; const uint32_t b[3] = {64, 16, 2};
        encode(fn, &P.tm[M_C1 + i], in[11 + i], 3, d, s, b);
    }
    {
        const uint64_t d[2] = {1024, 4096}, s[1] = {2048}; const uint32_t b[2] = {32, 32};
        encode(fn, &P.tm[M_CO], in[14], 2, d, s, b, CU_TENSOR_MAP_SWIZZLE_64B);
    }
    {
        const uint64_t d[3] = {64, 3 * 2048, 64}, s[2] = {8192, 128}; const uint32_t b[3] = {64, 32, 2};
        encode(fn, &P.tm[M_SEG], kvo, 3, d, s, b);
    }
    void* xs;
    cudaGetSymbolAddress(&xs, g_x);
    P.xb = (uint8_t*)(((uintptr_t)xs + (2u << 20) - 1) & ~(uintptr_t)((2u << 20) - 1));
    P.Wq = in[11]; P.Wk = in[12]; P.Wv = in[13]; P.Wo = in[14]; P.mem0 = in[10]; P.Bx = in[9];
    P.Ax = in[0]; P.Lre = in[1]; P.Lim = in[2]; P.logdt = in[7]; P.Dskip = in[8];
    P.out = (float*)d_out;
    int pv[10] = {1300, 0, 110, 0, 330, 0, 32, 32, 6, 0};
    int ef = 779;
    for (int i = 0; i < 12; i++) P.pol[i] = (ef >> i & 1) ? 0x12F0000000000000ull : 0x1000000000000000ull;
    P.dly = pv[0]; P.mrg = pv[2];
    P.rd = pv[4]; P.guard = pv[5]; P.clampv = pv[6]; P.clamp0 = pv[7]; P.kvd = pv[9]; P.xd = pv[8]; P.pd = pv[1];
    cudaLaunchConfig_t cfg = {};
    cudaLaunchAttribute at[2];
    cfg.blockDim = dim3(384); cfg.dynamicSmemBytes = S_TOTAL; cfg.stream = cudaStreamPerThread; cfg.attrs = at;
    at[0].id = cudaLaunchAttributeClusterDimension;
    at[0].val.clusterDim.y = at[0].val.clusterDim.z = 1;
    at[1].id = cudaLaunchAttributeProgrammaticStreamSerialization;
    at[1].val.programmaticStreamSerializationAllowed = 1;
    for (int i = 0; i < 2; i++) {
        P.cta0 = i ? 2 * NCHAIN : 0;
        cfg.gridDim = dim3(i ? 2 * (NPAIR - NCHAIN) : 2 * NCHAIN);
        at[0].val.clusterDim.x = i ? 2 : 6;
        cfg.numAttrs = 1 + i;
        cudaLaunchKernelEx(&cfg, fused_kernel, P);
    }
}
```

```cpp
#include <cuda_runtime.h>
#include <cuda_bf16.h>
#include <cuda.h>
#include <stdint.h>
#include <string.h>

typedef __nv_bfloat16 bf16;

namespace {

constexpr int SPIN_LIMIT = 1 << 22;
#define POLLNS 100
constexpr int NPAIR = 66;
constexpr int NCHAIN = 48;
enum { T_KV = 0, T_QA = 1, T_OP = 2, T_A1 = 3, T_A2 = 4, T_CHAIN = 5 };
constexpr int URGENT = 2048;
constexpr int HALF = 4096;
enum { M_BX = 1, M_OA, M_AB, M_HT, M_HALF = 4, M_WK = 9, M_WV, M_WQ, M_WO, M_AX, M_CRE, M_CIM, M_KVO, M_HTS, M_C1, M_CO = M_C1 + 3, M_SEG, M_COUNT };
enum { C_KV = 0, C_O = 8, C_HT = 16, C_DONE = 24, C_EPOCH = 25, C_COEF = 26, C_XMAX = 27, C_XCNT = 28, C_FLAG = 32 };

struct Params {
    CUtensorMap tm[M_COUNT];
    const bf16 *Wq, *Wk, *Wv, *Wo, *mem0, *Bx, *Ax, *Lre, *Lim, *logdt, *Dskip;
    float* out;
    uint8_t* xb;
    int swap_ri, zero;
    int dly, mrg, rd, guard, clampv, clamp0, kvd, xd, pd;
    uint64_t pol[12];
    uint16_t cta0;
};

__constant__ uint16_t c_off[67] = {0, 4, 8, 13, 18, 23, 27, 31, 35, 39, 43, 48, 53, 57, 61, 65, 70, 75, 80, 84, 88, 92, 97, 102, 106, 111, 116, 121, 125, 130, 135, 139, 143, 148, 153, 157, 162, 166, 171, 175, 180, 184, 189, 193, 198, 202, 206, 210, 214, 234, 252, 271, 291, 311, 331, 351, 371, 391, 411, 431, 451, 471, 490, 510, 529, 547, 565};
__constant__ uint16_t c_items[640] = {
    0, 1280, 2822, 515, 16, 1280, 865, 704, 32, 1280, 775, 2980, 1251, 1, 1280, 2435, 960, 1123, 17, 1280, 2508, 2944, 1027, 33,
    1280, 483, 578, 2, 1280, 2440, 513, 18, 1280, 2528, 512, 34, 1280, 451, 610, 3, 1280, 2505, 514, 19, 1280, 833, 3009, 1089,
    35, 1280, 2887, 2945, 1090, 4, 1280, 490, 546, 20, 1280, 461, 738, 36, 1280, 2535, 545, 5, 1280, 2502, 3014, 1185, 21, 1280,
    800, 2916, 1122, 37, 1280, 771, 2983, 1025, 6, 1280, 396, 609, 22, 1280, 453, 675, 38, 1280, 2500, 608, 7, 1280, 2445, 870,
    12993, 23, 1280, 2506, 962, 1184, 39, 1280, 2541, 706, 8, 1280, 802, 2886, 1088, 24, 1280, 2816, 2948, 1026, 40, 1280, 2818, 864,
    1056, 9, 1280, 834, 672, 25, 1280, 807, 867, 1216, 41, 1280, 801, 967, 1091, 10, 1280, 385, 643, 26, 1280, 2504, 641, 42,
    1280, 2532, 963, 12867, 11, 1280, 2447, 2979, 4675, 27, 1280, 2536, 544, 43, 1280, 2507, 2949, 1186, 12, 1280, 2540, 736, 28, 1280,
    2919, 2950, 1057, 44, 1280, 769, 737, 13, 1280, 449, 2884, 1121, 29, 1280, 2533, 577, 45, 1280, 2537, 804, 1249, 14, 1280, 2542,
    673, 30, 1280, 2539, 2947, 1155, 46, 1280, 2510, 576, 15, 1280, 486, 707, 31, 1280, 2498, 640, 47, 1280, 2529, 642, 48, 66,
    84, 102, 256, 124, 142, 160, 175, 191, 207, 224, 239, 298, 418, 359, 448, 903, 3042, 1217, 49, 67, 85, 103, 257, 125,
    143, 161, 176, 192, 208, 225, 240, 299, 352, 425, 360, 674, 50, 68, 86, 104, 258, 126, 144, 162, 177, 193, 209, 226,
    241, 300, 2411, 2478, 2439, 934, 1152, 51, 69, 87, 105, 259, 127, 145, 163, 178, 194, 210, 227, 242, 301, 4489, 419, 364,
    832, 2981, 1024, 52, 70, 88, 106, 260, 128, 146, 164, 179, 195, 211, 228, 243, 302, 421, 362, 12715, 805, 3013, 1059, 53,
    71, 89, 107, 261, 129, 147, 165, 180, 196, 212, 229, 244, 303, 333, 365, 361, 806, 3041, 1187, 54, 72, 90, 108, 262,
    130, 148, 166, 181, 197, 213, 230, 245, 320, 366, 331, 431, 869, 3046, 1250, 55, 73, 91, 109, 263, 131, 149, 167, 182,
    198, 214, 231, 246, 321, 356, 429, 398, 4869, 2976, 1154, 56, 74, 92, 110, 264, 132, 150, 168, 183, 199, 215, 232, 247,
    322, 388, 334, 463, 837, 3047, 1219, 57, 75, 93, 111, 265, 133, 151, 169, 184, 200, 216, 233, 248, 323, 394, 424, 482,
    803, 3040, 1153, 58, 76, 94, 112, 266, 134, 152, 170, 185, 201, 217, 234, 249, 324, 358, 455, 426, 898, 3044, 1120, 59,
    77, 95, 113, 267, 135, 153, 171, 186, 202, 218, 235, 250, 325, 4523, 384, 423, 772, 2977, 1058, 60, 78, 96, 114, 268,
    136, 154, 172, 187, 203, 219, 236, 251, 326, 330, 367, 355, 930, 995, 1218, 61, 79, 97, 115, 269, 137, 155, 173, 188,
    204, 220, 237, 252, 327, 332, 416, 389, 13061, 739, 62, 80, 98, 116, 270, 138, 156, 174, 189, 205, 221, 238, 253, 328,
    395, 390, 386, 835, 3045, 1248, 63, 81, 99, 117, 271, 139, 157, 288, 190, 292, 293, 296, 297, 2468, 12681, 428, 866, 3012,
    4801, 64, 82, 100, 118, 120, 122, 140, 158, 289, 206, 222, 294, 254, 329, 417, 2405, 2401, 611, 65, 83, 101, 119, 121,
    123, 141, 159, 290, 291, 223, 295, 255, 354, 335, 422, 495, 547,
};
#define ITEM_OFF(p) c_off[p]
#define ITEM(i) c_items[i]

__device__ __align__(1024) bf16 g_kvo[3 * 2048 * 4096];
__device__ __align__(1024) bf16 g_ht[2048 * 2048];
__device__ __align__(1024) uint8_t g_x[4 << 20];
__device__ __align__(1024) uint32_t g_km[64 * 32 * 512];
__device__ __align__(1024) uint32_t g_vmt[64 * 32 * 512];
__device__ __align__(1024) float2 g_agg[8 * 1024];
__device__ __align__(1024) float4 g_coef[1024];
__device__ __align__(1024) uint32_t g_cntl[128 * 32];
#define g_cnt(i) g_cntl[(i) * 32]
__device__ __align__(1024) uint32_t g_hint[96 * 32];
#define PROF(i)
#define PROFDUMP()
#define PROFP(i)
constexpr int XG_SIDE = 65536, XG_T = 98304;
__device__ __forceinline__ uint32_t xg_buf(int b) { return (b & 1) * 128 + (b & 2) * 256 + (b & 4) * 32768; }
__device__ __forceinline__ uint32_t xg_lane(uint32_t lane) { return (lane >> 4) * 1024 + (lane & 8) * 32 + (lane & 7) * 16; }
__device__ __forceinline__ uint32_t xg_side(int b) { return XG_SIDE + (b >> 1) * 1024 + (b & 1) * 256; }

constexpr int STAGE = 49152, NSTAGE = 4;
constexpr int S_STG = NSTAGE * STAGE;
constexpr int S_BAR = S_STG + 32768;
constexpr int B_FULL = S_BAR, B_EMPTY = S_BAR + 32, B_RESUME = S_BAR + 64, B_KVFULL = S_BAR + 72, B_GO = S_BAR + 88, B_X = S_BAR + 96, B_PERS = S_BAR + 104,
              B_INIT = S_BAR + 112, B_RELM = S_BAR + 120, B_READY = S_BAR + 136, B_SFULL = S_BAR + 144, B_SFREE = S_BAR + 160, S_DESC = S_BAR + 176, B_RED = S_BAR + 216;
constexpr int S_EV = S_BAR + 80, S_EO = S_BAR + 84, B_INIT2 = S_BAR + 128, S_SC = S_BAR + 208, S_ISC = S_EV;
constexpr int S_XV = S_BAR + 256, S_LOG = S_XV + 2048;
constexpr int S_TOTAL = S_LOG + 768;
#define NRA 5
#define NRB 3
constexpr int S_W1 = 0;
constexpr int S_W2 = 4 * 4096 * (16 - NRA - NRB);
constexpr int S_KV = 188416;
constexpr int S_P1 = S_KV + 16384;
constexpr int S_X = S_P1 + 16384;
constexpr int S_SX = S_P1, S_OX = S_P1 + 2048;
constexpr int S_EM = S_X + 4096, S_TO = S_EM + 32, B_DONE = S_BAR + 224, B_P1 = S_BAR + 232;
static_assert(S_TO + 32 <= S_BAR && S_KV % 1024 == 0 && S_TOTAL <= 232448, "chain smem layout");

template <int V> struct IC { static constexpr int value = V; };
template <int B, int E, typename F> __device__ __forceinline__ void static_for(F&& f) { if constexpr (B < E) { f(IC<B>{}); static_for<B + 1, E>(f); } }
__device__ __forceinline__ uint32_t cluster_rank() { uint32_t r; asm volatile("mov.u32 %0, %%cluster_ctarank;" : "=r"(r)); return r; }
__device__ __forceinline__ void spin_fault() { asm volatile("st.global.u32 [%0], 0;" ::"l"(0ull) : "memory"); }
__device__ __forceinline__ uint32_t smem_u32(const void* p) { return (uint32_t)__cvta_generic_to_shared(p); }
__device__ __forceinline__ uint32_t opq(uint32_t x, int lane) { return __shfl_sync(0xffffffffu, x, lane); }
__device__ __forceinline__ uint32_t mapa(uint32_t a, uint32_t r) { uint32_t d; asm volatile("mapa.shared::cluster.u32 %0, %1, %2;" : "=r"(d) : "r"(a), "r"(r)); return d; }
__device__ __forceinline__ void mma16816(float* d, uint32_t a0, uint32_t a1, uint32_t a2, uint32_t a3, uint32_t b0, uint32_t b1) {
    asm("mma.sync.aligned.m16n8k16.row.col.f32.bf16.bf16.f32 {%0,%1,%2,%3}, {%4,%5,%6,%7}, {%8,%9}, {%0,%1,%2,%3};"
        : "+f"(d[0]), "+f"(d[1]), "+f"(d[2]), "+f"(d[3]) : "r"(a0), "r"(a1), "r"(a2), "r"(a3), "r"(b0), "r"(b1));
}
__device__ __forceinline__ void mma1688(float* d, uint32_t a0, uint32_t a1, uint32_t b0) {
    asm("mma.sync.aligned.m16n8k8.row.col.f32.bf16.bf16.f32 {%0,%1,%2,%3}, {%4,%5}, {%6}, {%0,%1,%2,%3};"
        : "+f"(d[0]), "+f"(d[1]), "+f"(d[2]), "+f"(d[3]) : "r"(a0), "r"(a1), "r"(b0));
}
__device__ __forceinline__ void ldsm4(uint32_t* r, uint32_t a) {
    asm volatile("ldmatrix.sync.aligned.m8n8.x4.shared.b16 {%0,%1,%2,%3}, [%4];" : "=r"(r[0]), "=r"(r[1]), "=r"(r[2]), "=r"(r[3]) : "r"(a));
}
__device__ __forceinline__ void ldsm4t(uint32_t* r, uint32_t a) {
    asm volatile("ldmatrix.sync.aligned.m8n8.x4.trans.shared.b16 {%0,%1,%2,%3}, [%4];" : "=r"(r[0]), "=r"(r[1]), "=r"(r[2]), "=r"(r[3]) : "r"(a));
}
__device__ __forceinline__ void stsm4(uint32_t a, uint32_t r0, uint32_t r1, uint32_t r2, uint32_t r3) {
    asm volatile("stmatrix.sync.aligned.m8n8.x4.shared.b16 [%0], {%1,%2,%3,%4};" ::"r"(a), "r"(r0), "r"(r1), "r"(r2), "r"(r3) : "memory");
}
__device__ __forceinline__ void stsm4t(uint32_t a, uint32_t r0, uint32_t r1, uint32_t r2, uint32_t r3) {
    asm volatile("stmatrix.sync.aligned.m8n8.x4.trans.shared.b16 [%0], {%1,%2,%3,%4};" ::"r"(a), "r"(r0), "r"(r1), "r"(r2), "r"(r3) : "memory");
}
__device__ __forceinline__ uint32_t movm(uint32_t a) { uint32_t d; asm volatile("movmatrix.sync.aligned.m8n8.trans.b16 %0, %1;" : "=r"(d) : "r"(a)); return d; }
__device__ __forceinline__ uint32_t pack2(float lo, float hi) { uint32_t d; asm("cvt.rn.bf16x2.f32 %0, %1, %2;" : "=r"(d) : "f"(hi), "f"(lo)); return d; }
__device__ __forceinline__ uint32_t prmt(uint32_t a, uint32_t b, uint32_t s) { uint32_t d; asm("prmt.b32 %0, %1, %2, %3;" : "=r"(d) : "r"(a), "r"(b), "r"(s)); return d; }
__device__ __forceinline__ uint32_t pack2h(float lo, float hi) { uint32_t d; asm("cvt.rn.f16x2.f32 %0, %1, %2;" : "=r"(d) : "f"(hi), "f"(lo)); return d; }
__device__ __forceinline__ uint32_t h2bf(uint32_t a, uint32_t b) {
    uint32_t d;
    asm("{\n.reg .b16 l, h, u;\n.reg .f32 x, y;\nmov.b32 {l, u}, %1;\ncvt.f32.f16 x, l;\nmov.b32 {u, h}, %2;\ncvt.f32.f16 y, h;\ncvt.rn.bf16x2.f32 %0, y, x;\n}" : "=r"(d) : "r"(a), "r"(b));
    return d;
}
__device__ __forceinline__ void cvt_block(uint32_t* u, uint32_t& x, uint32_t sel) {
    const uint32_t a = prmt(u[0], u[0], sel), b = prmt(u[1], u[1], sel), c = prmt(u[2], u[2], sel), d = prmt(u[3], x, sel);
    x ^= u[3] ^ d;
    u[0] = h2bf(a, a); u[1] = h2bf(b, b); u[2] = h2bf(c, c); u[3] = h2bf(d, d);
}
__device__ __forceinline__ uint32_t amax(uint32_t a, uint32_t b) { uint32_t d; asm("max.xorsign.abs.bf16x2 %0, %1, %2;" : "=r"(d) : "r"(a), "r"(b)); return d; }
__device__ __forceinline__ uint32_t amax4(uint32_t m, const uint32_t* v) { return amax(amax(m, amax(v[0], v[1])), amax(v[2], v[3])); }
__device__ __forceinline__ uint32_t warp_exp(uint32_t m) { return __reduce_max_sync(0xffffffffu, max(m & 0x7f80u, (m >> 16) & 0x7f80u)) >> 7; }
__device__ __forceinline__ void red_max_shared(uint32_t a, uint32_t x) { asm volatile("red.shared.max.u32 [%0], %1;" ::"r"(a), "r"(x) : "memory"); }
__device__ __forceinline__ uint32_t mul_bf2(uint32_t a, uint32_t b) { uint32_t d; asm("mul.rn.bf16x2 %0, %1, %2;" : "=r"(d) : "r"(a), "r"(b)); return d; }
__device__ __forceinline__ float bf_lo(uint32_t u) { return __uint_as_float(u << 16); }
__device__ __forceinline__ float bf_hi(uint32_t u) { return __uint_as_float(u & 0xffff0000u); }
__device__ __forceinline__ float ex2(float x) { float y; asm("ex2.approx.ftz.f32 %0, %1;" : "=f"(y) : "f"(x)); return y; }
__device__ __forceinline__ float rcp(float x) { float y; asm("rcp.approx.ftz.f32 %0, %1;" : "=f"(y) : "f"(x)); return y; }
__device__ __forceinline__ void st_relaxed4(const void* p, uint32_t a, uint32_t b, uint32_t c, uint32_t d) {
    asm volatile("{\n.reg .b128 t;\nmov.b128 t, {%1,%2,%3,%4};\nst.relaxed.gpu.global.b128 [%0], t;\n}" ::"l"(p), "r"(a), "r"(b), "r"(c), "r"(d) : "memory");
}
__device__ __forceinline__ void st_relaxed2(const void* p, uint32_t a, uint32_t b) {
    asm volatile("{\n.reg .b64 t;\nmov.b64 t, {%1,%2};\nst.relaxed.gpu.global.b64 [%0], t;\n}" ::"l"(p), "r"(a), "r"(b) : "memory");
}
__device__ __forceinline__ void ld_relaxed2_if(uint32_t& a, uint32_t& b, const void* p, bool on) {
    asm volatile("{\n.reg .pred P;\n.reg .b64 t;\nsetp.ne.u32 P, %3, 0;\nmov.b64 t, {%0,%1};\n@P ld.relaxed.gpu.global.b64 t, [%2];\nmov.b64 {%0,%1}, t;\n}" : "+r"(a), "+r"(b) : "l"(p), "r"((uint32_t)on) : "memory");
}
__device__ __forceinline__ void ld_relaxed4(uint32_t* v, const void* p) {
    asm volatile("ld.relaxed.gpu.global.L1::no_allocate.v4.b32 {%0,%1,%2,%3}, [%4];" : "=r"(v[0]), "=r"(v[1]), "=r"(v[2]), "=r"(v[3]) : "l"(p) : "memory");
}
__device__ __forceinline__ void ld_relaxed1n(uint32_t& v, const void* p) { asm volatile("ld.relaxed.gpu.global.L1::no_allocate.b32 %0, [%1];" : "=r"(v) : "l"(p) : "memory"); }
__device__ __forceinline__ void red_add4(const void* p, uint32_t a, uint32_t b, uint32_t c, uint32_t d) {
    asm volatile("red.relaxed.gpu.global.add.noftz.v4.f16x2 [%0], {%1,%2,%3,%4};" ::"l"(p), "r"(a), "r"(b), "r"(c), "r"(d) : "memory");
}
__device__ __forceinline__ void red_add1(const void* p, uint32_t a) { asm volatile("red.relaxed.gpu.global.add.noftz.f16x2 [%0], %1;" ::"l"(p), "r"(a) : "memory"); }
__device__ __forceinline__ void ld_relaxed2(uint32_t* v, const void* p) {
    asm volatile("{\n.reg .b64 t;\nld.relaxed.gpu.global.L1::no_allocate.b64 t, [%2];\nmov.b64 {%0,%1}, t;\n}" : "=r"(v[0]), "=r"(v[1]) : "l"(p) : "memory");
}
__device__ __forceinline__ uint32_t ld_relaxed1(const void* p) { uint32_t v; asm volatile("ld.relaxed.gpu.global.u32 %0, [%1];" : "=r"(v) : "l"(p) : "memory"); return v; }
__device__ __forceinline__ void st_relaxed1(const void* p, uint32_t v) { asm volatile("st.relaxed.gpu.global.u32 [%0], %1;" ::"l"(p), "r"(v) : "memory"); }
__device__ __forceinline__ uint32_t ld_acquire(const void* p) { uint32_t v; asm volatile("ld.acquire.gpu.global.u32 %0, [%1];" : "=r"(v) : "l"(p) : "memory"); return v; }
__device__ __forceinline__ void red_relaxed(void* p) { asm volatile("red.relaxed.gpu.global.add.u32 [%0], 1;" ::"l"(p) : "memory"); }
__device__ __forceinline__ void red_release(void* p) { asm volatile("red.release.gpu.global.add.u32 [%0], 1;" ::"l"(p) : "memory"); }
__device__ __forceinline__ void st_stream2(float* p, float a, float b) { asm volatile("st.global.cs.v2.f32 [%0], {%1, %2};" ::"l"(p), "f"(a), "f"(b) : "memory"); }
__device__ __forceinline__ void fence_async() { asm volatile("fence.proxy.async.global;" ::: "memory"); }
__device__ __forceinline__ void fence_async_smem() { asm volatile("fence.proxy.async.shared::cta;" ::: "memory"); }
__device__ __forceinline__ void wait_count(const uint32_t* p, uint32_t target) {
    while ((int32_t)(ld_acquire(p) - target) < 0) __nanosleep(POLLNS);
}
__device__ __forceinline__ void bar_sync(int id, int n) { asm volatile("bar.sync %0, %1;" ::"r"(id), "r"(n) : "memory"); }
__device__ __forceinline__ bool bar_and(int id, bool v) {
    uint32_t r;
    asm volatile("{\n.reg .pred P, Q;\nsetp.ne.u32 Q, %2, 0;\nbar.red.and.pred P, %1, 128, Q;\nselp.u32 %0, 1, 0, P;\n}" : "=r"(r) : "r"(id), "r"((uint32_t)v) : "memory");
    return r;
}
__device__ __forceinline__ void bar_arrive(int id, int n) { asm volatile("bar.arrive %0, %1;" ::"r"(id), "r"(n) : "memory"); }
__device__ __forceinline__ void lds128(uint32_t* v, uint32_t a) { asm volatile("ld.shared.v4.b32 {%0,%1,%2,%3}, [%4];" : "=r"(v[0]), "=r"(v[1]), "=r"(v[2]), "=r"(v[3]) : "r"(a) : "memory"); }
__device__ __forceinline__ uint32_t lds32(uint32_t a) { uint32_t v; asm volatile("ld.shared.b32 %0, [%1];" : "=r"(v) : "r"(a) : "memory"); return v; }
__device__ __forceinline__ void lds64(uint32_t* v, uint32_t a) { asm volatile("ld.shared.v2.b32 {%0,%1}, [%2];" : "=r"(v[0]), "=r"(v[1]) : "r"(a) : "memory"); }
__device__ __forceinline__ void lds64f(float* v, uint32_t a) { asm volatile("ld.shared.v2.f32 {%0,%1}, [%2];" : "=f"(v[0]), "=f"(v[1]) : "r"(a) : "memory"); }
__device__ __forceinline__ void sts128(uint32_t a, const uint32_t* v) { asm volatile("st.shared.v4.b32 [%0], {%1,%2,%3,%4};" ::"r"(a), "r"(v[0]), "r"(v[1]), "r"(v[2]), "r"(v[3]) : "memory"); }
__device__ __forceinline__ void sts64(uint32_t a, uint32_t x, uint32_t y) { asm volatile("st.shared.v2.b32 [%0], {%1,%2};" ::"r"(a), "r"(x), "r"(y) : "memory"); }
__device__ __forceinline__ void sts32(uint32_t a, uint32_t x) { asm volatile("st.shared.b32 [%0], %1;" ::"r"(a), "r"(x) : "memory"); }
__device__ __forceinline__ bool mbar_try(uint32_t b, uint32_t par) {
    uint32_t ok;
    asm volatile("{\n.reg .pred P;\nmbarrier.test_wait.parity.shared::cta.b64 P, [%1], %2;\nselp.u32 %0, 1, 0, P;\n}" : "=r"(ok) : "r"(b), "r"(par) : "memory");
    return ok;
}
__device__ __forceinline__ void mbar_wait(uint32_t b, uint32_t par) {
    asm volatile("{\n.reg .pred P;\nW: mbarrier.try_wait.parity.shared::cta.b64 P, [%0], %1;\n@!P bra W;\n}" ::"r"(b), "r"(par) : "memory");
}
__device__ __forceinline__ void mbar_wait_bounded(uint32_t b, uint32_t par) {
    asm volatile("{\n.reg .pred P, Q;\n.reg .u32 t, u;\nmov.u32 t, %%globaltimer_lo;\nW: mbarrier.try_wait.parity.shared::cta.b64 P, [%0], %1;\n"
                 "mov.u32 u, %%globaltimer_lo;\nsub.u32 u, u, t;\nsetp.gt.u32 Q, u, 2000000000;\n@Q st.global.u32 [%2], 0;\n@!P bra W;\n}" ::"r"(b), "r"(par), "l"(0ull) : "memory");
}
__device__ __forceinline__ void declare_fence(int zero) { asm volatile(".reg .pred PNEVER;\nsetp.ne.u32 PNEVER, %0, 0;" ::"r"(zero)); }
__device__ __forceinline__ void sched_fence() { asm volatile("{\n.reg .pred Q;\n.reg .u32 x;\n@!PNEVER bra D;\nF: ld.volatile.global.u32 x, [%0];\nsetp.ne.u32 Q, x, 0;\n@Q bra F;\nD:\n}" ::"l"(0ull) : "memory"); }
__device__ __forceinline__ void mbar_init(uint32_t b, uint32_t n) { asm volatile("mbarrier.init.shared::cta.b64 [%0], %1;" ::"r"(b), "r"(n) : "memory"); }
__device__ __forceinline__ void mbar_expect(uint32_t b, uint32_t bytes) { asm volatile("mbarrier.arrive.expect_tx.shared::cta.b64 _, [%0], %1;" ::"r"(b), "r"(bytes) : "memory"); }
__device__ __forceinline__ void mbar_arrive(uint32_t b) { asm volatile("mbarrier.arrive.shared::cta.b64 _, [%0];" ::"r"(b) : "memory"); }
__device__ __forceinline__ void mbar_arrive_cluster(uint32_t b) { asm volatile("mbarrier.arrive.shared::cluster.b64 _, [%0];" ::"r"(b) : "memory"); }
__device__ __forceinline__ void cluster_sync() { asm volatile("barrier.cluster.arrive.aligned;\nbarrier.cluster.wait.aligned;" ::: "memory"); }
__device__ __forceinline__ void tma2d(uint32_t dst, const CUtensorMap* m, int c0, int c1, uint32_t bar) {
    asm volatile("cp.async.bulk.tensor.2d.shared::cluster.global.mbarrier::complete_tx::bytes [%0], [%1, {%2, %3}], [%4];" ::"r"(dst), "l"(m), "r"(c0), "r"(c1), "r"(bar) : "memory");
}
__device__ __forceinline__ void tma3d(uint32_t dst, const CUtensorMap* m, int c0, int c1, int c2, uint32_t bar) {
    asm volatile("cp.async.bulk.tensor.3d.shared::cluster.global.mbarrier::complete_tx::bytes [%0], [%1, {%2, %3, %4}], [%5];" ::"r"(dst), "l"(m), "r"(c0), "r"(c1), "r"(c2), "r"(bar) : "memory");
}
__device__ __forceinline__ void l2_prefetch(const void* src, uint32_t bytes) { asm volatile("cp.async.bulk.prefetch.L2.global [%0], %1;" ::"l"(src), "r"(bytes) : "memory"); }
__device__ __forceinline__ void mbar_expect_e(uint32_t b, uint32_t bytes) {
    asm volatile("{\n.reg .pred E;\nelect.sync _|E, 0xffffffff;\n@E mbarrier.arrive.expect_tx.shared::cta.b64 _, [%0], %1;\n}" ::"r"(b), "r"(bytes) : "memory");
}
__device__ __forceinline__ void tma3d_mc_e(uint32_t dst, const CUtensorMap* m, int c0, int c1, int c2, uint32_t bar, uint16_t mask, uint64_t pol) {
    asm volatile("{\n.reg .pred E;\nelect.sync _|E, 0xffffffff;\n@E cp.async.bulk.tensor.3d.shared::cluster.global.mbarrier::complete_tx::bytes.multicast::cluster.L2::cache_hint [%0], [%1, {%2, %3, %4}], [%5], %6, %7;\n}" ::"r"(dst), "l"(m), "r"(c0), "r"(c1), "r"(c2), "r"(bar), "h"(mask), "l"(pol) : "memory");
}
__device__ __forceinline__ void tma4d_e(uint32_t dst, const CUtensorMap* m, int c0, int c1, int c3, uint32_t bar, uint64_t pol) {
    asm volatile("{\n.reg .pred E;\nelect.sync _|E, 0xffffffff;\n@E cp.async.bulk.tensor.4d.shared::cluster.global.mbarrier::complete_tx::bytes.L2::cache_hint [%0], [%1, {%2, %3, 0, %4}], [%5], %6;\n}" ::"r"(dst), "l"(m), "r"(c0), "r"(c1), "r"(c3), "r"(bar), "l"(pol) : "memory");
}
__device__ __forceinline__ void tma4d_mc_e(uint32_t dst, const CUtensorMap* m, int c0, int c1, int c3, uint32_t bar, uint16_t mask, uint64_t pol) {
    asm volatile("{\n.reg .pred E;\nelect.sync _|E, 0xffffffff;\n@E cp.async.bulk.tensor.4d.shared::cluster.global.mbarrier::complete_tx::bytes.multicast::cluster.L2::cache_hint [%0], [%1, {%2, %3, 0, %4}], [%5], %6, %7;\n}" ::"r"(dst), "l"(m), "r"(c0), "r"(c1), "r"(c3), "r"(bar), "h"(mask), "l"(pol) : "memory");
}
__device__ __forceinline__ void tma_prefetch4d_e(const CUtensorMap* m, int c0, int c3) {
    asm volatile("{\n.reg .pred E;\nelect.sync _|E, 0xffffffff;\n@E cp.async.bulk.prefetch.tensor.4d.L2.global [%0, {%1, 0, 0, %2}];\n}" ::"l"(m), "r"(c0), "r"(c3) : "memory");
}
__device__ __forceinline__ void tma_prefetch3d_e(const CUtensorMap* m, int c0, int c1, int c2) {
    asm volatile("{\n.reg .pred E;\nelect.sync _|E, 0xffffffff;\n@E cp.async.bulk.prefetch.tensor.3d.L2.global [%0, {%1, %2, %3}];\n}" ::"l"(m), "r"(c0), "r"(c1), "r"(c2) : "memory");
}
__device__ __forceinline__ void l2_prefetch_e(const void* src, uint32_t bytes) {
    asm volatile("{\n.reg .pred E;\nelect.sync _|E, 0xffffffff;\n@E cp.async.bulk.prefetch.L2.global [%0], %1;\n}" ::"l"(src), "r"(bytes) : "memory");
}
__device__ __forceinline__ void bulk_g2s_e(uint32_t dst, const void* src, uint32_t bytes, uint32_t bar) {
    asm volatile("{\n.reg .pred E;\nelect.sync _|E, 0xffffffff;\n@E cp.async.bulk.shared::cluster.global.mbarrier::complete_tx::bytes [%0], [%1], %2, [%3];\n}" ::"r"(dst), "l"(src), "r"(bytes), "r"(bar) : "memory");
}
__device__ __forceinline__ bool elect_one() {
    uint32_t r;
    asm volatile("{\n.reg .pred E;\nelect.sync _|E, 0xffffffff;\nselp.u32 %0, 1, 0, E;\n}" : "=r"(r));
    return r;
}
__device__ __forceinline__ void tma_store2d(const CUtensorMap* m, int c0, int c1, uint32_t src, uint64_t pol) {
    asm volatile("cp.async.bulk.tensor.2d.global.shared::cta.bulk_group.L2::cache_hint [%0, {%1, %2}], [%3], %4;" ::"l"(m), "r"(c0), "r"(c1), "r"(src), "l"(pol) : "memory");
}
__device__ __forceinline__ void bulk_commit() { asm volatile("cp.async.bulk.commit_group;" ::: "memory"); }
__device__ __forceinline__ void bulk_wait_read() { asm volatile("cp.async.bulk.wait_group.read 0;" ::: "memory"); }
__device__ __forceinline__ void bulk_wait_all() { asm volatile("cp.async.bulk.wait_group 0;" ::: "memory"); }
__device__ __forceinline__ uint64_t mkdesc(uint32_t addr, uint32_t lbo, uint32_t sbo, uint32_t swz) {
    return (uint64_t)((addr & 0x3FFFF) >> 4) | ((uint64_t)(lbo >> 4) << 16) | ((uint64_t)(sbo >> 4) << 32) | ((uint64_t)swz << 62);
}
__device__ __forceinline__ void wg_fence() { asm volatile("wgmma.fence.sync.aligned;" ::: "memory"); }
__device__ __forceinline__ void wg_commit() { asm volatile("wgmma.commit_group.sync.aligned;" ::: "memory"); }
template <int N> __device__ __forceinline__ void wg_wait() { asm volatile("wgmma.wait_group.sync.aligned %0;" ::"n"(N) : "memory"); }
template <typename T> __device__ __forceinline__ void pin_ptr(T*& p) { asm volatile("" : "+l"(p)); }
template <int N> __device__ __forceinline__ void pin(uint32_t* d) {
#pragma unroll
    for (int i = 0; i < N; i++) asm volatile("" : "+r"(d[i])::"memory");
}
template <int N> __device__ __forceinline__ void pin(float* d) {
#pragma unroll
    for (int i = 0; i < N; i++) asm volatile("" : "+f"(d[i])::"memory");
}

template <int TA, int TB>
__device__ __forceinline__ void wgmma_ss256(float* d, uint64_t da, uint64_t db) {
    asm volatile("wgmma.mma_async.sync.aligned.m64n256k16.f32.bf16.bf16 "
        "{%0, %1, %2, %3, %4, %5, %6, %7, %8, %9, %10, %11, %12, %13, %14, %15, %16, %17, %18, %19, %20, %21, %22, %23, %24, %25, %26, %27, %28, %29, %30, %31, %32, %33, %34, %35, %36, %37, %38, %39, %40, %41, %42, %43, %44, %45, %46, %47, %48, %49, %50, %51, %52, %53, %54, %55, %56, %57, %58, %59, %60, %61, %62, %63, %64, %65, %66, %67, %68, %69, %70, %71, %72, %73, %74, %75, %76, %77, %78, %79, %80, %81, %82, %83, %84, %85, %86, %87, %88, %89, %90, %91, %92, %93, %94, %95, %96, %97, %98, %99, %100, %101, %102, %103, %104, %105, %106, %107, %108, %109, %110, %111, %112, %113, %114, %115, %116, %117, %118, %119, %120, %121, %122, %123, %124, %125, %126, %127}, %128, %129, 1, 1, 1, %130, %131;"
        : "+f"(d[0]), "+f"(d[1]), "+f"(d[2]), "+f"(d[3]), "+f"(d[4]), "+f"(d[5]), "+f"(d[6]), "+f"(d[7]), "+f"(d[8]), "+f"(d[9]), "+f"(d[10]), "+f"(d[11]), "+f"(d[12]), "+f"(d[13]), "+f"(d[14]), "+f"(d[15]), "+f"(d[16]), "+f"(d[17]), "+f"(d[18]), "+f"(d[19]), "+f"(d[20]), "+f"(d[21]), "+f"(d[22]), "+f"(d[23]), "+f"(d[24]), "+f"(d[25]), "+f"(d[26]), "+f"(d[27]), "+f"(d[28]), "+f"(d[29]), "+f"(d[30]), "+f"(d[31]), "+f"(d[32]), "+f"(d[33]), "+f"(d[34]), "+f"(d[35]), "+f"(d[36]), "+f"(d[37]), "+f"(d[38]), "+f"(d[39]), "+f"(d[40]), "+f"(d[41]), "+f"(d[42]), "+f"(d[43]), "+f"(d[44]), "+f"(d[45]), "+f"(d[46]), "+f"(d[47]), "+f"(d[48]), "+f"(d[49]), "+f"(d[50]), "+f"(d[51]), "+f"(d[52]), "+f"(d[53]), "+f"(d[54]), "+f"(d[55]), "+f"(d[56]), "+f"(d[57]), "+f"(d[58]), "+f"(d[59]), "+f"(d[60]), "+f"(d[61]), "+f"(d[62]), "+f"(d[63]), "+f"(d[64]), "+f"(d[65]), "+f"(d[66]), "+f"(d[67]), "+f"(d[68]), "+f"(d[69]), "+f"(d[70]), "+f"(d[71]), "+f"(d[72]), "+f"(d[73]), "+f"(d[74]), "+f"(d[75]), "+f"(d[76]), "+f"(d[77]), "+f"(d[78]), "+f"(d[79]), "+f"(d[80]), "+f"(d[81]), "+f"(d[82]), "+f"(d[83]), "+f"(d[84]), "+f"(d[85]), "+f"(d[86]), "+f"(d[87]), "+f"(d[88]), "+f"(d[89]), "+f"(d[90]), "+f"(d[91]), "+f"(d[92]), "+f"(d[93]), "+f"(d[94]), "+f"(d[95]), "+f"(d[96]), "+f"(d[97]), "+f"(d[98]), "+f"(d[99]), "+f"(d[100]), "+f"(d[101]), "+f"(d[102]), "+f"(d[103]), "+f"(d[104]), "+f"(d[105]), "+f"(d[106]), "+f"(d[107]), "+f"(d[108]), "+f"(d[109]), "+f"(d[110]), "+f"(d[111]), "+f"(d[112]), "+f"(d[113]), "+f"(d[114]), "+f"(d[115]), "+f"(d[116]), "+f"(d[117]), "+f"(d[118]), "+f"(d[119]), "+f"(d[120]), "+f"(d[121]), "+f"(d[122]), "+f"(d[123]), "+f"(d[124]), "+f"(d[125]), "+f"(d[126]), "+f"(d[127])
        : "l"(da), "l"(db), "n"(TA), "n"(TB));
}
template <int TA, int TB>
__device__ __forceinline__ void wgmma_ss256_first(float* d, uint64_t da, uint64_t db) {
    asm volatile("wgmma.mma_async.sync.aligned.m64n256k16.f32.bf16.bf16 "
        "{%0, %1, %2, %3, %4, %5, %6, %7, %8, %9, %10, %11, %12, %13, %14, %15, %16, %17, %18, %19, %20, %21, %22, %23, %24, %25, %26, %27, %28, %29, %30, %31, %32, %33, %34, %35, %36, %37, %38, %39, %40, %41, %42, %43, %44, %45, %46, %47, %48, %49, %50, %51, %52, %53, %54, %55, %56, %57, %58, %59, %60, %61, %62, %63, %64, %65, %66, %67, %68, %69, %70, %71, %72, %73, %74, %75, %76, %77, %78, %79, %80, %81, %82, %83, %84, %85, %86, %87, %88, %89, %90, %91, %92, %93, %94, %95, %96, %97, %98, %99, %100, %101, %102, %103, %104, %105, %106, %107, %108, %109, %110, %111, %112, %113, %114, %115, %116, %117, %118, %119, %120, %121, %122, %123, %124, %125, %126, %127}, %128, %129, 0, 1, 1, %130, %131;"
        : "=f"(d[0]), "=f"(d[1]), "=f"(d[2]), "=f"(d[3]), "=f"(d[4]), "=f"(d[5]), "=f"(d[6]), "=f"(d[7]), "=f"(d[8]), "=f"(d[9]), "=f"(d[10]), "=f"(d[11]), "=f"(d[12]), "=f"(d[13]), "=f"(d[14]), "=f"(d[15]), "=f"(d[16]), "=f"(d[17]), "=f"(d[18]), "=f"(d[19]), "=f"(d[20]), "=f"(d[21]), "=f"(d[22]), "=f"(d[23]), "=f"(d[24]), "=f"(d[25]), "=f"(d[26]), "=f"(d[27]), "=f"(d[28]), "=f"(d[29]), "=f"(d[30]), "=f"(d[31]), "=f"(d[32]), "=f"(d[33]), "=f"(d[34]), "=f"(d[35]), "=f"(d[36]), "=f"(d[37]), "=f"(d[38]), "=f"(d[39]), "=f"(d[40]), "=f"(d[41]), "=f"(d[42]), "=f"(d[43]), "=f"(d[44]), "=f"(d[45]), "=f"(d[46]), "=f"(d[47]), "=f"(d[48]), "=f"(d[49]), "=f"(d[50]), "=f"(d[51]), "=f"(d[52]), "=f"(d[53]), "=f"(d[54]), "=f"(d[55]), "=f"(d[56]), "=f"(d[57]), "=f"(d[58]), "=f"(d[59]), "=f"(d[60]), "=f"(d[61]), "=f"(d[62]), "=f"(d[63]), "=f"(d[64]), "=f"(d[65]), "=f"(d[66]), "=f"(d[67]), "=f"(d[68]), "=f"(d[69]), "=f"(d[70]), "=f"(d[71]), "=f"(d[72]), "=f"(d[73]), "=f"(d[74]), "=f"(d[75]), "=f"(d[76]), "=f"(d[77]), "=f"(d[78]), "=f"(d[79]), "=f"(d[80]), "=f"(d[81]), "=f"(d[82]), "=f"(d[83]), "=f"(d[84]), "=f"(d[85]), "=f"(d[86]), "=f"(d[87]), "=f"(d[88]), "=f"(d[89]), "=f"(d[90]), "=f"(d[91]), "=f"(d[92]), "=f"(d[93]), "=f"(d[94]), "=f"(d[95]), "=f"(d[96]), "=f"(d[97]), "=f"(d[98]), "=f"(d[99]), "=f"(d[100]), "=f"(d[101]), "=f"(d[102]), "=f"(d[103]), "=f"(d[104]), "=f"(d[105]), "=f"(d[106]), "=f"(d[107]), "=f"(d[108]), "=f"(d[109]), "=f"(d[110]), "=f"(d[111]), "=f"(d[112]), "=f"(d[113]), "=f"(d[114]), "=f"(d[115]), "=f"(d[116]), "=f"(d[117]), "=f"(d[118]), "=f"(d[119]), "=f"(d[120]), "=f"(d[121]), "=f"(d[122]), "=f"(d[123]), "=f"(d[124]), "=f"(d[125]), "=f"(d[126]), "=f"(d[127])
        : "l"(da), "l"(db), "n"(TA), "n"(TB));
}
template <int TB>
__device__ __forceinline__ void wgmma_rs128(float* d, const uint32_t* a, uint64_t db, uint32_t acc) {
    asm volatile("{\n.reg .pred P;\nsetp.ne.u32 P, %69, 0;\nwgmma.mma_async.sync.aligned.m64n128k16.f32.bf16.bf16 "
        "{%0, %1, %2, %3, %4, %5, %6, %7, %8, %9, %10, %11, %12, %13, %14, %15, %16, %17, %18, %19, %20, %21, %22, %23, %24, %25, %26, %27, %28, %29, %30, %31, %32, %33, %34, %35, %36, %37, %38, %39, %40, %41, %42, %43, %44, %45, %46, %47, %48, %49, %50, %51, %52, %53, %54, %55, %56, %57, %58, %59, %60, %61, %62, %63}, {%64, %65, %66, %67}, %68, P, 1, 1, %70;\n}"
        : "+f"(d[0]), "+f"(d[1]), "+f"(d[2]), "+f"(d[3]), "+f"(d[4]), "+f"(d[5]), "+f"(d[6]), "+f"(d[7]), "+f"(d[8]), "+f"(d[9]), "+f"(d[10]), "+f"(d[11]), "+f"(d[12]), "+f"(d[13]), "+f"(d[14]), "+f"(d[15]), "+f"(d[16]), "+f"(d[17]), "+f"(d[18]), "+f"(d[19]), "+f"(d[20]), "+f"(d[21]), "+f"(d[22]), "+f"(d[23]), "+f"(d[24]), "+f"(d[25]), "+f"(d[26]), "+f"(d[27]), "+f"(d[28]), "+f"(d[29]), "+f"(d[30]), "+f"(d[31]), "+f"(d[32]), "+f"(d[33]), "+f"(d[34]), "+f"(d[35]), "+f"(d[36]), "+f"(d[37]), "+f"(d[38]), "+f"(d[39]), "+f"(d[40]), "+f"(d[41]), "+f"(d[42]), "+f"(d[43]), "+f"(d[44]), "+f"(d[45]), "+f"(d[46]), "+f"(d[47]), "+f"(d[48]), "+f"(d[49]), "+f"(d[50]), "+f"(d[51]), "+f"(d[52]), "+f"(d[53]), "+f"(d[54]), "+f"(d[55]), "+f"(d[56]), "+f"(d[57]), "+f"(d[58]), "+f"(d[59]), "+f"(d[60]), "+f"(d[61]), "+f"(d[62]), "+f"(d[63])
        : "r"(a[0]), "r"(a[1]), "r"(a[2]), "r"(a[3]), "l"(db), "r"(acc), "n"(TB));
}
template <int TB>
__device__ __forceinline__ void wgmma_rs64(float* d, const uint32_t* a, uint64_t db, uint32_t acc) {
    asm volatile("{\n.reg .pred P;\nsetp.ne.u32 P, %37, 0;\nwgmma.mma_async.sync.aligned.m64n64k16.f32.bf16.bf16 "
        "{%0, %1, %2, %3, %4, %5, %6, %7, %8, %9, %10, %11, %12, %13, %14, %15, %16, %17, %18, %19, %20, %21, %22, %23, %24, %25, %26, %27, %28, %29, %30, %31}, {%32, %33, %34, %35}, %36, P, 1, 1, %38;\n}"
        : "+f"(d[0]), "+f"(d[1]), "+f"(d[2]), "+f"(d[3]), "+f"(d[4]), "+f"(d[5]), "+f"(d[6]), "+f"(d[7]), "+f"(d[8]), "+f"(d[9]), "+f"(d[10]), "+f"(d[11]), "+f"(d[12]), "+f"(d[13]), "+f"(d[14]), "+f"(d[15]), "+f"(d[16]), "+f"(d[17]), "+f"(d[18]), "+f"(d[19]), "+f"(d[20]), "+f"(d[21]), "+f"(d[22]), "+f"(d[23]), "+f"(d[24]), "+f"(d[25]), "+f"(d[26]), "+f"(d[27]), "+f"(d[28]), "+f"(d[29]), "+f"(d[30]), "+f"(d[31])
        : "r"(a[0]), "r"(a[1]), "r"(a[2]), "r"(a[3]), "l"(db), "r"(acc), "n"(TB));
}
template <int TB>
__device__ __forceinline__ void wgmma_rs16(float* d, const uint32_t* a, uint64_t db, uint32_t acc) {
    asm volatile("{\n.reg .pred P;\nsetp.ne.u32 P, %13, 0;\nwgmma.mma_async.sync.aligned.m64n16k16.f32.bf16.bf16 "
        "{%0, %1, %2, %3, %4, %5, %6, %7}, {%8, %9, %10, %11}, %12, P, 1, 1, %14;\n}"
        : "+f"(d[0]), "+f"(d[1]), "+f"(d[2]), "+f"(d[3]), "+f"(d[4]), "+f"(d[5]), "+f"(d[6]), "+f"(d[7])
        : "r"(a[0]), "r"(a[1]), "r"(a[2]), "r"(a[3]), "l"(db), "r"(acc), "n"(TB));
}

__device__ __forceinline__ uint32_t delay_loop(int n, uint32_t x0) {
    uint32_t z;
    asm volatile("{\n.reg .pred P;\n.reg .u32 c, x;\nmov.u32 c, %1;\nmov.u32 x, %2;\nDL: mad.lo.u32 x, x, 1664525, 1013904223;\nadd.u32 c, c, -1;\nsetp.gt.s32 P, c, 0;\n@P bra DL;\n"
                 "setp.eq.u32 P, x, 0x7fffffff;\nselp.u32 %0, 16, 0, P;\n}" : "=r"(z) : "r"(n), "r"(x0) : "memory");
    return z;
}
__device__ __forceinline__ void wait_clocks(uint32_t n) {
    asm volatile("{\n.reg .pred P;\n.reg .u32 a, b;\nmov.u32 a, %%clock;\nW: mov.u32 b, %%clock;\nsub.u32 b, b, a;\nsetp.lt.u32 P, b, %0;\n@P bra W;\n}" ::"r"(n) : "memory");
}
__device__ __forceinline__ uint32_t gtime() { uint32_t t; asm volatile("mov.u32 %0, %%globaltimer_lo;" : "=r"(t)); return t; }
#define COUNT_RETRY(i)
__device__ __forceinline__ uint32_t stamp_word(uint32_t seq) { return (gtime() & ~31u) | (seq & 31u); }
__device__ __forceinline__ void wait_time(uint32_t t, uint32_t sb) { while ((int32_t)(gtime() - t) < 0) {} }
#define NAPMODE 1
__device__ __forceinline__ void nap(uint32_t ns) { if (NAPMODE) wait_clocks(ns * 7 / 4); else __nanosleep(ns); }
template <int STRIDE>
__device__ __forceinline__ uint32_t latest_stamp(const uint32_t* p, uint32_t seq, uint32_t ref, uint32_t sb) {
#pragma unroll 1
    for (int n = opq(0, 0);; n++) {
        uint32_t bad = 0; int32_t m = INT32_MIN;
#pragma unroll
        for (int i = 0; i < 3; i++) { const uint32_t v = ld_relaxed1(p + i * STRIDE); bad |= (v ^ seq) & 31u; m = max(m, (int32_t)((v & ~31u) - ref)); }
        if (__all_sync(0xffffffffu, bad == 0)) return ref + __reduce_max_sync(0xffffffffu, m);
        nap(100);
        if (n > SPIN_LIMIT) spin_fault();
    }
}
constexpr uint32_t ONES = 0x3C003C00u, FULL = 0x50005000u;
__device__ __forceinline__ void pacer(const Params& P, const uint32_t sb, const int cta, const int lane, const uint32_t epoch) {
    uint8_t* const zp = P.xb + cta * 2048 + xg_lane(lane);
    if (lane < 3) asm volatile("prefetch.tensormap [%0];" ::"l"(&P.tm[lane == 0 ? M_C1 + cta % 3 : lane == 1 ? M_CO : M_SEG]) : "memory");
    uint32_t e0 = 0;
#pragma unroll 2
    for (int i = 0; i < 32; i++) { const uint4 u = __ldg((const uint4*)P.mem0 + i * 32 + lane); e0 = amax(amax(e0, amax(u.x, u.y)), amax(u.z, u.w)); }
    e0 = min(max(warp_exp(e0), 31u), 253u) - 14;
    if (cta < 32) {
        const uint32_t* m = (const uint32_t*)(P.mem0 + (lane >> 2) * 1024 + cta * 32 + (lane & 3) * 2);
        const float sc = __uint_as_float((254 - e0) << 23);
        auto cv = [&](uint32_t u) { return pack2h(bf_lo(u) * sc, bf_hi(u) * sc); };
        const uint32_t y = cv(m[12]);
        st_relaxed4(zp, cv(m[0]), cv(m[4]), cv(m[8]), prmt(y, FULL, 0x7610));
        st_relaxed1(P.xb + xg_side(cta) + lane * 4, prmt(y, FULL, 0x3254));
    }
    if (cta < 40) {
#pragma unroll 1
        for (int b = 1; b < 8; b++) st_relaxed4(zp + xg_buf(b), 0, 0, 0, 0);
    }
    __threadfence();
    const uint32_t* ts = (const uint32_t*)(P.xb + XG_T) + lane;
    int32_t d0 = P.dly;
    const uint32_t go = mapa(sb + B_GO, (cta / 3 & 1) * 3 + 1 + (lane & 1));
    auto free_segment = [&]() { if (lane == 0) mbar_expect(sb + B_KVFULL, 16384); __syncwarp(); if (lane < 2) mbar_arrive_cluster(go); };
    for (int n = 0; (int32_t)(ld_acquire(&g_cnt(C_XCNT)) - (epoch + 1) * 256) < 0; n++) { __nanosleep(500); if (n > SPIN_LIMIT) spin_fault(); }
    const uint32_t ex = max(ld_relaxed1(&g_cnt(C_XMAX)) & 255, 67u);
    mbar_wait_bounded(sb + B_READY, 0);
    free_segment();
    if (lane == 0) st_relaxed2(g_hint + cta * 32, stamp_word(epoch + 1), lds32(sb + S_EV) | lds32(sb + S_EO) << 16);
    uint32_t a = gtime();
    for (int n = 0;; n++) {
        uint32_t bad = 0, e = 0; int32_t m = INT32_MIN;
#pragma unroll
        for (int i = 0; i < 3; i++) {
            uint32_t v[2];
            ld_relaxed2(v, g_hint + lane * 32 + i * 1024);
            bad |= (v[0] ^ (epoch + 1)) & 31u; m = max(m, (int32_t)((v[0] & ~31u) - a)); e = __vmaxu2(e, v[1]);
        }
        if (__all_sync(0xffffffffu, bad == 0)) {
            a += __reduce_max_sync(0xffffffffu, m);
            const uint32_t ev = __reduce_max_sync(0xffffffffu, e & 255), eo = __reduce_max_sync(0xffffffffu, e >> 16);
            if (lane == 0) { sts64(sb + S_SC, max(ev, 97u) + max(eo, 97u) - 244, ex); sts32(sb + S_ISC, e0 * 0x800080u); }
            break;
        }
        wait_clocks(100);
        if (n > SPIN_LIMIT) spin_fault();
    }
    wait_time(a, sb);
    if (lane == 0) mbar_arrive(sb + B_RELM);
#pragma unroll 1
    for (int s = 0; s < 63; s++) {
        const uint32_t seq = epoch * 63 + s + 1;
        mbar_wait_bounded(sb + B_P1, s & 1);
        const uint32_t tx = gtime();
        if (lane == 0) st_relaxed1(ts + (s & 1) * 256 + cta, (tx & ~31u) | (seq & 31u));
        { const uint32_t t = tx; PROFP(3) }
        if (s > 0) {
            const int32_t e0 = latest_stamp<32>(ts + (~s & 1) * 256 + 128, seq - 1, a, sb) + P.mrg - a;
            d0 += s < 3 ? e0 : min(max(e0, -P.clamp0), P.clampv) / 2;
        }
        while ((int32_t)(gtime() - tx) < P.rd) nap(20);
        a = latest_stamp<32>(ts + (s & 1) * 256, seq, tx, sb) + d0;
        { const uint32_t t = gtime(); PROFP(0) }
        while ((int32_t)(a - gtime()) > 250) nap(40);
        wait_time(a, sb);
        if (lane == 0) mbar_arrive(sb + B_RELM);
        { const uint32_t t = a; PROFP(2) }
        mbar_wait_bounded(sb + B_RED, s & 1);
        { const uint32_t t = gtime(); PROFP(1) }
        const uint32_t g = tx + __reduce_max_sync(0xffffffffu, lds32(sb + S_TO + (lane & 7) * 4) - tx);
        if (lane == 0) st_relaxed1(ts + (s & 1) * 256 + 128 + cta, (g & ~31u) | (seq & 31u));
        if (s < 62) { if (P.kvd) nap(P.kvd); free_segment(); }
    }
}
__device__ __forceinline__ void st_async2(uint32_t a, uint32_t x, uint32_t y, uint32_t bar) {
    asm volatile("st.async.weak.shared::cluster.mbarrier::complete_tx::bytes.v2.b32 [%0], {%1,%2}, [%3];" ::"r"(a), "r"(x), "r"(y), "r"(bar) : "memory");
}
__device__ __forceinline__ uint32_t xor_or(uint32_t a, uint32_t b, uint32_t t) { uint32_t d; asm("lop3.b32 %0, %1, %2, %3, 0x7E;" : "=r"(d) : "r"(a), "r"(b), "r"(t)); return d; }
__device__ __forceinline__ uint32_t or3(uint32_t a, uint32_t b, uint32_t c) { uint32_t d; asm("lop3.b32 %0, %1, %2, %3, 0xFE;" : "=r"(d) : "r"(a), "r"(b), "r"(c)); return d; }
__device__ __forceinline__ bool tags_ok(uint32_t bad, uint32_t mask = 1) {
    uint32_t r;
    asm volatile("{\n.reg .pred P;\n.reg .b32 x;\nand.b32 x, %1, %2;\nsetp.ne.b32 P, x, 0;\nvote.sync.any.pred P, P, 0xffffffff;\nselp.u32 %0, 0, 1, P;\n}" : "=r"(r) : "r"(bad), "r"(mask));
    return r;
}
constexpr int SROW = 56;
#define PREA 8
#define PREB 9
#define RING1 6
#define RING2 7
#define RING3 8
#define PRE2 10
#define PRE2A 0
#define PRE3 0
#define EFENCE 0
#define RFENCE 1
#define PROG 16
#define EARLY 0
#define PLATE 1
#define NDEP 0
#define EFENCE2 0
#define LAG2 8
#define LAG 4
#define PUT1 33
#define DEPS 3
#define ADELAY 120
#define BDELAY 0
#define HOLD 1
#define XDELAY 330
#define FENCEA 0x80
#define FENCEB 0x80
#define FENCE2 0x220
#define OFENCE 0
#define MASK3 0x57
#define MASK4 0x55
#define MASK5 0x25
#define OFF3 0x5320
#define OFF4 0x6420
#define OFF5 0x0520
#define RESA (NRA == 3 ? 15 : NRA == 4 ? 3 : 0)
#define RESB (NRB == 3 ? 0xcc : NRB == 4 ? 0x30 : 0)
#define RESB1 (NRB == 3 ? 0xcc : NRB == 4 ? 0xc : 0)
__host__ __device__ constexpr int smem_mask(int NR) { return NR == 3 ? MASK3 : NR == 4 ? MASK4 : MASK5; }
__host__ __device__ constexpr bool round_smem(int r, int NR) { return smem_mask(NR) >> r & 1; }
__host__ __device__ constexpr int kord(int r, int NR) { int c = 0; for (int i = 0; i < r; i++) c += round_smem(i, NR) == round_smem(r, NR); return round_smem(r, NR) ? NR + c : c; }
__host__ __device__ constexpr int slot_r(int n, int NR) { return n < 32 ? n >> 2 : (((n & 31) >> 2) + ((NR == 3 ? OFF3 : NR == 4 ? OFF4 : OFF5) >> (n & 3) * 4)) & 7; }
__host__ __device__ constexpr int slot_k(int n, int NR) { return kord(slot_r(n, NR), NR); }
__host__ __device__ constexpr int slot_sord(int n, int NR) { int c = 0; for (int i = 0; i < n; i++) c += slot_k(i, NR) >= NR; return c; }
__host__ __device__ constexpr int sfrag_slot(int q, int NR) { for (int n = 0; n < 64; n++) if (slot_k(n, NR) >= NR && slot_sord(n, NR) == q) return n; return -1; }
__host__ __device__ constexpr int w1_loaded(int n, int NR, int PRE) {
    int q = PRE;
    for (int i = 0; i <= n; i++) q += q < (8 - NR) * 8 && q - slot_sord(i + 1, NR) < (i < 32 ? RING1 : RING2);
    return q;
}
template <int Q, int NR>
__device__ __forceinline__ void load_w1(uint32_t* w, const uint32_t* a) {
    constexpr int n = sfrag_slot(Q, NR);
    ldsm4t(w, a[n & 3] + ((slot_k(n, NR) - NR) * 2 + (n >> 5)) * 2048);
}
constexpr int AB = NRA < 5, BB = 3 - AB;
__device__ __forceinline__ bool w2_full(int role, int warp) { return warp < (role == 2 ? 2 : 3); }
__device__ __forceinline__ int w2_nblk(int role, int warp) { return warp < 4 ? BB - !w2_full(role, warp) : AB; }
__host__ __device__ constexpr int w2_step(bool full, int i) { return AB ? (full ? 2 * i : 0) : full ? (i == 0 ? 0 : i == 1 ? 16 - 2 * EARLY : 18 - 2 * EARLY) : i; }
__device__ __forceinline__ int w2_block(int role, int warp) {
    const int f = role * 3 + warp, g = role == 2 ? warp : role;
    if (AB) return (warp >= 4 ? role * 4 + (warp - 4) : w2_full(role, warp) ? 16 + 4 * (f >> 1) + (f & 1) : 12 + g) ^ EARLY;
    return w2_full(role, warp) ? EARLY + 4 * (f >> 1) + (f & 1) : EARLY + 2 + 4 * g;
}
__device__ __forceinline__ int w2_res(int role, int warp) { return warp >= 4 ? RESA : w2_full(role, warp) ? RESB : RESB1; }
__device__ __forceinline__ int w2_units(int role, int warp) { return w2_nblk(role, warp) * 4 - (5 - (warp < 4 ? NRB : NRA)) * 2; }
constexpr int W2B = (BB * 4 - (5 - NRB) * 2) * 2048, W2A = (AB * 4 - (5 - NRA) * 2) * 2048;
static_assert(S_W2 + 4 * W2B - 8192 + 4 * W2A == S_KV, "weights");
__device__ __forceinline__ int w1_base(int warp) { return S_W1 + (warp < 4 ? warp * (8 - NRB) : 4 * (8 - NRB) + (warp - 4) * (8 - NRA)) * 4096; }
__device__ __forceinline__ int w2_base(int warp) { return S_W2 + (warp < 4 ? warp * W2B : 4 * W2B - 8192 + (warp - 4) * W2A); }
__device__ __forceinline__ void chain_load(const Params& P, uint32_t sb, int cta, int warp, int lane, int round) {
    const int role = cta % 3, h = cta / 3;
    mbar_expect_e(sb + B_INIT, round ? (8 - (warp < 4 ? NRB : NRA)) * 4096 : 20480);
    if (round) mbar_expect_e(sb + B_INIT2, w2_units(role, warp) * 2048);
    __syncwarp();
    const int m1 = (warp < 4 ? smem_mask(NRB) : smem_mask(NRA)) ^ (round ? 0 : 255), below = (1 << lane) - 1;
    const int m2 = (w2_res(role, warp) ^ (round ? 0xfff : 0)) & ((1 << w2_nblk(role, warp) * 4) - 1);
    const uint32_t d1 = sb + (round ? w1_base(warp) : warp * 20480), d2 = round ? sb + w2_base(warp) : d1 + __popc(m1) * 4096;
    if (m1 >> lane & 1) tma3d(d1 + __popc(m1 & below) * 4096, &P.tm[M_C1 + role], 0, warp * 128 + lane * 16, h * 2, sb + B_INIT);
    __syncwarp();
    if (m2 >> lane & 1)
        tma2d(d2 + __popc(m2 & below) * 2048, &P.tm[M_CO], (w2_block(role, warp) + w2_step(w2_full(role, warp), lane >> 2)) * 32, h * 128 + (lane & 3) * 32, sb + (round ? B_INIT2 : B_INIT));
    __syncwarp();
}

__device__ __forceinline__ void put_partials(bool TR, uint32_t a, const float* x, const float* y) {
    if (TR) stsm4t(a, pack2(x[0], x[1]), pack2(x[2], x[3]), pack2(y[0], y[1]), pack2(y[2], y[3]));
    else stsm4(a, pack2(x[0], x[1]), pack2(x[2], x[3]), pack2(y[0], y[1]), pack2(y[2], y[3]));
}
template <int NR, int PRE, int FM, int B, int E>
__device__ __forceinline__ void project(float (*acc)[4], bool TR, const uint32_t (*wr)[4], uint32_t (*as)[4], uint32_t (*v)[4], uint32_t* x, const uint32_t* w1a, uint32_t pp, uint32_t zero) {
    static_for<B, E>([&](auto I) {
        constexpr int n = I.value, kk = slot_k(n, NR), T = (n >> 5) * 4 + (n & 3), so = slot_sord(n, NR), q = w1_loaded(n - 1, NR, PRE);
        constexpr bool sm = kk >= NR;
        const uint32_t* w = sm ? as[so] : wr[sm ? 0 : (kk * 2 + (n >> 5)) * 4 + (n & 3)];
        if constexpr (n == 32 && PUT1 < 32) { put_partials(TR, pp, acc[0], acc[1]); put_partials(TR, pp + 4096, acc[2], acc[3]); }
        if constexpr (n == 0) {
            const uint32_t c = prmt(v[0][3], x[0], 0x3254);
            v[0][0] = h2bf(v[0][0], v[0][0]); v[0][1] = h2bf(v[0][1], v[0][1]); v[0][2] = h2bf(v[0][2], v[0][2]); v[0][3] = h2bf(v[0][3], x[0]);
            x[0] = c;
        }
        if constexpr ((n & 31) < 4) acc[T][0] = acc[T][1] = acc[T][2] = acc[T][3] = 0.f;
        mma16816(acc[T], w[0], w[1], w[2], w[3], v[slot_r(n, NR) >> 1][(slot_r(n, NR) & 1) * 2], v[slot_r(n, NR) >> 1][(slot_r(n, NR) & 1) * 2 + 1]);
        if constexpr (n == DEPS) {
            const uint32_t sel = __float_as_uint(acc[T][0]) * zero + 0x7610;
#pragma unroll
            for (int b = 1; b < 4; b++) {
                if (b <= NDEP) cvt_block(v[b], x[b], sel);
                else {
                    const uint32_t c = prmt(v[b][3], x[b], 0x3254);
                    v[b][0] = h2bf(v[b][0], v[b][0]); v[b][1] = h2bf(v[b][1], v[b][1]); v[b][2] = h2bf(v[b][2], v[b][2]); v[b][3] = h2bf(v[b][3], x[b]);
                    x[b] = c;
                }
            }
        }
        if constexpr (w1_loaded(n, NR, PRE) > q) load_w1<q, NR>(as[q], w1a);
        if constexpr (n == PUT1 && n >= 32) { put_partials(TR, pp, acc[0], acc[1]); put_partials(TR, pp + 4096, acc[2], acc[3]); }
        if constexpr (n % 4 == 3 && (FM >> (n / 4) & 1) && n != E - 1) sched_fence();
    });
    if constexpr (E == 64) { put_partials(TR, pp + 8192, acc[4], acc[5]); put_partials(TR, pp + 12288, acc[6], acc[7]); }
}
__device__ __forceinline__ void reduce8(const uint32_t (*x)[4], const uint32_t* sel, float sc, uint32_t& r0, uint32_t& r1) {
    float d[4][4];
#pragma unroll
    for (int i = 0; i < 4; i++) {
        d[i][0] = d[i][1] = d[i][2] = d[i][3] = 0.f;
        mma16816(d[i], x[i][0], x[i][1], x[i][2], x[i][3], sel[2 * i], sel[2 * i + 1]);
    }
    r0 = pack2(((d[0][0] + d[1][0]) + (d[2][0] + d[3][0])) * sc, ((d[0][1] + d[1][1]) + (d[2][1] + d[3][1])) * sc);
    r1 = pack2(((d[0][2] + d[1][2]) + (d[2][2] + d[3][2])) * sc, ((d[0][3] + d[1][3]) + (d[2][3] + d[3][3])) * sc);
}

#define ISTAMP(i)
__host__ __device__ constexpr int wo_count(int n, int RES, bool res) { int c = 0; for (int i = 0; i < n; i++) c += (RES >> (i >> 2) & 1) == res; return c; }
__host__ __device__ constexpr int wo_loaded(int n, int RES, int PRE, int end) { int q = PRE; for (int i = 0; i <= n; i++) q += q < end && q - wo_count(i + 1, RES, false) < RING3; return q; }
template <int Q>
__device__ __forceinline__ void load_w2(uint32_t* w, const uint32_t* a) { ldsm4t(w, a[Q & 1] + (Q >> 1) * 1024); }
template <int NB, int RES, int PRE, int FM>
__device__ __forceinline__ void wo_blocks(uint32_t (*w)[4], const uint32_t (*wp)[4], uint32_t oa, const uint32_t* wa, const uint8_t* dst, const uint8_t* dsd, bool odd) {
    float a[NB][4][4];
    uint32_t o[4][4], r[5];
    bar_sync(3, 256);
#pragma unroll
    for (int i = 0; i < 4; i++) ldsm4(o[i], oa + i * 512);
    if (FM & 1) sched_fence();
    static_for<0, NB * 16>([&](auto I) {
        constexpr int n = I.value, i = n & 15, end = wo_count(NB * 16, RES, false), q = wo_loaded(n - 1, RES, PRE, end);
        constexpr bool res = RES >> (n >> 2) & 1;
        const uint32_t* b = o[i >> 2] + (i & 2);
        const uint32_t* x = res ? wp[wo_count(n, RES, true)] : w[wo_count(n, RES, false)];
        float* d = a[n >> 4][i & 3];
        if constexpr (i < 4) d[0] = d[1] = d[2] = d[3] = 0.f;
        mma16816(d, x[0], x[1], x[2], x[3], b[0], b[1]);
        if constexpr (wo_loaded(n, RES, PRE, end) > q) load_w2<q>(w[q], wa);
        if constexpr (n == NB * 16 - 1 || (n >= 16 && i == LAG - 1)) {
            const float (*e)[4] = a[n == NB * 16 - 1 ? NB - 1 : (n >> 4) - 1];
            const uint32_t y = pack2h(e[1][2] + e[3][2], e[1][3] + e[3][3]);
            r[0] = movm(pack2h(e[0][0] + e[2][0], e[0][1] + e[2][1])); r[1] = movm(pack2h(e[0][2] + e[2][2], e[0][3] + e[2][3]));
            r[2] = movm(pack2h(e[1][0] + e[3][0], e[1][1] + e[3][1])); r[3] = movm(odd ? ONES : y); r[4] = movm(odd ? y : ONES);
        }
        if constexpr (n == NB * 16 - 1 || (n >= 16 && i == LAG2 - 1)) {
            constexpr int bs = w2_step(NB == BB, n == NB * 16 - 1 ? NB - 1 : (n >> 4) - 1);
            red_add4(dst + bs * 2048, r[0], r[1], r[2], r[3]);
            red_add1(dsd + (bs >> 1) * 1024 + (bs & 1) * 256, r[4]);
        }
        if constexpr (((FM >> (n / 4 + 1)) & 1) && (n & 3) == 3 && n != NB * 16 - 1) sched_fence();
    });
}
#define FRAG1(ln) ((((ln) & 7) + ((ln) >> 4) * 8) * 128 + ((((((ln) >> 3) & 1) << (ROLE == 1)) ^ ((ln) & 7)) << 4))
#define FRAG2(ln) ((((ln) & 7) + ((ln) >> 4) * 8) * 64 + (((((ln) >> 3) & 1) ^ (((ln) >> 1) & 3)) << 4))
#define TILE_X(i) (ROLE == 1 ? (((i) >> 1) << 6) | (((i) & 1) << 4) : (i) << 5)
__device__ __forceinline__ void chain_fetch(const Params& P, const uint32_t sb, const int cta, const int warp, const int lane, uint32_t (*wr)[4]) {
    const int ROLE = cta % 3, nr = warp < 4 ? NRB : NRA;
    mbar_wait(sb + B_INIT, 0);
    ISTAMP(0)
#pragma unroll
    for (int f = 0; f < 40; f++) {
        const bool w1 = f < (NRA < NRB ? NRA : NRB) * 8 || f < nr * 8;
        ldsm4t(wr[f], sb + warp * 20480 + (f >> 2) * 2048 + (w1 ? FRAG1(lane) ^ TILE_X(f & 3) : (f & 2) * 512 + (FRAG2(lane) ^ ((f & 1) << 5))));
    }
    fence_async_smem();
    mbar_wait(sb + B_SFREE + (warp >> 2) * 8, 0);
    bar_sync(1, 256);
    chain_load(P, sb, cta, warp, lane, 1);
    ISTAMP(1)
}
__device__ __forceinline__ void chain_bounds(const uint32_t sb, const int cta, const int warp, const int lane, const uint32_t (*wr)[4]) {
    const int ROLE = cta % 3, nr = warp < 4 ? NRB : NRA;
    uint32_t m[6] = {}, u[4];
#pragma unroll
    for (int f = 0; f < 40; f++) m[f < 24 ? 0 : f >> 3] = amax4(m[f < 24 ? 0 : f >> 3], wr[f]);
    uint32_t m1 = amax(m[0], amax(nr > 3 ? m[3] : 0, nr > 4 ? m[4] : 0)), m2 = amax(nr > 3 ? 0 : m[3], nr > 4 ? 0 : m[4]);
    ISTAMP(5)
    mbar_wait(sb + B_INIT, 1);
    ISTAMP(3)
    if (ROLE == 2) {
#pragma unroll 4
        for (int i = 0; i < S_W2 / 4096; i++) { lds128(u, sb + S_W1 + warp * (S_W2 / 8) + i * 512 + lane * 16); m1 = amax4(m1, u); }
    }
    mbar_wait(sb + B_INIT2, 0);
    ISTAMP(7)
    const int n = w2_units(ROLE, warp) * 4;
#pragma unroll 4
    for (int i = 0; i < n; i++) { lds128(u, sb + w2_base(warp) + i * 512 + lane * 16); m2 = amax4(m2, u); }
    m1 = warp_exp(m1); m2 = warp_exp(m2);
    if (lane == 0) { if (ROLE == 2) red_max_shared(sb + S_EV, m1); red_max_shared(sb + S_EO, m2); }
}
template <bool ATT>
__device__ __forceinline__ void chain_role(const Params& P, const uint32_t sb, const int cta, const int warp, const int lane, const uint32_t epoch, const uint32_t (*wr)[4]) {
    constexpr int NR = ATT ? NRA : NRB, PRE = ATT ? PREA : PREB;
    const int h = cta / 3, ROLE = cta - h * 3;
    ISTAMP(6)
    uint32_t l8 = opq(sb + lane * 8, lane);
    const uint8_t* persu = (const uint8_t*)((ROLE == 1 ? g_km : g_vmt) + h * 512) - (sb >> 1);
    auto persist = [&](int s, int tile, uint32_t r0, uint32_t r1) {
        uint32_t* pp = (uint32_t*)(persu + s * 65536 + (ROLE == 1 ? (tile >> 1) * 512 + (tile & 1) * 128 : tile * 256) + (l8 >> 1));
        pp[0] = r0; pp[ROLE == 1 ? 64 : 32] = r1;
    };
    const uint32_t rk0 = (h & 1) * 3, rd1 = __shfl_sync(0xffffffffu, mapa(sb, rk0 + (ROLE + 1) % 3) - sb, 0), rd2 = __shfl_sync(0xffffffffu, mapa(sb, rk0 + (ROLE + 2) % 3) - sb, 0);
    const uint32_t xo = (ROLE == 2 ? S_XV : S_X + ROLE * 2048) + warp * 256;
    const bool full = w2_full(ROLE, warp);
    const int blk = w2_block(ROLE, warp);
    const uint32_t om = blk * 2048, os = xg_side(blk);
    const uint32_t w1o = sb + w1_base(warp), w2o = sb + w2_base(warp);
    ISTAMP(2)
    if (lane == 0) mbar_arrive(sb + B_READY);
#pragma unroll 1
    for (int s = 0;; s++) {
        l8 += s & P.zero;
        uint32_t r0, r1;
        {
            uint32_t v[4][4], as[(8 - NR) * 8][4], w1a[4];
            float acc[8][4];
            const uint32_t pst = sb + S_P1 + (l8 - sb) * 16 + ((warp * 16) ^ ((l8 & 56) * 2));
#pragma unroll
            for (int i = 0; i < 4; i++) w1a[i] = w1o + (FRAG1((l8 - sb) >> 3) ^ TILE_X(i));
            auto preload = [&]() { static_for<0, PRE>([&](auto I) { load_w1<I.value, NR>(as[I.value], w1a); }); };
#pragma unroll 1
            while (true) {
                uint32_t x[4];
                if (!(PLATE >> ATT & 1)) preload();
                const uint32_t lm = opq(l8 - sb, (l8 - sb) >> 3);
                const uint8_t* pm = P.xb + xg_buf(s) + warp * 8192 + xg_lane(lm >> 3);
                const uint8_t* ps = P.xb + xg_buf(s) + XG_SIDE + warp * 2048 + (lm >> 1);
                pin_ptr(pm); pin_ptr(ps);
                mbar_wait(sb + B_RELM, s & 1);
                if (ATT ? ADELAY : BDELAY) wait_clocks(ATT ? ADELAY : BDELAY);
                PROF(10)
#pragma unroll
                for (int b = 0; b < 4; b++) { ld_relaxed4(v[b], pm + b * 2048); ld_relaxed1n(x[b], ps + (b >> 1) * 1024 + (b & 1) * 256); }
                if (PLATE >> ATT & 1) { preload(); if (PLATE >> (ATT + 2) & 1) sched_fence(); }
                project<NR, PRE, ATT ? FENCEA : FENCEB, 0, PROG>(acc, ROLE == 2, wr, as, v, x, w1a, pst, P.zero);
                const uint32_t bad = xor_or(x[0], x[1], FULL) | xor_or(x[2], x[3], FULL);
                if (tags_ok(bad, 0xffffffffu)) break;
                COUNT_RETRY(warp >> 1)
            }
            PROF(0)
            project<NR, PRE, ATT ? FENCEA : FENCEB, PROG, 64>(acc, ROLE == 2, wr, as, v, nullptr, w1a, pst, 0);
            PROF(1)
            const uint32_t isc = lds32(sb + S_ISC + (s & 1) * 4);
            const uint32_t lq = l8 + ((s >> 3) & P.zero), e1 = s == 63 ? 0 : rd1, e2 = s == 63 ? 0 : rd2;
            uint32_t x[4][4], sel[8], xd[6] = {l8 + xo, l8 + xo + e1, l8 + xo + e2, sb + B_X + e1, sb + B_X + e2, sb + S_P1 + warp * 2048 + (lq & 64) * 16 + (lq & 128) + (lq & 56) * 2};
#pragma unroll
            for (int i = 0; i < 8; i++) sel[i] = (lq & 224) == i * 32 ? 0x3F803F80u : 0u;
            pin<6>(xd); pin<8>(sel);
            if (RFENCE) sched_fence();
            bar_sync(1, 256);
#pragma unroll
            for (int i = 0; i < 4; i++) ldsm4t(x[i], xd[5] + i * 256);
            if (!ATT && l8 == sb + (warp - 3) * 1024) mbar_arrive(sb + B_P1);
            uint32_t em = warp_exp(amax(amax4(amax(amax(v[0][0], v[0][1]), amax(v[0][2], v[0][3])), v[1]), amax4(amax(amax(v[2][0], v[2][1]), amax(v[2][2], v[2][3])), v[3])));
            if (EFENCE2) sched_fence();
            reduce8(x, sel, bf_hi(isc), r0, r1);
            st_async2(xd[1], r0, r1, xd[3]);
            st_async2(xd[2], r0, r1, xd[4]);
            sts64(xd[0], r0, r1);
            if (s == 63) { persist(s, warp, r0, r1); break; }
            if (l8 == sb) sts32(sb + S_EM + warp * 4, em + (isc >> 23));
            __syncwarp();
            if (l8 == sb) mbar_arrive(sb + B_X);
            PROF(2)
        }
        uint32_t w[40][4], w2a[2], odd;
        const uint8_t *po, *pd;
        auto wo_addr = [&]() {
            const uint32_t lo = (l8 + ((s >> 2) & P.zero) - sb) >> 3;
            w2a[0] = w2o + FRAG2(lo); w2a[1] = w2o + (FRAG2(lo) ^ 32);
            po = P.xb + xg_buf(s + 1) + om + xg_lane(lo);
            pd = P.xb + xg_buf(s + 1) + os + lo * 4;
            odd = lo & 4;
            pin_ptr(po); pin_ptr(pd); pin<2>(w2a); pin<1>(&odd);
        };
        uint32_t oa = l8 * 2 + (S_OX - sb);
        if constexpr (ATT) {
            const uint32_t ln = (l8 + ((s >> 4) & P.zero) - sb) >> 3;
            const uint32_t va = sb + S_KV + 8192 + ((warp >> 1) & 1) * 4096 + ((ln & 7) + (ln >> 4) * 8) * 128 + ((((warp & 1) * 4 + ((ln >> 3) & 1)) ^ (ln & 7)) << 4);
            const uint32_t ka = sb + S_KV + (warp & 1) * 2048 + (ln & 15) * 128 + (((ln >> 4) ^ (ln & 7)) << 4);
            uint32_t ad[5] = {sb + S_SX + (ln & 3) * (8 * SROW) + (ln >> 2) * 4 + (warp < 6 ? (warp - 4) * 64 : 128 + (warp - 6) * 32), l8 + S_XV + (warp - 4) * 512,
                              l8 + S_SX + (ln >> 2) * (4 * SROW - 32), oa + (warp - 4) * 512, sb + S_ISC + (~s & 1) * 4};
            if constexpr (AB) { wo_addr(); pin<1>(&oa); }
            pin<5>(ad);
            const uint32_t sa = ad[0], sr = ad[2];
            uint32_t vf[4][4], vm[2][2], q[8][2];
            float S[4][4];
#pragma unroll
            for (int n = 0; n < 4; n++) { S[n][0] = S[n][1] = S[n][2] = S[n][3] = 0.f; }
            mbar_wait(sb + B_KVFULL, s & 1);
            if (warp < 6) {
                uint32_t kf[8][4];
#pragma unroll
                for (int k = 0; k < 8; k++) ldsm4(kf[k], (ka ^ ((k & 3) << 5)) + (k >> 2) * 4096);
#pragma unroll
                for (int i = 0; i < 4; i++) ldsm4t(vf[i], (va ^ ((i & 1) << 5)) + (i >> 1) * 2048);
                mbar_wait(sb + B_X, s & 1);
                PROF(11)
#pragma unroll
                for (int k = 0; k < 8; k++) lds64(q[k], l8 + S_X + k * 256);
#pragma unroll
                for (int k = 0; k < 8; k++) mma16816(S[k & 3], kf[k][0], kf[k][1], kf[k][2], kf[k][3], q[k][0], q[k][1]);
                sts32(sa, __float_as_uint((S[0][0] + S[1][0]) + (S[2][0] + S[3][0])));
                sts32(sa + 4 * SROW, __float_as_uint((S[0][1] + S[1][1]) + (S[2][1] + S[3][1])));
                sts32(sa + 32, __float_as_uint((S[0][2] + S[1][2]) + (S[2][2] + S[3][2])));
                sts32(sa + 4 * SROW + 32, __float_as_uint((S[0][3] + S[1][3]) + (S[2][3] + S[3][3])));
            } else {
#pragma unroll
                for (int i = 0; i < 4; i++) ldsm4t(vf[i], (va ^ ((i & 1) << 5)) + (i >> 1) * 2048);
                uint32_t xa = l8 + S_X + (warp - 6) * 1024;
                pin<1>(&xa);
                mbar_wait(sb + B_X, s & 1);
                PROF(11)
#pragma unroll
                for (int k = 0; k < 8; k++) lds64(q[k], xa + (k >> 2) * 2048 + (k & 3) * 256);
#pragma unroll
                for (int k = 0; k < 4; k++) mma16816(S[k], q[4 + (k & 2)][0], q[4 + (k & 2)][1], q[5 + (k & 2)][0], q[5 + (k & 2)][1], q[k][0], q[k][1]);
                sts32(sa, __float_as_uint((S[0][0] + S[2][0]) + (S[1][2] + S[3][2])));
                sts32(sa + 4 * SROW, __float_as_uint((S[0][1] + S[2][1]) + (S[1][3] + S[3][3])));
            }
            lds64(vm[0], ad[1]); lds64(vm[1], ad[1] + 256);
            PROF(7)
            bar_sync(2, 160);
            const float cs = 0.08838834764831845f * 1.4426950408889634f;
            float E[6][2];
#pragma unroll
            for (int i = 0; i < 6; i++) lds64f(E[(i + 4) % 6], sr + ((i + 4) % 6) * 32);
            const uint32_t isn = lds32(ad[4]);
            E[4][0] += E[5][0]; E[4][1] += E[5][1];
            float m = fmaxf(fmaxf(fmaxf(fmaxf(E[0][0], E[0][1]), fmaxf(E[1][0], E[1][1])), fmaxf(fmaxf(E[2][0], E[2][1]), fmaxf(E[3][0], E[3][1]))), fmaxf(E[4][0], E[4][1]));
            m = fmaxf(m, __shfl_xor_sync(0xffffffffu, m, 1));
            m = fmaxf(m, __shfl_xor_sync(0xffffffffu, m, 2));
            m *= cs;
            if constexpr (AB) static_for<0, PRE3>([&](auto I) { load_w2<I.value>(w[I.value], w2a); });
            uint32_t pa[5];
#pragma unroll
            for (int i = 0; i < 5; i++) { const int k = (i + 4) % 5; E[k][0] = ex2(fmaf(E[k][0], cs, -m)); E[k][1] = ex2(fmaf(E[k][1], cs, -m)); pa[k] = pack2(E[k][0], E[k][1]); }
            if (EFENCE) sched_fence();
            float O[2][4], Z[4];
#pragma unroll
            for (int i = 0; i < 4; i++) { O[0][i] = O[1][i] = Z[i] = 0.f; }
#pragma unroll
            for (int i = 0; i < 2; i++) {
                mma1688(O[i], vm[i][0], vm[i][1], pa[4]);
                mma16816(O[i], vf[i][0], vf[i][1], vf[i][2], vf[i][3], pa[0], pa[1]);
                mma16816(O[i], vf[2 + i][0], vf[2 + i][1], vf[2 + i][2], vf[2 + i][3], pa[2], pa[3]);
            }
            const float z = (((E[4][0] + E[4][1]) + (E[0][0] + E[0][1])) + ((E[1][0] + E[1][1]) + (E[2][0] + E[2][1]))) + (E[3][0] + E[3][1]);
            const float zh = __uint_as_float(__float_as_uint(z) & 0xffff0000u);
            mma1688(Z, isn, isn, pack2(zh, z - zh));
            const float i0 = rcp(Z[0]), i1 = rcp(Z[1]);
            stsm4t(ad[3], pack2(O[0][0] * i0, O[0][1] * i1), pack2(O[0][2] * i0, O[0][3] * i1), pack2(O[1][0] * i0, O[1][1] * i1), pack2(O[1][2] * i0, O[1][3] * i1));
            PROF(4)
            if constexpr (AB) wo_blocks<1, RESA, PRE3, OFENCE / 2>(w, wr + NR * 8, oa, w2a, po, pd, odd);
            else bar_arrive(3, 256);
            if (ROLE != 0) persist(s, warp, r0, r1);
            if (warp == 7 && l8 == sb) mbar_expect(sb + B_X, 4096);
        } else {
            if (ROLE != 0) persist(s, warp, r0, r1);
            wo_addr(); pin<1>(&oa);
            static_for<0, PRE2A>([&](auto I) { load_w2<I.value>(w[I.value], w2a); });
            mbar_wait(sb + B_X, s & 1);
            if (warp == 0) {
                uint32_t sc[2];
                lds64(sc, sb + S_SC);
                const int em = __reduce_max_sync(0xffffffffu, lds32(sb + S_EM + ((l8 >> 1) & 28)));
                if (l8 == sb) sts32(sb + S_ISC + (~s & 1) * 4, min(max(em - 127, (int)sc[1]) + (int)sc[0], 253) * 0x800080u);
                bar_arrive(2, 160);
            }
            wait_clocks(XDELAY - (warp == 0) * 100);
            constexpr int PRE1 = (BB - 1) * 16 - (5 - NRB) * 8 < PRE2 ? (BB - 1) * 16 - (5 - NRB) * 8 : PRE2;
            static_for<PRE2A, PRE1>([&](auto I) { load_w2<I.value>(w[I.value], w2a); });
            if (full) {
                static_for<PRE1, PRE2>([&](auto I) { load_w2<I.value>(w[I.value], w2a); });
                wo_blocks<BB, RESB, PRE2, FENCE2 * 2 + OFENCE % 2>(w, wr + NR * 8, oa, w2a, po, pd, odd);
            } else wo_blocks<BB - 1, RESB1, PRE1, FENCE2 * 2 + OFENCE % 2>(w, wr + NR * 8, oa, w2a, po, pd, odd);
        }
        PROF(5)
        if (l8 == sb) { sts32(sb + S_TO + warp * 4, gtime()); mbar_arrive(sb + B_RED); }
        if (HOLD && !(PLATE >> ATT & 1)) mbar_wait(sb + B_RED, s & 1);
        if (ROLE != 0 && (s & 3) == 3 && l8 == sb) mbar_arrive(sb + B_PERS);
        if (ROLE == 0 && s == 62) return;
    }
    __syncwarp();
    if (l8 == sb) mbar_arrive(sb + B_PERS);
}
#define IP(i)
struct Pipe { uint32_t stage, phase; };
struct Cons {
    uint32_t sb, rel;
    int wg, wq, lane, rank, pair;
    uint32_t atag, nst;
    Pipe p;
};
__device__ __forceinline__ void pipe_next(Pipe& p) { p.stage = (p.stage + 1) & (NSTAGE - 1); p.phase ^= (p.stage == 0); }
__device__ __forceinline__ void release(const Cons& c, uint32_t stage) { if (c.lane < 2) mbar_arrive_cluster(c.rel + stage * 8); }
__device__ __forceinline__ void wait_full(const Cons& c) { mbar_wait(c.sb + B_FULL + c.p.stage * 8, c.p.phase); }

enum { PEND_NONE = 0, PEND_KVO = 1, PEND_HT = 2, PEND_OUT = 3 };
struct Pend { uint32_t pk[64]; int kind, row, col, cnt; };

__device__ __forceinline__ void staging_wait(const Cons& c) { if (c.nst) mbar_wait(c.sb + B_SFREE + c.wg * 8, (c.nst - 1) & 1); }
__device__ __forceinline__ void staging_post(Cons& c, int kind, int row, int col, int cnt) {
    __syncwarp();
    if (c.lane == 0) {
        if (c.wq == 0) { const uint32_t x[4] = {(uint32_t)kind, (uint32_t)row, (uint32_t)col, (uint32_t)cnt}; sts128(c.sb + S_DESC + c.wg * 16, x); }
        mbar_arrive(c.sb + B_SFULL + c.wg * 8);
    }
    c.nst++;
}
__device__ __forceinline__ void drain(const Params& P, Cons& c, Pend& d) {
    const uint32_t* pk = d.pk;
    if (d.kind == PEND_OUT) {
        float* o = P.out + (size_t)(d.row + c.wq * 16 + (c.lane >> 2)) * 2048 + d.col + (c.lane & 3) * 2;
#pragma unroll
        for (int j = 0; j < 16; j++) {
            st_stream2(o + j * 8, bf_lo(pk[j * 2]), bf_hi(pk[j * 2]));
            st_stream2(o + 8 * 2048 + j * 8, bf_lo(pk[j * 2 + 1]), bf_hi(pk[j * 2 + 1]));
        }
    } else {
        const bool ht = d.kind == PEND_HT;
        const int hi = (c.lane >> 3) & 1;
        const uint32_t base = c.sb + S_STG + c.wg * 16384 + ((ht ? hi * 32 + c.wq * 8 : c.wq * 16 + hi * 8) + (c.lane & 7)) * 128;
        staging_wait(c);
#pragma unroll
        for (int j = 0; j < 8; j++) {
            const int ch = (j & 3) * 2 + (c.lane >> 4);
            stsm4(base + (j >> 2) * 8192 + ((ch ^ (c.lane & 7)) << 4), pk[j * 4], pk[j * 4 + 1], pk[j * 4 + 2], pk[j * 4 + 3]);
        }
        fence_async_smem();
        staging_post(c, d.kind, d.row, d.col, (d.col & 128) ? d.cnt : -1);
    }
    if (d.col & 128) d.kind = PEND_NONE;
    d.col += 128;
#pragma unroll
    for (int i = 0; i < 32; i++) d.pk[i] = d.pk[32 + i];
}

constexpr int S_STG2 = 8 * 20480, PEND_BOTH = 8;
__device__ __forceinline__ void drain_both(Cons& c, const Pend& d) {
    const uint32_t base = c.sb + c.wg * 16384 + (c.wq * 16 + ((c.lane >> 3) & 1) * 8 + (c.lane & 7)) * 128;
#pragma unroll
    for (int j = 0; j < 16; j++)
        stsm4(base + (j < 8 ? S_STG : S_STG2) + (j >> 2 & 1) * 8192 + ((((j & 3) * 2 + (c.lane >> 4)) ^ (c.lane & 7)) << 4), d.pk[j * 4], d.pk[j * 4 + 1], d.pk[j * 4 + 2], d.pk[j * 4 + 3]);
    fence_async_smem();
    staging_post(c, PEND_KVO | PEND_BOTH, d.row, d.col, d.cnt);
}

__device__ __forceinline__ void store_warp(const Params& P, uint32_t sb, int wg, int cta) {
    if (cta < 128) {
        for (int i = 0; i < P.xd; i++) __nanosleep(1000);
        const uint32_t e1 = ld_acquire(&g_cnt(C_EPOCH)) + 1;
        const uint4* x = (const uint4*)P.Bx + (cta * 2 + wg) * 1024 + (threadIdx.x & 31);
        uint32_t m = 0;
#pragma unroll 4
        for (int i = 0; i < 32; i++) { const uint4 u = __ldg(x + i * 32); m = amax(amax(m, amax(u.x, u.y)), amax(u.z, u.w)); }
        m = warp_exp(m);
        if (elect_one()) { atomicMax(&g_cnt(C_XMAX), e1 << 8 | m); red_release(&g_cnt(C_XCNT)); }
        __syncwarp();
    }
    const uint32_t stg = sb + S_STG + wg * 16384;
#pragma unroll 1
    for (uint32_t n = 0;; n++) {
        mbar_wait(sb + B_SFULL + wg * 8, n & 1);
        uint32_t x[4];
        lds128(x, sb + S_DESC + wg * 16);
#pragma unroll
        for (int i = 0; i < 4; i++) x[i] = __shfl_sync(0xffffffffu, x[i], 0);
        if (x[0] == PEND_NONE) break;
        const bool ht = x[0] == PEND_HT;
        const CUtensorMap* m = &P.tm[ht ? M_HTS : M_KVO];
        const uint64_t pol = P.pol[ht ? 2 : x[1] >= 4096 ? 1 : (x[1] & 2047) < 1536 ? 0 : 10];
        if (elect_one()) {
#pragma unroll
            for (int i = 0; i < 4; i++) tma_store2d(m, x[2] + (i >> 1) * 64, x[1] + (i & 1) * (ht ? 1024 : 32), stg + i * 4096, pol);
            if (x[0] & PEND_BOTH) {
#pragma unroll 1
                for (int i = 0; i < 4; i++) tma_store2d(m, x[2] + 128 + (i >> 1) * 64, x[1] + (i & 1) * 32, stg + (S_STG2 - S_STG) + i * 4096, pol);
            }
            bulk_commit();
            bulk_wait_read();
            mbar_arrive(sb + B_SFREE + wg * 8);
            if ((int)x[3] >= 0) { bulk_wait_all(); fence_async(); red_release(&g_cnt(x[3])); }
        }
        __syncwarp();
    }
}

template <int TA, int TB, bool FIRST>
__device__ __forceinline__ void issue_ktile(float* acc, const Cons& c) {
    const uint32_t a = c.sb + c.p.stage * STAGE + c.wg * 8192, b = c.sb + c.p.stage * STAGE + 16384;
    const uint64_t da = mkdesc(a, TA ? 8192 : 16, 1024, 1), db = mkdesc(b, TB ? 8192 : 16, 1024, 1);
    wg_fence();
#pragma unroll
    for (int k = 0; k < 4; k++) {
        if (FIRST && k == 0) wgmma_ss256_first<TA, TB>(acc, da, db);
        else wgmma_ss256<TA, TB>(acc, da + (TA ? 128 : 2) * k, db + (TB ? 128 : 2) * k);
    }
    wg_commit();
}
template <bool KVONLY, bool FIRST>
__device__ __forceinline__ void issue_any(float* acc, const Cons& c, int type) {
    wait_full(c);
    if (!KVONLY && type == T_A1) issue_ktile<0, 0, FIRST>(acc, c);
    else if (!KVONLY && type == T_A2) issue_ktile<1, 0, FIRST>(acc, c);
    else issue_ktile<0, 1, FIRST>(acc, c);
}
template <bool KVONLY = false>
__device__ __forceinline__ void mainloop(float* acc, const Params& P, Cons& c, Pend& d, int type, int nk) {
    issue_any<KVONLY, true>(acc, c, type);
    if (!KVONLY) { IP(0) }
    uint32_t prev = c.p.stage;
    pipe_next(c.p);
#pragma unroll 1
    for (int kt = 1; kt < nk; kt++) {
        if (!KVONLY && d.kind != PEND_NONE && kt != 2) drain(P, c, d);
        issue_any<KVONLY, false>(acc, c, type);
        wg_wait<1>();
        release(c, prev);
        prev = c.p.stage;
        pipe_next(c.p);
    }
    d.kind = PEND_NONE;
    wg_wait<0>();
    pin<128>(acc);
    release(c, prev);
    if (!KVONLY) { IP(1) }
}
__device__ __forceinline__ void pack_half(uint32_t* pk, const float* a) {
#pragma unroll
    for (int i = 0; i < 32; i++) pk[i] = pack2(a[2 * i], a[2 * i + 1]);
}

__device__ __forceinline__ void epi_kv(const float* acc, const Cons& c, Pend& d, int mb, int nb) {
    pack_half(d.pk, acc); pack_half(d.pk + 32, acc + 64);
    d.kind = PEND_KVO; d.row = (nb >> 4) * 2048 + mb * 256 + c.rank * 128 + c.wg * 64; d.col = (nb & 15) * 256; d.cnt = C_KV + mb;
}

__device__ __forceinline__ void qa_scores(float* S, float* Sm, const uint32_t* q, Cons& c) {
    wait_full(c);
    const uint32_t st = c.sb + c.p.stage * STAGE;
    const uint64_t dk = mkdesc(st + c.wg * 8192, 16, 1024, 1), dm = mkdesc(st + 32768 + c.wg * 4096, 128, 2048, 0);
    wg_fence();
#pragma unroll
    for (int i = 0; i < 8; i++) wgmma_rs64<0>(S, q + i * 4, dk + (i >> 2) * 1024 + (i & 3) * 2, i != 0);
#pragma unroll
    for (int i = 0; i < 8; i++) wgmma_rs16<0>(Sm, q + i * 4, dm + i * 16, i != 0);
    wg_commit();
    pipe_next(c.p);
}
__device__ __forceinline__ void qa_softmax(uint32_t (*pa)[4], const float* S, const float* Sm, const Cons& c) {
    const int t = c.lane & 3, i0 = (c.wq & 1) * 16 + (c.lane >> 2) - 2 * t;
    const bool sg = c.wq >= 2;
    const float cs = 0.08838834764831845f * 1.4426950408889634f;
    float x[2][10];
#pragma unroll
    for (int r = 0; r < 2; r++) {
#pragma unroll
        for (int j = 0; j < 4; j++)
#pragma unroll
            for (int e = 0; e < 2; e++) {
                const float v = sg ? S[16 + j * 4 + r * 2 + e] : S[j * 4 + r * 2 + e];
                x[r][j * 2 + e] = (j * 8 + e - r * 8 > i0) ? -1e9f / 0.08838834764831845f : v;
            }
        x[r][8] = sg ? Sm[4 + r * 2] : Sm[r * 2];
        x[r][9] = sg ? Sm[5 + r * 2] : Sm[1 + r * 2];
        float m = fmaxf(fmaxf(fmaxf(fmaxf(x[r][0], x[r][1]), fmaxf(x[r][2], x[r][3])), fmaxf(fmaxf(x[r][4], x[r][5]), fmaxf(x[r][6], x[r][7]))), fmaxf(x[r][8], x[r][9]));
        m = fmaxf(m, __shfl_xor_sync(0xffffffffu, m, 1));
        m = fmaxf(m, __shfl_xor_sync(0xffffffffu, m, 2));
        m *= -cs;
#pragma unroll
        for (int i = 0; i < 10; i++) x[r][i] = ex2(fmaf(x[r][i], cs, m));
        float sum = (((x[r][0] + x[r][1]) + (x[r][2] + x[r][3])) + ((x[r][4] + x[r][5]) + (x[r][6] + x[r][7]))) + (x[r][8] + x[r][9]);
        sum += __shfl_xor_sync(0xffffffffu, sum, 1);
        sum += __shfl_xor_sync(0xffffffffu, sum, 2);
        const float inv = rcp(sum);
#pragma unroll
        for (int i = 0; i < 10; i++) x[r][i] *= inv;
    }
#pragma unroll
    for (int ks = 0; ks < 2; ks++)
#pragma unroll
        for (int i = 0; i < 4; i++) {
            const uint32_t p = pack2(x[i & 1][ks * 4 + (i >> 1) * 2], x[i & 1][ks * 4 + (i >> 1) * 2 + 1]);
            pa[ks][i] = sg ? 0u : p;
            pa[2 + ks][i] = sg ? p : 0u;
        }
#pragma unroll
    for (int r = 0; r < 2; r++) {
        const uint32_t p = pack2(x[r][8], x[r][9]);
        pa[4][r] = sg ? 0u : p;
        pa[4][2 + r] = sg ? p : 0u;
    }
}
__device__ __forceinline__ void qa_values(float* O, uint32_t (*pa)[4], Cons& c) {
    wait_full(c);
    const uint32_t st = c.sb + c.p.stage * STAGE;
    const uint64_t dv = mkdesc(st + c.wg * 8192, 16384, 1024, 1), dm = mkdesc(st + 32768 + c.wg * 4096, 2048, 128, 0);
    pin<20>(&pa[0][0]);
    wg_fence();
#pragma unroll
    for (int ks = 0; ks < 4; ks++) wgmma_rs128<1>(O, pa[ks], dv + ks * 128, ks != 0);
    wgmma_rs128<0>(O, pa[4], dm, 1);
    wg_commit();
    pipe_next(c.p);
}
__device__ __forceinline__ void epi_qa(const float* acc, Cons& c, Pend& d, int mb, int nb) {
    uint32_t q[64], pa[2][5][4];
    float S0[32] = {}, M0[8] = {}, S1[32] = {}, M1[8] = {}, O0[64] = {}, O1[64] = {};
    const uint32_t k0 = c.p.stage;
    pack_half(q, acc);
    pin<32>(q); pin<32>(S0); pin<8>(M0);
    qa_scores(S0, M0, q, c);
    pack_half(q + 32, acc + 64);
    pin<32>(q + 32); pin<32>(S1); pin<8>(M1);
    qa_scores(S1, M1, q + 32, c);
    wg_wait<1>();
    pin<32>(S0); pin<8>(M0);
    release(c, k0);
    qa_softmax(pa[0], S0, M0, c);
    wg_wait<0>();
    pin<32>(S1); pin<8>(M1); pin<64>(q);
    release(c, (k0 + 1) & (NSTAGE - 1));
    pin<64>(O0);
    qa_values(O0, pa[0], c);
    qa_softmax(pa[1], S1, M1, c);
    pin<64>(O1);
    qa_values(O1, pa[1], c);
    wg_wait<1>();
    pin<64>(O0); pin<20>(&pa[0][0][0]);
    release(c, (k0 + 2) & (NSTAGE - 1));
    pack_half(d.pk, O0);
    wg_wait<0>();
    pin<64>(O1); pin<20>(&pa[1][0][0]);
    release(c, (k0 + 3) & (NSTAGE - 1));
    pack_half(d.pk + 32, O1);
    d.kind = PEND_KVO; d.row = 4096 + mb * 256 + c.rank * 128 + c.wg * 64; d.col = nb * 256; d.cnt = C_O + mb;
}

__device__ __forceinline__ void epi_op(const float* acc, const Cons& c, Pend& d, int mb, int nb) {
    pack_half(d.pk, acc); pack_half(d.pk + 32, acc + 64);
    d.kind = PEND_OUT; d.row = mb * 256 + c.rank * 128 + c.wg * 64; d.col = 1024 + nb * 256;
}

__device__ __forceinline__ void epi_a2(float* acc, const Params& P, Cons& c, int mb, int col0) {
    const int g = c.lane >> 2, t = c.lane & 3;
    const int row = mb * 256 + (g >> 1) * 64 + (c.rank * 16 + c.wg * 8 + c.wq * 2) * 2 + (g & 1);
    float* o = P.out + (size_t)row * 2048 + col0 + t * 2;
#pragma unroll 1
    for (int hf = P.zero; hf < 2; hf++) {
    wait_full(c);
    const uint32_t st = c.sb + c.p.stage * STAGE, xa = st + (c.wg * 64 + c.wq * 16 + g) * 128 + t * 4 + (g << 4), da = st + 32768 + t * 4;
#pragma unroll
    for (int j = 0; j < 16; j++) {
        const float* a = acc + j * 4;
        const uint32_t ad = (xa ^ ((j & 7) << 4)) + (j >> 3) * 16384;
        const uint32_t x0 = lds32(ad), x1 = lds32(ad + 1024), dv = lds32(da + j * 16);
        const uint32_t u0 = mul_bf2(x0, dv), u1 = mul_bf2(x1, dv);
        st_stream2(o + j * 8, a[0] + bf_lo(u0), a[1] + bf_hi(u0));
        st_stream2(o + 2 * 2048 + j * 8, a[2] + bf_lo(u1), a[3] + bf_hi(u1));
    }
    __syncwarp();
    release(c, c.p.stage);
    pipe_next(c.p);
    o += 128;
#pragma unroll
    for (int i = 0; i < 64; i++) acc[i] = acc[64 + i];
    }
}

#define TSTAMP(i)
__device__ __forceinline__ float2 cmul(float2 a, float2 b) { return make_float2(fmaf(a.x, b.x, -a.y * b.y), fmaf(a.x, b.y, a.y * b.x)); }
__device__ __forceinline__ float2 cfma(float2 a, float2 b, float2 u) { return make_float2(fmaf(a.x, b.x, fmaf(-a.y, b.y, u.x)), fmaf(a.x, b.y, fmaf(a.y, b.x, u.y))); }
__device__ __forceinline__ float4 ssm_coef(float lre, float lim, float logdt) {
    const float dt = __bfloat162float(__float2bfloat16(expf(logdt)));
    const float ea = expf(dt * lre);
    float sn, cn;
    sincosf(dt * lim, &sn, &cn);
    const float br = ea * cn, bi = ea * sn, nr = br - 1.f;
    float cr, ci;
    if (fabsf(lre) >= fabsf(lim)) { const float r = lim / lre, dn = lre + lim * r; cr = (nr + bi * r) / dn; ci = (bi - nr * r) / dn; }
    else { const float r = lre / lim, dn = lre * r + lim; cr = (nr * r + bi) / dn; ci = (bi * r - nr) / dn; }
    return make_float4(br, bi, cr, ci);
}
__device__ __forceinline__ void epi_a1(const float* acc, const Params& P, const Cons& c, Pend& d, int mb, int nb, uint32_t atag) {
    const int t = c.lane & 3;
    const int p = nb * 128 + c.rank * 64 + c.wg * 32 + c.wq * 8 + (c.lane >> 2);
    const float4 cf = __ldcg(&g_coef[p]);
    const float2 lam = make_float2(cf.x, P.swap_ri ? -cf.y : cf.y);
    const float a0 = P.swap_ri ? -2.f * cf.w : 2.f * cf.z, a1 = P.swap_ri ? 2.f * cf.z : -2.f * cf.w;
    const float b0 = P.swap_ri ? -2.f * cf.z : -2.f * cf.w, b1 = P.swap_ri ? -2.f * cf.w : -2.f * cf.z;
    float2 h = make_float2(0.f, 0.f);
#pragma unroll 1
    for (int round = P.zero; round < 2; round++) {
#pragma unroll
        for (int j = 0; j < 32; j++) {
            h = cfma(lam, h, make_float2(acc[j * 4], acc[j * 4 + 2]));
            const float r0 = fmaf(a0, h.x, a1 * h.y), m0 = fmaf(b0, h.x, b1 * h.y);
            h = cfma(lam, h, make_float2(acc[j * 4 + 1], acc[j * 4 + 3]));
            d.pk[j * 2] = pack2(r0, fmaf(a0, h.x, a1 * h.y));
            d.pk[j * 2 + 1] = pack2(m0, fmaf(b0, h.x, b1 * h.y));
        }
        if (round) continue;
        float2 l64 = lam;
#pragma unroll
        for (int i = 0; i < 6; i++) l64 = cmul(l64, l64);
        const float2 l128 = cmul(l64, l64), l256 = cmul(l128, l128);
        float2 o = make_float2(__shfl_up_sync(0xffffffffu, h.x, 1), __shfl_up_sync(0xffffffffu, h.y, 1));
        if (t >= 1) h = cfma(l64, o, h);
        o = make_float2(__shfl_up_sync(0xffffffffu, h.x, 2), __shfl_up_sync(0xffffffffu, h.y, 2));
        if (t >= 2) h = cfma(l128, o, h);
        IP(2)
        if (t == 3) st_relaxed2(&g_agg[mb * 1024 + p], (__float_as_uint(h.x) & ~1u) | atag, __float_as_uint(h.y));
        h = make_float2(__shfl_up_sync(0xffffffffu, h.x, 1), __shfl_up_sync(0xffffffffu, h.y, 1));
        if (t == 0) h = make_float2(0.f, 0.f);
        uint32_t ax[7], ay[7];
        while (true) {
            uint32_t bad = 0;
#pragma unroll
            for (int j = 0; j < 7; j++) { ax[j] = atag; ay[j] = 0; ld_relaxed2_if(ax[j], ay[j], &g_agg[j * 1024 + p], j < mb); }
#pragma unroll
            for (int j = 0; j < 7; j++) bad |= ax[j] ^ atag;
            if (tags_ok(bad)) break;
            __nanosleep(2 * POLLNS);
        }
        float2 carry = make_float2(0.f, 0.f);
#pragma unroll
        for (int j = 0; j < 7; j++) if (j < mb) carry = cfma(l256, carry, make_float2(__uint_as_float(ax[j]), __uint_as_float(ay[j])));
        float2 w = (t & 1) ? l64 : make_float2(1.f, 0.f);
        if (t & 2) w = cmul(w, l128);
        h = cfma(w, carry, h);
        IP(3)
    }
    IP(4)
    d.kind = PEND_HT; d.row = nb * 128 + c.rank * 64 + c.wg * 32; d.col = mb * 256; d.cnt = C_HT + mb;
}

__device__ __forceinline__ uint32_t fresh_tid() { uint32_t t; asm volatile("mov.u32 %0, %%tid.x;" : "=r"(t)); return t; }
__device__ __forceinline__ uint32_t acquire_stage(uint32_t sb, Pipe& p, uint32_t bytes) {
    mbar_wait(sb + B_EMPTY + p.stage * 8, p.phase ^ 1);
    mbar_expect_e(sb + B_FULL + p.stage * 8, bytes);
    return p.stage;
}
__device__ __forceinline__ void producer(const Params& P, const uint32_t sb, const int cta, const uint32_t epoch) {
    Pipe p = {0, 0};
    uint32_t resume = 1;
    const uint32_t e1 = epoch + 1;
    const int rank = cta & 1;
    const uint16_t both = 3 << (__shfl_sync(0xffffffffu, cluster_rank(), 0) & ~1u);
    for (int it = ITEM_OFF(cta >> 1); it < ITEM_OFF((cta >> 1) + 1); it++) {
        const int item = ITEM(it), type = (item >> 8) & 7, mb = (item >> 5) & 7, nb = item & 31, half = item >> 12 & 1, hw = item >> 13;
        if (type == T_CHAIN) {
            const int h = cta / 3, role = cta - h * 3;
            uint32_t* flag = &g_cnt(C_FLAG + (role == 2 ? 32 : 0) + h);
            if (role) { wait_count(&g_cnt(C_KV), e1 * 128); fence_async(); }
#pragma unroll 1
            for (int s = 0; s < 64 && role != 0; s++) {
                if (s < 63) {
                    mbar_wait(sb + B_GO, s & 1);
                    tma3d_mc_e(sb + S_KV + (role - 1) * 8192, &P.tm[M_SEG], 0, (role - 1) * 2048 + s * 32, h * 2, sb + B_KVFULL, 7 << ((h & 1) * 3), P.pol[s < 48 ? 8 : 11]);
                    if ((s & 7) == 7) { wait_count(&g_cnt(C_KV + 1 + (s >> 3)), e1 * 128); fence_async(); }
                    tma_prefetch3d_e(&P.tm[M_SEG], 0, (role - 1) * 2048 + s * 32 + 32, h * 2);
                }
                if (s > 0 && ((s & 3) == 0 || s == 63)) {
                    const int i = (s - 1) >> 2;
                    mbar_wait(sb + B_PERS, i & 1);
                    asm volatile("{\n.reg .pred E;\nelect.sync _|E, 0xffffffff;\n@E st.release.gpu.global.u32 [%0], %1;\n}" ::"l"(flag), "r"(epoch * 64 + i * 4 + 4) : "memory");
                }
            }
            if (role == 0) {
                const int lane = threadIdx.x & 31;
                if (lane == 0) mbar_arrive(sb + B_RELM);
#pragma unroll 1
                for (int s = 0; s < 63; s++) {
                    mbar_wait(sb + B_P1, s & 1);
                    if (s > 0) {
                        st_relaxed4(P.xb + xg_buf(s - 1) + h * 2048 + xg_lane(lane), 0, 0, 0, 0);
                        st_relaxed1(P.xb + xg_buf(s - 1) + xg_side(h) + lane * 4, 0);
                        __threadfence();
                    }
                    __syncwarp();
                    if (lane == 0) mbar_arrive(sb + B_RELM);
                }
            }
            if ((threadIdx.x & 31) < M_C1 - 1) asm volatile("prefetch.tensormap [%0];" ::"l"(&P.tm[1 + (threadIdx.x & 31)]) : "memory");
            resume = 0;
            continue;
        }
        const int m0 = mb * 256 + rank * 128, ssm = type >= T_A1;
        const CUtensorMap* ma = &P.tm[max(type, 1) + half * M_HALF];
        const CUtensorMap* mw = &P.tm[type ? M_WV + type : M_WK + (nb >> 4)];
        const int nk = type == T_OP ? 64 : type == T_A2 ? 32 : 16;
        const int a3 = type == T_A1 ? nb * 16 + rank * 8 + hw * 4 : type == T_A2 ? mb * 4 + rank * 2 + hw : (type == T_OP ? 4096 : 0) + m0 + hw * 64;
        const int b3 = type == T_A1 ? mb * 128 + rank * 16 : type == T_A2 ? (nb * 2 + rank) * 128 : (nb & 15) * 4 + rank * 2;
        if (type) {
            wait_count(&g_cnt(type == T_A1 ? C_COEF : (type >> 1) * 8 + mb), e1 * (type == T_A1 ? 4 : 128 >> (type >> 1)));
            fence_async();
        }
        if (type == T_A1) l2_prefetch_e(g_coef + nb * 128 + rank * 64, 1024);
        auto arrived = [&]() {
            const uint32_t t = fresh_tid();
            return __all_sync(0xffffffffu, (int32_t)(ld_acquire(&g_cnt(C_FLAG + (t & 2) * 16 + nb * 2 + (t & 1))) - (epoch * 64 + mb * 8 + rank * 4 + 4)) >= 0);
        };
        bool passed = false;
        mbar_wait(sb + B_RESUME, resume);
#pragma unroll 1
        for (int kt = 0; kt < nk; kt++) {
            if (type == T_QA && kt == 9) passed = arrived();
            const uint32_t st = acquire_stage(sb, p, STAGE - half * 8192), bar = sb + B_FULL + st * 8;
            const int a1 = type == T_A2 ? kt * 64 : 0, b0 = ssm ? (kt & 15) * 64 : 0;
            tma4d_e(sb + st * STAGE + hw * 8192, ma, kt * 64 - a1, a1, a3, bar, P.pol[11]);
            tma4d_mc_e(sb + st * STAGE + 16384 + rank * 16384, mw + (ssm & kt >> 4), b0, ssm ? 0 : kt * 64, b3, bar, both, P.pol[item == (item & 31) + 224 ? 9 : 11]);
            if (type == T_QA && kt < 8) tma_prefetch4d_e(&P.tm[M_OA], nb * 256 + (kt & 3) * 64, (kt >> 2) * 2048 + m0);
            pipe_next(p);
        }
        if (type == T_QA) {
            while (!passed) { passed = arrived(); if (!passed) __nanosleep(POLLNS); }
            fence_async();
        }
        const int q = type == T_QA;
#pragma unroll 1
        for (int e = 0; e < (q ? 4 : type == T_A2 ? 2 : 0); e++) {
            const uint32_t st = acquire_stage(sb, p, q ? 40960 : 32768 + 256), bar = sb + B_FULL + st * 8, dst = sb + st * STAGE;
#pragma unroll 1
            for (int i = 0; i < 2; i++) tma4d_e(dst + i * 16384, &P.tm[q ? M_OA : M_AX], nb * 256 + (e & 1) * 128 + i * 64, 0, q ? (e >> 1) * 2048 + m0 : mb * 128 + rank * 16, bar, P.pol[q ? 3 : 11]);
            const uint8_t* src = q ? (const uint8_t*)(((e >> 1) ? g_vmt : g_km) + ((mb * 8 + rank * 4) * 32 + nb * 2 + (e & 1)) * 512) : (const uint8_t*)(P.Dskip + nb * 256 + e * 128);
#pragma unroll 1
            for (int i = 0; i < (q ? 4 : 1); i++) bulk_g2s_e(dst + 32768 + i * 2048, src + i * 65536, q ? 2048 : 256, bar);
            pipe_next(p);
        }
    }
}

__device__ __forceinline__ uint32_t fresh_ctaid() { uint32_t t; asm volatile("mov.u32 %0, %%ctaid.x;" : "=r"(t)); return t; }
__device__ __forceinline__ void reset_state(const Params& P, Cons& c, Pend& d, uint32_t sb, bool resumed) {
    const uint32_t t = fresh_tid(), b = fresh_ctaid() + P.cta0;
    const int w = __shfl_sync(0xffffffffu, t >> 5, 0);
    c.sb = sb; c.wg = w >> 2; c.wq = w & 3; c.lane = t & 31;
    c.rank = __shfl_sync(0xffffffffu, b & 1, 0); c.pair = __shfl_sync(0xffffffffu, b >> 1, 0);
    c.rel = mapa(sb + B_EMPTY, cluster_rank() ^ (c.lane & 1));
    c.atag = (ld_acquire(&g_cnt(C_EPOCH)) + 1) & 1;
    c.p.stage = 0; c.p.phase = 0;
    c.nst = resumed && c.pair < NCHAIN;
    d = Pend{};
}
#define PROF_ITEM(i, item)

__global__ void __launch_bounds__(384, 1) fused_kernel(const __grid_constant__ Params P) {
    extern __shared__ __align__(1024) uint8_t smem[];
    const uint32_t sb = smem_u32(smem);
    asm volatile("griddepcontrol.launch_dependents;");
    declare_fence(P.zero);
    const int tid = threadIdx.x, lane = tid & 31;
    const int warp = __shfl_sync(0xffffffffu, tid >> 5, 0);
    const int cta = __shfl_sync(0xffffffffu, blockIdx.x + P.cta0, 0), pair = cta >> 1, rank = cta & 1;
    if (tid == 0) {
        if (sb & 1023) spin_fault();
        for (int i = 0; i < NSTAGE; i++) { mbar_init(sb + B_FULL + i * 8, 1); mbar_init(sb + B_EMPTY + i * 8, 16); }
        mbar_init(sb + B_RESUME, 2);
        mbar_init(sb + B_KVFULL, 1);
        mbar_init(sb + B_GO, 3); mbar_init(sb + B_RED, 8); mbar_init(sb + B_P1, 1); mbar_init(sb + B_PERS, 8); mbar_init(sb + B_INIT, 8); mbar_init(sb + B_INIT2, 8);
        mbar_init(sb + B_READY, 8);
        for (int i = 0; i < 2; i++) { mbar_init(sb + B_SFULL + i * 8, 4); mbar_init(sb + B_SFREE + i * 8, 1); }
        mbar_init(sb + B_RELM, cta % 3 ? 1 : 2); mbar_init(sb + B_X, 9);
        asm volatile("fence.mbarrier_init.release.cluster;" ::: "memory");
        mbar_expect(sb + B_X, 4096);
        sts64(sb + S_EV, 0, 0); mbar_init(sb + B_DONE, 2);
    }
    cluster_sync();
    if (warp >= 8) {
        asm volatile("setmaxnreg.dec.sync.aligned.u32 24;");
        if (warp == 8) {
            producer(P, sb, cta, __shfl_sync(0xffffffffu, ld_acquire(&g_cnt(C_EPOCH)), 0));
            asm volatile("barrier.cluster.arrive.relaxed.aligned;\nbarrier.cluster.wait.aligned;" ::: "memory");
        } else if (warp == 9) {
            for (int i = 0; i < P.pd; i++) __nanosleep(1000);
            if (pair < 64) l2_prefetch((const char*)(rank ? P.Wo : P.Wq) + (size_t)(pair * 32 + lane) * 4096, 4096);
            if (pair < NCHAIN) pacer(P, sb, cta, lane, __shfl_sync(0xffffffffu, ld_acquire(&g_cnt(C_EPOCH)), 0));
            mbar_wait_bounded(sb + B_DONE, 0);
        } else {
            store_warp(P, sb, warp - 10, cta);
        }
    } else {
        asm volatile("setmaxnreg.inc.sync.aligned.u32 240;");
        Cons c;
        Pend d;
        if (pair < NCHAIN) {
            reset_state(P, c, d, sb, false);
            {
                const int item = ITEM(ITEM_OFF(pair));
                PROF_ITEM(0, item)
                float acc[128];
                mainloop<true>(acc, P, c, d, T_KV, 16);
                ISTAMP(4)
                mbar_wait(sb + B_EMPTY + warp * 20480 / STAGE * 8, 1);
                mbar_wait(sb + B_EMPTY + (warp * 20480 + 20479) / STAGE * 8, 1);
                chain_load(P, sb, cta, warp, lane, 0);
                epi_kv(acc, c, d, (item >> 5) & 7, item & 31);
            }
            ISTAMP(9)
            mbar_wait(sb + B_EMPTY + 3 * 8, 1);
            drain_both(c, d);
            ISTAMP(10)
            uint32_t wr[40][4];
            chain_fetch(P, sb, cta, warp, lane, wr);
            PROF_ITEM(1, T_CHAIN << 8)
            chain_bounds(sb, cta, warp, lane, wr);
            ISTAMP(11)
            const uint32_t epoch = __shfl_sync(0xffffffffu, ld_acquire(&g_cnt(C_EPOCH)), 0);
            if (warp < 4) chain_role<false>(P, sb, cta, warp, lane, epoch, wr);
            else chain_role<true>(P, sb, cta, warp, lane, epoch, wr);
            fence_async_smem();
            bar_sync(1, 256);
            const uint32_t t2 = fresh_tid();
            if (t2 < 2) mbar_arrive_cluster(mapa(sb + B_RESUME, cluster_rank() ^ t2));
        } else if (pair >= NPAIR - 2) {
            const int ch = (pair - (NPAIR - 2)) * 512 + rank * 256 + tid;
            g_coef[ch] = ssm_coef(__bfloat162float(P.Lre[ch]), __bfloat162float(P.Lim[ch]), __bfloat162float(P.logdt[ch]));
            bar_sync(1, 256);
            if (tid == 0) red_release(&g_cnt(C_COEF));
        }
        reset_state(P, c, d, sb, true);
        int it = ITEM_OFF(c.pair) + (c.pair < NCHAIN ? 2 : 0);
        const int end = ITEM_OFF(c.pair + 1);
        for (;; it++) {
            const bool last = it == end;
            const int item = ITEM(it), type = (item >> 8) & 7, mb = (item >> 5) & 7, nb = item & 31;
            const bool idle = (item >> 12) == 3 - 2 * c.wg;
            if (d.kind != PEND_NONE && (last || idle || (ITEM(it - 1) & URGENT) || !bar_and(5 + c.wg, mbar_try(sb + B_FULL + c.p.stage * 8, c.p.phase)))) {
#pragma unroll 1
                while (d.kind != PEND_NONE) drain(P, c, d);
            }
            if (last) break;
            const int nk = type == T_OP ? 64 : type == T_A2 ? 32 : 16;
            PROF_ITEM(it - ITEM_OFF(c.pair), item)
            if (idle) {
#pragma unroll 1
                for (int kt = nk + (type == T_A2 ? 2 : type == T_QA ? 4 : 0); kt > 0; kt--) { wait_full(c); release(c, c.p.stage); pipe_next(c.p); }
                continue;
            }
            float acc[128];
            mainloop(acc, P, c, d, type, nk);
            if (type == T_KV) epi_kv(acc, c, d, mb, nb);
            else if (type == T_QA) epi_qa(acc, c, d, mb, nb);
            else if (type == T_OP) epi_op(acc, c, d, mb, nb);
            else if (type == T_A1) epi_a1(acc, P, c, d, mb, nb, c.atag);
            else epi_a2(acc, P, c, mb, nb * 256);
        }
        staging_wait(c);
        staging_post(c, PEND_NONE, 0, 0, 0);
        if (c.wq == 0 && c.lane == 0) mbar_arrive(sb + B_DONE);
        cluster_sync();
        if (c.wg == 0 && c.wq == 0 && c.lane == 0 && atomicInc(&g_cnt(C_DONE), NPAIR * 2 - 1) == NPAIR * 2 - 1) { __threadfence(); atomicAdd(&g_cnt(C_EPOCH), 1); }
    }
}

typedef CUresult (*EncodeFn)(CUtensorMap*, CUtensorMapDataType, cuuint32_t, void*, const cuuint64_t*, const cuuint64_t*, const cuuint32_t*, const cuuint32_t*,
                             CUtensorMapInterleave, CUtensorMapSwizzle, CUtensorMapL2promotion, CUtensorMapFloatOOBfill);
void encode(EncodeFn fn, CUtensorMap* m, const void* base, int rank, const uint64_t* dims, const uint64_t* strides, const uint32_t* box, CUtensorMapSwizzle swz = CU_TENSOR_MAP_SWIZZLE_128B) {
    cuuint64_t d[5], s[5]; cuuint32_t b[5], e[5];
    for (int i = 0; i < rank; i++) { d[i] = dims[i]; b[i] = box[i]; e[i] = 1; if (i) s[i - 1] = strides[i - 1]; }
    fn(m, CU_TENSOR_MAP_DATA_TYPE_BFLOAT16, rank, (void*)base, d, s, b, e, CU_TENSOR_MAP_INTERLEAVE_NONE, swz,
       CU_TENSOR_MAP_L2_PROMOTION_L2_256B, CU_TENSOR_MAP_FLOAT_OOB_FILL_NONE);
}
void map_kmajor(EncodeFn fn, CUtensorMap* m, const void* base, uint64_t rows, uint64_t cols, uint32_t box_rows) {
    const uint64_t d[4] = {cols, 1, 1, rows}, s[3] = {cols * 2, cols * 2, cols * 2}; const uint32_t b[4] = {64, 1, 1, box_rows};
    encode(fn, m, base, 4, d, s, b);
}
void map_mnmajor(EncodeFn fn, CUtensorMap* m, const void* base, uint64_t krows, uint64_t cols, uint32_t groups = 2) {
    const uint64_t d[4] = {64, krows, 1, cols / 64}, s[3] = {cols * 2, 128, 128}; const uint32_t b[4] = {64, 64, 1, groups};
    encode(fn, m, base, 4, d, s, b);
}
void map_store(EncodeFn fn, CUtensorMap* m, const void* base, uint64_t rows, uint64_t cols) {
    const uint64_t d[2] = {cols, rows}, s[1] = {cols * 2}; const uint32_t b[2] = {64, 32};
    encode(fn, m, base, 2, d, s, b);
}

}

extern "C" void kernel_launch(void* const* d_in, const int* in_sizes, int n_in, void* d_out, int out_size) {
    static Params P;
    static EncodeFn fn = nullptr;
    if (!fn) {
        cudaDriverEntryPointQueryResult q;
        cudaGetDriverEntryPoint("cuTensorMapEncodeTiled", (void**)&fn, cudaEnableDefault, &q);
        cudaFuncSetAttribute(fused_kernel, cudaFuncAttributeMaxDynamicSharedMemorySize, S_TOTAL);
    }
    const bf16* in[15];
    for (int i = 0; i < 15; i++) in[i] = (const bf16*)d_in[i];
    void *kvo, *ht;
    cudaGetSymbolAddress(&kvo, g_kvo);
    cudaGetSymbolAddress(&ht, g_ht);
    map_kmajor(fn, &P.tm[M_BX], in[9], 2048, 1024, 128);
    map_mnmajor(fn, &P.tm[M_WQ], in[11], 1024, 4096);
    map_mnmajor(fn, &P.tm[M_WK], in[12], 1024, 4096);
    map_mnmajor(fn, &P.tm[M_WV], in[13], 1024, 4096);
    map_mnmajor(fn, &P.tm[M_WO], in[14], 4096, 1024);
    map_kmajor(fn, &P.tm[M_OA], kvo, 3 * 2048, 4096, 128);
    P.swap_ri = in[4] < in[3];
    {
        const bf16* lo = P.swap_ri ? in[4] : in[3];
        const uint64_t diff = (uint64_t)((const char*)(P.swap_ri ? in[3] : in[4]) - (const char*)lo);
        const uint64_t d[4] = {1024, 8, 2, 128}, s[3] = {2048, diff, 16384}; const uint32_t b[4] = {64, 8, 2, 8}, bh[4] = {64, 8, 2, 4};
        encode(fn, &P.tm[M_AB], lo, 4, d, s, b);
        encode(fn, &P.tm[M_AB + M_HALF], lo, 4, d, s, bh);
    }
    {
        const uint64_t d[4] = {1024, 2, 4, 1024}, s[3] = {2048, 64 * 2048, 4096}; const uint32_t b[4] = {64, 2, 4, 16};
        encode(fn, &P.tm[M_AX], in[0], 4, d, s, b);
    }
    map_mnmajor(fn, &P.tm[M_HT], ht, 2048, 2048);
    map_kmajor(fn, &P.tm[M_CRE], in[5], 1024, 1024, 128);
    map_kmajor(fn, &P.tm[M_CIM], in[6], 1024, 1024, 128);
    map_store(fn, &P.tm[M_KVO], kvo, 3 * 2048, 4096);
    map_store(fn, &P.tm[M_HTS], ht, 2048, 2048);
    map_kmajor(fn, &P.tm[M_BX + M_HALF], in[9], 2048, 1024, 64);
    map_kmajor(fn, &P.tm[M_OA + M_HALF], kvo, 3 * 2048, 4096, 64);
    map_mnmajor(fn, &P.tm[M_HT + M_HALF], ht, 2048, 2048, 1);
    for (int i = 0; i < 3; i++) {
        const uint64_t d[3] = {64, 1024, 64}, s[2] = {8192, 128}; const uint32_t b[3] = {64, 16, 2};
        encode(fn, &P.tm[M_C1 + i], in[11 + i], 3, d, s, b);
    }
    {
        const uint64_t d[2] = {1024, 4096}, s[1] = {2048}; const uint32_t b[2] = {32, 32};
        encode(fn, &P.tm[M_CO], in[14], 2, d, s, b, CU_TENSOR_MAP_SWIZZLE_64B);
    }
    {
        const uint64_t d[3] = {64, 3 * 2048, 64}, s[2] = {8192, 128}; const uint32_t b[3] = {64, 32, 2};
        encode(fn, &P.tm[M_SEG], kvo, 3, d, s, b);
    }
    void* xs;
    cudaGetSymbolAddress(&xs, g_x);
    P.xb = (uint8_t*)(((uintptr_t)xs + (2u << 20) - 1) & ~(uintptr_t)((2u << 20) - 1));
    P.Wq = in[11]; P.Wk = in[12]; P.Wv = in[13]; P.Wo = in[14]; P.mem0 = in[10]; P.Bx = in[9];
    P.Ax = in[0]; P.Lre = in[1]; P.Lim = in[2]; P.logdt = in[7]; P.Dskip = in[8];
    P.out = (float*)d_out;
    int pv[10] = {1300, 0, 110, 0, 330, 0, 32, 32, 6, 0};
    int ef = 779;
    for (int i = 0; i < 12; i++) P.pol[i] = (ef >> i & 1) ? 0x12F0000000000000ull : 0x1000000000000000ull;
    P.dly = pv[0]; P.mrg = pv[2];
    P.rd = pv[4]; P.guard = pv[5]; P.clampv = pv[6]; P.clamp0 = pv[7]; P.kvd = pv[9]; P.xd = pv[8]; P.pd = pv[1];
    cudaLaunchConfig_t cfg = {};
    cudaLaunchAttribute at[2];
    cfg.blockDim = dim3(384); cfg.dynamicSmemBytes = S_TOTAL; cfg.stream = cudaStreamPerThread; cfg.attrs = at;
    at[0].id = cudaLaunchAttributeClusterDimension;
    at[0].val.clusterDim.y = at[0].val.clusterDim.z = 1;
    at[1].id = cudaLaunchAttributeProgrammaticStreamSerialization;
    at[1].val.programmaticStreamSerializationAllowed = 1;
    for (int i = 0; i < 2; i++) {
        P.cta0 = i ? 2 * NCHAIN : 0;
        cfg.gridDim = dim3(i ? 2 * (NPAIR - NCHAIN) : 2 * NCHAIN);
        at[0].val.clusterDim.x = i ? 2 : 6;
        cfg.numAttrs = 1 + i;
        cudaLaunchKernelEx(&cfg, fused_kernel, P);
    }
}
```

```cpp
#include <cuda_runtime.h>
#include <cuda_bf16.h>
#include <cuda.h>
#include <stdint.h>
#include <string.h>

typedef __nv_bfloat16 bf16;

namespace {

constexpr int SPIN_LIMIT = 1 << 22;
#define POLLNS 100
constexpr int NPAIR = 66;
constexpr int NCHAIN = 48;
enum { T_KV = 0, T_QA = 1, T_OP = 2, T_A1 = 3, T_A2 = 4, T_CHAIN = 5 };
constexpr int URGENT = 2048;
constexpr int HALF = 4096;
enum { M_BX = 1, M_OA, M_AB, M_HT, M_HALF = 4, M_WK = 9, M_WV, M_WQ, M_WO, M_AX, M_CRE, M_CIM, M_KVO, M_HTS, M_C1, M_CO = M_C1 + 3, M_SEG, M_COUNT };
enum { C_KV = 0, C_O = 8, C_HT = 16, C_DONE = 24, C_EPOCH = 25, C_COEF = 26, C_XMAX = 27, C_XCNT = 28, C_FLAG = 32 };

struct Params {
    CUtensorMap tm[M_COUNT];
    const bf16 *Wq, *Wk, *Wv, *Wo, *mem0, *Bx, *Ax, *Lre, *Lim, *logdt, *Dskip;
    float* out;
    uint8_t* xb;
    int swap_ri, zero;
    int dly, mrg, rd, guard, clampv, clamp0, kvd, xd;
    uint64_t pol[12];
    uint16_t cta0;
};

__constant__ uint16_t c_off[67] = {0, 4, 8, 12, 17, 21, 25, 29, 33, 38, 43, 48, 53, 58, 63, 68, 72, 76, 81, 86, 90, 94, 98, 102, 106, 110, 114, 118, 122, 127, 131, 135, 139, 144, 149, 153, 157, 162, 166, 170, 174, 179, 183, 188, 192, 196, 201, 206, 211, 231, 251, 270, 289, 308, 328, 347, 365, 385, 405, 425, 445, 465, 485, 505, 524, 543, 562};
__constant__ uint16_t c_items[640] = {
    0, 1280, 2473, 642, 16, 1280, 2474, 514, 32, 1280, 2476, 611, 1, 1280, 486, 2823, 1089, 17, 1280, 495, 675, 33, 1280, 417,
    544, 2, 1280, 773, 578, 18, 1280, 870, 739, 34, 1280, 806, 807, 1187, 3, 1280, 2504, 2979, 12962, 19, 1280, 2503, 2945, 1121,
    35, 1280, 2529, 3043, 4770, 4, 1280, 2502, 770, 1056, 20, 1280, 2539, 932, 1153, 36, 1280, 2509, 2946, 1027, 5, 1280, 482, 547,
    21, 1280, 2475, 512, 37, 1280, 2471, 2919, 1088, 6, 1280, 2510, 834, 1123, 22, 1280, 489, 609, 38, 1280, 2469, 705, 7, 1280,
    2820, 515, 23, 1280, 833, 737, 39, 1280, 774, 704, 8, 1280, 483, 576, 24, 1280, 488, 706, 40, 1280, 453, 738, 9, 1280,
    449, 608, 25, 1280, 2506, 963, 1025, 41, 1280, 492, 641, 10, 1280, 451, 513, 26, 1280, 416, 545, 42, 1280, 2532, 866, 1184,
    11, 1280, 459, 802, 1250, 27, 1280, 2538, 577, 43, 1280, 448, 643, 12, 1280, 2508, 2948, 4832, 28, 1280, 2498, 672, 44, 1280,
    431, 707, 13, 1280, 2511, 640, 29, 1280, 2466, 934, 1248, 45, 1280, 424, 546, 14, 1280, 494, 868, 1154, 30, 1280, 430, 610,
    46, 1280, 2528, 579, 15, 1280, 838, 839, 1217, 31, 1280, 804, 2951, 1026, 47, 1280, 836, 2977, 1122, 48, 66, 84, 102, 256,
    124, 142, 160, 175, 191, 207, 224, 239, 230, 328, 386, 331, 928, 3010, 1120, 49, 67, 85, 103, 257, 125, 143, 161, 176,
    192, 208, 225, 240, 241, 399, 354, 335, 835, 998, 1090, 50, 68, 86, 104, 258, 126, 144, 162, 177, 193, 209, 226, 2350,
    388, 2412, 2819, 803, 2983, 1058, 51, 69, 87, 105, 259, 127, 145, 163, 178, 194, 210, 2438, 2446, 385, 355, 391, 899, 997,
    1216, 52, 70, 88, 106, 260, 128, 146, 164, 179, 195, 211, 329, 298, 2817, 395, 367, 2913, 3041, 1024, 53, 71, 89, 107,
    261, 129, 147, 165, 180, 196, 212, 229, 244, 245, 330, 297, 397, 837, 3008, 1185, 54, 72, 90, 108, 262, 130, 148, 166,
    181, 197, 213, 321, 394, 396, 326, 2370, 902, 2981, 1155, 55, 73, 91, 109, 263, 131, 149, 167, 182, 198, 214, 231, 327,
    362, 387, 299, 487, 673, 56, 74, 92, 110, 264, 132, 150, 168, 183, 199, 215, 232, 247, 227, 323, 358, 366, 800, 3047,
    1251, 57, 75, 93, 111, 265, 133, 151, 169, 184, 200, 216, 233, 248, 254, 359, 334, 360, 896, 965, 1152, 58, 76, 94,
    112, 266, 134, 152, 170, 185, 201, 217, 234, 249, 243, 352, 332, 384, 901, 992, 1218, 59, 77, 95, 113, 267, 135, 153,
    171, 186, 202, 218, 235, 250, 255, 420, 356, 320, 832, 3009, 1091, 60, 78, 96, 114, 268, 136, 154, 172, 187, 203, 219,
    236, 251, 246, 419, 452, 361, 805, 3014, 1186, 61, 79, 97, 115, 269, 137, 155, 173, 188, 204, 220, 237, 252, 242, 392,
    457, 485, 864, 3015, 1057, 62, 80, 98, 116, 270, 138, 156, 174, 189, 205, 221, 238, 253, 228, 2349, 333, 295, 867, 3044,
    1059, 63, 81, 99, 117, 271, 139, 157, 288, 190, 292, 293, 296, 300, 429, 303, 493, 869, 3042, 1249, 64, 82, 100, 118,
    120, 122, 140, 158, 289, 206, 222, 294, 393, 422, 2413, 363, 801, 930, 1219, 65, 83, 101, 119, 121, 123, 141, 159, 290,
    291, 223, 389, 353, 2405, 324, 325, 768, 3012, 13024,
};
#define ITEM_OFF(p) c_off[p]
#define ITEM(i) c_items[i]

__device__ __align__(1024) bf16 g_kvo[3 * 2048 * 4096];
__device__ __align__(1024) bf16 g_ht[2048 * 2048];
__device__ __align__(1024) uint8_t g_x[4 << 20];
__device__ __align__(1024) uint32_t g_km[64 * 32 * 512];
__device__ __align__(1024) uint32_t g_vmt[64 * 32 * 512];
__device__ __align__(1024) float2 g_agg[8 * 1024];
__device__ __align__(1024) float4 g_coef[1024];
__device__ __align__(1024) uint32_t g_cntl[128 * 32];
#define g_cnt(i) g_cntl[(i) * 32]
__device__ __align__(1024) uint32_t g_hint[96 * 32];
#define PROF(i)
#define PROFDUMP()
#define PROFP(i)
constexpr int XG_SIDE = 65536, XG_T = 98304;
__device__ __forceinline__ uint32_t xg_buf(int b) { return (b & 1) * 128 + (b & 2) * 256 + (b & 4) * 32768; }
__device__ __forceinline__ uint32_t xg_lane(uint32_t lane) { return (lane >> 4) * 1024 + (lane & 8) * 32 + (lane & 7) * 16; }
__device__ __forceinline__ uint32_t xg_side(int b) { return XG_SIDE + (b >> 1) * 1024 + (b & 1) * 256; }

constexpr int STAGE = 49152, NSTAGE = 4;
constexpr int S_STG = NSTAGE * STAGE;
constexpr int S_BAR = S_STG + 32768;
constexpr int B_FULL = S_BAR, B_EMPTY = S_BAR + 32, B_RESUME = S_BAR + 64, B_KVFULL = S_BAR + 72, B_GO = S_BAR + 88, B_X = S_BAR + 96, B_PERS = S_BAR + 104,
              B_INIT = S_BAR + 112, B_RELM = S_BAR + 120, B_READY = S_BAR + 136, B_SFULL = S_BAR + 144, B_SFREE = S_BAR + 160, S_DESC = S_BAR + 176, B_RED = S_BAR + 216;
constexpr int S_EV = S_BAR + 80, S_EO = S_BAR + 84, B_INIT2 = S_BAR + 128, S_SC = S_BAR + 208, S_ISC = S_EV;
constexpr int S_XV = S_BAR + 256, S_LOG = S_XV + 2048;
constexpr int S_TOTAL = S_LOG + 768;
#define NRA 5
#define NRB 3
constexpr int S_W1 = 0;
constexpr int S_W2 = 4 * 4096 * (16 - NRA - NRB);
constexpr int S_KV = 188416;
constexpr int S_P1 = S_KV + 16384;
constexpr int S_X = S_P1 + 16384;
constexpr int S_SX = S_P1, S_OX = S_P1 + 2048;
constexpr int S_EM = S_X + 4096, S_TO = S_EM + 32, B_DONE = S_BAR + 224, B_P1 = S_BAR + 232;
static_assert(S_TO + 32 <= S_BAR && S_KV % 1024 == 0 && S_TOTAL <= 232448, "chain smem layout");

template <int V> struct IC { static constexpr int value = V; };
template <int B, int E, typename F> __device__ __forceinline__ void static_for(F&& f) { if constexpr (B < E) { f(IC<B>{}); static_for<B + 1, E>(f); } }
__device__ __forceinline__ uint32_t cluster_rank() { uint32_t r; asm volatile("mov.u32 %0, %%cluster_ctarank;" : "=r"(r)); return r; }
__device__ __forceinline__ void spin_fault() { asm volatile("st.global.u32 [%0], 0;" ::"l"(0ull) : "memory"); }
__device__ __forceinline__ uint32_t smem_u32(const void* p) { return (uint32_t)__cvta_generic_to_shared(p); }
__device__ __forceinline__ uint32_t opq(uint32_t x, int lane) { return __shfl_sync(0xffffffffu, x, lane); }
__device__ __forceinline__ uint32_t mapa(uint32_t a, uint32_t r) { uint32_t d; asm volatile("mapa.shared::cluster.u32 %0, %1, %2;" : "=r"(d) : "r"(a), "r"(r)); return d; }
__device__ __forceinline__ void mma16816(float* d, uint32_t a0, uint32_t a1, uint32_t a2, uint32_t a3, uint32_t b0, uint32_t b1) {
    asm("mma.sync.aligned.m16n8k16.row.col.f32.bf16.bf16.f32 {%0,%1,%2,%3}, {%4,%5,%6,%7}, {%8,%9}, {%0,%1,%2,%3};"
        : "+f"(d[0]), "+f"(d[1]), "+f"(d[2]), "+f"(d[3]) : "r"(a0), "r"(a1), "r"(a2), "r"(a3), "r"(b0), "r"(b1));
}
__device__ __forceinline__ void mma1688(float* d, uint32_t a0, uint32_t a1, uint32_t b0) {
    asm("mma.sync.aligned.m16n8k8.row.col.f32.bf16.bf16.f32 {%0,%1,%2,%3}, {%4,%5}, {%6}, {%0,%1,%2,%3};"
        : "+f"(d[0]), "+f"(d[1]), "+f"(d[2]), "+f"(d[3]) : "r"(a0), "r"(a1), "r"(b0));
}
__device__ __forceinline__ void ldsm4(uint32_t* r, uint32_t a) {
    asm volatile("ldmatrix.sync.aligned.m8n8.x4.shared.b16 {%0,%1,%2,%3}, [%4];" : "=r"(r[0]), "=r"(r[1]), "=r"(r[2]), "=r"(r[3]) : "r"(a));
}
__device__ __forceinline__ void ldsm4t(uint32_t* r, uint32_t a) {
    asm volatile("ldmatrix.sync.aligned.m8n8.x4.trans.shared.b16 {%0,%1,%2,%3}, [%4];" : "=r"(r[0]), "=r"(r[1]), "=r"(r[2]), "=r"(r[3]) : "r"(a));
}
__device__ __forceinline__ void stsm4(uint32_t a, uint32_t r0, uint32_t r1, uint32_t r2, uint32_t r3) {
    asm volatile("stmatrix.sync.aligned.m8n8.x4.shared.b16 [%0], {%1,%2,%3,%4};" ::"r"(a), "r"(r0), "r"(r1), "r"(r2), "r"(r3) : "memory");
}
__device__ __forceinline__ void stsm4t(uint32_t a, uint32_t r0, uint32_t r1, uint32_t r2, uint32_t r3) {
    asm volatile("stmatrix.sync.aligned.m8n8.x4.trans.shared.b16 [%0], {%1,%2,%3,%4};" ::"r"(a), "r"(r0), "r"(r1), "r"(r2), "r"(r3) : "memory");
}
__device__ __forceinline__ uint32_t movm(uint32_t a) { uint32_t d; asm volatile("movmatrix.sync.aligned.m8n8.trans.b16 %0, %1;" : "=r"(d) : "r"(a)); return d; }
__device__ __forceinline__ uint32_t pack2(float lo, float hi) { uint32_t d; asm("cvt.rn.bf16x2.f32 %0, %1, %2;" : "=r"(d) : "f"(hi), "f"(lo)); return d; }
__device__ __forceinline__ uint32_t prmt(uint32_t a, uint32_t b, uint32_t s) { uint32_t d; asm("prmt.b32 %0, %1, %2, %3;" : "=r"(d) : "r"(a), "r"(b), "r"(s)); return d; }
__device__ __forceinline__ uint32_t pack2h(float lo, float hi) { uint32_t d; asm("cvt.rn.f16x2.f32 %0, %1, %2;" : "=r"(d) : "f"(hi), "f"(lo)); return d; }
__device__ __forceinline__ uint32_t h2bf(uint32_t a, uint32_t b) {
    uint32_t d;
    asm("{\n.reg .b16 l, h, u;\n.reg .f32 x, y;\nmov.b32 {l, u}, %1;\ncvt.f32.f16 x, l;\nmov.b32 {u, h}, %2;\ncvt.f32.f16 y, h;\ncvt.rn.bf16x2.f32 %0, y, x;\n}" : "=r"(d) : "r"(a), "r"(b));
    return d;
}
__device__ __forceinline__ void cvt_block(uint32_t* u, uint32_t& x, uint32_t sel) {
    const uint32_t a = prmt(u[0], u[0], sel), b = prmt(u[1], u[1], sel), c = prmt(u[2], u[2], sel), d = prmt(u[3], x, sel);
    x ^= u[3] ^ d;
    u[0] = h2bf(a, a); u[1] = h2bf(b, b); u[2] = h2bf(c, c); u[3] = h2bf(d, d);
}
__device__ __forceinline__ uint32_t amax(uint32_t a, uint32_t b) { uint32_t d; asm("max.xorsign.abs.bf16x2 %0, %1, %2;" : "=r"(d) : "r"(a), "r"(b)); return d; }
__device__ __forceinline__ uint32_t amax4(uint32_t m, const uint32_t* v) { return amax(amax(m, amax(v[0], v[1])), amax(v[2], v[3])); }
__device__ __forceinline__ uint32_t warp_exp(uint32_t m) { return __reduce_max_sync(0xffffffffu, max(m & 0x7f80u, (m >> 16) & 0x7f80u)) >> 7; }
__device__ __forceinline__ void red_max_shared(uint32_t a, uint32_t x) { asm volatile("red.shared.max.u32 [%0], %1;" ::"r"(a), "r"(x) : "memory"); }
__device__ __forceinline__ uint32_t mul_bf2(uint32_t a, uint32_t b) { uint32_t d; asm("mul.rn.bf16x2 %0, %1, %2;" : "=r"(d) : "r"(a), "r"(b)); return d; }
__device__ __forceinline__ float bf_lo(uint32_t u) { return __uint_as_float(u << 16); }
__device__ __forceinline__ float bf_hi(uint32_t u) { return __uint_as_float(u & 0xffff0000u); }
__device__ __forceinline__ float ex2(float x) { float y; asm("ex2.approx.ftz.f32 %0, %1;" : "=f"(y) : "f"(x)); return y; }
__device__ __forceinline__ float rcp(float x) { float y; asm("rcp.approx.ftz.f32 %0, %1;" : "=f"(y) : "f"(x)); return y; }
__device__ __forceinline__ void st_relaxed4(const void* p, uint32_t a, uint32_t b, uint32_t c, uint32_t d) {
    asm volatile("{\n.reg .b128 t;\nmov.b128 t, {%1,%2,%3,%4};\nst.relaxed.gpu.global.b128 [%0], t;\n}" ::"l"(p), "r"(a), "r"(b), "r"(c), "r"(d) : "memory");
}
__device__ __forceinline__ void st_relaxed2(const void* p, uint32_t a, uint32_t b) {
    asm volatile("{\n.reg .b64 t;\nmov.b64 t, {%1,%2};\nst.relaxed.gpu.global.b64 [%0], t;\n}" ::"l"(p), "r"(a), "r"(b) : "memory");
}
__device__ __forceinline__ void ld_relaxed2_if(uint32_t& a, uint32_t& b, const void* p, bool on) {
    asm volatile("{\n.reg .pred P;\n.reg .b64 t;\nsetp.ne.u32 P, %3, 0;\nmov.b64 t, {%0,%1};\n@P ld.relaxed.gpu.global.b64 t, [%2];\nmov.b64 {%0,%1}, t;\n}" : "+r"(a), "+r"(b) : "l"(p), "r"((uint32_t)on) : "memory");
}
__device__ __forceinline__ void ld_relaxed4(uint32_t* v, const void* p) {
    asm volatile("ld.relaxed.gpu.global.L1::no_allocate.v4.b32 {%0,%1,%2,%3}, [%4];" : "=r"(v[0]), "=r"(v[1]), "=r"(v[2]), "=r"(v[3]) : "l"(p) : "memory");
}
__device__ __forceinline__ void ld_relaxed1n(uint32_t& v, const void* p) { asm volatile("ld.relaxed.gpu.global.L1::no_allocate.b32 %0, [%1];" : "=r"(v) : "l"(p) : "memory"); }
__device__ __forceinline__ void red_add4(const void* p, uint32_t a, uint32_t b, uint32_t c, uint32_t d) {
    asm volatile("red.relaxed.gpu.global.add.noftz.v4.f16x2 [%0], {%1,%2,%3,%4};" ::"l"(p), "r"(a), "r"(b), "r"(c), "r"(d) : "memory");
}
__device__ __forceinline__ void red_add1(const void* p, uint32_t a) { asm volatile("red.relaxed.gpu.global.add.noftz.f16x2 [%0], %1;" ::"l"(p), "r"(a) : "memory"); }
__device__ __forceinline__ void ld_relaxed2(uint32_t* v, const void* p) {
    asm volatile("{\n.reg .b64 t;\nld.relaxed.gpu.global.L1::no_allocate.b64 t, [%2];\nmov.b64 {%0,%1}, t;\n}" : "=r"(v[0]), "=r"(v[1]) : "l"(p) : "memory");
}
__device__ __forceinline__ uint32_t ld_relaxed1(const void* p) { uint32_t v; asm volatile("ld.relaxed.gpu.global.u32 %0, [%1];" : "=r"(v) : "l"(p) : "memory"); return v; }
__device__ __forceinline__ void st_relaxed1(const void* p, uint32_t v) { asm volatile("st.relaxed.gpu.global.u32 [%0], %1;" ::"l"(p), "r"(v) : "memory"); }
__device__ __forceinline__ uint32_t ld_acquire(const void* p) { uint32_t v; asm volatile("ld.acquire.gpu.global.u32 %0, [%1];" : "=r"(v) : "l"(p) : "memory"); return v; }
__device__ __forceinline__ void red_relaxed(void* p) { asm volatile("red.relaxed.gpu.global.add.u32 [%0], 1;" ::"l"(p) : "memory"); }
__device__ __forceinline__ void red_release(void* p) { asm volatile("red.release.gpu.global.add.u32 [%0], 1;" ::"l"(p) : "memory"); }
__device__ __forceinline__ void st_stream2(float* p, float a, float b) { asm volatile("st.global.cs.v2.f32 [%0], {%1, %2};" ::"l"(p), "f"(a), "f"(b) : "memory"); }
__device__ __forceinline__ void fence_async() { asm volatile("fence.proxy.async.global;" ::: "memory"); }
__device__ __forceinline__ void fence_async_smem() { asm volatile("fence.proxy.async.shared::cta;" ::: "memory"); }
__device__ __forceinline__ void wait_count(const uint32_t* p, uint32_t target) {
    while ((int32_t)(ld_acquire(p) - target) < 0) __nanosleep(POLLNS);
}
__device__ __forceinline__ void bar_sync(int id, int n) { asm volatile("bar.sync %0, %1;" ::"r"(id), "r"(n) : "memory"); }
__device__ __forceinline__ bool bar_and(int id, bool v) {
    uint32_t r;
    asm volatile("{\n.reg .pred P, Q;\nsetp.ne.u32 Q, %2, 0;\nbar.red.and.pred P, %1, 128, Q;\nselp.u32 %0, 1, 0, P;\n}" : "=r"(r) : "r"(id), "r"((uint32_t)v) : "memory");
    return r;
}
__device__ __forceinline__ void bar_arrive(int id, int n) { asm volatile("bar.arrive %0, %1;" ::"r"(id), "r"(n) : "memory"); }
__device__ __forceinline__ void lds128(uint32_t* v, uint32_t a) { asm volatile("ld.shared.v4.b32 {%0,%1,%2,%3}, [%4];" : "=r"(v[0]), "=r"(v[1]), "=r"(v[2]), "=r"(v[3]) : "r"(a) : "memory"); }
__device__ __forceinline__ uint32_t lds32(uint32_t a) { uint32_t v; asm volatile("ld.shared.b32 %0, [%1];" : "=r"(v) : "r"(a) : "memory"); return v; }
__device__ __forceinline__ void lds64(uint32_t* v, uint32_t a) { asm volatile("ld.shared.v2.b32 {%0,%1}, [%2];" : "=r"(v[0]), "=r"(v[1]) : "r"(a) : "memory"); }
__device__ __forceinline__ void lds64f(float* v, uint32_t a) { asm volatile("ld.shared.v2.f32 {%0,%1}, [%2];" : "=f"(v[0]), "=f"(v[1]) : "r"(a) : "memory"); }
__device__ __forceinline__ void sts128(uint32_t a, const uint32_t* v) { asm volatile("st.shared.v4.b32 [%0], {%1,%2,%3,%4};" ::"r"(a), "r"(v[0]), "r"(v[1]), "r"(v[2]), "r"(v[3]) : "memory"); }
__device__ __forceinline__ void sts64(uint32_t a, uint32_t x, uint32_t y) { asm volatile("st.shared.v2.b32 [%0], {%1,%2};" ::"r"(a), "r"(x), "r"(y) : "memory"); }
__device__ __forceinline__ void sts32(uint32_t a, uint32_t x) { asm volatile("st.shared.b32 [%0], %1;" ::"r"(a), "r"(x) : "memory"); }
__device__ __forceinline__ bool mbar_try(uint32_t b, uint32_t par) {
    uint32_t ok;
    asm volatile("{\n.reg .pred P;\nmbarrier.test_wait.parity.shared::cta.b64 P, [%1], %2;\nselp.u32 %0, 1, 0, P;\n}" : "=r"(ok) : "r"(b), "r"(par) : "memory");
    return ok;
}
__device__ __forceinline__ void mbar_wait(uint32_t b, uint32_t par) {
    asm volatile("{\n.reg .pred P;\nW: mbarrier.try_wait.parity.shared::cta.b64 P, [%0], %1;\n@!P bra W;\n}" ::"r"(b), "r"(par) : "memory");
}
__device__ __forceinline__ void mbar_wait_bounded(uint32_t b, uint32_t par) {
    asm volatile("{\n.reg .pred P, Q;\n.reg .u32 t, u;\nmov.u32 t, %%globaltimer_lo;\nW: mbarrier.try_wait.parity.shared::cta.b64 P, [%0], %1;\n"
                 "mov.u32 u, %%globaltimer_lo;\nsub.u32 u, u, t;\nsetp.gt.u32 Q, u, 2000000000;\n@Q st.global.u32 [%2], 0;\n@!P bra W;\n}" ::"r"(b), "r"(par), "l"(0ull) : "memory");
}
__device__ __forceinline__ void declare_fence(int zero) { asm volatile(".reg .pred PNEVER;\nsetp.ne.u32 PNEVER, %0, 0;" ::"r"(zero)); }
__device__ __forceinline__ void sched_fence() { asm volatile("{\n.reg .pred Q;\n.reg .u32 x;\n@!PNEVER bra D;\nF: ld.volatile.global.u32 x, [%0];\nsetp.ne.u32 Q, x, 0;\n@Q bra F;\nD:\n}" ::"l"(0ull) : "memory"); }
__device__ __forceinline__ void mbar_init(uint32_t b, uint32_t n) { asm volatile("mbarrier.init.shared::cta.b64 [%0], %1;" ::"r"(b), "r"(n) : "memory"); }
__device__ __forceinline__ void mbar_expect(uint32_t b, uint32_t bytes) { asm volatile("mbarrier.arrive.expect_tx.shared::cta.b64 _, [%0], %1;" ::"r"(b), "r"(bytes) : "memory"); }
__device__ __forceinline__ void mbar_arrive(uint32_t b) { asm volatile("mbarrier.arrive.shared::cta.b64 _, [%0];" ::"r"(b) : "memory"); }
__device__ __forceinline__ void mbar_arrive_cluster(uint32_t b) { asm volatile("mbarrier.arrive.shared::cluster.b64 _, [%0];" ::"r"(b) : "memory"); }
__device__ __forceinline__ void cluster_sync() { asm volatile("barrier.cluster.arrive.aligned;\nbarrier.cluster.wait.aligned;" ::: "memory"); }
__device__ __forceinline__ void tma2d(uint32_t dst, const CUtensorMap* m, int c0, int c1, uint32_t bar) {
    asm volatile("cp.async.bulk.tensor.2d.shared::cluster.global.mbarrier::complete_tx::bytes [%0], [%1, {%2, %3}], [%4];" ::"r"(dst), "l"(m), "r"(c0), "r"(c1), "r"(bar) : "memory");
}
__device__ __forceinline__ void tma3d(uint32_t dst, const CUtensorMap* m, int c0, int c1, int c2, uint32_t bar) {
    asm volatile("cp.async.bulk.tensor.3d.shared::cluster.global.mbarrier::complete_tx::bytes [%0], [%1, {%2, %3, %4}], [%5];" ::"r"(dst), "l"(m), "r"(c0), "r"(c1), "r"(c2), "r"(bar) : "memory");
}
__device__ __forceinline__ void l2_prefetch(const void* src, uint32_t bytes) { asm volatile("cp.async.bulk.prefetch.L2.global [%0], %1;" ::"l"(src), "r"(bytes) : "memory"); }
__device__ __forceinline__ void mbar_expect_e(uint32_t b, uint32_t bytes) {
    asm volatile("{\n.reg .pred E;\nelect.sync _|E, 0xffffffff;\n@E mbarrier.arrive.expect_tx.shared::cta.b64 _, [%0], %1;\n}" ::"r"(b), "r"(bytes) : "memory");
}
__device__ __forceinline__ void tma3d_mc_e(uint32_t dst, const CUtensorMap* m, int c0, int c1, int c2, uint32_t bar, uint16_t mask, uint64_t pol) {
    asm volatile("{\n.reg .pred E;\nelect.sync _|E, 0xffffffff;\n@E cp.async.bulk.tensor.3d.shared::cluster.global.mbarrier::complete_tx::bytes.multicast::cluster.L2::cache_hint [%0], [%1, {%2, %3, %4}], [%5], %6, %7;\n}" ::"r"(dst), "l"(m), "r"(c0), "r"(c1), "r"(c2), "r"(bar), "h"(mask), "l"(pol) : "memory");
}
__device__ __forceinline__ void tma4d_e(uint32_t dst, const CUtensorMap* m, int c0, int c1, int c3, uint32_t bar, uint64_t pol) {
    asm volatile("{\n.reg .pred E;\nelect.sync _|E, 0xffffffff;\n@E cp.async.bulk.tensor.4d.shared::cluster.global.mbarrier::complete_tx::bytes.L2::cache_hint [%0], [%1, {%2, %3, 0, %4}], [%5], %6;\n}" ::"r"(dst), "l"(m), "r"(c0), "r"(c1), "r"(c3), "r"(bar), "l"(pol) : "memory");
}
__device__ __forceinline__ void tma4d_mc_e(uint32_t dst, const CUtensorMap* m, int c0, int c1, int c3, uint32_t bar, uint16_t mask, uint64_t pol) {
    asm volatile("{\n.reg .pred E;\nelect.sync _|E, 0xffffffff;\n@E cp.async.bulk.tensor.4d.shared::cluster.global.mbarrier::complete_tx::bytes.multicast::cluster.L2::cache_hint [%0], [%1, {%2, %3, 0, %4}], [%5], %6, %7;\n}" ::"r"(dst), "l"(m), "r"(c0), "r"(c1), "r"(c3), "r"(bar), "h"(mask), "l"(pol) : "memory");
}
__device__ __forceinline__ void tma_prefetch4d_e(const CUtensorMap* m, int c0, int c3) {
    asm volatile("{\n.reg .pred E;\nelect.sync _|E, 0xffffffff;\n@E cp.async.bulk.prefetch.tensor.4d.L2.global [%0, {%1, 0, 0, %2}];\n}" ::"l"(m), "r"(c0), "r"(c3) : "memory");
}
__device__ __forceinline__ void tma_prefetch3d_e(const CUtensorMap* m, int c0, int c1, int c2) {
    asm volatile("{\n.reg .pred E;\nelect.sync _|E, 0xffffffff;\n@E cp.async.bulk.prefetch.tensor.3d.L2.global [%0, {%1, %2, %3}];\n}" ::"l"(m), "r"(c0), "r"(c1), "r"(c2) : "memory");
}
__device__ __forceinline__ void l2_prefetch_e(const void* src, uint32_t bytes) {
    asm volatile("{\n.reg .pred E;\nelect.sync _|E, 0xffffffff;\n@E cp.async.bulk.prefetch.L2.global [%0], %1;\n}" ::"l"(src), "r"(bytes) : "memory");
}
__device__ __forceinline__ void bulk_g2s_e(uint32_t dst, const void* src, uint32_t bytes, uint32_t bar) {
    asm volatile("{\n.reg .pred E;\nelect.sync _|E, 0xffffffff;\n@E cp.async.bulk.shared::cluster.global.mbarrier::complete_tx::bytes [%0], [%1], %2, [%3];\n}" ::"r"(dst), "l"(src), "r"(bytes), "r"(bar) : "memory");
}
__device__ __forceinline__ bool elect_one() {
    uint32_t r;
    asm volatile("{\n.reg .pred E;\nelect.sync _|E, 0xffffffff;\nselp.u32 %0, 1, 0, E;\n}" : "=r"(r));
    return r;
}
__device__ __forceinline__ void tma_store2d(const CUtensorMap* m, int c0, int c1, uint32_t src, uint64_t pol) {
    asm volatile("cp.async.bulk.tensor.2d.global.shared::cta.bulk_group.L2::cache_hint [%0, {%1, %2}], [%3], %4;" ::"l"(m), "r"(c0), "r"(c1), "r"(src), "l"(pol) : "memory");
}
__device__ __forceinline__ void bulk_commit() { asm volatile("cp.async.bulk.commit_group;" ::: "memory"); }
__device__ __forceinline__ void bulk_wait_read() { asm volatile("cp.async.bulk.wait_group.read 0;" ::: "memory"); }
__device__ __forceinline__ void bulk_wait_all() { asm volatile("cp.async.bulk.wait_group 0;" ::: "memory"); }
__device__ __forceinline__ uint64_t mkdesc(uint32_t addr, uint32_t lbo, uint32_t sbo, uint32_t swz) {
    return (uint64_t)((addr & 0x3FFFF) >> 4) | ((uint64_t)(lbo >> 4) << 16) | ((uint64_t)(sbo >> 4) << 32) | ((uint64_t)swz << 62);
}
__device__ __forceinline__ void wg_fence() { asm volatile("wgmma.fence.sync.aligned;" ::: "memory"); }
__device__ __forceinline__ void wg_commit() { asm volatile("wgmma.commit_group.sync.aligned;" ::: "memory"); }
template <int N> __device__ __forceinline__ void wg_wait() { asm volatile("wgmma.wait_group.sync.aligned %0;" ::"n"(N) : "memory"); }
template <typename T> __device__ __forceinline__ void pin_ptr(T*& p) { asm volatile("" : "+l"(p)); }
template <int N> __device__ __forceinline__ void pin(uint32_t* d) {
#pragma unroll
    for (int i = 0; i < N; i++) asm volatile("" : "+r"(d[i])::"memory");
}
template <int N> __device__ __forceinline__ void pin(float* d) {
#pragma unroll
    for (int i = 0; i < N; i++) asm volatile("" : "+f"(d[i])::"memory");
}

template <int TA, int TB>
__device__ __forceinline__ void wgmma_ss256(float* d, uint64_t da, uint64_t db) {
    asm volatile("wgmma.mma_async.sync.aligned.m64n256k16.f32.bf16.bf16 "
        "{%0, %1, %2, %3, %4, %5, %6, %7, %8, %9, %10, %11, %12, %13, %14, %15, %16, %17, %18, %19, %20, %21, %22, %23, %24, %25, %26, %27, %28, %29, %30, %31, %32, %33, %34, %35, %36, %37, %38, %39, %40, %41, %42, %43, %44, %45, %46, %47, %48, %49, %50, %51, %52, %53, %54, %55, %56, %57, %58, %59, %60, %61, %62, %63, %64, %65, %66, %67, %68, %69, %70, %71, %72, %73, %74, %75, %76, %77, %78, %79, %80, %81, %82, %83, %84, %85, %86, %87, %88, %89, %90, %91, %92, %93, %94, %95, %96, %97, %98, %99, %100, %101, %102, %103, %104, %105, %106, %107, %108, %109, %110, %111, %112, %113, %114, %115, %116, %117, %118, %119, %120, %121, %122, %123, %124, %125, %126, %127}, %128, %129, 1, 1, 1, %130, %131;"
        : "+f"(d[0]), "+f"(d[1]), "+f"(d[2]), "+f"(d[3]), "+f"(d[4]), "+f"(d[5]), "+f"(d[6]), "+f"(d[7]), "+f"(d[8]), "+f"(d[9]), "+f"(d[10]), "+f"(d[11]), "+f"(d[12]), "+f"(d[13]), "+f"(d[14]), "+f"(d[15]), "+f"(d[16]), "+f"(d[17]), "+f"(d[18]), "+f"(d[19]), "+f"(d[20]), "+f"(d[21]), "+f"(d[22]), "+f"(d[23]), "+f"(d[24]), "+f"(d[25]), "+f"(d[26]), "+f"(d[27]), "+f"(d[28]), "+f"(d[29]), "+f"(d[30]), "+f"(d[31]), "+f"(d[32]), "+f"(d[33]), "+f"(d[34]), "+f"(d[35]), "+f"(d[36]), "+f"(d[37]), "+f"(d[38]), "+f"(d[39]), "+f"(d[40]), "+f"(d[41]), "+f"(d[42]), "+f"(d[43]), "+f"(d[44]), "+f"(d[45]), "+f"(d[46]), "+f"(d[47]), "+f"(d[48]), "+f"(d[49]), "+f"(d[50]), "+f"(d[51]), "+f"(d[52]), "+f"(d[53]), "+f"(d[54]), "+f"(d[55]), "+f"(d[56]), "+f"(d[57]), "+f"(d[58]), "+f"(d[59]), "+f"(d[60]), "+f"(d[61]), "+f"(d[62]), "+f"(d[63]), "+f"(d[64]), "+f"(d[65]), "+f"(d[66]), "+f"(d[67]), "+f"(d[68]), "+f"(d[69]), "+f"(d[70]), "+f"(d[71]), "+f"(d[72]), "+f"(d[73]), "+f"(d[74]), "+f"(d[75]), "+f"(d[76]), "+f"(d[77]), "+f"(d[78]), "+f"(d[79]), "+f"(d[80]), "+f"(d[81]), "+f"(d[82]), "+f"(d[83]), "+f"(d[84]), "+f"(d[85]), "+f"(d[86]), "+f"(d[87]), "+f"(d[88]), "+f"(d[89]), "+f"(d[90]), "+f"(d[91]), "+f"(d[92]), "+f"(d[93]), "+f"(d[94]), "+f"(d[95]), "+f"(d[96]), "+f"(d[97]), "+f"(d[98]), "+f"(d[99]), "+f"(d[100]), "+f"(d[101]), "+f"(d[102]), "+f"(d[103]), "+f"(d[104]), "+f"(d[105]), "+f"(d[106]), "+f"(d[107]), "+f"(d[108]), "+f"(d[109]), "+f"(d[110]), "+f"(d[111]), "+f"(d[112]), "+f"(d[113]), "+f"(d[114]), "+f"(d[115]), "+f"(d[116]), "+f"(d[117]), "+f"(d[118]), "+f"(d[119]), "+f"(d[120]), "+f"(d[121]), "+f"(d[122]), "+f"(d[123]), "+f"(d[124]), "+f"(d[125]), "+f"(d[126]), "+f"(d[127])
        : "l"(da), "l"(db), "n"(TA), "n"(TB));
}
template <int TA, int TB>
__device__ __forceinline__ void wgmma_ss256_first(float* d, uint64_t da, uint64_t db) {
    asm volatile("wgmma.mma_async.sync.aligned.m64n256k16.f32.bf16.bf16 "
        "{%0, %1, %2, %3, %4, %5, %6, %7, %8, %9, %10, %11, %12, %13, %14, %15, %16, %17, %18, %19, %20, %21, %22, %23, %24, %25, %26, %27, %28, %29, %30, %31, %32, %33, %34, %35, %36, %37, %38, %39, %40, %41, %42, %43, %44, %45, %46, %47, %48, %49, %50, %51, %52, %53, %54, %55, %56, %57, %58, %59, %60, %61, %62, %63, %64, %65, %66, %67, %68, %69, %70, %71, %72, %73, %74, %75, %76, %77, %78, %79, %80, %81, %82, %83, %84, %85, %86, %87, %88, %89, %90, %91, %92, %93, %94, %95, %96, %97, %98, %99, %100, %101, %102, %103, %104, %105, %106, %107, %108, %109, %110, %111, %112, %113, %114, %115, %116, %117, %118, %119, %120, %121, %122, %123, %124, %125, %126, %127}, %128, %129, 0, 1, 1, %130, %131;"
        : "=f"(d[0]), "=f"(d[1]), "=f"(d[2]), "=f"(d[3]), "=f"(d[4]), "=f"(d[5]), "=f"(d[6]), "=f"(d[7]), "=f"(d[8]), "=f"(d[9]), "=f"(d[10]), "=f"(d[11]), "=f"(d[12]), "=f"(d[13]), "=f"(d[14]), "=f"(d[15]), "=f"(d[16]), "=f"(d[17]), "=f"(d[18]), "=f"(d[19]), "=f"(d[20]), "=f"(d[21]), "=f"(d[22]), "=f"(d[23]), "=f"(d[24]), "=f"(d[25]), "=f"(d[26]), "=f"(d[27]), "=f"(d[28]), "=f"(d[29]), "=f"(d[30]), "=f"(d[31]), "=f"(d[32]), "=f"(d[33]), "=f"(d[34]), "=f"(d[35]), "=f"(d[36]), "=f"(d[37]), "=f"(d[38]), "=f"(d[39]), "=f"(d[40]), "=f"(d[41]), "=f"(d[42]), "=f"(d[43]), "=f"(d[44]), "=f"(d[45]), "=f"(d[46]), "=f"(d[47]), "=f"(d[48]), "=f"(d[49]), "=f"(d[50]), "=f"(d[51]), "=f"(d[52]), "=f"(d[53]), "=f"(d[54]), "=f"(d[55]), "=f"(d[56]), "=f"(d[57]), "=f"(d[58]), "=f"(d[59]), "=f"(d[60]), "=f"(d[61]), "=f"(d[62]), "=f"(d[63]), "=f"(d[64]), "=f"(d[65]), "=f"(d[66]), "=f"(d[67]), "=f"(d[68]), "=f"(d[69]), "=f"(d[70]), "=f"(d[71]), "=f"(d[72]), "=f"(d[73]), "=f"(d[74]), "=f"(d[75]), "=f"(d[76]), "=f"(d[77]), "=f"(d[78]), "=f"(d[79]), "=f"(d[80]), "=f"(d[81]), "=f"(d[82]), "=f"(d[83]), "=f"(d[84]), "=f"(d[85]), "=f"(d[86]), "=f"(d[87]), "=f"(d[88]), "=f"(d[89]), "=f"(d[90]), "=f"(d[91]), "=f"(d[92]), "=f"(d[93]), "=f"(d[94]), "=f"(d[95]), "=f"(d[96]), "=f"(d[97]), "=f"(d[98]), "=f"(d[99]), "=f"(d[100]), "=f"(d[101]), "=f"(d[102]), "=f"(d[103]), "=f"(d[104]), "=f"(d[105]), "=f"(d[106]), "=f"(d[107]), "=f"(d[108]), "=f"(d[109]), "=f"(d[110]), "=f"(d[111]), "=f"(d[112]), "=f"(d[113]), "=f"(d[114]), "=f"(d[115]), "=f"(d[116]), "=f"(d[117]), "=f"(d[118]), "=f"(d[119]), "=f"(d[120]), "=f"(d[121]), "=f"(d[122]), "=f"(d[123]), "=f"(d[124]), "=f"(d[125]), "=f"(d[126]), "=f"(d[127])
        : "l"(da), "l"(db), "n"(TA), "n"(TB));
}
template <int TB>
__device__ __forceinline__ void wgmma_rs128(float* d, const uint32_t* a, uint64_t db, uint32_t acc) {
    asm volatile("{\n.reg .pred P;\nsetp.ne.u32 P, %69, 0;\nwgmma.mma_async.sync.aligned.m64n128k16.f32.bf16.bf16 "
        "{%0, %1, %2, %3, %4, %5, %6, %7, %8, %9, %10, %11, %12, %13, %14, %15, %16, %17, %18, %19, %20, %21, %22, %23, %24, %25, %26, %27, %28, %29, %30, %31, %32, %33, %34, %35, %36, %37, %38, %39, %40, %41, %42, %43, %44, %45, %46, %47, %48, %49, %50, %51, %52, %53, %54, %55, %56, %57, %58, %59, %60, %61, %62, %63}, {%64, %65, %66, %67}, %68, P, 1, 1, %70;\n}"
        : "+f"(d[0]), "+f"(d[1]), "+f"(d[2]), "+f"(d[3]), "+f"(d[4]), "+f"(d[5]), "+f"(d[6]), "+f"(d[7]), "+f"(d[8]), "+f"(d[9]), "+f"(d[10]), "+f"(d[11]), "+f"(d[12]), "+f"(d[13]), "+f"(d[14]), "+f"(d[15]), "+f"(d[16]), "+f"(d[17]), "+f"(d[18]), "+f"(d[19]), "+f"(d[20]), "+f"(d[21]), "+f"(d[22]), "+f"(d[23]), "+f"(d[24]), "+f"(d[25]), "+f"(d[26]), "+f"(d[27]), "+f"(d[28]), "+f"(d[29]), "+f"(d[30]), "+f"(d[31]), "+f"(d[32]), "+f"(d[33]), "+f"(d[34]), "+f"(d[35]), "+f"(d[36]), "+f"(d[37]), "+f"(d[38]), "+f"(d[39]), "+f"(d[40]), "+f"(d[41]), "+f"(d[42]), "+f"(d[43]), "+f"(d[44]), "+f"(d[45]), "+f"(d[46]), "+f"(d[47]), "+f"(d[48]), "+f"(d[49]), "+f"(d[50]), "+f"(d[51]), "+f"(d[52]), "+f"(d[53]), "+f"(d[54]), "+f"(d[55]), "+f"(d[56]), "+f"(d[57]), "+f"(d[58]), "+f"(d[59]), "+f"(d[60]), "+f"(d[61]), "+f"(d[62]), "+f"(d[63])
        : "r"(a[0]), "r"(a[1]), "r"(a[2]), "r"(a[3]), "l"(db), "r"(acc), "n"(TB));
}
template <int TB>
__device__ __forceinline__ void wgmma_rs64(float* d, const uint32_t* a, uint64_t db, uint32_t acc) {
    asm volatile("{\n.reg .pred P;\nsetp.ne.u32 P, %37, 0;\nwgmma.mma_async.sync.aligned.m64n64k16.f32.bf16.bf16 "
        "{%0, %1, %2, %3, %4, %5, %6, %7, %8, %9, %10, %11, %12, %13, %14, %15, %16, %17, %18, %19, %20, %21, %22, %23, %24, %25, %26, %27, %28, %29, %30, %31}, {%32, %33, %34, %35}, %36, P, 1, 1, %38;\n}"
        : "+f"(d[0]), "+f"(d[1]), "+f"(d[2]), "+f"(d[3]), "+f"(d[4]), "+f"(d[5]), "+f"(d[6]), "+f"(d[7]), "+f"(d[8]), "+f"(d[9]), "+f"(d[10]), "+f"(d[11]), "+f"(d[12]), "+f"(d[13]), "+f"(d[14]), "+f"(d[15]), "+f"(d[16]), "+f"(d[17]), "+f"(d[18]), "+f"(d[19]), "+f"(d[20]), "+f"(d[21]), "+f"(d[22]), "+f"(d[23]), "+f"(d[24]), "+f"(d[25]), "+f"(d[26]), "+f"(d[27]), "+f"(d[28]), "+f"(d[29]), "+f"(d[30]), "+f"(d[31])
        : "r"(a[0]), "r"(a[1]), "r"(a[2]), "r"(a[3]), "l"(db), "r"(acc), "n"(TB));
}
template <int TB>
__device__ __forceinline__ void wgmma_rs16(float* d, const uint32_t* a, uint64_t db, uint32_t acc) {
    asm volatile("{\n.reg .pred P;\nsetp.ne.u32 P, %13, 0;\nwgmma.mma_async.sync.aligned.m64n16k16.f32.bf16.bf16 "
        "{%0, %1, %2, %3, %4, %5, %6, %7}, {%8, %9, %10, %11}, %12, P, 1, 1, %14;\n}"
        : "+f"(d[0]), "+f"(d[1]), "+f"(d[2]), "+f"(d[3]), "+f"(d[4]), "+f"(d[5]), "+f"(d[6]), "+f"(d[7])
        : "r"(a[0]), "r"(a[1]), "r"(a[2]), "r"(a[3]), "l"(db), "r"(acc), "n"(TB));
}

__device__ __forceinline__ uint32_t delay_loop(int n, uint32_t x0) {
    uint32_t z;
    asm volatile("{\n.reg .pred P;\n.reg .u32 c, x;\nmov.u32 c, %1;\nmov.u32 x, %2;\nDL: mad.lo.u32 x, x, 1664525, 1013904223;\nadd.u32 c, c, -1;\nsetp.gt.s32 P, c, 0;\n@P bra DL;\n"
                 "setp.eq.u32 P, x, 0x7fffffff;\nselp.u32 %0, 16, 0, P;\n}" : "=r"(z) : "r"(n), "r"(x0) : "memory");
    return z;
}
__device__ __forceinline__ void wait_clocks(uint32_t n) {
    asm volatile("{\n.reg .pred P;\n.reg .u32 a, b;\nmov.u32 a, %%clock;\nW: mov.u32 b, %%clock;\nsub.u32 b, b, a;\nsetp.lt.u32 P, b, %0;\n@P bra W;\n}" ::"r"(n) : "memory");
}
__device__ __forceinline__ uint32_t gtime() { uint32_t t; asm volatile("mov.u32 %0, %%globaltimer_lo;" : "=r"(t)); return t; }
#define COUNT_RETRY(i)
__device__ __forceinline__ uint32_t stamp_word(uint32_t seq) { return (gtime() & ~31u) | (seq & 31u); }
__device__ __forceinline__ void wait_time(uint32_t t, uint32_t sb) { while ((int32_t)(gtime() - t) < 0) {} }
#define NAPMODE 1
__device__ __forceinline__ void nap(uint32_t ns) { if (NAPMODE) wait_clocks(ns * 7 / 4); else __nanosleep(ns); }
template <int STRIDE>
__device__ __forceinline__ uint32_t latest_stamp(const uint32_t* p, uint32_t seq, uint32_t ref, uint32_t sb) {
#pragma unroll 1
    for (int n = opq(0, 0);; n++) {
        uint32_t bad = 0; int32_t m = INT32_MIN;
#pragma unroll
        for (int i = 0; i < 3; i++) { const uint32_t v = ld_relaxed1(p + i * STRIDE); bad |= (v ^ seq) & 31u; m = max(m, (int32_t)((v & ~31u) - ref)); }
        if (__all_sync(0xffffffffu, bad == 0)) return ref + __reduce_max_sync(0xffffffffu, m);
        nap(100);
        if (n > SPIN_LIMIT) spin_fault();
    }
}
constexpr uint32_t ONES = 0x3C003C00u, FULL = 0x50005000u;
__device__ __forceinline__ void pacer(const Params& P, const uint32_t sb, const int cta, const int lane, const uint32_t epoch) {
    uint8_t* const zp = P.xb + cta * 2048 + xg_lane(lane);
    if (lane < 3) asm volatile("prefetch.tensormap [%0];" ::"l"(&P.tm[lane == 0 ? M_C1 + cta % 3 : lane == 1 ? M_CO : M_SEG]) : "memory");
    uint32_t e0 = 0;
#pragma unroll 2
    for (int i = 0; i < 32; i++) { const uint4 u = __ldg((const uint4*)P.mem0 + i * 32 + lane); e0 = amax(amax(e0, amax(u.x, u.y)), amax(u.z, u.w)); }
    e0 = min(max(warp_exp(e0), 31u), 253u) - 14;
    if (cta < 32) {
        const uint32_t* m = (const uint32_t*)(P.mem0 + (lane >> 2) * 1024 + cta * 32 + (lane & 3) * 2);
        const float sc = __uint_as_float((254 - e0) << 23);
        auto cv = [&](uint32_t u) { return pack2h(bf_lo(u) * sc, bf_hi(u) * sc); };
        const uint32_t y = cv(m[12]);
        st_relaxed4(zp, cv(m[0]), cv(m[4]), cv(m[8]), prmt(y, FULL, 0x7610));
        st_relaxed1(P.xb + xg_side(cta) + lane * 4, prmt(y, FULL, 0x3254));
    }
    if (cta < 40) {
#pragma unroll 1
        for (int b = 1; b < 8; b++) st_relaxed4(zp + xg_buf(b), 0, 0, 0, 0);
    }
    __threadfence();
    const uint32_t* ts = (const uint32_t*)(P.xb + XG_T) + lane;
    int32_t d0 = P.dly;
    const uint32_t go = mapa(sb + B_GO, (cta / 3 & 1) * 3 + 1 + (lane & 1));
    auto free_segment = [&]() { if (lane == 0) mbar_expect(sb + B_KVFULL, 16384); __syncwarp(); if (lane < 2) mbar_arrive_cluster(go); };
    for (int n = 0; (int32_t)(ld_acquire(&g_cnt(C_XCNT)) - (epoch + 1) * 256) < 0; n++) { __nanosleep(500); if (n > SPIN_LIMIT) spin_fault(); }
    const uint32_t ex = max(ld_relaxed1(&g_cnt(C_XMAX)) & 255, 67u);
    mbar_wait_bounded(sb + B_READY, 0);
    free_segment();
    if (lane == 0) st_relaxed2(g_hint + cta * 32, stamp_word(epoch + 1), lds32(sb + S_EV) | lds32(sb + S_EO) << 16);
    uint32_t a = gtime();
    for (int n = 0;; n++) {
        uint32_t bad = 0, e = 0; int32_t m = INT32_MIN;
#pragma unroll
        for (int i = 0; i < 3; i++) {
            uint32_t v[2];
            ld_relaxed2(v, g_hint + lane * 32 + i * 1024);
            bad |= (v[0] ^ (epoch + 1)) & 31u; m = max(m, (int32_t)((v[0] & ~31u) - a)); e = __vmaxu2(e, v[1]);
        }
        if (__all_sync(0xffffffffu, bad == 0)) {
            a += __reduce_max_sync(0xffffffffu, m);
            const uint32_t ev = __reduce_max_sync(0xffffffffu, e & 255), eo = __reduce_max_sync(0xffffffffu, e >> 16);
            if (lane == 0) { sts64(sb + S_SC, max(ev, 97u) + max(eo, 97u) - 244, ex); sts32(sb + S_ISC, e0 * 0x800080u); }
            break;
        }
        wait_clocks(100);
        if (n > SPIN_LIMIT) spin_fault();
    }
    wait_time(a, sb);
    if (lane == 0) mbar_arrive(sb + B_RELM);
#pragma unroll 1
    for (int s = 0; s < 63; s++) {
        const uint32_t seq = epoch * 63 + s + 1;
        mbar_wait_bounded(sb + B_P1, s & 1);
        const uint32_t tx = gtime();
        if (lane == 0) st_relaxed1(ts + (s & 1) * 256 + cta, (tx & ~31u) | (seq & 31u));
        { const uint32_t t = tx; PROFP(3) }
        if (s > 0) {
            const int32_t e0 = latest_stamp<32>(ts + (~s & 1) * 256 + 128, seq - 1, a, sb) + P.mrg - a;
            d0 += s < 3 ? e0 : min(max(e0, -P.clamp0), P.clampv) / 2;
        }
        while ((int32_t)(gtime() - tx) < P.rd) nap(20);
        a = latest_stamp<32>(ts + (s & 1) * 256, seq, tx, sb) + d0;
        { const uint32_t t = gtime(); PROFP(0) }
        while ((int32_t)(a - gtime()) > 250) nap(40);
        wait_time(a, sb);
        if (lane == 0) mbar_arrive(sb + B_RELM);
        { const uint32_t t = a; PROFP(2) }
        mbar_wait_bounded(sb + B_RED, s & 1);
        { const uint32_t t = gtime(); PROFP(1) }
        const uint32_t g = tx + __reduce_max_sync(0xffffffffu, lds32(sb + S_TO + (lane & 7) * 4) - tx);
        if (lane == 0) st_relaxed1(ts + (s & 1) * 256 + 128 + cta, (g & ~31u) | (seq & 31u));
        if (s < 62) { if (P.kvd) nap(P.kvd); free_segment(); }
    }
}
__device__ __forceinline__ void st_async2(uint32_t a, uint32_t x, uint32_t y, uint32_t bar) {
    asm volatile("st.async.weak.shared::cluster.mbarrier::complete_tx::bytes.v2.b32 [%0], {%1,%2}, [%3];" ::"r"(a), "r"(x), "r"(y), "r"(bar) : "memory");
}
__device__ __forceinline__ uint32_t xor_or(uint32_t a, uint32_t b, uint32_t t) { uint32_t d; asm("lop3.b32 %0, %1, %2, %3, 0x7E;" : "=r"(d) : "r"(a), "r"(b), "r"(t)); return d; }
__device__ __forceinline__ uint32_t or3(uint32_t a, uint32_t b, uint32_t c) { uint32_t d; asm("lop3.b32 %0, %1, %2, %3, 0xFE;" : "=r"(d) : "r"(a), "r"(b), "r"(c)); return d; }
__device__ __forceinline__ bool tags_ok(uint32_t bad, uint32_t mask = 1) {
    uint32_t r;
    asm volatile("{\n.reg .pred P;\n.reg .b32 x;\nand.b32 x, %1, %2;\nsetp.ne.b32 P, x, 0;\nvote.sync.any.pred P, P, 0xffffffff;\nselp.u32 %0, 0, 1, P;\n}" : "=r"(r) : "r"(bad), "r"(mask));
    return r;
}
constexpr int SROW = 56;
#define PREA 8
#define PREB 9
#define RING1 6
#define RING2 7
#define RING3 8
#define PRE2 10
#define PRE2A 0
#define PRE3 0
#define EFENCE 0
#define RFENCE 1
#define PROG 16
#define EARLY 0
#define PLATE 1
#define NDEP 0
#define EFENCE2 0
#define LAG2 8
#define LAG 4
#define PUT1 33
#define DEPS 3
#define ADELAY 120
#define BDELAY 0
#define HOLD 1
#define XDELAY 330
#define FENCEA 0x80
#define FENCEB 0x80
#define FENCE2 0x220
#define OFENCE 0
#define MASK3 0x57
#define MASK4 0x55
#define MASK5 0x25
#define OFF3 0x5320
#define OFF4 0x6420
#define OFF5 0x0520
#define RESA (NRA == 3 ? 15 : NRA == 4 ? 3 : 0)
#define RESB (NRB == 3 ? 0xcc : NRB == 4 ? 0x30 : 0)
#define RESB1 (NRB == 3 ? 0xcc : NRB == 4 ? 0xc : 0)
__host__ __device__ constexpr int smem_mask(int NR) { return NR == 3 ? MASK3 : NR == 4 ? MASK4 : MASK5; }
__host__ __device__ constexpr bool round_smem(int r, int NR) { return smem_mask(NR) >> r & 1; }
__host__ __device__ constexpr int kord(int r, int NR) { int c = 0; for (int i = 0; i < r; i++) c += round_smem(i, NR) == round_smem(r, NR); return round_smem(r, NR) ? NR + c : c; }
__host__ __device__ constexpr int slot_r(int n, int NR) { return n < 32 ? n >> 2 : (((n & 31) >> 2) + ((NR == 3 ? OFF3 : NR == 4 ? OFF4 : OFF5) >> (n & 3) * 4)) & 7; }
__host__ __device__ constexpr int slot_k(int n, int NR) { return kord(slot_r(n, NR), NR); }
__host__ __device__ constexpr int slot_sord(int n, int NR) { int c = 0; for (int i = 0; i < n; i++) c += slot_k(i, NR) >= NR; return c; }
__host__ __device__ constexpr int sfrag_slot(int q, int NR) { for (int n = 0; n < 64; n++) if (slot_k(n, NR) >= NR && slot_sord(n, NR) == q) return n; return -1; }
__host__ __device__ constexpr int w1_loaded(int n, int NR, int PRE) {
    int q = PRE;
    for (int i = 0; i <= n; i++) q += q < (8 - NR) * 8 && q - slot_sord(i + 1, NR) < (i < 32 ? RING1 : RING2);
    return q;
}
template <int Q, int NR>
__device__ __forceinline__ void load_w1(uint32_t* w, const uint32_t* a) {
    constexpr int n = sfrag_slot(Q, NR);
    ldsm4t(w, a[n & 3] + ((slot_k(n, NR) - NR) * 2 + (n >> 5)) * 2048);
}
constexpr int AB = NRA < 5, BB = 3 - AB;
__device__ __forceinline__ bool w2_full(int role, int warp) { return warp < (role == 2 ? 2 : 3); }
__device__ __forceinline__ int w2_nblk(int role, int warp) { return warp < 4 ? BB - !w2_full(role, warp) : AB; }
__host__ __device__ constexpr int w2_step(bool full, int i) { return AB ? (full ? 2 * i : 0) : full ? (i == 0 ? 0 : i == 1 ? 16 - 2 * EARLY : 18 - 2 * EARLY) : i; }
__device__ __forceinline__ int w2_block(int role, int warp) {
    const int f = role * 3 + warp, g = role == 2 ? warp : role;
    if (AB) return (warp >= 4 ? role * 4 + (warp - 4) : w2_full(role, warp) ? 16 + 4 * (f >> 1) + (f & 1) : 12 + g) ^ EARLY;
    return w2_full(role, warp) ? EARLY + 4 * (f >> 1) + (f & 1) : EARLY + 2 + 4 * g;
}
__device__ __forceinline__ int w2_res(int role, int warp) { return warp >= 4 ? RESA : w2_full(role, warp) ? RESB : RESB1; }
__device__ __forceinline__ int w2_units(int role, int warp) { return w2_nblk(role, warp) * 4 - (5 - (warp < 4 ? NRB : NRA)) * 2; }
constexpr int W2B = (BB * 4 - (5 - NRB) * 2) * 2048, W2A = (AB * 4 - (5 - NRA) * 2) * 2048;
static_assert(S_W2 + 4 * W2B - 8192 + 4 * W2A == S_KV, "weights");
__device__ __forceinline__ int w1_base(int warp) { return S_W1 + (warp < 4 ? warp * (8 - NRB) : 4 * (8 - NRB) + (warp - 4) * (8 - NRA)) * 4096; }
__device__ __forceinline__ int w2_base(int warp) { return S_W2 + (warp < 4 ? warp * W2B : 4 * W2B - 8192 + (warp - 4) * W2A); }
__device__ __forceinline__ void chain_load(const Params& P, uint32_t sb, int cta, int warp, int lane, int round) {
    const int role = cta % 3, h = cta / 3;
    mbar_expect_e(sb + B_INIT, round ? (8 - (warp < 4 ? NRB : NRA)) * 4096 : 20480);
    if (round) mbar_expect_e(sb + B_INIT2, w2_units(role, warp) * 2048);
    __syncwarp();
    const int m1 = (warp < 4 ? smem_mask(NRB) : smem_mask(NRA)) ^ (round ? 0 : 255), below = (1 << lane) - 1;
    const int m2 = (w2_res(role, warp) ^ (round ? 0xfff : 0)) & ((1 << w2_nblk(role, warp) * 4) - 1);
    const uint32_t d1 = sb + (round ? w1_base(warp) : warp * 20480), d2 = round ? sb + w2_base(warp) : d1 + __popc(m1) * 4096;
    if (m1 >> lane & 1) tma3d(d1 + __popc(m1 & below) * 4096, &P.tm[M_C1 + role], 0, warp * 128 + lane * 16, h * 2, sb + B_INIT);
    __syncwarp();
    if (m2 >> lane & 1)
        tma2d(d2 + __popc(m2 & below) * 2048, &P.tm[M_CO], (w2_block(role, warp) + w2_step(w2_full(role, warp), lane >> 2)) * 32, h * 128 + (lane & 3) * 32, sb + (round ? B_INIT2 : B_INIT));
    __syncwarp();
}

__device__ __forceinline__ void put_partials(bool TR, uint32_t a, const float* x, const float* y) {
    if (TR) stsm4t(a, pack2(x[0], x[1]), pack2(x[2], x[3]), pack2(y[0], y[1]), pack2(y[2], y[3]));
    else stsm4(a, pack2(x[0], x[1]), pack2(x[2], x[3]), pack2(y[0], y[1]), pack2(y[2], y[3]));
}
template <int NR, int PRE, int FM, int B, int E>
__device__ __forceinline__ void project(float (*acc)[4], bool TR, const uint32_t (*wr)[4], uint32_t (*as)[4], uint32_t (*v)[4], uint32_t* x, const uint32_t* w1a, uint32_t pp, uint32_t zero) {
    static_for<B, E>([&](auto I) {
        constexpr int n = I.value, kk = slot_k(n, NR), T = (n >> 5) * 4 + (n & 3), so = slot_sord(n, NR), q = w1_loaded(n - 1, NR, PRE);
        constexpr bool sm = kk >= NR;
        const uint32_t* w = sm ? as[so] : wr[sm ? 0 : (kk * 2 + (n >> 5)) * 4 + (n & 3)];
        if constexpr (n == 32 && PUT1 < 32) { put_partials(TR, pp, acc[0], acc[1]); put_partials(TR, pp + 4096, acc[2], acc[3]); }
        if constexpr (n == 0) {
            const uint32_t c = prmt(v[0][3], x[0], 0x3254);
            v[0][0] = h2bf(v[0][0], v[0][0]); v[0][1] = h2bf(v[0][1], v[0][1]); v[0][2] = h2bf(v[0][2], v[0][2]); v[0][3] = h2bf(v[0][3], x[0]);
            x[0] = c;
        }
        if constexpr ((n & 31) < 4) acc[T][0] = acc[T][1] = acc[T][2] = acc[T][3] = 0.f;
        mma16816(acc[T], w[0], w[1], w[2], w[3], v[slot_r(n, NR) >> 1][(slot_r(n, NR) & 1) * 2], v[slot_r(n, NR) >> 1][(slot_r(n, NR) & 1) * 2 + 1]);
        if constexpr (n == DEPS) {
            const uint32_t sel = __float_as_uint(acc[T][0]) * zero + 0x7610;
#pragma unroll
            for (int b = 1; b < 4; b++) {
                if (b <= NDEP) cvt_block(v[b], x[b], sel);
                else {
                    const uint32_t c = prmt(v[b][3], x[b], 0x3254);
                    v[b][0] = h2bf(v[b][0], v[b][0]); v[b][1] = h2bf(v[b][1], v[b][1]); v[b][2] = h2bf(v[b][2], v[b][2]); v[b][3] = h2bf(v[b][3], x[b]);
                    x[b] = c;
                }
            }
        }
        if constexpr (w1_loaded(n, NR, PRE) > q) load_w1<q, NR>(as[q], w1a);
        if constexpr (n == PUT1 && n >= 32) { put_partials(TR, pp, acc[0], acc[1]); put_partials(TR, pp + 4096, acc[2], acc[3]); }
        if constexpr (n % 4 == 3 && (FM >> (n / 4) & 1) && n != E - 1) sched_fence();
    });
    if constexpr (E == 64) { put_partials(TR, pp + 8192, acc[4], acc[5]); put_partials(TR, pp + 12288, acc[6], acc[7]); }
}
__device__ __forceinline__ void reduce8(const uint32_t (*x)[4], const uint32_t* sel, float sc, uint32_t& r0, uint32_t& r1) {
    float d[4][4];
#pragma unroll
    for (int i = 0; i < 4; i++) {
        d[i][0] = d[i][1] = d[i][2] = d[i][3] = 0.f;
        mma16816(d[i], x[i][0], x[i][1], x[i][2], x[i][3], sel[2 * i], sel[2 * i + 1]);
    }
    r0 = pack2(((d[0][0] + d[1][0]) + (d[2][0] + d[3][0])) * sc, ((d[0][1] + d[1][1]) + (d[2][1] + d[3][1])) * sc);
    r1 = pack2(((d[0][2] + d[1][2]) + (d[2][2] + d[3][2])) * sc, ((d[0][3] + d[1][3]) + (d[2][3] + d[3][3])) * sc);
}

#define ISTAMP(i)
__host__ __device__ constexpr int wo_count(int n, int RES, bool res) { int c = 0; for (int i = 0; i < n; i++) c += (RES >> (i >> 2) & 1) == res; return c; }
__host__ __device__ constexpr int wo_loaded(int n, int RES, int PRE, int end) { int q = PRE; for (int i = 0; i <= n; i++) q += q < end && q - wo_count(i + 1, RES, false) < RING3; return q; }
template <int Q>
__device__ __forceinline__ void load_w2(uint32_t* w, const uint32_t* a) { ldsm4t(w, a[Q & 1] + (Q >> 1) * 1024); }
template <int NB, int RES, int PRE, int FM>
__device__ __forceinline__ void wo_blocks(uint32_t (*w)[4], const uint32_t (*wp)[4], uint32_t oa, const uint32_t* wa, const uint8_t* dst, const uint8_t* dsd, bool odd) {
    float a[NB][4][4];
    uint32_t o[4][4], r[5];
    bar_sync(3, 256);
#pragma unroll
    for (int i = 0; i < 4; i++) ldsm4(o[i], oa + i * 512);
    if (FM & 1) sched_fence();
    static_for<0, NB * 16>([&](auto I) {
        constexpr int n = I.value, i = n & 15, end = wo_count(NB * 16, RES, false), q = wo_loaded(n - 1, RES, PRE, end);
        constexpr bool res = RES >> (n >> 2) & 1;
        const uint32_t* b = o[i >> 2] + (i & 2);
        const uint32_t* x = res ? wp[wo_count(n, RES, true)] : w[wo_count(n, RES, false)];
        float* d = a[n >> 4][i & 3];
        if constexpr (i < 4) d[0] = d[1] = d[2] = d[3] = 0.f;
        mma16816(d, x[0], x[1], x[2], x[3], b[0], b[1]);
        if constexpr (wo_loaded(n, RES, PRE, end) > q) load_w2<q>(w[q], wa);
        if constexpr (n == NB * 16 - 1 || (n >= 16 && i == LAG - 1)) {
            const float (*e)[4] = a[n == NB * 16 - 1 ? NB - 1 : (n >> 4) - 1];
            const uint32_t y = pack2h(e[1][2] + e[3][2], e[1][3] + e[3][3]);
            r[0] = movm(pack2h(e[0][0] + e[2][0], e[0][1] + e[2][1])); r[1] = movm(pack2h(e[0][2] + e[2][2], e[0][3] + e[2][3]));
            r[2] = movm(pack2h(e[1][0] + e[3][0], e[1][1] + e[3][1])); r[3] = movm(odd ? ONES : y); r[4] = movm(odd ? y : ONES);
        }
        if constexpr (n == NB * 16 - 1 || (n >= 16 && i == LAG2 - 1)) {
            constexpr int bs = w2_step(NB == BB, n == NB * 16 - 1 ? NB - 1 : (n >> 4) - 1);
            red_add4(dst + bs * 2048, r[0], r[1], r[2], r[3]);
            red_add1(dsd + (bs >> 1) * 1024 + (bs & 1) * 256, r[4]);
        }
        if constexpr (((FM >> (n / 4 + 1)) & 1) && (n & 3) == 3 && n != NB * 16 - 1) sched_fence();
    });
}
#define FRAG1(ln) ((((ln) & 7) + ((ln) >> 4) * 8) * 128 + ((((((ln) >> 3) & 1) << (ROLE == 1)) ^ ((ln) & 7)) << 4))
#define FRAG2(ln) ((((ln) & 7) + ((ln) >> 4) * 8) * 64 + (((((ln) >> 3) & 1) ^ (((ln) >> 1) & 3)) << 4))
#define TILE_X(i) (ROLE == 1 ? (((i) >> 1) << 6) | (((i) & 1) << 4) : (i) << 5)
__device__ __forceinline__ void chain_fetch(const Params& P, const uint32_t sb, const int cta, const int warp, const int lane, uint32_t (*wr)[4]) {
    const int ROLE = cta % 3, nr = warp < 4 ? NRB : NRA;
    mbar_wait(sb + B_INIT, 0);
    ISTAMP(0)
#pragma unroll
    for (int f = 0; f < 40; f++) {
        const bool w1 = f < (NRA < NRB ? NRA : NRB) * 8 || f < nr * 8;
        ldsm4t(wr[f], sb + warp * 20480 + (f >> 2) * 2048 + (w1 ? FRAG1(lane) ^ TILE_X(f & 3) : (f & 2) * 512 + (FRAG2(lane) ^ ((f & 1) << 5))));
    }
    fence_async_smem();
    mbar_wait(sb + B_SFREE + (warp >> 2) * 8, 0);
    bar_sync(1, 256);
    chain_load(P, sb, cta, warp, lane, 1);
    ISTAMP(1)
}
__device__ __forceinline__ void chain_bounds(const uint32_t sb, const int cta, const int warp, const int lane, const uint32_t (*wr)[4]) {
    const int ROLE = cta % 3, nr = warp < 4 ? NRB : NRA;
    uint32_t m[6] = {}, u[4];
#pragma unroll
    for (int f = 0; f < 40; f++) m[f < 24 ? 0 : f >> 3] = amax4(m[f < 24 ? 0 : f >> 3], wr[f]);
    uint32_t m1 = amax(m[0], amax(nr > 3 ? m[3] : 0, nr > 4 ? m[4] : 0)), m2 = amax(nr > 3 ? 0 : m[3], nr > 4 ? 0 : m[4]);
    ISTAMP(5)
    mbar_wait(sb + B_INIT, 1);
    ISTAMP(3)
    if (ROLE == 2) {
#pragma unroll 4
        for (int i = 0; i < S_W2 / 4096; i++) { lds128(u, sb + S_W1 + warp * (S_W2 / 8) + i * 512 + lane * 16); m1 = amax4(m1, u); }
    }
    mbar_wait(sb + B_INIT2, 0);
    ISTAMP(7)
    const int n = w2_units(ROLE, warp) * 4;
#pragma unroll 4
    for (int i = 0; i < n; i++) { lds128(u, sb + w2_base(warp) + i * 512 + lane * 16); m2 = amax4(m2, u); }
    m1 = warp_exp(m1); m2 = warp_exp(m2);
    if (lane == 0) { if (ROLE == 2) red_max_shared(sb + S_EV, m1); red_max_shared(sb + S_EO, m2); }
}
template <bool ATT>
__device__ __forceinline__ void chain_role(const Params& P, const uint32_t sb, const int cta, const int warp, const int lane, const uint32_t epoch, const uint32_t (*wr)[4]) {
    constexpr int NR = ATT ? NRA : NRB, PRE = ATT ? PREA : PREB;
    const int h = cta / 3, ROLE = cta - h * 3;
    ISTAMP(6)
    uint32_t l8 = opq(sb + lane * 8, lane);
    const uint8_t* persu = (const uint8_t*)((ROLE == 1 ? g_km : g_vmt) + h * 512) - (sb >> 1);
    auto persist = [&](int s, int tile, uint32_t r0, uint32_t r1) {
        uint32_t* pp = (uint32_t*)(persu + s * 65536 + (ROLE == 1 ? (tile >> 1) * 512 + (tile & 1) * 128 : tile * 256) + (l8 >> 1));
        pp[0] = r0; pp[ROLE == 1 ? 64 : 32] = r1;
    };
    const uint32_t rk0 = (h & 1) * 3, rd1 = __shfl_sync(0xffffffffu, mapa(sb, rk0 + (ROLE + 1) % 3) - sb, 0), rd2 = __shfl_sync(0xffffffffu, mapa(sb, rk0 + (ROLE + 2) % 3) - sb, 0);
    const uint32_t xo = (ROLE == 2 ? S_XV : S_X + ROLE * 2048) + warp * 256;
    const bool full = w2_full(ROLE, warp);
    const int blk = w2_block(ROLE, warp);
    const uint32_t om = blk * 2048, os = xg_side(blk);
    const uint32_t w1o = sb + w1_base(warp), w2o = sb + w2_base(warp);
    ISTAMP(2)
    if (lane == 0) mbar_arrive(sb + B_READY);
#pragma unroll 1
    for (int s = 0;; s++) {
        l8 += s & P.zero;
        uint32_t r0, r1;
        {
            uint32_t v[4][4], as[(8 - NR) * 8][4], w1a[4];
            float acc[8][4];
            const uint32_t pst = sb + S_P1 + (l8 - sb) * 16 + ((warp * 16) ^ ((l8 & 56) * 2));
#pragma unroll
            for (int i = 0; i < 4; i++) w1a[i] = w1o + (FRAG1((l8 - sb) >> 3) ^ TILE_X(i));
            auto preload = [&]() { static_for<0, PRE>([&](auto I) { load_w1<I.value, NR>(as[I.value], w1a); }); };
#pragma unroll 1
            while (true) {
                uint32_t x[4];
                if (!(PLATE >> ATT & 1)) preload();
                const uint32_t lm = opq(l8 - sb, (l8 - sb) >> 3);
                const uint8_t* pm = P.xb + xg_buf(s) + warp * 8192 + xg_lane(lm >> 3);
                const uint8_t* ps = P.xb + xg_buf(s) + XG_SIDE + warp * 2048 + (lm >> 1);
                pin_ptr(pm); pin_ptr(ps);
                mbar_wait(sb + B_RELM, s & 1);
                if (ATT ? ADELAY : BDELAY) wait_clocks(ATT ? ADELAY : BDELAY);
                PROF(10)
#pragma unroll
                for (int b = 0; b < 4; b++) { ld_relaxed4(v[b], pm + b * 2048); ld_relaxed1n(x[b], ps + (b >> 1) * 1024 + (b & 1) * 256); }
                if (PLATE >> ATT & 1) { preload(); if (PLATE >> (ATT + 2) & 1) sched_fence(); }
                project<NR, PRE, ATT ? FENCEA : FENCEB, 0, PROG>(acc, ROLE == 2, wr, as, v, x, w1a, pst, P.zero);
                const uint32_t bad = xor_or(x[0], x[1], FULL) | xor_or(x[2], x[3], FULL);
                if (tags_ok(bad, 0xffffffffu)) break;
                COUNT_RETRY(warp >> 1)
            }
            PROF(0)
            project<NR, PRE, ATT ? FENCEA : FENCEB, PROG, 64>(acc, ROLE == 2, wr, as, v, nullptr, w1a, pst, 0);
            PROF(1)
            const uint32_t isc = lds32(sb + S_ISC + (s & 1) * 4);
            const uint32_t lq = l8 + ((s >> 3) & P.zero), e1 = s == 63 ? 0 : rd1, e2 = s == 63 ? 0 : rd2;
            uint32_t x[4][4], sel[8], xd[6] = {l8 + xo, l8 + xo + e1, l8 + xo + e2, sb + B_X + e1, sb + B_X + e2, sb + S_P1 + warp * 2048 + (lq & 64) * 16 + (lq & 128) + (lq & 56) * 2};
#pragma unroll
            for (int i = 0; i < 8; i++) sel[i] = (lq & 224) == i * 32 ? 0x3F803F80u : 0u;
            pin<6>(xd); pin<8>(sel);
            if (RFENCE) sched_fence();
            bar_sync(1, 256);
#pragma unroll
            for (int i = 0; i < 4; i++) ldsm4t(x[i], xd[5] + i * 256);
            if (!ATT && l8 == sb + (warp - 3) * 1024) mbar_arrive(sb + B_P1);
            uint32_t em = warp_exp(amax(amax4(amax(amax(v[0][0], v[0][1]), amax(v[0][2], v[0][3])), v[1]), amax4(amax(amax(v[2][0], v[2][1]), amax(v[2][2], v[2][3])), v[3])));
            if (EFENCE2) sched_fence();
            reduce8(x, sel, bf_hi(isc), r0, r1);
            st_async2(xd[1], r0, r1, xd[3]);
            st_async2(xd[2], r0, r1, xd[4]);
            sts64(xd[0], r0, r1);
            if (s == 63) { persist(s, warp, r0, r1); break; }
            if (l8 == sb) sts32(sb + S_EM + warp * 4, em + (isc >> 23));
            __syncwarp();
            if (l8 == sb) mbar_arrive(sb + B_X);
            PROF(2)
        }
        uint32_t w[40][4], w2a[2], odd;
        const uint8_t *po, *pd;
        auto wo_addr = [&]() {
            const uint32_t lo = (l8 + ((s >> 2) & P.zero) - sb) >> 3;
            w2a[0] = w2o + FRAG2(lo); w2a[1] = w2o + (FRAG2(lo) ^ 32);
            po = P.xb + xg_buf(s + 1) + om + xg_lane(lo);
            pd = P.xb + xg_buf(s + 1) + os + lo * 4;
            odd = lo & 4;
            pin_ptr(po); pin_ptr(pd); pin<2>(w2a); pin<1>(&odd);
        };
        uint32_t oa = l8 * 2 + (S_OX - sb);
        if constexpr (ATT) {
            const uint32_t ln = (l8 + ((s >> 4) & P.zero) - sb) >> 3;
            const uint32_t va = sb + S_KV + 8192 + ((warp >> 1) & 1) * 4096 + ((ln & 7) + (ln >> 4) * 8) * 128 + ((((warp & 1) * 4 + ((ln >> 3) & 1)) ^ (ln & 7)) << 4);
            const uint32_t ka = sb + S_KV + (warp & 1) * 2048 + (ln & 15) * 128 + (((ln >> 4) ^ (ln & 7)) << 4);
            uint32_t ad[5] = {sb + S_SX + (ln & 3) * (8 * SROW) + (ln >> 2) * 4 + (warp < 6 ? (warp - 4) * 64 : 128 + (warp - 6) * 32), l8 + S_XV + (warp - 4) * 512,
                              l8 + S_SX + (ln >> 2) * (4 * SROW - 32), oa + (warp - 4) * 512, sb + S_ISC + (~s & 1) * 4};
            if constexpr (AB) { wo_addr(); pin<1>(&oa); }
            pin<5>(ad);
            const uint32_t sa = ad[0], sr = ad[2];
            uint32_t vf[4][4], vm[2][2], q[8][2];
            float S[4][4];
#pragma unroll
            for (int n = 0; n < 4; n++) { S[n][0] = S[n][1] = S[n][2] = S[n][3] = 0.f; }
            mbar_wait(sb + B_KVFULL, s & 1);
            if (warp < 6) {
                uint32_t kf[8][4];
#pragma unroll
                for (int k = 0; k < 8; k++) ldsm4(kf[k], (ka ^ ((k & 3) << 5)) + (k >> 2) * 4096);
#pragma unroll
                for (int i = 0; i < 4; i++) ldsm4t(vf[i], (va ^ ((i & 1) << 5)) + (i >> 1) * 2048);
                mbar_wait(sb + B_X, s & 1);
                PROF(11)
#pragma unroll
                for (int k = 0; k < 8; k++) lds64(q[k], l8 + S_X + k * 256);
#pragma unroll
                for (int k = 0; k < 8; k++) mma16816(S[k & 3], kf[k][0], kf[k][1], kf[k][2], kf[k][3], q[k][0], q[k][1]);
                sts32(sa, __float_as_uint((S[0][0] + S[1][0]) + (S[2][0] + S[3][0])));
                sts32(sa + 4 * SROW, __float_as_uint((S[0][1] + S[1][1]) + (S[2][1] + S[3][1])));
                sts32(sa + 32, __float_as_uint((S[0][2] + S[1][2]) + (S[2][2] + S[3][2])));
                sts32(sa + 4 * SROW + 32, __float_as_uint((S[0][3] + S[1][3]) + (S[2][3] + S[3][3])));
            } else {
#pragma unroll
                for (int i = 0; i < 4; i++) ldsm4t(vf[i], (va ^ ((i & 1) << 5)) + (i >> 1) * 2048);
                uint32_t xa = l8 + S_X + (warp - 6) * 1024;
                pin<1>(&xa);
                mbar_wait(sb + B_X, s & 1);
                PROF(11)
#pragma unroll
                for (int k = 0; k < 8; k++) lds64(q[k], xa + (k >> 2) * 2048 + (k & 3) * 256);
#pragma unroll
                for (int k = 0; k < 4; k++) mma16816(S[k], q[4 + (k & 2)][0], q[4 + (k & 2)][1], q[5 + (k & 2)][0], q[5 + (k & 2)][1], q[k][0], q[k][1]);
                sts32(sa, __float_as_uint((S[0][0] + S[2][0]) + (S[1][2] + S[3][2])));
                sts32(sa + 4 * SROW, __float_as_uint((S[0][1] + S[2][1]) + (S[1][3] + S[3][3])));
            }
            lds64(vm[0], ad[1]); lds64(vm[1], ad[1] + 256);
            PROF(7)
            bar_sync(2, 160);
            const float cs = 0.08838834764831845f * 1.4426950408889634f;
            float E[6][2];
#pragma unroll
            for (int i = 0; i < 6; i++) lds64f(E[(i + 4) % 6], sr + ((i + 4) % 6) * 32);
            const uint32_t isn = lds32(ad[4]);
            E[4][0] += E[5][0]; E[4][1] += E[5][1];
            float m = fmaxf(fmaxf(fmaxf(fmaxf(E[0][0], E[0][1]), fmaxf(E[1][0], E[1][1])), fmaxf(fmaxf(E[2][0], E[2][1]), fmaxf(E[3][0], E[3][1]))), fmaxf(E[4][0], E[4][1]));
            m = fmaxf(m, __shfl_xor_sync(0xffffffffu, m, 1));
            m = fmaxf(m, __shfl_xor_sync(0xffffffffu, m, 2));
            m *= cs;
            if constexpr (AB) static_for<0, PRE3>([&](auto I) { load_w2<I.value>(w[I.value], w2a); });
            uint32_t pa[5];
#pragma unroll
            for (int i = 0; i < 5; i++) { const int k = (i + 4) % 5; E[k][0] = ex2(fmaf(E[k][0], cs, -m)); E[k][1] = ex2(fmaf(E[k][1], cs, -m)); pa[k] = pack2(E[k][0], E[k][1]); }
            if (EFENCE) sched_fence();
            float O[2][4], Z[4];
#pragma unroll
            for (int i = 0; i < 4; i++) { O[0][i] = O[1][i] = Z[i] = 0.f; }
#pragma unroll
            for (int i = 0; i < 2; i++) {
                mma1688(O[i], vm[i][0], vm[i][1], pa[4]);
                mma16816(O[i], vf[i][0], vf[i][1], vf[i][2], vf[i][3], pa[0], pa[1]);
                mma16816(O[i], vf[2 + i][0], vf[2 + i][1], vf[2 + i][2], vf[2 + i][3], pa[2], pa[3]);
            }
            const float z = (((E[4][0] + E[4][1]) + (E[0][0] + E[0][1])) + ((E[1][0] + E[1][1]) + (E[2][0] + E[2][1]))) + (E[3][0] + E[3][1]);
            const float zh = __uint_as_float(__float_as_uint(z) & 0xffff0000u);
            mma1688(Z, isn, isn, pack2(zh, z - zh));
            const float i0 = rcp(Z[0]), i1 = rcp(Z[1]);
            stsm4t(ad[3], pack2(O[0][0] * i0, O[0][1] * i1), pack2(O[0][2] * i0, O[0][3] * i1), pack2(O[1][0] * i0, O[1][1] * i1), pack2(O[1][2] * i0, O[1][3] * i1));
            PROF(4)
            if constexpr (AB) wo_blocks<1, RESA, PRE3, OFENCE / 2>(w, wr + NR * 8, oa, w2a, po, pd, odd);
            else bar_arrive(3, 256);
            if (ROLE != 0) persist(s, warp, r0, r1);
            if (warp == 7 && l8 == sb) mbar_expect(sb + B_X, 4096);
        } else {
            if (ROLE != 0) persist(s, warp, r0, r1);
            wo_addr(); pin<1>(&oa);
            static_for<0, PRE2A>([&](auto I) { load_w2<I.value>(w[I.value], w2a); });
            mbar_wait(sb + B_X, s & 1);
            if (warp == 0) {
                uint32_t sc[2];
                lds64(sc, sb + S_SC);
                const int em = __reduce_max_sync(0xffffffffu, lds32(sb + S_EM + ((l8 >> 1) & 28)));
                if (l8 == sb) sts32(sb + S_ISC + (~s & 1) * 4, min(max(em - 127, (int)sc[1]) + (int)sc[0], 253) * 0x800080u);
                bar_arrive(2, 160);
            }
            wait_clocks(XDELAY - (warp == 0) * 100);
            constexpr int PRE1 = (BB - 1) * 16 - (5 - NRB) * 8 < PRE2 ? (BB - 1) * 16 - (5 - NRB) * 8 : PRE2;
            static_for<PRE2A, PRE1>([&](auto I) { load_w2<I.value>(w[I.value], w2a); });
            if (full) {
                static_for<PRE1, PRE2>([&](auto I) { load_w2<I.value>(w[I.value], w2a); });
                wo_blocks<BB, RESB, PRE2, FENCE2 * 2 + OFENCE % 2>(w, wr + NR * 8, oa, w2a, po, pd, odd);
            } else wo_blocks<BB - 1, RESB1, PRE1, FENCE2 * 2 + OFENCE % 2>(w, wr + NR * 8, oa, w2a, po, pd, odd);
        }
        PROF(5)
        if (l8 == sb) { sts32(sb + S_TO + warp * 4, gtime()); mbar_arrive(sb + B_RED); }
        if (HOLD && !(PLATE >> ATT & 1)) mbar_wait(sb + B_RED, s & 1);
        if (ROLE != 0 && (s & 3) == 3 && l8 == sb) mbar_arrive(sb + B_PERS);
        if (ROLE == 0 && s == 62) return;
    }
    __syncwarp();
    if (l8 == sb) mbar_arrive(sb + B_PERS);
}
#define IP(i)
struct Pipe { uint32_t stage, phase; };
struct Cons {
    uint32_t sb, rel;
    int wg, wq, lane, rank, pair;
    uint32_t atag, nst;
    Pipe p;
};
__device__ __forceinline__ void pipe_next(Pipe& p) { p.stage = (p.stage + 1) & (NSTAGE - 1); p.phase ^= (p.stage == 0); }
__device__ __forceinline__ void release(const Cons& c, uint32_t stage) { if (c.lane < 2) mbar_arrive_cluster(c.rel + stage * 8); }
__device__ __forceinline__ void wait_full(const Cons& c) { mbar_wait(c.sb + B_FULL + c.p.stage * 8, c.p.phase); }

enum { PEND_NONE = 0, PEND_KVO = 1, PEND_HT = 2, PEND_OUT = 3 };
struct Pend { uint32_t pk[64]; int kind, row, col, cnt; };

__device__ __forceinline__ void staging_wait(const Cons& c) { if (c.nst) mbar_wait(c.sb + B_SFREE + c.wg * 8, (c.nst - 1) & 1); }
__device__ __forceinline__ void staging_post(Cons& c, int kind, int row, int col, int cnt) {
    __syncwarp();
    if (c.lane == 0) {
        if (c.wq == 0) { const uint32_t x[4] = {(uint32_t)kind, (uint32_t)row, (uint32_t)col, (uint32_t)cnt}; sts128(c.sb + S_DESC + c.wg * 16, x); }
        mbar_arrive(c.sb + B_SFULL + c.wg * 8);
    }
    c.nst++;
}
__device__ __forceinline__ void drain(const Params& P, Cons& c, Pend& d) {
    const uint32_t* pk = d.pk;
    if (d.kind == PEND_OUT) {
        float* o = P.out + (size_t)(d.row + c.wq * 16 + (c.lane >> 2)) * 2048 + d.col + (c.lane & 3) * 2;
#pragma unroll
        for (int j = 0; j < 16; j++) {
            st_stream2(o + j * 8, bf_lo(pk[j * 2]), bf_hi(pk[j * 2]));
            st_stream2(o + 8 * 2048 + j * 8, bf_lo(pk[j * 2 + 1]), bf_hi(pk[j * 2 + 1]));
        }
    } else {
        const bool ht = d.kind == PEND_HT;
        const int hi = (c.lane >> 3) & 1;
        const uint32_t base = c.sb + S_STG + c.wg * 16384 + ((ht ? hi * 32 + c.wq * 8 : c.wq * 16 + hi * 8) + (c.lane & 7)) * 128;
        staging_wait(c);
#pragma unroll
        for (int j = 0; j < 8; j++) {
            const int ch = (j & 3) * 2 + (c.lane >> 4);
            stsm4(base + (j >> 2) * 8192 + ((ch ^ (c.lane & 7)) << 4), pk[j * 4], pk[j * 4 + 1], pk[j * 4 + 2], pk[j * 4 + 3]);
        }
        fence_async_smem();
        staging_post(c, d.kind, d.row, d.col, (d.col & 128) ? d.cnt : -1);
    }
    if (d.col & 128) d.kind = PEND_NONE;
    d.col += 128;
#pragma unroll
    for (int i = 0; i < 32; i++) d.pk[i] = d.pk[32 + i];
}

constexpr int S_STG2 = 8 * 20480, PEND_BOTH = 8;
__device__ __forceinline__ void drain_both(Cons& c, const Pend& d) {
    const uint32_t base = c.sb + c.wg * 16384 + (c.wq * 16 + ((c.lane >> 3) & 1) * 8 + (c.lane & 7)) * 128;
#pragma unroll
    for (int j = 0; j < 16; j++)
        stsm4(base + (j < 8 ? S_STG : S_STG2) + (j >> 2 & 1) * 8192 + ((((j & 3) * 2 + (c.lane >> 4)) ^ (c.lane & 7)) << 4), d.pk[j * 4], d.pk[j * 4 + 1], d.pk[j * 4 + 2], d.pk[j * 4 + 3]);
    fence_async_smem();
    staging_post(c, PEND_KVO | PEND_BOTH, d.row, d.col, d.cnt);
}

__device__ __forceinline__ void store_warp(const Params& P, uint32_t sb, int wg, int cta) {
    if (cta < 128) {
        for (int i = 0; i < P.xd; i++) __nanosleep(1000);
        const uint32_t e1 = ld_acquire(&g_cnt(C_EPOCH)) + 1;
        const uint4* x = (const uint4*)P.Bx + (cta * 2 + wg) * 1024 + (threadIdx.x & 31);
        uint32_t m = 0;
#pragma unroll 4
        for (int i = 0; i < 32; i++) { const uint4 u = __ldg(x + i * 32); m = amax(amax(m, amax(u.x, u.y)), amax(u.z, u.w)); }
        m = warp_exp(m);
        if (elect_one()) { atomicMax(&g_cnt(C_XMAX), e1 << 8 | m); red_release(&g_cnt(C_XCNT)); }
        __syncwarp();
    }
    const uint32_t stg = sb + S_STG + wg * 16384;
#pragma unroll 1
    for (uint32_t n = 0;; n++) {
        mbar_wait(sb + B_SFULL + wg * 8, n & 1);
        uint32_t x[4];
        lds128(x, sb + S_DESC + wg * 16);
#pragma unroll
        for (int i = 0; i < 4; i++) x[i] = __shfl_sync(0xffffffffu, x[i], 0);
        if (x[0] == PEND_NONE) break;
        const bool ht = x[0] == PEND_HT;
        const CUtensorMap* m = &P.tm[ht ? M_HTS : M_KVO];
        const uint64_t pol = P.pol[ht ? 2 : x[1] >= 4096 ? 1 : (x[1] & 2047) < 1536 ? 0 : 10];
        if (elect_one()) {
#pragma unroll
            for (int i = 0; i < 4; i++) tma_store2d(m, x[2] + (i >> 1) * 64, x[1] + (i & 1) * (ht ? 1024 : 32), stg + i * 4096, pol);
            if (x[0] & PEND_BOTH) {
#pragma unroll 1
                for (int i = 0; i < 4; i++) tma_store2d(m, x[2] + 128 + (i >> 1) * 64, x[1] + (i & 1) * 32, stg + (S_STG2 - S_STG) + i * 4096, pol);
            }
            bulk_commit();
            bulk_wait_read();
            mbar_arrive(sb + B_SFREE + wg * 8);
            if ((int)x[3] >= 0) { bulk_wait_all(); fence_async(); red_release(&g_cnt(x[3])); }
        }
        __syncwarp();
    }
}

template <int TA, int TB, bool FIRST>
__device__ __forceinline__ void issue_ktile(float* acc, const Cons& c) {
    const uint32_t a = c.sb + c.p.stage * STAGE + c.wg * 8192, b = c.sb + c.p.stage * STAGE + 16384;
    const uint64_t da = mkdesc(a, TA ? 8192 : 16, 1024, 1), db = mkdesc(b, TB ? 8192 : 16, 1024, 1);
    wg_fence();
#pragma unroll
    for (int k = 0; k < 4; k++) {
        if (FIRST && k == 0) wgmma_ss256_first<TA, TB>(acc, da, db);
        else wgmma_ss256<TA, TB>(acc, da + (TA ? 128 : 2) * k, db + (TB ? 128 : 2) * k);
    }
    wg_commit();
}
template <bool KVONLY, bool FIRST>
__device__ __forceinline__ void issue_any(float* acc, const Cons& c, int type) {
    wait_full(c);
    if (!KVONLY && type == T_A1) issue_ktile<0, 0, FIRST>(acc, c);
    else if (!KVONLY && type == T_A2) issue_ktile<1, 0, FIRST>(acc, c);
    else issue_ktile<0, 1, FIRST>(acc, c);
}
template <bool KVONLY = false>
__device__ __forceinline__ void mainloop(float* acc, const Params& P, Cons& c, Pend& d, int type, int nk) {
    issue_any<KVONLY, true>(acc, c, type);
    if (!KVONLY) { IP(0) }
    uint32_t prev = c.p.stage;
    pipe_next(c.p);
#pragma unroll 1
    for (int kt = 1; kt < nk; kt++) {
        if (!KVONLY && d.kind != PEND_NONE && kt != 2) drain(P, c, d);
        issue_any<KVONLY, false>(acc, c, type);
        wg_wait<1>();
        release(c, prev);
        prev = c.p.stage;
        pipe_next(c.p);
    }
    d.kind = PEND_NONE;
    wg_wait<0>();
    pin<128>(acc);
    release(c, prev);
    if (!KVONLY) { IP(1) }
}
__device__ __forceinline__ void pack_half(uint32_t* pk, const float* a) {
#pragma unroll
    for (int i = 0; i < 32; i++) pk[i] = pack2(a[2 * i], a[2 * i + 1]);
}

__device__ __forceinline__ void epi_kv(const float* acc, const Cons& c, Pend& d, int mb, int nb) {
    pack_half(d.pk, acc); pack_half(d.pk + 32, acc + 64);
    d.kind = PEND_KVO; d.row = (nb >> 4) * 2048 + mb * 256 + c.rank * 128 + c.wg * 64; d.col = (nb & 15) * 256; d.cnt = C_KV + mb;
}

__device__ __forceinline__ void qa_scores(float* S, float* Sm, const uint32_t* q, Cons& c) {
    wait_full(c);
    const uint32_t st = c.sb + c.p.stage * STAGE;
    const uint64_t dk = mkdesc(st + c.wg * 8192, 16, 1024, 1), dm = mkdesc(st + 32768 + c.wg * 4096, 128, 2048, 0);
    wg_fence();
#pragma unroll
    for (int i = 0; i < 8; i++) wgmma_rs64<0>(S, q + i * 4, dk + (i >> 2) * 1024 + (i & 3) * 2, i != 0);
#pragma unroll
    for (int i = 0; i < 8; i++) wgmma_rs16<0>(Sm, q + i * 4, dm + i * 16, i != 0);
    wg_commit();
    pipe_next(c.p);
}
__device__ __forceinline__ void qa_softmax(uint32_t (*pa)[4], const float* S, const float* Sm, const Cons& c) {
    const int t = c.lane & 3, i0 = (c.wq & 1) * 16 + (c.lane >> 2) - 2 * t;
    const bool sg = c.wq >= 2;
    const float cs = 0.08838834764831845f * 1.4426950408889634f;
    float x[2][10];
#pragma unroll
    for (int r = 0; r < 2; r++) {
#pragma unroll
        for (int j = 0; j < 4; j++)
#pragma unroll
            for (int e = 0; e < 2; e++) {
                const float v = sg ? S[16 + j * 4 + r * 2 + e] : S[j * 4 + r * 2 + e];
                x[r][j * 2 + e] = (j * 8 + e - r * 8 > i0) ? -1e9f / 0.08838834764831845f : v;
            }
        x[r][8] = sg ? Sm[4 + r * 2] : Sm[r * 2];
        x[r][9] = sg ? Sm[5 + r * 2] : Sm[1 + r * 2];
        float m = fmaxf(fmaxf(fmaxf(fmaxf(x[r][0], x[r][1]), fmaxf(x[r][2], x[r][3])), fmaxf(fmaxf(x[r][4], x[r][5]), fmaxf(x[r][6], x[r][7]))), fmaxf(x[r][8], x[r][9]));
        m = fmaxf(m, __shfl_xor_sync(0xffffffffu, m, 1));
        m = fmaxf(m, __shfl_xor_sync(0xffffffffu, m, 2));
        m *= -cs;
#pragma unroll
        for (int i = 0; i < 10; i++) x[r][i] = ex2(fmaf(x[r][i], cs, m));
        float sum = (((x[r][0] + x[r][1]) + (x[r][2] + x[r][3])) + ((x[r][4] + x[r][5]) + (x[r][6] + x[r][7]))) + (x[r][8] + x[r][9]);
        sum += __shfl_xor_sync(0xffffffffu, sum, 1);
        sum += __shfl_xor_sync(0xffffffffu, sum, 2);
        const float inv = rcp(sum);
#pragma unroll
        for (int i = 0; i < 10; i++) x[r][i] *= inv;
    }
#pragma unroll
    for (int ks = 0; ks < 2; ks++)
#pragma unroll
        for (int i = 0; i < 4; i++) {
            const uint32_t p = pack2(x[i & 1][ks * 4 + (i >> 1) * 2], x[i & 1][ks * 4 + (i >> 1) * 2 + 1]);
            pa[ks][i] = sg ? 0u : p;
            pa[2 + ks][i] = sg ? p : 0u;
        }
#pragma unroll
    for (int r = 0; r < 2; r++) {
        const uint32_t p = pack2(x[r][8], x[r][9]);
        pa[4][r] = sg ? 0u : p;
        pa[4][2 + r] = sg ? p : 0u;
    }
}
__device__ __forceinline__ void qa_values(float* O, uint32_t (*pa)[4], Cons& c) {
    wait_full(c);
    const uint32_t st = c.sb + c.p.stage * STAGE;
    const uint64_t dv = mkdesc(st + c.wg * 8192, 16384, 1024, 1), dm = mkdesc(st + 32768 + c.wg * 4096, 2048, 128, 0);
    pin<20>(&pa[0][0]);
    wg_fence();
#pragma unroll
    for (int ks = 0; ks < 4; ks++) wgmma_rs128<1>(O, pa[ks], dv + ks * 128, ks != 0);
    wgmma_rs128<0>(O, pa[4], dm, 1);
    wg_commit();
    pipe_next(c.p);
}
__device__ __forceinline__ void epi_qa(const float* acc, Cons& c, Pend& d, int mb, int nb) {
    uint32_t q[64], pa[2][5][4];
    float S0[32] = {}, M0[8] = {}, S1[32] = {}, M1[8] = {}, O0[64] = {}, O1[64] = {};
    const uint32_t k0 = c.p.stage;
    pack_half(q, acc);
    pin<32>(q); pin<32>(S0); pin<8>(M0);
    qa_scores(S0, M0, q, c);
    pack_half(q + 32, acc + 64);
    pin<32>(q + 32); pin<32>(S1); pin<8>(M1);
    qa_scores(S1, M1, q + 32, c);
    wg_wait<1>();
    pin<32>(S0); pin<8>(M0);
    release(c, k0);
    qa_softmax(pa[0], S0, M0, c);
    wg_wait<0>();
    pin<32>(S1); pin<8>(M1); pin<64>(q);
    release(c, (k0 + 1) & (NSTAGE - 1));
    pin<64>(O0);
    qa_values(O0, pa[0], c);
    qa_softmax(pa[1], S1, M1, c);
    pin<64>(O1);
    qa_values(O1, pa[1], c);
    wg_wait<1>();
    pin<64>(O0); pin<20>(&pa[0][0][0]);
    release(c, (k0 + 2) & (NSTAGE - 1));
    pack_half(d.pk, O0);
    wg_wait<0>();
    pin<64>(O1); pin<20>(&pa[1][0][0]);
    release(c, (k0 + 3) & (NSTAGE - 1));
    pack_half(d.pk + 32, O1);
    d.kind = PEND_KVO; d.row = 4096 + mb * 256 + c.rank * 128 + c.wg * 64; d.col = nb * 256; d.cnt = C_O + mb;
}

__device__ __forceinline__ void epi_op(const float* acc, const Cons& c, Pend& d, int mb, int nb) {
    pack_half(d.pk, acc); pack_half(d.pk + 32, acc + 64);
    d.kind = PEND_OUT; d.row = mb * 256 + c.rank * 128 + c.wg * 64; d.col = 1024 + nb * 256;
}

__device__ __forceinline__ void epi_a2(float* acc, const Params& P, Cons& c, int mb, int col0) {
    const int g = c.lane >> 2, t = c.lane & 3;
    const int row = mb * 256 + (g >> 1) * 64 + (c.rank * 16 + c.wg * 8 + c.wq * 2) * 2 + (g & 1);
    float* o = P.out + (size_t)row * 2048 + col0 + t * 2;
#pragma unroll 1
    for (int hf = P.zero; hf < 2; hf++) {
    wait_full(c);
    const uint32_t st = c.sb + c.p.stage * STAGE, xa = st + (c.wg * 64 + c.wq * 16 + g) * 128 + t * 4 + (g << 4), da = st + 32768 + t * 4;
#pragma unroll
    for (int j = 0; j < 16; j++) {
        const float* a = acc + j * 4;
        const uint32_t ad = (xa ^ ((j & 7) << 4)) + (j >> 3) * 16384;
        const uint32_t x0 = lds32(ad), x1 = lds32(ad + 1024), dv = lds32(da + j * 16);
        const uint32_t u0 = mul_bf2(x0, dv), u1 = mul_bf2(x1, dv);
        st_stream2(o + j * 8, a[0] + bf_lo(u0), a[1] + bf_hi(u0));
        st_stream2(o + 2 * 2048 + j * 8, a[2] + bf_lo(u1), a[3] + bf_hi(u1));
    }
    __syncwarp();
    release(c, c.p.stage);
    pipe_next(c.p);
    o += 128;
#pragma unroll
    for (int i = 0; i < 64; i++) acc[i] = acc[64 + i];
    }
}

#define TSTAMP(i)
__device__ __forceinline__ float2 cmul(float2 a, float2 b) { return make_float2(fmaf(a.x, b.x, -a.y * b.y), fmaf(a.x, b.y, a.y * b.x)); }
__device__ __forceinline__ float2 cfma(float2 a, float2 b, float2 u) { return make_float2(fmaf(a.x, b.x, fmaf(-a.y, b.y, u.x)), fmaf(a.x, b.y, fmaf(a.y, b.x, u.y))); }
__device__ __forceinline__ float4 ssm_coef(float lre, float lim, float logdt) {
    const float dt = __bfloat162float(__float2bfloat16(expf(logdt)));
    const float ea = expf(dt * lre);
    float sn, cn;
    sincosf(dt * lim, &sn, &cn);
    const float br = ea * cn, bi = ea * sn, nr = br - 1.f;
    float cr, ci;
    if (fabsf(lre) >= fabsf(lim)) { const float r = lim / lre, dn = lre + lim * r; cr = (nr + bi * r) / dn; ci = (bi - nr * r) / dn; }
    else { const float r = lre / lim, dn = lre * r + lim; cr = (nr * r + bi) / dn; ci = (bi * r - nr) / dn; }
    return make_float4(br, bi, cr, ci);
}
__device__ __forceinline__ void epi_a1(const float* acc, const Params& P, const Cons& c, Pend& d, int mb, int nb, uint32_t atag) {
    const int t = c.lane & 3;
    const int p = nb * 128 + c.rank * 64 + c.wg * 32 + c.wq * 8 + (c.lane >> 2);
    const float4 cf = __ldcg(&g_coef[p]);
    const float2 lam = make_float2(cf.x, P.swap_ri ? -cf.y : cf.y);
    const float a0 = P.swap_ri ? -2.f * cf.w : 2.f * cf.z, a1 = P.swap_ri ? 2.f * cf.z : -2.f * cf.w;
    const float b0 = P.swap_ri ? -2.f * cf.z : -2.f * cf.w, b1 = P.swap_ri ? -2.f * cf.w : -2.f * cf.z;
    float2 h = make_float2(0.f, 0.f);
#pragma unroll 1
    for (int round = P.zero; round < 2; round++) {
#pragma unroll
        for (int j = 0; j < 32; j++) {
            h = cfma(lam, h, make_float2(acc[j * 4], acc[j * 4 + 2]));
            const float r0 = fmaf(a0, h.x, a1 * h.y), m0 = fmaf(b0, h.x, b1 * h.y);
            h = cfma(lam, h, make_float2(acc[j * 4 + 1], acc[j * 4 + 3]));
            d.pk[j * 2] = pack2(r0, fmaf(a0, h.x, a1 * h.y));
            d.pk[j * 2 + 1] = pack2(m0, fmaf(b0, h.x, b1 * h.y));
        }
        if (round) continue;
        float2 l64 = lam;
#pragma unroll
        for (int i = 0; i < 6; i++) l64 = cmul(l64, l64);
        const float2 l128 = cmul(l64, l64), l256 = cmul(l128, l128);
        float2 o = make_float2(__shfl_up_sync(0xffffffffu, h.x, 1), __shfl_up_sync(0xffffffffu, h.y, 1));
        if (t >= 1) h = cfma(l64, o, h);
        o = make_float2(__shfl_up_sync(0xffffffffu, h.x, 2), __shfl_up_sync(0xffffffffu, h.y, 2));
        if (t >= 2) h = cfma(l128, o, h);
        IP(2)
        if (t == 3) st_relaxed2(&g_agg[mb * 1024 + p], (__float_as_uint(h.x) & ~1u) | atag, __float_as_uint(h.y));
        h = make_float2(__shfl_up_sync(0xffffffffu, h.x, 1), __shfl_up_sync(0xffffffffu, h.y, 1));
        if (t == 0) h = make_float2(0.f, 0.f);
        uint32_t ax[7], ay[7];
        while (true) {
            uint32_t bad = 0;
#pragma unroll
            for (int j = 0; j < 7; j++) { ax[j] = atag; ay[j] = 0; ld_relaxed2_if(ax[j], ay[j], &g_agg[j * 1024 + p], j < mb); }
#pragma unroll
            for (int j = 0; j < 7; j++) bad |= ax[j] ^ atag;
            if (tags_ok(bad)) break;
            __nanosleep(2 * POLLNS);
        }
        float2 carry = make_float2(0.f, 0.f);
#pragma unroll
        for (int j = 0; j < 7; j++) if (j < mb) carry = cfma(l256, carry, make_float2(__uint_as_float(ax[j]), __uint_as_float(ay[j])));
        float2 w = (t & 1) ? l64 : make_float2(1.f, 0.f);
        if (t & 2) w = cmul(w, l128);
        h = cfma(w, carry, h);
        IP(3)
    }
    IP(4)
    d.kind = PEND_HT; d.row = nb * 128 + c.rank * 64 + c.wg * 32; d.col = mb * 256; d.cnt = C_HT + mb;
}

__device__ __forceinline__ uint32_t fresh_tid() { uint32_t t; asm volatile("mov.u32 %0, %%tid.x;" : "=r"(t)); return t; }
__device__ __forceinline__ uint32_t acquire_stage(uint32_t sb, Pipe& p, uint32_t bytes) {
    mbar_wait(sb + B_EMPTY + p.stage * 8, p.phase ^ 1);
    mbar_expect_e(sb + B_FULL + p.stage * 8, bytes);
    return p.stage;
}
__device__ __forceinline__ void producer(const Params& P, const uint32_t sb, const int cta, const uint32_t epoch) {
    Pipe p = {0, 0};
    uint32_t resume = 1;
    const uint32_t e1 = epoch + 1;
    const int rank = cta & 1;
    const uint16_t both = 3 << (__shfl_sync(0xffffffffu, cluster_rank(), 0) & ~1u);
    for (int it = ITEM_OFF(cta >> 1); it < ITEM_OFF((cta >> 1) + 1); it++) {
        const int item = ITEM(it), type = (item >> 8) & 7, mb = (item >> 5) & 7, nb = item & 31, half = item >> 12 & 1, hw = item >> 13;
        if (type == T_CHAIN) {
            const int h = cta / 3, role = cta - h * 3;
            uint32_t* flag = &g_cnt(C_FLAG + (role == 2 ? 32 : 0) + h);
            if (role) { wait_count(&g_cnt(C_KV), e1 * 128); fence_async(); }
#pragma unroll 1
            for (int s = 0; s < 64 && role != 0; s++) {
                if (s < 63) {
                    mbar_wait(sb + B_GO, s & 1);
                    tma3d_mc_e(sb + S_KV + (role - 1) * 8192, &P.tm[M_SEG], 0, (role - 1) * 2048 + s * 32, h * 2, sb + B_KVFULL, 7 << ((h & 1) * 3), P.pol[s < 48 ? 8 : 11]);
                    if ((s & 7) == 7) { wait_count(&g_cnt(C_KV + 1 + (s >> 3)), e1 * 128); fence_async(); }
                    tma_prefetch3d_e(&P.tm[M_SEG], 0, (role - 1) * 2048 + s * 32 + 32, h * 2);
                }
                if (s > 0 && ((s & 3) == 0 || s == 63)) {
                    const int i = (s - 1) >> 2;
                    mbar_wait(sb + B_PERS, i & 1);
                    asm volatile("{\n.reg .pred E;\nelect.sync _|E, 0xffffffff;\n@E st.release.gpu.global.u32 [%0], %1;\n}" ::"l"(flag), "r"(epoch * 64 + i * 4 + 4) : "memory");
                }
            }
            if (role == 0) {
                const int lane = threadIdx.x & 31;
                if (lane == 0) mbar_arrive(sb + B_RELM);
#pragma unroll 1
                for (int s = 0; s < 63; s++) {
                    mbar_wait(sb + B_P1, s & 1);
                    if (s > 0) {
                        st_relaxed4(P.xb + xg_buf(s - 1) + h * 2048 + xg_lane(lane), 0, 0, 0, 0);
                        st_relaxed1(P.xb + xg_buf(s - 1) + xg_side(h) + lane * 4, 0);
                        __threadfence();
                    }
                    __syncwarp();
                    if (lane == 0) mbar_arrive(sb + B_RELM);
                }
            }
            if ((threadIdx.x & 31) < M_C1 - 1) asm volatile("prefetch.tensormap [%0];" ::"l"(&P.tm[1 + (threadIdx.x & 31)]) : "memory");
            resume = 0;
            continue;
        }
        const int m0 = mb * 256 + rank * 128, ssm = type >= T_A1;
        const CUtensorMap* ma = &P.tm[max(type, 1) + half * M_HALF];
        const CUtensorMap* mw = &P.tm[type ? M_WV + type : M_WK + (nb >> 4)];
        const int nk = type == T_OP ? 64 : type == T_A2 ? 32 : 16;
        const int a3 = type == T_A1 ? nb * 16 + rank * 8 + hw * 4 : type == T_A2 ? mb * 4 + rank * 2 + hw : (type == T_OP ? 4096 : 0) + m0 + hw * 64;
        const int b3 = type == T_A1 ? mb * 128 + rank * 16 : type == T_A2 ? (nb * 2 + rank) * 128 : (nb & 15) * 4 + rank * 2;
        if (type) {
            wait_count(&g_cnt(type == T_A1 ? C_COEF : (type >> 1) * 8 + mb), e1 * (type == T_A1 ? 4 : 128 >> (type >> 1)));
            fence_async();
        }
        if (type == T_A1) l2_prefetch_e(g_coef + nb * 128 + rank * 64, 1024);
        auto arrived = [&]() {
            const uint32_t t = fresh_tid();
            return __all_sync(0xffffffffu, (int32_t)(ld_acquire(&g_cnt(C_FLAG + (t & 2) * 16 + nb * 2 + (t & 1))) - (epoch * 64 + mb * 8 + rank * 4 + 4)) >= 0);
        };
        bool passed = false;
        mbar_wait(sb + B_RESUME, resume);
#pragma unroll 1
        for (int kt = 0; kt < nk; kt++) {
            if (type == T_QA && kt == 9) passed = arrived();
            const uint32_t st = acquire_stage(sb, p, STAGE - half * 8192), bar = sb + B_FULL + st * 8;
            const int a1 = type == T_A2 ? kt * 64 : 0, b0 = ssm ? (kt & 15) * 64 : 0;
            tma4d_e(sb + st * STAGE + hw * 8192, ma, kt * 64 - a1, a1, a3, bar, P.pol[11]);
            tma4d_mc_e(sb + st * STAGE + 16384 + rank * 16384, mw + (ssm & kt >> 4), b0, ssm ? 0 : kt * 64, b3, bar, both, P.pol[item == (item & 31) + 224 ? 9 : 11]);
            if (type == T_QA && kt < 8) tma_prefetch4d_e(&P.tm[M_OA], nb * 256 + (kt & 3) * 64, (kt >> 2) * 2048 + m0);
            pipe_next(p);
        }
        if (type == T_QA) {
            while (!passed) { passed = arrived(); if (!passed) __nanosleep(POLLNS); }
            fence_async();
        }
        const int q = type == T_QA;
#pragma unroll 1
        for (int e = 0; e < (q ? 4 : type == T_A2 ? 2 : 0); e++) {
            const uint32_t st = acquire_stage(sb, p, q ? 40960 : 32768 + 256), bar = sb + B_FULL + st * 8, dst = sb + st * STAGE;
#pragma unroll 1
            for (int i = 0; i < 2; i++) tma4d_e(dst + i * 16384, &P.tm[q ? M_OA : M_AX], nb * 256 + (e & 1) * 128 + i * 64, 0, q ? (e >> 1) * 2048 + m0 : mb * 128 + rank * 16, bar, P.pol[q ? 3 : 11]);
            const uint8_t* src = q ? (const uint8_t*)(((e >> 1) ? g_vmt : g_km) + ((mb * 8 + rank * 4) * 32 + nb * 2 + (e & 1)) * 512) : (const uint8_t*)(P.Dskip + nb * 256 + e * 128);
#pragma unroll 1
            for (int i = 0; i < (q ? 4 : 1); i++) bulk_g2s_e(dst + 32768 + i * 2048, src + i * 65536, q ? 2048 : 256, bar);
            pipe_next(p);
        }
    }
}

__device__ __forceinline__ uint32_t fresh_ctaid() { uint32_t t; asm volatile("mov.u32 %0, %%ctaid.x;" : "=r"(t)); return t; }
__device__ __forceinline__ void reset_state(const Params& P, Cons& c, Pend& d, uint32_t sb, bool resumed) {
    const uint32_t t = fresh_tid(), b = fresh_ctaid() + P.cta0;
    const int w = __shfl_sync(0xffffffffu, t >> 5, 0);
    c.sb = sb; c.wg = w >> 2; c.wq = w & 3; c.lane = t & 31;
    c.rank = __shfl_sync(0xffffffffu, b & 1, 0); c.pair = __shfl_sync(0xffffffffu, b >> 1, 0);
    c.rel = mapa(sb + B_EMPTY, cluster_rank() ^ (c.lane & 1));
    c.atag = (ld_acquire(&g_cnt(C_EPOCH)) + 1) & 1;
    c.p.stage = 0; c.p.phase = 0;
    c.nst = resumed && c.pair < NCHAIN;
    d = Pend{};
}
#define PROF_ITEM(i, item)

__global__ void __launch_bounds__(384, 1) fused_kernel(const __grid_constant__ Params P) {
    extern __shared__ __align__(1024) uint8_t smem[];
    const uint32_t sb = smem_u32(smem);
    asm volatile("griddepcontrol.launch_dependents;");
    declare_fence(P.zero);
    const int tid = threadIdx.x, lane = tid & 31;
    const int warp = __shfl_sync(0xffffffffu, tid >> 5, 0);
    const int cta = __shfl_sync(0xffffffffu, blockIdx.x + P.cta0, 0), pair = cta >> 1, rank = cta & 1;
    if (tid == 0) {
        if (sb & 1023) spin_fault();
        for (int i = 0; i < NSTAGE; i++) { mbar_init(sb + B_FULL + i * 8, 1); mbar_init(sb + B_EMPTY + i * 8, 16); }
        mbar_init(sb + B_RESUME, 2);
        mbar_init(sb + B_KVFULL, 1);
        mbar_init(sb + B_GO, 3); mbar_init(sb + B_RED, 8); mbar_init(sb + B_P1, 1); mbar_init(sb + B_PERS, 8); mbar_init(sb + B_INIT, 8); mbar_init(sb + B_INIT2, 8);
        mbar_init(sb + B_READY, 8);
        for (int i = 0; i < 2; i++) { mbar_init(sb + B_SFULL + i * 8, 4); mbar_init(sb + B_SFREE + i * 8, 1); }
        mbar_init(sb + B_RELM, cta % 3 ? 1 : 2); mbar_init(sb + B_X, 9);
        asm volatile("fence.mbarrier_init.release.cluster;" ::: "memory");
        mbar_expect(sb + B_X, 4096);
        sts64(sb + S_EV, 0, 0); mbar_init(sb + B_DONE, 2);
    }
    cluster_sync();
    if (warp >= 8) {
        asm volatile("setmaxnreg.dec.sync.aligned.u32 24;");
        if (warp == 8) {
            producer(P, sb, cta, __shfl_sync(0xffffffffu, ld_acquire(&g_cnt(C_EPOCH)), 0));
            asm volatile("barrier.cluster.arrive.relaxed.aligned;\nbarrier.cluster.wait.aligned;" ::: "memory");
        } else if (warp == 9) {
            if (pair < NCHAIN) pacer(P, sb, cta, lane, __shfl_sync(0xffffffffu, ld_acquire(&g_cnt(C_EPOCH)), 0));
            mbar_wait_bounded(sb + B_DONE, 0);
        } else {
            store_warp(P, sb, warp - 10, cta);
        }
    } else {
        asm volatile("setmaxnreg.inc.sync.aligned.u32 240;");
        Cons c;
        Pend d;
        if (pair < NCHAIN) {
            reset_state(P, c, d, sb, false);
            {
                const int item = ITEM(ITEM_OFF(pair));
                PROF_ITEM(0, item)
                float acc[128];
                mainloop<true>(acc, P, c, d, T_KV, 16);
                ISTAMP(4)
                mbar_wait(sb + B_EMPTY + warp * 20480 / STAGE * 8, 1);
                mbar_wait(sb + B_EMPTY + (warp * 20480 + 20479) / STAGE * 8, 1);
                chain_load(P, sb, cta, warp, lane, 0);
                epi_kv(acc, c, d, (item >> 5) & 7, item & 31);
            }
            ISTAMP(9)
            mbar_wait(sb + B_EMPTY + 3 * 8, 1);
            drain_both(c, d);
            ISTAMP(10)
            uint32_t wr[40][4];
            chain_fetch(P, sb, cta, warp, lane, wr);
            PROF_ITEM(1, T_CHAIN << 8)
            chain_bounds(sb, cta, warp, lane, wr);
            ISTAMP(11)
            const uint32_t epoch = __shfl_sync(0xffffffffu, ld_acquire(&g_cnt(C_EPOCH)), 0);
            if (warp < 4) chain_role<false>(P, sb, cta, warp, lane, epoch, wr);
            else chain_role<true>(P, sb, cta, warp, lane, epoch, wr);
            fence_async_smem();
            bar_sync(1, 256);
            const uint32_t t2 = fresh_tid();
            if (t2 < 2) mbar_arrive_cluster(mapa(sb + B_RESUME, cluster_rank() ^ t2));
        } else if (pair >= NPAIR - 2) {
            const int ch = (pair - (NPAIR - 2)) * 512 + rank * 256 + tid;
            g_coef[ch] = ssm_coef(__bfloat162float(P.Lre[ch]), __bfloat162float(P.Lim[ch]), __bfloat162float(P.logdt[ch]));
            bar_sync(1, 256);
            if (tid == 0) red_release(&g_cnt(C_COEF));
        }
        reset_state(P, c, d, sb, true);
        int it = ITEM_OFF(c.pair) + (c.pair < NCHAIN ? 2 : 0);
        const int end = ITEM_OFF(c.pair + 1);
        for (;; it++) {
            const bool last = it == end;
            const int item = ITEM(it), type = (item >> 8) & 7, mb = (item >> 5) & 7, nb = item & 31;
            const bool idle = (item >> 12) == 3 - 2 * c.wg;
            if (d.kind != PEND_NONE && (last || idle || (ITEM(it - 1) & URGENT) || !bar_and(5 + c.wg, mbar_try(sb + B_FULL + c.p.stage * 8, c.p.phase)))) {
#pragma unroll 1
                while (d.kind != PEND_NONE) drain(P, c, d);
            }
            if (last) break;
            const int nk = type == T_OP ? 64 : type == T_A2 ? 32 : 16;
            PROF_ITEM(it - ITEM_OFF(c.pair), item)
            if (idle) {
#pragma unroll 1
                for (int kt = nk + (type == T_A2 ? 2 : type == T_QA ? 4 : 0); kt > 0; kt--) { wait_full(c); release(c, c.p.stage); pipe_next(c.p); }
                continue;
            }
            float acc[128];
            mainloop(acc, P, c, d, type, nk);
            if (type == T_KV) epi_kv(acc, c, d, mb, nb);
            else if (type == T_QA) epi_qa(acc, c, d, mb, nb);
            else if (type == T_OP) epi_op(acc, c, d, mb, nb);
            else if (type == T_A1) epi_a1(acc, P, c, d, mb, nb, c.atag);
            else epi_a2(acc, P, c, mb, nb * 256);
        }
        staging_wait(c);
        staging_post(c, PEND_NONE, 0, 0, 0);
        if (c.wq == 0 && c.lane == 0) mbar_arrive(sb + B_DONE);
        cluster_sync();
        if (c.wg == 0 && c.wq == 0 && c.lane == 0 && atomicInc(&g_cnt(C_DONE), NPAIR * 2 - 1) == NPAIR * 2 - 1) { __threadfence(); atomicAdd(&g_cnt(C_EPOCH), 1); }
    }
}

typedef CUresult (*EncodeFn)(CUtensorMap*, CUtensorMapDataType, cuuint32_t, void*, const cuuint64_t*, const cuuint64_t*, const cuuint32_t*, const cuuint32_t*,
                             CUtensorMapInterleave, CUtensorMapSwizzle, CUtensorMapL2promotion, CUtensorMapFloatOOBfill);
void encode(EncodeFn fn, CUtensorMap* m, const void* base, int rank, const uint64_t* dims, const uint64_t* strides, const uint32_t* box, CUtensorMapSwizzle swz = CU_TENSOR_MAP_SWIZZLE_128B) {
    cuuint64_t d[5], s[5]; cuuint32_t b[5], e[5];
    for (int i = 0; i < rank; i++) { d[i] = dims[i]; b[i] = box[i]; e[i] = 1; if (i) s[i - 1] = strides[i - 1]; }
    fn(m, CU_TENSOR_MAP_DATA_TYPE_BFLOAT16, rank, (void*)base, d, s, b, e, CU_TENSOR_MAP_INTERLEAVE_NONE, swz,
       CU_TENSOR_MAP_L2_PROMOTION_L2_256B, CU_TENSOR_MAP_FLOAT_OOB_FILL_NONE);
}
void map_kmajor(EncodeFn fn, CUtensorMap* m, const void* base, uint64_t rows, uint64_t cols, uint32_t box_rows) {
    const uint64_t d[4] = {cols, 1, 1, rows}, s[3] = {cols * 2, cols * 2, cols * 2}; const uint32_t b[4] = {64, 1, 1, box_rows};
    encode(fn, m, base, 4, d, s, b);
}
void map_mnmajor(EncodeFn fn, CUtensorMap* m, const void* base, uint64_t krows, uint64_t cols, uint32_t groups = 2) {
    const uint64_t d[4] = {64, krows, 1, cols / 64}, s[3] = {cols * 2, 128, 128}; const uint32_t b[4] = {64, 64, 1, groups};
    encode(fn, m, base, 4, d, s, b);
}
void map_store(EncodeFn fn, CUtensorMap* m, const void* base, uint64_t rows, uint64_t cols) {
    const uint64_t d[2] = {cols, rows}, s[1] = {cols * 2}; const uint32_t b[2] = {64, 32};
    encode(fn, m, base, 2, d, s, b);
}

}

extern "C" void kernel_launch(void* const* d_in, const int* in_sizes, int n_in, void* d_out, int out_size) {
    static Params P;
    static EncodeFn fn = nullptr;
    if (!fn) {
        cudaDriverEntryPointQueryResult q;
        cudaGetDriverEntryPoint("cuTensorMapEncodeTiled", (void**)&fn, cudaEnableDefault, &q);
        cudaFuncSetAttribute(fused_kernel, cudaFuncAttributeMaxDynamicSharedMemorySize, S_TOTAL);
    }
    const bf16* in[15];
    for (int i = 0; i < 15; i++) in[i] = (const bf16*)d_in[i];
    void *kvo, *ht;
    cudaGetSymbolAddress(&kvo, g_kvo);
    cudaGetSymbolAddress(&ht, g_ht);
    map_kmajor(fn, &P.tm[M_BX], in[9], 2048, 1024, 128);
    map_mnmajor(fn, &P.tm[M_WQ], in[11], 1024, 4096);
    map_mnmajor(fn, &P.tm[M_WK], in[12], 1024, 4096);
    map_mnmajor(fn, &P.tm[M_WV], in[13], 1024, 4096);
    map_mnmajor(fn, &P.tm[M_WO], in[14], 4096, 1024);
    map_kmajor(fn, &P.tm[M_OA], kvo, 3 * 2048, 4096, 128);
    P.swap_ri = in[4] < in[3];
    {
        const bf16* lo = P.swap_ri ? in[4] : in[3];
        const uint64_t diff = (uint64_t)((const char*)(P.swap_ri ? in[3] : in[4]) - (const char*)lo);
        const uint64_t d[4] = {1024, 8, 2, 128}, s[3] = {2048, diff, 16384}; const uint32_t b[4] = {64, 8, 2, 8}, bh[4] = {64, 8, 2, 4};
        encode(fn, &P.tm[M_AB], lo, 4, d, s, b);
        encode(fn, &P.tm[M_AB + M_HALF], lo, 4, d, s, bh);
    }
    {
        const uint64_t d[4] = {1024, 2, 4, 1024}, s[3] = {2048, 64 * 2048, 4096}; const uint32_t b[4] = {64, 2, 4, 16};
        encode(fn, &P.tm[M_AX], in[0], 4, d, s, b);
    }
    map_mnmajor(fn, &P.tm[M_HT], ht, 2048, 2048);
    map_kmajor(fn, &P.tm[M_CRE], in[5], 1024, 1024, 128);
    map_kmajor(fn, &P.tm[M_CIM], in[6], 1024, 1024, 128);
    map_store(fn, &P.tm[M_KVO], kvo, 3 * 2048, 4096);
    map_store(fn, &P.tm[M_HTS], ht, 2048, 2048);
    map_kmajor(fn, &P.tm[M_BX + M_HALF], in[9], 2048, 1024, 64);
    map_kmajor(fn, &P.tm[M_OA + M_HALF], kvo, 3 * 2048, 4096, 64);
    map_mnmajor(fn, &P.tm[M_HT + M_HALF], ht, 2048, 2048, 1);
    for (int i = 0; i < 3; i++) {
        const uint64_t d[3] = {64, 1024, 64}, s[2] = {8192, 128}; const uint32_t b[3] = {64, 16, 2};
        encode(fn, &P.tm[M_C1 + i], in[11 + i], 3, d, s, b);
    }
    {
        const uint64_t d[2] = {1024, 4096}, s[1] = {2048}; const uint32_t b[2] = {32, 32};
        encode(fn, &P.tm[M_CO], in[14], 2, d, s, b, CU_TENSOR_MAP_SWIZZLE_64B);
    }
    {
        const uint64_t d[3] = {64, 3 * 2048, 64}, s[2] = {8192, 128}; const uint32_t b[3] = {64, 32, 2};
        encode(fn, &P.tm[M_SEG], kvo, 3, d, s, b);
    }
    void* xs;
    cudaGetSymbolAddress(&xs, g_x);
    P.xb = (uint8_t*)(((uintptr_t)xs + (2u << 20) - 1) & ~(uintptr_t)((2u << 20) - 1));
    P.Wq = in[11]; P.Wk = in[12]; P.Wv = in[13]; P.Wo = in[14]; P.mem0 = in[10]; P.Bx = in[9];
    P.Ax = in[0]; P.Lre = in[1]; P.Lim = in[2]; P.logdt = in[7]; P.Dskip = in[8];
    P.out = (float*)d_out;
    int pv[10] = {1300, 0, 110, 0, 330, 0, 32, 32, 0, 0};
    int ef = 779;
    for (int i = 0; i < 12; i++) P.pol[i] = (ef >> i & 1) ? 0x12F0000000000000ull : 0x1000000000000000ull;
    P.dly = pv[0]; P.mrg = pv[2];
    P.rd = pv[4]; P.guard = pv[5]; P.clampv = pv[6]; P.clamp0 = pv[7]; P.kvd = pv[9]; P.xd = pv[8];
    cudaLaunchConfig_t cfg = {};
    cudaLaunchAttribute at[2];
    cfg.blockDim = dim3(384); cfg.dynamicSmemBytes = S_TOTAL; cfg.stream = cudaStreamPerThread; cfg.attrs = at;
    at[0].id = cudaLaunchAttributeClusterDimension;
    at[0].val.clusterDim.y = at[0].val.clusterDim.z = 1;
    at[1].id = cudaLaunchAttributeProgrammaticStreamSerialization;
    at[1].val.programmaticStreamSerializationAllowed = 1;
    for (int i = 0; i < 2; i++) {
        P.cta0 = i ? 2 * NCHAIN : 0;
        cfg.gridDim = dim3(i ? 2 * (NPAIR - NCHAIN) : 2 * NCHAIN);
        at[0].val.clusterDim.x = i ? 2 : 6;
        cfg.numAttrs = 1 + i;
        cudaLaunchKernelEx(&cfg, fused_kernel, P);
    }
}
```

```cpp
#include <cuda_runtime.h>
#include <cuda_bf16.h>
#include <cuda.h>
#include <stdint.h>
#include <string.h>

typedef __nv_bfloat16 bf16;

namespace {

constexpr int SPIN_LIMIT = 1 << 22;
#define POLLNS 100
constexpr int NPAIR = 66;
constexpr int NCHAIN = 48;
enum { T_KV = 0, T_QA = 1, T_OP = 2, T_A1 = 3, T_A2 = 4, T_CHAIN = 5 };
constexpr int URGENT = 2048;
constexpr int HALF = 4096;
enum { M_BX = 1, M_OA, M_AB, M_HT, M_HALF = 4, M_WK = 9, M_WV, M_WQ, M_WO, M_AX, M_CRE, M_CIM, M_KVO, M_HTS, M_C1, M_CO = M_C1 + 3, M_SEG, M_COUNT };
enum { C_KV = 0, C_O = 8, C_HT = 16, C_READ = 24, C_EPOCH = 25, C_COEF = 26, C_XMAX = 27, C_XCNT = 28, C_FLAG = 32 };

struct Params {
    CUtensorMap tm[M_COUNT];
    const bf16 *Wq, *Wk, *Wv, *Wo, *mem0, *Bx, *Ax, *Lre, *Lim, *logdt, *Dskip;
    float* out;
    uint8_t* xb;
    int swap_ri, zero;
    int dly, mrg, rd, guard, clampv, clamp0, kvd, xd;
    uint64_t pol[12];
    uint16_t cta0;
};

__constant__ uint16_t c_off[67] = {0, 4, 8, 12, 17, 21, 25, 29, 33, 38, 43, 48, 53, 58, 63, 68, 72, 76, 81, 86, 90, 94, 98, 102, 106, 110, 114, 118, 122, 127, 131, 135, 139, 144, 149, 153, 157, 162, 166, 170, 174, 179, 183, 188, 192, 196, 201, 206, 211, 231, 251, 270, 289, 308, 328, 347, 365, 385, 405, 425, 445, 465, 485, 505, 524, 543, 562};
__constant__ uint16_t c_items[700] = {
    0, 1280, 2473, 642, 16, 1280, 2474, 514, 32, 1280, 2476, 611, 1, 1280, 486, 2823, 1089, 17, 1280, 495, 675, 33, 1280, 417,
    544, 2, 1280, 773, 578, 18, 1280, 870, 739, 34, 1280, 806, 807, 1187, 3, 1280, 2504, 2979, 12962, 19, 1280, 2503, 2945, 1121,
    35, 1280, 2529, 3043, 4770, 4, 1280, 2502, 770, 1056, 20, 1280, 2539, 932, 1153, 36, 1280, 2509, 2946, 1027, 5, 1280, 482, 547,
    21, 1280, 2475, 512, 37, 1280, 2471, 2919, 1088, 6, 1280, 2510, 834, 1123, 22, 1280, 489, 609, 38, 1280, 2469, 705, 7, 1280,
    2820, 515, 23, 1280, 833, 737, 39, 1280, 774, 704, 8, 1280, 483, 576, 24, 1280, 488, 706, 40, 1280, 453, 738, 9, 1280,
    449, 608, 25, 1280, 2506, 963, 1025, 41, 1280, 492, 641, 10, 1280, 451, 513, 26, 1280, 416, 545, 42, 1280, 2532, 866, 1184,
    11, 1280, 459, 802, 1250, 27, 1280, 2538, 577, 43, 1280, 448, 643, 12, 1280, 2508, 2948, 4832, 28, 1280, 2498, 672, 44, 1280,
    431, 707, 13, 1280, 2511, 640, 29, 1280, 2466, 934, 1248, 45, 1280, 424, 546, 14, 1280, 494, 868, 1154, 30, 1280, 430, 610,
    46, 1280, 2528, 579, 15, 1280, 838, 839, 1217, 31, 1280, 804, 2951, 1026, 47, 1280, 836, 2977, 1122, 48, 66, 84, 102, 256,
    124, 142, 160, 175, 191, 207, 224, 239, 230, 328, 386, 331, 928, 3010, 1120, 49, 67, 85, 103, 257, 125, 143, 161, 176,
    192, 208, 225, 240, 241, 399, 354, 335, 835, 998, 1090, 50, 68, 86, 104, 258, 126, 144, 162, 177, 193, 209, 226, 2350,
    388, 2412, 2819, 803, 2983, 1058, 51, 69, 87, 105, 259, 127, 145, 163, 178, 194, 210, 2438, 2446, 385, 355, 391, 899, 997,
    1216, 52, 70, 88, 106, 260, 128, 146, 164, 179, 195, 211, 329, 298, 2817, 395, 367, 2913, 3041, 1024, 53, 71, 89, 107,
    261, 129, 147, 165, 180, 196, 212, 229, 244, 245, 330, 297, 397, 837, 3008, 1185, 54, 72, 90, 108, 262, 130, 148, 166,
    181, 197, 213, 321, 394, 396, 326, 2370, 902, 2981, 1155, 55, 73, 91, 109, 263, 131, 149, 167, 182, 198, 214, 231, 327,
    362, 387, 299, 487, 673, 56, 74, 92, 110, 264, 132, 150, 168, 183, 199, 215, 232, 247, 227, 323, 358, 366, 800, 3047,
    1251, 57, 75, 93, 111, 265, 133, 151, 169, 184, 200, 216, 233, 248, 254, 359, 334, 360, 896, 965, 1152, 58, 76, 94,
    112, 266, 134, 152, 170, 185, 201, 217, 234, 249, 243, 352, 332, 384, 901, 992, 1218, 59, 77, 95, 113, 267, 135, 153,
    171, 186, 202, 218, 235, 250, 255, 420, 356, 320, 832, 3009, 1091, 60, 78, 96, 114, 268, 136, 154, 172, 187, 203, 219,
    236, 251, 246, 419, 452, 361, 805, 3014, 1186, 61, 79, 97, 115, 269, 137, 155, 173, 188, 204, 220, 237, 252, 242, 392,
    457, 485, 864, 3015, 1057, 62, 80, 98, 116, 270, 138, 156, 174, 189, 205, 221, 238, 253, 228, 2349, 333, 295, 867, 3044,
    1059, 63, 81, 99, 117, 271, 139, 157, 288, 190, 292, 293, 296, 300, 429, 303, 493, 869, 3042, 1249, 64, 82, 100, 118,
    120, 122, 140, 158, 289, 206, 222, 294, 393, 422, 2413, 363, 801, 930, 1219, 65, 83, 101, 119, 121, 123, 141, 159, 290,
    291, 223, 389, 353, 2405, 324, 325, 768, 3012, 13024,
};
#define ITEM_OFF(p) c_off[p]
#define ITEM(i) c_items[i]

__device__ __align__(1024) bf16 g_kvo[3 * 2048 * 4096];
__device__ __align__(1024) bf16 g_ht[2048 * 2048];
__device__ __align__(1024) uint8_t g_x[4 << 20];
__device__ __align__(1024) uint32_t g_km[64 * 32 * 512];
__device__ __align__(1024) uint32_t g_vmt[64 * 32 * 512];
__device__ __align__(1024) float2 g_agg[8 * 1024];
__device__ __align__(1024) float4 g_coef[1024];
__device__ __align__(1024) uint32_t g_cntl[128 * 32];
#define g_cnt(i) g_cntl[(i) * 32]
__device__ __align__(1024) uint32_t g_hint[96 * 32];
#define PROF(i)
#define PROFDUMP()
#define PROFP(i)
constexpr int XG_SIDE = 65536, XG_T = 98304;
__device__ __forceinline__ uint32_t xg_buf(int b) { return (b & 1) * 128 + (b & 2) * 256 + (b & 4) * 32768; }
__device__ __forceinline__ uint32_t xg_lane(uint32_t lane) { return (lane >> 4) * 1024 + (lane & 8) * 32 + (lane & 7) * 16; }
__device__ __forceinline__ uint32_t xg_side(int b) { return XG_SIDE + (b >> 1) * 1024 + (b & 1) * 256; }

constexpr int STAGE = 49152, NSTAGE = 4;
constexpr int S_STG = NSTAGE * STAGE;
constexpr int S_BAR = S_STG + 32768;
constexpr int B_FULL = S_BAR, B_EMPTY = S_BAR + 32, B_RESUME = S_BAR + 64, B_KVFULL = S_BAR + 72, B_GO = S_BAR + 88, B_X = S_BAR + 96, B_PERS = S_BAR + 104,
              B_INIT = S_BAR + 112, B_RELM = S_BAR + 120, B_READY = S_BAR + 136, B_SFULL = S_BAR + 144, B_SFREE = S_BAR + 160, S_DESC = S_BAR + 176, B_RED = S_BAR + 216;
constexpr int S_EV = S_BAR + 80, S_EO = S_BAR + 84, B_INIT2 = S_BAR + 128, S_SC = S_BAR + 208, S_ISC = S_EV;
constexpr int S_XV = S_BAR + 256, S_LOG = S_XV + 2048;
constexpr int S_TOTAL = S_LOG + 768;
#define NRA 5
#define NRB 3
constexpr int S_W1 = 0;
constexpr int S_W2 = 4 * 4096 * (16 - NRA - NRB);
constexpr int S_KV = 188416;
constexpr int S_P1 = S_KV + 16384;
constexpr int S_X = S_P1 + 16384;
constexpr int S_SX = S_P1, S_OX = S_P1 + 2048;
constexpr int S_EM = S_X + 4096, S_TO = S_EM + 32, B_DONE = S_BAR + 224, B_P1 = S_BAR + 232, B_EPOCH = S_BAR + 240, S_EPOCH = S_BAR + 248;
static_assert(S_TO + 32 <= S_BAR && S_KV % 1024 == 0 && S_TOTAL <= 232448, "chain smem layout");

template <int V> struct IC { static constexpr int value = V; };
template <int B, int E, typename F> __device__ __forceinline__ void static_for(F&& f) { if constexpr (B < E) { f(IC<B>{}); static_for<B + 1, E>(f); } }
__device__ __forceinline__ uint32_t cluster_rank() { uint32_t r; asm volatile("mov.u32 %0, %%cluster_ctarank;" : "=r"(r)); return r; }
__device__ __forceinline__ void spin_fault() { asm volatile("st.global.u32 [%0], 0;" ::"l"(0ull) : "memory"); }
__device__ __forceinline__ uint32_t smem_u32(const void* p) { return (uint32_t)__cvta_generic_to_shared(p); }
__device__ __forceinline__ uint32_t opq(uint32_t x, int lane) { return __shfl_sync(0xffffffffu, x, lane); }
__device__ __forceinline__ uint32_t mapa(uint32_t a, uint32_t r) { uint32_t d; asm volatile("mapa.shared::cluster.u32 %0, %1, %2;" : "=r"(d) : "r"(a), "r"(r)); return d; }
__device__ __forceinline__ void mma16816(float* d, uint32_t a0, uint32_t a1, uint32_t a2, uint32_t a3, uint32_t b0, uint32_t b1) {
    asm("mma.sync.aligned.m16n8k16.row.col.f32.bf16.bf16.f32 {%0,%1,%2,%3}, {%4,%5,%6,%7}, {%8,%9}, {%0,%1,%2,%3};"
        : "+f"(d[0]), "+f"(d[1]), "+f"(d[2]), "+f"(d[3]) : "r"(a0), "r"(a1), "r"(a2), "r"(a3), "r"(b0), "r"(b1));
}
__device__ __forceinline__ void mma1688(float* d, uint32_t a0, uint32_t a1, uint32_t b0) {
    asm("mma.sync.aligned.m16n8k8.row.col.f32.bf16.bf16.f32 {%0,%1,%2,%3}, {%4,%5}, {%6}, {%0,%1,%2,%3};"
        : "+f"(d[0]), "+f"(d[1]), "+f"(d[2]), "+f"(d[3]) : "r"(a0), "r"(a1), "r"(b0));
}
__device__ __forceinline__ void ldsm4(uint32_t* r, uint32_t a) {
    asm volatile("ldmatrix.sync.aligned.m8n8.x4.shared.b16 {%0,%1,%2,%3}, [%4];" : "=r"(r[0]), "=r"(r[1]), "=r"(r[2]), "=r"(r[3]) : "r"(a));
}
__device__ __forceinline__ void ldsm4t(uint32_t* r, uint32_t a) {
    asm volatile("ldmatrix.sync.aligned.m8n8.x4.trans.shared.b16 {%0,%1,%2,%3}, [%4];" : "=r"(r[0]), "=r"(r[1]), "=r"(r[2]), "=r"(r[3]) : "r"(a));
}
__device__ __forceinline__ void stsm4(uint32_t a, uint32_t r0, uint32_t r1, uint32_t r2, uint32_t r3) {
    asm volatile("stmatrix.sync.aligned.m8n8.x4.shared.b16 [%0], {%1,%2,%3,%4};" ::"r"(a), "r"(r0), "r"(r1), "r"(r2), "r"(r3) : "memory");
}
__device__ __forceinline__ void stsm4t(uint32_t a, uint32_t r0, uint32_t r1, uint32_t r2, uint32_t r3) {
    asm volatile("stmatrix.sync.aligned.m8n8.x4.trans.shared.b16 [%0], {%1,%2,%3,%4};" ::"r"(a), "r"(r0), "r"(r1), "r"(r2), "r"(r3) : "memory");
}
__device__ __forceinline__ uint32_t movm(uint32_t a) { uint32_t d; asm volatile("movmatrix.sync.aligned.m8n8.trans.b16 %0, %1;" : "=r"(d) : "r"(a)); return d; }
__device__ __forceinline__ uint32_t pack2(float lo, float hi) { uint32_t d; asm("cvt.rn.bf16x2.f32 %0, %1, %2;" : "=r"(d) : "f"(hi), "f"(lo)); return d; }
__device__ __forceinline__ uint32_t prmt(uint32_t a, uint32_t b, uint32_t s) { uint32_t d; asm("prmt.b32 %0, %1, %2, %3;" : "=r"(d) : "r"(a), "r"(b), "r"(s)); return d; }
__device__ __forceinline__ uint32_t pack2h(float lo, float hi) { uint32_t d; asm("cvt.rn.f16x2.f32 %0, %1, %2;" : "=r"(d) : "f"(hi), "f"(lo)); return d; }
__device__ __forceinline__ uint32_t h2bf(uint32_t a, uint32_t b) {
    uint32_t d;
    asm("{\n.reg .b16 l, h, u;\n.reg .f32 x, y;\nmov.b32 {l, u}, %1;\ncvt.f32.f16 x, l;\nmov.b32 {u, h}, %2;\ncvt.f32.f16 y, h;\ncvt.rn.bf16x2.f32 %0, y, x;\n}" : "=r"(d) : "r"(a), "r"(b));
    return d;
}
__device__ __forceinline__ void cvt_block(uint32_t* u, uint32_t& x, uint32_t sel) {
    const uint32_t a = prmt(u[0], u[0], sel), b = prmt(u[1], u[1], sel), c = prmt(u[2], u[2], sel), d = prmt(u[3], x, sel);
    x ^= u[3] ^ d;
    u[0] = h2bf(a, a); u[1] = h2bf(b, b); u[2] = h2bf(c, c); u[3] = h2bf(d, d);
}
__device__ __forceinline__ uint32_t amax(uint32_t a, uint32_t b) { uint32_t d; asm("max.xorsign.abs.bf16x2 %0, %1, %2;" : "=r"(d) : "r"(a), "r"(b)); return d; }
__device__ __forceinline__ uint32_t amax4(uint32_t m, const uint32_t* v) { return amax(amax(m, amax(v[0], v[1])), amax(v[2], v[3])); }
__device__ __forceinline__ uint32_t warp_exp(uint32_t m) { return __reduce_max_sync(0xffffffffu, max(m & 0x7f80u, (m >> 16) & 0x7f80u)) >> 7; }
__device__ __forceinline__ void red_max_shared(uint32_t a, uint32_t x) { asm volatile("red.shared.max.u32 [%0], %1;" ::"r"(a), "r"(x) : "memory"); }
__device__ __forceinline__ uint32_t mul_bf2(uint32_t a, uint32_t b) { uint32_t d; asm("mul.rn.bf16x2 %0, %1, %2;" : "=r"(d) : "r"(a), "r"(b)); return d; }
__device__ __forceinline__ float bf_lo(uint32_t u) { return __uint_as_float(u << 16); }
__device__ __forceinline__ float bf_hi(uint32_t u) { return __uint_as_float(u & 0xffff0000u); }
__device__ __forceinline__ float ex2(float x) { float y; asm("ex2.approx.ftz.f32 %0, %1;" : "=f"(y) : "f"(x)); return y; }
__device__ __forceinline__ float rcp(float x) { float y; asm("rcp.approx.ftz.f32 %0, %1;" : "=f"(y) : "f"(x)); return y; }
__device__ __forceinline__ void st_relaxed4(const void* p, uint32_t a, uint32_t b, uint32_t c, uint32_t d) {
    asm volatile("{\n.reg .b128 t;\nmov.b128 t, {%1,%2,%3,%4};\nst.relaxed.gpu.global.b128 [%0], t;\n}" ::"l"(p), "r"(a), "r"(b), "r"(c), "r"(d) : "memory");
}
__device__ __forceinline__ void st_relaxed2(const void* p, uint32_t a, uint32_t b) {
    asm volatile("{\n.reg .b64 t;\nmov.b64 t, {%1,%2};\nst.relaxed.gpu.global.b64 [%0], t;\n}" ::"l"(p), "r"(a), "r"(b) : "memory");
}
__device__ __forceinline__ void ld_relaxed2_if(uint32_t& a, uint32_t& b, const void* p, bool on) {
    asm volatile("{\n.reg .pred P;\n.reg .b64 t;\nsetp.ne.u32 P, %3, 0;\nmov.b64 t, {%0,%1};\n@P ld.relaxed.gpu.global.b64 t, [%2];\nmov.b64 {%0,%1}, t;\n}" : "+r"(a), "+r"(b) : "l"(p), "r"((uint32_t)on) : "memory");
}
__device__ __forceinline__ void ld_relaxed4(uint32_t* v, const void* p) {
    asm volatile("ld.relaxed.gpu.global.L1::no_allocate.v4.b32 {%0,%1,%2,%3}, [%4];" : "=r"(v[0]), "=r"(v[1]), "=r"(v[2]), "=r"(v[3]) : "l"(p) : "memory");
}
__device__ __forceinline__ void ld_relaxed1n(uint32_t& v, const void* p) { asm volatile("ld.relaxed.gpu.global.L1::no_allocate.b32 %0, [%1];" : "=r"(v) : "l"(p) : "memory"); }
__device__ __forceinline__ void red_add4(const void* p, uint32_t a, uint32_t b, uint32_t c, uint32_t d) {
    asm volatile("red.relaxed.gpu.global.add.noftz.v4.f16x2 [%0], {%1,%2,%3,%4};" ::"l"(p), "r"(a), "r"(b), "r"(c), "r"(d) : "memory");
}
__device__ __forceinline__ void red_add1(const void* p, uint32_t a) { asm volatile("red.relaxed.gpu.global.add.noftz.f16x2 [%0], %1;" ::"l"(p), "r"(a) : "memory"); }
__device__ __forceinline__ void ld_relaxed2(uint32_t* v, const void* p) {
    asm volatile("{\n.reg .b64 t;\nld.relaxed.gpu.global.L1::no_allocate.b64 t, [%2];\nmov.b64 {%0,%1}, t;\n}" : "=r"(v[0]), "=r"(v[1]) : "l"(p) : "memory");
}
__device__ __forceinline__ uint32_t ld_relaxed1(const void* p) { uint32_t v; asm volatile("ld.relaxed.gpu.global.u32 %0, [%1];" : "=r"(v) : "l"(p) : "memory"); return v; }
__device__ __forceinline__ void st_relaxed1(const void* p, uint32_t v) { asm volatile("st.relaxed.gpu.global.u32 [%0], %1;" ::"l"(p), "r"(v) : "memory"); }
__device__ __forceinline__ uint32_t ld_acquire(const void* p) { uint32_t v; asm volatile("ld.acquire.gpu.global.u32 %0, [%1];" : "=r"(v) : "l"(p) : "memory"); return v; }
__device__ __forceinline__ void red_relaxed(void* p) { asm volatile("red.relaxed.gpu.global.add.u32 [%0], 1;" ::"l"(p) : "memory"); }
__device__ __forceinline__ void red_release(void* p) { asm volatile("red.release.gpu.global.add.u32 [%0], 1;" ::"l"(p) : "memory"); }
__device__ __forceinline__ void st_stream2(float* p, float a, float b) { asm volatile("st.global.cs.v2.f32 [%0], {%1, %2};" ::"l"(p), "f"(a), "f"(b) : "memory"); }
__device__ __forceinline__ void fence_async() { asm volatile("fence.proxy.async.global;" ::: "memory"); }
__device__ __forceinline__ void fence_async_smem() { asm volatile("fence.proxy.async.shared::cta;" ::: "memory"); }
__device__ __forceinline__ void wait_count(const uint32_t* p, uint32_t target) {
    while ((int32_t)(ld_acquire(p) - target) < 0) __nanosleep(POLLNS);
}
__device__ __forceinline__ void bar_sync(int id, int n) { asm volatile("bar.sync %0, %1;" ::"r"(id), "r"(n) : "memory"); }
__device__ __forceinline__ bool bar_and(int id, bool v) {
    uint32_t r;
    asm volatile("{\n.reg .pred P, Q;\nsetp.ne.u32 Q, %2, 0;\nbar.red.and.pred P, %1, 128, Q;\nselp.u32 %0, 1, 0, P;\n}" : "=r"(r) : "r"(id), "r"((uint32_t)v) : "memory");
    return r;
}
__device__ __forceinline__ void bar_arrive(int id, int n) { asm volatile("bar.arrive %0, %1;" ::"r"(id), "r"(n) : "memory"); }
__device__ __forceinline__ void lds128(uint32_t* v, uint32_t a) { asm volatile("ld.shared.v4.b32 {%0,%1,%2,%3}, [%4];" : "=r"(v[0]), "=r"(v[1]), "=r"(v[2]), "=r"(v[3]) : "r"(a) : "memory"); }
__device__ __forceinline__ uint32_t lds32(uint32_t a) { uint32_t v; asm volatile("ld.shared.b32 %0, [%1];" : "=r"(v) : "r"(a) : "memory"); return v; }
__device__ __forceinline__ void lds64(uint32_t* v, uint32_t a) { asm volatile("ld.shared.v2.b32 {%0,%1}, [%2];" : "=r"(v[0]), "=r"(v[1]) : "r"(a) : "memory"); }
__device__ __forceinline__ void lds64f(float* v, uint32_t a) { asm volatile("ld.shared.v2.f32 {%0,%1}, [%2];" : "=f"(v[0]), "=f"(v[1]) : "r"(a) : "memory"); }
__device__ __forceinline__ void sts128(uint32_t a, const uint32_t* v) { asm volatile("st.shared.v4.b32 [%0], {%1,%2,%3,%4};" ::"r"(a), "r"(v[0]), "r"(v[1]), "r"(v[2]), "r"(v[3]) : "memory"); }
__device__ __forceinline__ void sts64(uint32_t a, uint32_t x, uint32_t y) { asm volatile("st.shared.v2.b32 [%0], {%1,%2};" ::"r"(a), "r"(x), "r"(y) : "memory"); }
__device__ __forceinline__ void sts32(uint32_t a, uint32_t x) { asm volatile("st.shared.b32 [%0], %1;" ::"r"(a), "r"(x) : "memory"); }
__device__ __forceinline__ bool mbar_try(uint32_t b, uint32_t par) {
    uint32_t ok;
    asm volatile("{\n.reg .pred P;\nmbarrier.test_wait.parity.shared::cta.b64 P, [%1], %2;\nselp.u32 %0, 1, 0, P;\n}" : "=r"(ok) : "r"(b), "r"(par) : "memory");
    return ok;
}
__device__ __forceinline__ void mbar_wait(uint32_t b, uint32_t par) {
    asm volatile("{\n.reg .pred P;\nW: mbarrier.try_wait.parity.shared::cta.b64 P, [%0], %1;\n@!P bra W;\n}" ::"r"(b), "r"(par) : "memory");
}
__device__ __forceinline__ void mbar_wait_bounded(uint32_t b, uint32_t par) {
    asm volatile("{\n.reg .pred P, Q;\n.reg .u32 t, u;\nmov.u32 t, %%globaltimer_lo;\nW: mbarrier.try_wait.parity.shared::cta.b64 P, [%0], %1;\n"
                 "mov.u32 u, %%globaltimer_lo;\nsub.u32 u, u, t;\nsetp.gt.u32 Q, u, 2000000000;\n@Q st.global.u32 [%2], 0;\n@!P bra W;\n}" ::"r"(b), "r"(par), "l"(0ull) : "memory");
}
__device__ __forceinline__ void declare_fence(int zero) { asm volatile(".reg .pred PNEVER;\nsetp.ne.u32 PNEVER, %0, 0;" ::"r"(zero)); }
__device__ __forceinline__ void sched_fence() { asm volatile("{\n.reg .pred Q;\n.reg .u32 x;\n@!PNEVER bra D;\nF: ld.volatile.global.u32 x, [%0];\nsetp.ne.u32 Q, x, 0;\n@Q bra F;\nD:\n}" ::"l"(0ull) : "memory"); }
__device__ __forceinline__ void mbar_init(uint32_t b, uint32_t n) { asm volatile("mbarrier.init.shared::cta.b64 [%0], %1;" ::"r"(b), "r"(n) : "memory"); }
__device__ __forceinline__ void mbar_expect(uint32_t b, uint32_t bytes) { asm volatile("mbarrier.arrive.expect_tx.shared::cta.b64 _, [%0], %1;" ::"r"(b), "r"(bytes) : "memory"); }
__device__ __forceinline__ void mbar_arrive(uint32_t b) { asm volatile("mbarrier.arrive.shared::cta.b64 _, [%0];" ::"r"(b) : "memory"); }
__device__ __forceinline__ void mbar_arrive_cluster(uint32_t b) { asm volatile("mbarrier.arrive.shared::cluster.b64 _, [%0];" ::"r"(b) : "memory"); }
__device__ __forceinline__ void cluster_sync() { asm volatile("barrier.cluster.arrive.relaxed.aligned;\nbarrier.cluster.wait.aligned;" ::: "memory"); }
__device__ __forceinline__ uint32_t get_epoch(uint32_t sb) { mbar_wait(sb + B_EPOCH, 0); return __shfl_sync(0xffffffffu, lds32(sb + S_EPOCH), 0); }
__device__ __forceinline__ void tma2d(uint32_t dst, const CUtensorMap* m, int c0, int c1, uint32_t bar) {
    asm volatile("cp.async.bulk.tensor.2d.shared::cluster.global.mbarrier::complete_tx::bytes [%0], [%1, {%2, %3}], [%4];" ::"r"(dst), "l"(m), "r"(c0), "r"(c1), "r"(bar) : "memory");
}
__device__ __forceinline__ void tma3d(uint32_t dst, const CUtensorMap* m, int c0, int c1, int c2, uint32_t bar) {
    asm volatile("cp.async.bulk.tensor.3d.shared::cluster.global.mbarrier::complete_tx::bytes [%0], [%1, {%2, %3, %4}], [%5];" ::"r"(dst), "l"(m), "r"(c0), "r"(c1), "r"(c2), "r"(bar) : "memory");
}
__device__ __forceinline__ void l2_prefetch(const void* src, uint32_t bytes) { asm volatile("cp.async.bulk.prefetch.L2.global [%0], %1;" ::"l"(src), "r"(bytes) : "memory"); }
__device__ __forceinline__ void mbar_expect_e(uint32_t b, uint32_t bytes) {
    asm volatile("{\n.reg .pred E;\nelect.sync _|E, 0xffffffff;\n@E mbarrier.arrive.expect_tx.shared::cta.b64 _, [%0], %1;\n}" ::"r"(b), "r"(bytes) : "memory");
}
__device__ __forceinline__ void tma3d_mc_e(uint32_t dst, const CUtensorMap* m, int c0, int c1, int c2, uint32_t bar, uint16_t mask, uint64_t pol) {
    asm volatile("{\n.reg .pred E;\nelect.sync _|E, 0xffffffff;\n@E cp.async.bulk.tensor.3d.shared::cluster.global.mbarrier::complete_tx::bytes.multicast::cluster.L2::cache_hint [%0], [%1, {%2, %3, %4}], [%5], %6, %7;\n}" ::"r"(dst), "l"(m), "r"(c0), "r"(c1), "r"(c2), "r"(bar), "h"(mask), "l"(pol) : "memory");
}
__device__ __forceinline__ void tma4d_e(uint32_t dst, const CUtensorMap* m, int c0, int c1, int c3, uint32_t bar, uint64_t pol) {
    asm volatile("{\n.reg .pred E;\nelect.sync _|E, 0xffffffff;\n@E cp.async.bulk.tensor.4d.shared::cluster.global.mbarrier::complete_tx::bytes.L2::cache_hint [%0], [%1, {%2, %3, 0, %4}], [%5], %6;\n}" ::"r"(dst), "l"(m), "r"(c0), "r"(c1), "r"(c3), "r"(bar), "l"(pol) : "memory");
}
__device__ __forceinline__ void tma4d_mc_e(uint32_t dst, const CUtensorMap* m, int c0, int c1, int c3, uint32_t bar, uint16_t mask, uint64_t pol) {
    asm volatile("{\n.reg .pred E;\nelect.sync _|E, 0xffffffff;\n@E cp.async.bulk.tensor.4d.shared::cluster.global.mbarrier::complete_tx::bytes.multicast::cluster.L2::cache_hint [%0], [%1, {%2, %3, 0, %4}], [%5], %6, %7;\n}" ::"r"(dst), "l"(m), "r"(c0), "r"(c1), "r"(c3), "r"(bar), "h"(mask), "l"(pol) : "memory");
}
__device__ __forceinline__ void tma_prefetch4d_e(const CUtensorMap* m, int c0, int c3) {
    asm volatile("{\n.reg .pred E;\nelect.sync _|E, 0xffffffff;\n@E cp.async.bulk.prefetch.tensor.4d.L2.global [%0, {%1, 0, 0, %2}];\n}" ::"l"(m), "r"(c0), "r"(c3) : "memory");
}
__device__ __forceinline__ void tma_prefetch3d_e(const CUtensorMap* m, int c0, int c1, int c2) {
    asm volatile("{\n.reg .pred E;\nelect.sync _|E, 0xffffffff;\n@E cp.async.bulk.prefetch.tensor.3d.L2.global [%0, {%1, %2, %3}];\n}" ::"l"(m), "r"(c0), "r"(c1), "r"(c2) : "memory");
}
__device__ __forceinline__ void l2_prefetch_e(const void* src, uint32_t bytes) {
    asm volatile("{\n.reg .pred E;\nelect.sync _|E, 0xffffffff;\n@E cp.async.bulk.prefetch.L2.global [%0], %1;\n}" ::"l"(src), "r"(bytes) : "memory");
}
__device__ __forceinline__ void bulk_g2s_e(uint32_t dst, const void* src, uint32_t bytes, uint32_t bar) {
    asm volatile("{\n.reg .pred E;\nelect.sync _|E, 0xffffffff;\n@E cp.async.bulk.shared::cluster.global.mbarrier::complete_tx::bytes [%0], [%1], %2, [%3];\n}" ::"r"(dst), "l"(src), "r"(bytes), "r"(bar) : "memory");
}
__device__ __forceinline__ bool elect_one() {
    uint32_t r;
    asm volatile("{\n.reg .pred E;\nelect.sync _|E, 0xffffffff;\nselp.u32 %0, 1, 0, E;\n}" : "=r"(r));
    return r;
}
__device__ __forceinline__ void tma_store2d(const CUtensorMap* m, int c0, int c1, uint32_t src, uint64_t pol) {
    asm volatile("cp.async.bulk.tensor.2d.global.shared::cta.bulk_group.L2::cache_hint [%0, {%1, %2}], [%3], %4;" ::"l"(m), "r"(c0), "r"(c1), "r"(src), "l"(pol) : "memory");
}
__device__ __forceinline__ void bulk_commit() { asm volatile("cp.async.bulk.commit_group;" ::: "memory"); }
__device__ __forceinline__ void bulk_wait_read() { asm volatile("cp.async.bulk.wait_group.read 0;" ::: "memory"); }
__device__ __forceinline__ void bulk_wait_all() { asm volatile("cp.async.bulk.wait_group 0;" ::: "memory"); }
__device__ __forceinline__ uint64_t mkdesc(uint32_t addr, uint32_t lbo, uint32_t sbo, uint32_t swz) {
    return (uint64_t)((addr & 0x3FFFF) >> 4) | ((uint64_t)(lbo >> 4) << 16) | ((uint64_t)(sbo >> 4) << 32) | ((uint64_t)swz << 62);
}
__device__ __forceinline__ void wg_fence() { asm volatile("wgmma.fence.sync.aligned;" ::: "memory"); }
__device__ __forceinline__ void wg_commit() { asm volatile("wgmma.commit_group.sync.aligned;" ::: "memory"); }
template <int N> __device__ __forceinline__ void wg_wait() { asm volatile("wgmma.wait_group.sync.aligned %0;" ::"n"(N) : "memory"); }
template <typename T> __device__ __forceinline__ void pin_ptr(T*& p) { asm volatile("" : "+l"(p)); }
template <int N> __device__ __forceinline__ void pin(uint32_t* d) {
#pragma unroll
    for (int i = 0; i < N; i++) asm volatile("" : "+r"(d[i])::"memory");
}
template <int N> __device__ __forceinline__ void pin(float* d) {
#pragma unroll
    for (int i = 0; i < N; i++) asm volatile("" : "+f"(d[i])::"memory");
}

template <int TA, int TB>
__device__ __forceinline__ void wgmma_ss256(float* d, uint64_t da, uint64_t db) {
    asm volatile("wgmma.mma_async.sync.aligned.m64n256k16.f32.bf16.bf16 "
        "{%0, %1, %2, %3, %4, %5, %6, %7, %8, %9, %10, %11, %12, %13, %14, %15, %16, %17, %18, %19, %20, %21, %22, %23, %24, %25, %26, %27, %28, %29, %30, %31, %32, %33, %34, %35, %36, %37, %38, %39, %40, %41, %42, %43, %44, %45, %46, %47, %48, %49, %50, %51, %52, %53, %54, %55, %56, %57, %58, %59, %60, %61, %62, %63, %64, %65, %66, %67, %68, %69, %70, %71, %72, %73, %74, %75, %76, %77, %78, %79, %80, %81, %82, %83, %84, %85, %86, %87, %88, %89, %90, %91, %92, %93, %94, %95, %96, %97, %98, %99, %100, %101, %102, %103, %104, %105, %106, %107, %108, %109, %110, %111, %112, %113, %114, %115, %116, %117, %118, %119, %120, %121, %122, %123, %124, %125, %126, %127}, %128, %129, 1, 1, 1, %130, %131;"
        : "+f"(d[0]), "+f"(d[1]), "+f"(d[2]), "+f"(d[3]), "+f"(d[4]), "+f"(d[5]), "+f"(d[6]), "+f"(d[7]), "+f"(d[8]), "+f"(d[9]), "+f"(d[10]), "+f"(d[11]), "+f"(d[12]), "+f"(d[13]), "+f"(d[14]), "+f"(d[15]), "+f"(d[16]), "+f"(d[17]), "+f"(d[18]), "+f"(d[19]), "+f"(d[20]), "+f"(d[21]), "+f"(d[22]), "+f"(d[23]), "+f"(d[24]), "+f"(d[25]), "+f"(d[26]), "+f"(d[27]), "+f"(d[28]), "+f"(d[29]), "+f"(d[30]), "+f"(d[31]), "+f"(d[32]), "+f"(d[33]), "+f"(d[34]), "+f"(d[35]), "+f"(d[36]), "+f"(d[37]), "+f"(d[38]), "+f"(d[39]), "+f"(d[40]), "+f"(d[41]), "+f"(d[42]), "+f"(d[43]), "+f"(d[44]), "+f"(d[45]), "+f"(d[46]), "+f"(d[47]), "+f"(d[48]), "+f"(d[49]), "+f"(d[50]), "+f"(d[51]), "+f"(d[52]), "+f"(d[53]), "+f"(d[54]), "+f"(d[55]), "+f"(d[56]), "+f"(d[57]), "+f"(d[58]), "+f"(d[59]), "+f"(d[60]), "+f"(d[61]), "+f"(d[62]), "+f"(d[63]), "+f"(d[64]), "+f"(d[65]), "+f"(d[66]), "+f"(d[67]), "+f"(d[68]), "+f"(d[69]), "+f"(d[70]), "+f"(d[71]), "+f"(d[72]), "+f"(d[73]), "+f"(d[74]), "+f"(d[75]), "+f"(d[76]), "+f"(d[77]), "+f"(d[78]), "+f"(d[79]), "+f"(d[80]), "+f"(d[81]), "+f"(d[82]), "+f"(d[83]), "+f"(d[84]), "+f"(d[85]), "+f"(d[86]), "+f"(d[87]), "+f"(d[88]), "+f"(d[89]), "+f"(d[90]), "+f"(d[91]), "+f"(d[92]), "+f"(d[93]), "+f"(d[94]), "+f"(d[95]), "+f"(d[96]), "+f"(d[97]), "+f"(d[98]), "+f"(d[99]), "+f"(d[100]), "+f"(d[101]), "+f"(d[102]), "+f"(d[103]), "+f"(d[104]), "+f"(d[105]), "+f"(d[106]), "+f"(d[107]), "+f"(d[108]), "+f"(d[109]), "+f"(d[110]), "+f"(d[111]), "+f"(d[112]), "+f"(d[113]), "+f"(d[114]), "+f"(d[115]), "+f"(d[116]), "+f"(d[117]), "+f"(d[118]), "+f"(d[119]), "+f"(d[120]), "+f"(d[121]), "+f"(d[122]), "+f"(d[123]), "+f"(d[124]), "+f"(d[125]), "+f"(d[126]), "+f"(d[127])
        : "l"(da), "l"(db), "n"(TA), "n"(TB));
}
template <int TA, int TB>
__device__ __forceinline__ void wgmma_ss256_first(float* d, uint64_t da, uint64_t db) {
    asm volatile("wgmma.mma_async.sync.aligned.m64n256k16.f32.bf16.bf16 "
        "{%0, %1, %2, %3, %4, %5, %6, %7, %8, %9, %10, %11, %12, %13, %14, %15, %16, %17, %18, %19, %20, %21, %22, %23, %24, %25, %26, %27, %28, %29, %30, %31, %32, %33, %34, %35, %36, %37, %38, %39, %40, %41, %42, %43, %44, %45, %46, %47, %48, %49, %50, %51, %52, %53, %54, %55, %56, %57, %58, %59, %60, %61, %62, %63, %64, %65, %66, %67, %68, %69, %70, %71, %72, %73, %74, %75, %76, %77, %78, %79, %80, %81, %82, %83, %84, %85, %86, %87, %88, %89, %90, %91, %92, %93, %94, %95, %96, %97, %98, %99, %100, %101, %102, %103, %104, %105, %106, %107, %108, %109, %110, %111, %112, %113, %114, %115, %116, %117, %118, %119, %120, %121, %122, %123, %124, %125, %126, %127}, %128, %129, 0, 1, 1, %130, %131;"
        : "=f"(d[0]), "=f"(d[1]), "=f"(d[2]), "=f"(d[3]), "=f"(d[4]), "=f"(d[5]), "=f"(d[6]), "=f"(d[7]), "=f"(d[8]), "=f"(d[9]), "=f"(d[10]), "=f"(d[11]), "=f"(d[12]), "=f"(d[13]), "=f"(d[14]), "=f"(d[15]), "=f"(d[16]), "=f"(d[17]), "=f"(d[18]), "=f"(d[19]), "=f"(d[20]), "=f"(d[21]), "=f"(d[22]), "=f"(d[23]), "=f"(d[24]), "=f"(d[25]), "=f"(d[26]), "=f"(d[27]), "=f"(d[28]), "=f"(d[29]), "=f"(d[30]), "=f"(d[31]), "=f"(d[32]), "=f"(d[33]), "=f"(d[34]), "=f"(d[35]), "=f"(d[36]), "=f"(d[37]), "=f"(d[38]), "=f"(d[39]), "=f"(d[40]), "=f"(d[41]), "=f"(d[42]), "=f"(d[43]), "=f"(d[44]), "=f"(d[45]), "=f"(d[46]), "=f"(d[47]), "=f"(d[48]), "=f"(d[49]), "=f"(d[50]), "=f"(d[51]), "=f"(d[52]), "=f"(d[53]), "=f"(d[54]), "=f"(d[55]), "=f"(d[56]), "=f"(d[57]), "=f"(d[58]), "=f"(d[59]), "=f"(d[60]), "=f"(d[61]), "=f"(d[62]), "=f"(d[63]), "=f"(d[64]), "=f"(d[65]), "=f"(d[66]), "=f"(d[67]), "=f"(d[68]), "=f"(d[69]), "=f"(d[70]), "=f"(d[71]), "=f"(d[72]), "=f"(d[73]), "=f"(d[74]), "=f"(d[75]), "=f"(d[76]), "=f"(d[77]), "=f"(d[78]), "=f"(d[79]), "=f"(d[80]), "=f"(d[81]), "=f"(d[82]), "=f"(d[83]), "=f"(d[84]), "=f"(d[85]), "=f"(d[86]), "=f"(d[87]), "=f"(d[88]), "=f"(d[89]), "=f"(d[90]), "=f"(d[91]), "=f"(d[92]), "=f"(d[93]), "=f"(d[94]), "=f"(d[95]), "=f"(d[96]), "=f"(d[97]), "=f"(d[98]), "=f"(d[99]), "=f"(d[100]), "=f"(d[101]), "=f"(d[102]), "=f"(d[103]), "=f"(d[104]), "=f"(d[105]), "=f"(d[106]), "=f"(d[107]), "=f"(d[108]), "=f"(d[109]), "=f"(d[110]), "=f"(d[111]), "=f"(d[112]), "=f"(d[113]), "=f"(d[114]), "=f"(d[115]), "=f"(d[116]), "=f"(d[117]), "=f"(d[118]), "=f"(d[119]), "=f"(d[120]), "=f"(d[121]), "=f"(d[122]), "=f"(d[123]), "=f"(d[124]), "=f"(d[125]), "=f"(d[126]), "=f"(d[127])
        : "l"(da), "l"(db), "n"(TA), "n"(TB));
}
template <int TB>
__device__ __forceinline__ void wgmma_rs128(float* d, const uint32_t* a, uint64_t db, uint32_t acc) {
    asm volatile("{\n.reg .pred P;\nsetp.ne.u32 P, %69, 0;\nwgmma.mma_async.sync.aligned.m64n128k16.f32.bf16.bf16 "
        "{%0, %1, %2, %3, %4, %5, %6, %7, %8, %9, %10, %11, %12, %13, %14, %15, %16, %17, %18, %19, %20, %21, %22, %23, %24, %25, %26, %27, %28, %29, %30, %31, %32, %33, %34, %35, %36, %37, %38, %39, %40, %41, %42, %43, %44, %45, %46, %47, %48, %49, %50, %51, %52, %53, %54, %55, %56, %57, %58, %59, %60, %61, %62, %63}, {%64, %65, %66, %67}, %68, P, 1, 1, %70;\n}"
        : "+f"(d[0]), "+f"(d[1]), "+f"(d[2]), "+f"(d[3]), "+f"(d[4]), "+f"(d[5]), "+f"(d[6]), "+f"(d[7]), "+f"(d[8]), "+f"(d[9]), "+f"(d[10]), "+f"(d[11]), "+f"(d[12]), "+f"(d[13]), "+f"(d[14]), "+f"(d[15]), "+f"(d[16]), "+f"(d[17]), "+f"(d[18]), "+f"(d[19]), "+f"(d[20]), "+f"(d[21]), "+f"(d[22]), "+f"(d[23]), "+f"(d[24]), "+f"(d[25]), "+f"(d[26]), "+f"(d[27]), "+f"(d[28]), "+f"(d[29]), "+f"(d[30]), "+f"(d[31]), "+f"(d[32]), "+f"(d[33]), "+f"(d[34]), "+f"(d[35]), "+f"(d[36]), "+f"(d[37]), "+f"(d[38]), "+f"(d[39]), "+f"(d[40]), "+f"(d[41]), "+f"(d[42]), "+f"(d[43]), "+f"(d[44]), "+f"(d[45]), "+f"(d[46]), "+f"(d[47]), "+f"(d[48]), "+f"(d[49]), "+f"(d[50]), "+f"(d[51]), "+f"(d[52]), "+f"(d[53]), "+f"(d[54]), "+f"(d[55]), "+f"(d[56]), "+f"(d[57]), "+f"(d[58]), "+f"(d[59]), "+f"(d[60]), "+f"(d[61]), "+f"(d[62]), "+f"(d[63])
        : "r"(a[0]), "r"(a[1]), "r"(a[2]), "r"(a[3]), "l"(db), "r"(acc), "n"(TB));
}
template <int TB>
__device__ __forceinline__ void wgmma_rs64(float* d, const uint32_t* a, uint64_t db, uint32_t acc) {
    asm volatile("{\n.reg .pred P;\nsetp.ne.u32 P, %37, 0;\nwgmma.mma_async.sync.aligned.m64n64k16.f32.bf16.bf16 "
        "{%0, %1, %2, %3, %4, %5, %6, %7, %8, %9, %10, %11, %12, %13, %14, %15, %16, %17, %18, %19, %20, %21, %22, %23, %24, %25, %26, %27, %28, %29, %30, %31}, {%32, %33, %34, %35}, %36, P, 1, 1, %38;\n}"
        : "+f"(d[0]), "+f"(d[1]), "+f"(d[2]), "+f"(d[3]), "+f"(d[4]), "+f"(d[5]), "+f"(d[6]), "+f"(d[7]), "+f"(d[8]), "+f"(d[9]), "+f"(d[10]), "+f"(d[11]), "+f"(d[12]), "+f"(d[13]), "+f"(d[14]), "+f"(d[15]), "+f"(d[16]), "+f"(d[17]), "+f"(d[18]), "+f"(d[19]), "+f"(d[20]), "+f"(d[21]), "+f"(d[22]), "+f"(d[23]), "+f"(d[24]), "+f"(d[25]), "+f"(d[26]), "+f"(d[27]), "+f"(d[28]), "+f"(d[29]), "+f"(d[30]), "+f"(d[31])
        : "r"(a[0]), "r"(a[1]), "r"(a[2]), "r"(a[3]), "l"(db), "r"(acc), "n"(TB));
}
template <int TB>
__device__ __forceinline__ void wgmma_rs16(float* d, const uint32_t* a, uint64_t db, uint32_t acc) {
    asm volatile("{\n.reg .pred P;\nsetp.ne.u32 P, %13, 0;\nwgmma.mma_async.sync.aligned.m64n16k16.f32.bf16.bf16 "
        "{%0, %1, %2, %3, %4, %5, %6, %7}, {%8, %9, %10, %11}, %12, P, 1, 1, %14;\n}"
        : "+f"(d[0]), "+f"(d[1]), "+f"(d[2]), "+f"(d[3]), "+f"(d[4]), "+f"(d[5]), "+f"(d[6]), "+f"(d[7])
        : "r"(a[0]), "r"(a[1]), "r"(a[2]), "r"(a[3]), "l"(db), "r"(acc), "n"(TB));
}

__device__ __forceinline__ uint32_t delay_loop(int n, uint32_t x0) {
    uint32_t z;
    asm volatile("{\n.reg .pred P;\n.reg .u32 c, x;\nmov.u32 c, %1;\nmov.u32 x, %2;\nDL: mad.lo.u32 x, x, 1664525, 1013904223;\nadd.u32 c, c, -1;\nsetp.gt.s32 P, c, 0;\n@P bra DL;\n"
                 "setp.eq.u32 P, x, 0x7fffffff;\nselp.u32 %0, 16, 0, P;\n}" : "=r"(z) : "r"(n), "r"(x0) : "memory");
    return z;
}
__device__ __forceinline__ void wait_clocks(uint32_t n) {
    asm volatile("{\n.reg .pred P;\n.reg .u32 a, b;\nmov.u32 a, %%clock;\nW: mov.u32 b, %%clock;\nsub.u32 b, b, a;\nsetp.lt.u32 P, b, %0;\n@P bra W;\n}" ::"r"(n) : "memory");
}
__device__ __forceinline__ uint32_t gtime() { uint32_t t; asm volatile("mov.u32 %0, %%globaltimer_lo;" : "=r"(t)); return t; }
#define COUNT_RETRY(i)
__device__ __forceinline__ uint32_t stamp_word(uint32_t seq) { return (gtime() & ~31u) | (seq & 31u); }
__device__ __forceinline__ void wait_time(uint32_t t, uint32_t sb) { while ((int32_t)(gtime() - t) < 0) {} }
#define NAPMODE 1
__device__ __forceinline__ void nap(uint32_t ns) { if (NAPMODE) wait_clocks(ns * 7 / 4); else __nanosleep(ns); }
template <int STRIDE>
__device__ __forceinline__ uint32_t latest_stamp(const uint32_t* p, uint32_t seq, uint32_t ref, uint32_t sb) {
#pragma unroll 1
    for (int n = opq(0, 0);; n++) {
        uint32_t bad = 0; int32_t m = INT32_MIN;
#pragma unroll
        for (int i = 0; i < 3; i++) { const uint32_t v = ld_relaxed1(p + i * STRIDE); bad |= (v ^ seq) & 31u; m = max(m, (int32_t)((v & ~31u) - ref)); }
        if (__all_sync(0xffffffffu, bad == 0)) return ref + __reduce_max_sync(0xffffffffu, m);
        nap(100);
        if (n > SPIN_LIMIT) spin_fault();
    }
}
constexpr uint32_t ONES = 0x3C003C00u, FULL = 0x50005000u;
__device__ __forceinline__ void pacer(const Params& P, const uint32_t sb, const int cta, const int lane, const uint32_t epoch) {
    uint8_t* const zp = P.xb + cta * 2048 + xg_lane(lane);
    if (lane < 3) asm volatile("prefetch.tensormap [%0];" ::"l"(&P.tm[lane == 0 ? M_C1 + cta % 3 : lane == 1 ? M_CO : M_SEG]) : "memory");
    uint32_t e0 = 0;
#pragma unroll 2
    for (int i = 0; i < 32; i++) { const uint4 u = __ldg((const uint4*)P.mem0 + i * 32 + lane); e0 = amax(amax(e0, amax(u.x, u.y)), amax(u.z, u.w)); }
    e0 = min(max(warp_exp(e0), 31u), 253u) - 14;
    if (cta < 32) {
        const uint32_t* m = (const uint32_t*)(P.mem0 + (lane >> 2) * 1024 + cta * 32 + (lane & 3) * 2);
        const float sc = __uint_as_float((254 - e0) << 23);
        auto cv = [&](uint32_t u) { return pack2h(bf_lo(u) * sc, bf_hi(u) * sc); };
        const uint32_t y = cv(m[12]);
        st_relaxed4(zp, cv(m[0]), cv(m[4]), cv(m[8]), prmt(y, FULL, 0x7610));
        st_relaxed1(P.xb + xg_side(cta) + lane * 4, prmt(y, FULL, 0x3254));
    }
    if (cta < 40) {
#pragma unroll 1
        for (int b = 1; b < 8; b++) st_relaxed4(zp + xg_buf(b), 0, 0, 0, 0);
    }
    __threadfence();
    const uint32_t* ts = (const uint32_t*)(P.xb + XG_T) + lane;
    int32_t d0 = P.dly;
    const uint32_t go = mapa(sb + B_GO, (cta / 3 & 1) * 3 + 1 + (lane & 1));
    auto free_segment = [&]() { if (lane == 0) mbar_expect(sb + B_KVFULL, 16384); __syncwarp(); if (lane < 2) mbar_arrive_cluster(go); };
    for (int n = 0; (int32_t)(ld_acquire(&g_cnt(C_XCNT)) - (epoch + 1) * 256) < 0; n++) { __nanosleep(500); if (n > SPIN_LIMIT) spin_fault(); }
    const uint32_t ex = max(ld_relaxed1(&g_cnt(C_XMAX)) & 255, 67u);
    mbar_wait_bounded(sb + B_READY, 0);
    free_segment();
    if (lane == 0) st_relaxed2(g_hint + cta * 32, stamp_word(epoch + 1), lds32(sb + S_EV) | lds32(sb + S_EO) << 16);
    uint32_t a = gtime();
    for (int n = 0;; n++) {
        uint32_t bad = 0, e = 0; int32_t m = INT32_MIN;
#pragma unroll
        for (int i = 0; i < 3; i++) {
            uint32_t v[2];
            ld_relaxed2(v, g_hint + lane * 32 + i * 1024);
            bad |= (v[0] ^ (epoch + 1)) & 31u; m = max(m, (int32_t)((v[0] & ~31u) - a)); e = __vmaxu2(e, v[1]);
        }
        if (__all_sync(0xffffffffu, bad == 0)) {
            a += __reduce_max_sync(0xffffffffu, m);
            const uint32_t ev = __reduce_max_sync(0xffffffffu, e & 255), eo = __reduce_max_sync(0xffffffffu, e >> 16);
            if (lane == 0) { sts64(sb + S_SC, max(ev, 97u) + max(eo, 97u) - 244, ex); sts32(sb + S_ISC, e0 * 0x800080u); }
            break;
        }
        wait_clocks(100);
        if (n > SPIN_LIMIT) spin_fault();
    }
    wait_time(a, sb);
    if (lane == 0) mbar_arrive(sb + B_RELM);
#pragma unroll 1
    for (int s = 0; s < 63; s++) {
        const uint32_t seq = epoch * 63 + s + 1;
        mbar_wait_bounded(sb + B_P1, s & 1);
        const uint32_t tx = gtime();
        if (lane == 0) st_relaxed1(ts + (s & 1) * 256 + cta, (tx & ~31u) | (seq & 31u));
        { const uint32_t t = tx; PROFP(3) }
        if (s > 0) {
            const int32_t e0 = latest_stamp<32>(ts + (~s & 1) * 256 + 128, seq - 1, a, sb) + P.mrg - a;
            d0 += s < 3 ? e0 : min(max(e0, -P.clamp0), P.clampv) / 2;
        }
        while ((int32_t)(gtime() - tx) < P.rd) nap(20);
        a = latest_stamp<32>(ts + (s & 1) * 256, seq, tx, sb) + d0;
        { const uint32_t t = gtime(); PROFP(0) }
        while ((int32_t)(a - gtime()) > 250) nap(40);
        wait_time(a, sb);
        if (lane == 0) mbar_arrive(sb + B_RELM);
        { const uint32_t t = a; PROFP(2) }
        mbar_wait_bounded(sb + B_RED, s & 1);
        { const uint32_t t = gtime(); PROFP(1) }
        const uint32_t g = tx + __reduce_max_sync(0xffffffffu, lds32(sb + S_TO + (lane & 7) * 4) - tx);
        if (lane == 0) st_relaxed1(ts + (s & 1) * 256 + 128 + cta, (g & ~31u) | (seq & 31u));
        if (s < 62) { if (P.kvd) nap(P.kvd); free_segment(); }
    }
}
__device__ __forceinline__ void st_async2(uint32_t a, uint32_t x, uint32_t y, uint32_t bar) {
    asm volatile("st.async.weak.shared::cluster.mbarrier::complete_tx::bytes.v2.b32 [%0], {%1,%2}, [%3];" ::"r"(a), "r"(x), "r"(y), "r"(bar) : "memory");
}
__device__ __forceinline__ uint32_t xor_or(uint32_t a, uint32_t b, uint32_t t) { uint32_t d; asm("lop3.b32 %0, %1, %2, %3, 0x7E;" : "=r"(d) : "r"(a), "r"(b), "r"(t)); return d; }
__device__ __forceinline__ uint32_t or3(uint32_t a, uint32_t b, uint32_t c) { uint32_t d; asm("lop3.b32 %0, %1, %2, %3, 0xFE;" : "=r"(d) : "r"(a), "r"(b), "r"(c)); return d; }
__device__ __forceinline__ bool tags_ok(uint32_t bad, uint32_t mask = 1) {
    uint32_t r;
    asm volatile("{\n.reg .pred P;\n.reg .b32 x;\nand.b32 x, %1, %2;\nsetp.ne.b32 P, x, 0;\nvote.sync.any.pred P, P, 0xffffffff;\nselp.u32 %0, 0, 1, P;\n}" : "=r"(r) : "r"(bad), "r"(mask));
    return r;
}
constexpr int SROW = 56;
#define PREA 8
#define PREB 9
#define RING1 6
#define RING2 7
#define RING3 8
#define PRE2 10
#define PRE2A 0
#define PRE3 0
#define EFENCE 0
#define RFENCE 1
#define PROG 16
#define EARLY 0
#define PLATE 1
#define NDEP 0
#define EFENCE2 0
#define LAG2 8
#define LAG 4
#define PUT1 33
#define DEPS 3
#define ADELAY 120
#define BDELAY 0
#define HOLD 1
#define XDELAY 330
#define FENCEA 0x80
#define FENCEB 0x80
#define FENCE2 0x220
#define OFENCE 0
#define MASK3 0x57
#define MASK4 0x55
#define MASK5 0x25
#define OFF3 0x5320
#define OFF4 0x6420
#define OFF5 0x0520
#define RESA (NRA == 3 ? 15 : NRA == 4 ? 3 : 0)
#define RESB (NRB == 3 ? 0xcc : NRB == 4 ? 0x30 : 0)
#define RESB1 (NRB == 3 ? 0xcc : NRB == 4 ? 0xc : 0)
__host__ __device__ constexpr int smem_mask(int NR) { return NR == 3 ? MASK3 : NR == 4 ? MASK4 : MASK5; }
__host__ __device__ constexpr bool round_smem(int r, int NR) { return smem_mask(NR) >> r & 1; }
__host__ __device__ constexpr int kord(int r, int NR) { int c = 0; for (int i = 0; i < r; i++) c += round_smem(i, NR) == round_smem(r, NR); return round_smem(r, NR) ? NR + c : c; }
__host__ __device__ constexpr int slot_r(int n, int NR) { return n < 32 ? n >> 2 : (((n & 31) >> 2) + ((NR == 3 ? OFF3 : NR == 4 ? OFF4 : OFF5) >> (n & 3) * 4)) & 7; }
__host__ __device__ constexpr int slot_k(int n, int NR) { return kord(slot_r(n, NR), NR); }
__host__ __device__ constexpr int slot_sord(int n, int NR) { int c = 0; for (int i = 0; i < n; i++) c += slot_k(i, NR) >= NR; return c; }
__host__ __device__ constexpr int sfrag_slot(int q, int NR) { for (int n = 0; n < 64; n++) if (slot_k(n, NR) >= NR && slot_sord(n, NR) == q) return n; return -1; }
__host__ __device__ constexpr int w1_loaded(int n, int NR, int PRE) {
    int q = PRE;
    for (int i = 0; i <= n; i++) q += q < (8 - NR) * 8 && q - slot_sord(i + 1, NR) < (i < 32 ? RING1 : RING2);
    return q;
}
template <int Q, int NR>
__device__ __forceinline__ void load_w1(uint32_t* w, const uint32_t* a) {
    constexpr int n = sfrag_slot(Q, NR);
    ldsm4t(w, a[n & 3] + ((slot_k(n, NR) - NR) * 2 + (n >> 5)) * 2048);
}
constexpr int AB = NRA < 5, BB = 3 - AB;
__device__ __forceinline__ bool w2_full(int role, int warp) { return warp < (role == 2 ? 2 : 3); }
__device__ __forceinline__ int w2_nblk(int role, int warp) { return warp < 4 ? BB - !w2_full(role, warp) : AB; }
__host__ __device__ constexpr int w2_step(bool full, int i) { return AB ? (full ? 2 * i : 0) : full ? (i == 0 ? 0 : i == 1 ? 16 - 2 * EARLY : 18 - 2 * EARLY) : i; }
__device__ __forceinline__ int w2_block(int role, int warp) {
    const int f = role * 3 + warp, g = role == 2 ? warp : role;
    if (AB) return (warp >= 4 ? role * 4 + (warp - 4) : w2_full(role, warp) ? 16 + 4 * (f >> 1) + (f & 1) : 12 + g) ^ EARLY;
    return w2_full(role, warp) ? EARLY + 4 * (f >> 1) + (f & 1) : EARLY + 2 + 4 * g;
}
__device__ __forceinline__ int w2_res(int role, int warp) { return warp >= 4 ? RESA : w2_full(role, warp) ? RESB : RESB1; }
__device__ __forceinline__ int w2_units(int role, int warp) { return w2_nblk(role, warp) * 4 - (5 - (warp < 4 ? NRB : NRA)) * 2; }
constexpr int W2B = (BB * 4 - (5 - NRB) * 2) * 2048, W2A = (AB * 4 - (5 - NRA) * 2) * 2048;
static_assert(S_W2 + 4 * W2B - 8192 + 4 * W2A == S_KV, "weights");
__device__ __forceinline__ int w1_base(int warp) { return S_W1 + (warp < 4 ? warp * (8 - NRB) : 4 * (8 - NRB) + (warp - 4) * (8 - NRA)) * 4096; }
__device__ __forceinline__ int w2_base(int warp) { return S_W2 + (warp < 4 ? warp * W2B : 4 * W2B - 8192 + (warp - 4) * W2A); }
__device__ __forceinline__ void chain_load(const Params& P, uint32_t sb, int cta, int warp, int lane, int round) {
    const int role = cta % 3, h = cta / 3;
    mbar_expect_e(sb + B_INIT, round ? (8 - (warp < 4 ? NRB : NRA)) * 4096 : 20480);
    if (round) mbar_expect_e(sb + B_INIT2, w2_units(role, warp) * 2048);
    __syncwarp();
    const int m1 = (warp < 4 ? smem_mask(NRB) : smem_mask(NRA)) ^ (round ? 0 : 255), below = (1 << lane) - 1;
    const int m2 = (w2_res(role, warp) ^ (round ? 0xfff : 0)) & ((1 << w2_nblk(role, warp) * 4) - 1);
    const uint32_t d1 = sb + (round ? w1_base(warp) : warp * 20480), d2 = round ? sb + w2_base(warp) : d1 + __popc(m1) * 4096;
    if (m1 >> lane & 1) tma3d(d1 + __popc(m1 & below) * 4096, &P.tm[M_C1 + role], 0, warp * 128 + lane * 16, h * 2, sb + B_INIT);
    __syncwarp();
    if (m2 >> lane & 1)
        tma2d(d2 + __popc(m2 & below) * 2048, &P.tm[M_CO], (w2_block(role, warp) + w2_step(w2_full(role, warp), lane >> 2)) * 32, h * 128 + (lane & 3) * 32, sb + (round ? B_INIT2 : B_INIT));
    __syncwarp();
}

__device__ __forceinline__ void put_partials(bool TR, uint32_t a, const float* x, const float* y) {
    if (TR) stsm4t(a, pack2(x[0], x[1]), pack2(x[2], x[3]), pack2(y[0], y[1]), pack2(y[2], y[3]));
    else stsm4(a, pack2(x[0], x[1]), pack2(x[2], x[3]), pack2(y[0], y[1]), pack2(y[2], y[3]));
}
template <int NR, int PRE, int FM, int B, int E>
__device__ __forceinline__ void project(float (*acc)[4], bool TR, const uint32_t (*wr)[4], uint32_t (*as)[4], uint32_t (*v)[4], uint32_t* x, const uint32_t* w1a, uint32_t pp, uint32_t zero) {
    static_for<B, E>([&](auto I) {
        constexpr int n = I.value, kk = slot_k(n, NR), T = (n >> 5) * 4 + (n & 3), so = slot_sord(n, NR), q = w1_loaded(n - 1, NR, PRE);
        constexpr bool sm = kk >= NR;
        const uint32_t* w = sm ? as[so] : wr[sm ? 0 : (kk * 2 + (n >> 5)) * 4 + (n & 3)];
        if constexpr (n == 32 && PUT1 < 32) { put_partials(TR, pp, acc[0], acc[1]); put_partials(TR, pp + 4096, acc[2], acc[3]); }
        if constexpr (n == 0) {
            const uint32_t c = prmt(v[0][3], x[0], 0x3254);
            v[0][0] = h2bf(v[0][0], v[0][0]); v[0][1] = h2bf(v[0][1], v[0][1]); v[0][2] = h2bf(v[0][2], v[0][2]); v[0][3] = h2bf(v[0][3], x[0]);
            x[0] = c;
        }
        if constexpr ((n & 31) < 4) acc[T][0] = acc[T][1] = acc[T][2] = acc[T][3] = 0.f;
        mma16816(acc[T], w[0], w[1], w[2], w[3], v[slot_r(n, NR) >> 1][(slot_r(n, NR) & 1) * 2], v[slot_r(n, NR) >> 1][(slot_r(n, NR) & 1) * 2 + 1]);
        if constexpr (n == DEPS) {
            const uint32_t sel = __float_as_uint(acc[T][0]) * zero + 0x7610;
#pragma unroll
            for (int b = 1; b < 4; b++) {
                if (b <= NDEP) cvt_block(v[b], x[b], sel);
                else {
                    const uint32_t c = prmt(v[b][3], x[b], 0x3254);
                    v[b][0] = h2bf(v[b][0], v[b][0]); v[b][1] = h2bf(v[b][1], v[b][1]); v[b][2] = h2bf(v[b][2], v[b][2]); v[b][3] = h2bf(v[b][3], x[b]);
                    x[b] = c;
                }
            }
        }
        if constexpr (w1_loaded(n, NR, PRE) > q) load_w1<q, NR>(as[q], w1a);
        if constexpr (n == PUT1 && n >= 32) { put_partials(TR, pp, acc[0], acc[1]); put_partials(TR, pp + 4096, acc[2], acc[3]); }
        if constexpr (n % 4 == 3 && (FM >> (n / 4) & 1) && n != E - 1) sched_fence();
    });
    if constexpr (E == 64) { put_partials(TR, pp + 8192, acc[4], acc[5]); put_partials(TR, pp + 12288, acc[6], acc[7]); }
}
__device__ __forceinline__ void reduce8(const uint32_t (*x)[4], const uint32_t* sel, float sc, uint32_t& r0, uint32_t& r1) {
    float d[4][4];
#pragma unroll
    for (int i = 0; i < 4; i++) {
        d[i][0] = d[i][1] = d[i][2] = d[i][3] = 0.f;
        mma16816(d[i], x[i][0], x[i][1], x[i][2], x[i][3], sel[2 * i], sel[2 * i + 1]);
    }
    r0 = pack2(((d[0][0] + d[1][0]) + (d[2][0] + d[3][0])) * sc, ((d[0][1] + d[1][1]) + (d[2][1] + d[3][1])) * sc);
    r1 = pack2(((d[0][2] + d[1][2]) + (d[2][2] + d[3][2])) * sc, ((d[0][3] + d[1][3]) + (d[2][3] + d[3][3])) * sc);
}

#define ISTAMP(i)
__host__ __device__ constexpr int wo_count(int n, int RES, bool res) { int c = 0; for (int i = 0; i < n; i++) c += (RES >> (i >> 2) & 1) == res; return c; }
__host__ __device__ constexpr int wo_loaded(int n, int RES, int PRE, int end) { int q = PRE; for (int i = 0; i <= n; i++) q += q < end && q - wo_count(i + 1, RES, false) < RING3; return q; }
template <int Q>
__device__ __forceinline__ void load_w2(uint32_t* w, const uint32_t* a) { ldsm4t(w, a[Q & 1] + (Q >> 1) * 1024); }
template <int NB, int RES, int PRE, int FM>
__device__ __forceinline__ void wo_blocks(uint32_t (*w)[4], const uint32_t (*wp)[4], uint32_t oa, const uint32_t* wa, const uint8_t* dst, const uint8_t* dsd, bool odd) {
    float a[NB][4][4];
    uint32_t o[4][4], r[5];
    bar_sync(3, 256);
#pragma unroll
    for (int i = 0; i < 4; i++) ldsm4(o[i], oa + i * 512);
    if (FM & 1) sched_fence();
    static_for<0, NB * 16>([&](auto I) {
        constexpr int n = I.value, i = n & 15, end = wo_count(NB * 16, RES, false), q = wo_loaded(n - 1, RES, PRE, end);
        constexpr bool res = RES >> (n >> 2) & 1;
        const uint32_t* b = o[i >> 2] + (i & 2);
        const uint32_t* x = res ? wp[wo_count(n, RES, true)] : w[wo_count(n, RES, false)];
        float* d = a[n >> 4][i & 3];
        if constexpr (i < 4) d[0] = d[1] = d[2] = d[3] = 0.f;
        mma16816(d, x[0], x[1], x[2], x[3], b[0], b[1]);
        if constexpr (wo_loaded(n, RES, PRE, end) > q) load_w2<q>(w[q], wa);
        if constexpr (n == NB * 16 - 1 || (n >= 16 && i == LAG - 1)) {
            const float (*e)[4] = a[n == NB * 16 - 1 ? NB - 1 : (n >> 4) - 1];
            const uint32_t y = pack2h(e[1][2] + e[3][2], e[1][3] + e[3][3]);
            r[0] = movm(pack2h(e[0][0] + e[2][0], e[0][1] + e[2][1])); r[1] = movm(pack2h(e[0][2] + e[2][2], e[0][3] + e[2][3]));
            r[2] = movm(pack2h(e[1][0] + e[3][0], e[1][1] + e[3][1])); r[3] = movm(odd ? ONES : y); r[4] = movm(odd ? y : ONES);
        }
        if constexpr (n == NB * 16 - 1 || (n >= 16 && i == LAG2 - 1)) {
            constexpr int bs = w2_step(NB == BB, n == NB * 16 - 1 ? NB - 1 : (n >> 4) - 1);
            red_add4(dst + bs * 2048, r[0], r[1], r[2], r[3]);
            red_add1(dsd + (bs >> 1) * 1024 + (bs & 1) * 256, r[4]);
        }
        if constexpr (((FM >> (n / 4 + 1)) & 1) && (n & 3) == 3 && n != NB * 16 - 1) sched_fence();
    });
}
#define FRAG1(ln) ((((ln) & 7) + ((ln) >> 4) * 8) * 128 + ((((((ln) >> 3) & 1) << (ROLE == 1)) ^ ((ln) & 7)) << 4))
#define FRAG2(ln) ((((ln) & 7) + ((ln) >> 4) * 8) * 64 + (((((ln) >> 3) & 1) ^ (((ln) >> 1) & 3)) << 4))
#define TILE_X(i) (ROLE == 1 ? (((i) >> 1) << 6) | (((i) & 1) << 4) : (i) << 5)
__device__ __forceinline__ void chain_fetch(const Params& P, const uint32_t sb, const int cta, const int warp, const int lane, uint32_t (*wr)[4]) {
    const int ROLE = cta % 3, nr = warp < 4 ? NRB : NRA;
    mbar_wait(sb + B_INIT, 0);
    ISTAMP(0)
#pragma unroll
    for (int f = 0; f < 40; f++) {
        const bool w1 = f < (NRA < NRB ? NRA : NRB) * 8 || f < nr * 8;
        ldsm4t(wr[f], sb + warp * 20480 + (f >> 2) * 2048 + (w1 ? FRAG1(lane) ^ TILE_X(f & 3) : (f & 2) * 512 + (FRAG2(lane) ^ ((f & 1) << 5))));
    }
    fence_async_smem();
    mbar_wait(sb + B_SFREE + (warp >> 2) * 8, 0);
    bar_sync(1, 256);
    chain_load(P, sb, cta, warp, lane, 1);
    ISTAMP(1)
}
__device__ __forceinline__ void chain_bounds(const uint32_t sb, const int cta, const int warp, const int lane, const uint32_t (*wr)[4]) {
    const int ROLE = cta % 3, nr = warp < 4 ? NRB : NRA;
    uint32_t m[6] = {}, u[4];
#pragma unroll
    for (int f = 0; f < 40; f++) m[f < 24 ? 0 : f >> 3] = amax4(m[f < 24 ? 0 : f >> 3], wr[f]);
    uint32_t m1 = amax(m[0], amax(nr > 3 ? m[3] : 0, nr > 4 ? m[4] : 0)), m2 = amax(nr > 3 ? 0 : m[3], nr > 4 ? 0 : m[4]);
    ISTAMP(5)
    mbar_wait(sb + B_INIT, 1);
    ISTAMP(3)
    if (ROLE == 2) {
#pragma unroll 4
        for (int i = 0; i < S_W2 / 4096; i++) { lds128(u, sb + S_W1 + warp * (S_W2 / 8) + i * 512 + lane * 16); m1 = amax4(m1, u); }
    }
    mbar_wait(sb + B_INIT2, 0);
    ISTAMP(7)
    const int n = w2_units(ROLE, warp) * 4;
#pragma unroll 4
    for (int i = 0; i < n; i++) { lds128(u, sb + w2_base(warp) + i * 512 + lane * 16); m2 = amax4(m2, u); }
    m1 = warp_exp(m1); m2 = warp_exp(m2);
    if (lane == 0) { if (ROLE == 2) red_max_shared(sb + S_EV, m1); red_max_shared(sb + S_EO, m2); }
}
template <bool ATT>
__device__ __forceinline__ void chain_role(const Params& P, const uint32_t sb, const int cta, const int warp, const int lane, const uint32_t (*wr)[4]) {
    constexpr int NR = ATT ? NRA : NRB, PRE = ATT ? PREA : PREB;
    const int h = cta / 3, ROLE = cta - h * 3;
    ISTAMP(6)
    uint32_t l8 = opq(sb + lane * 8, lane);
    const uint8_t* persu = (const uint8_t*)((ROLE == 1 ? g_km : g_vmt) + h * 512) - (sb >> 1);
    auto persist = [&](int s, int tile, uint32_t r0, uint32_t r1) {
        uint32_t* pp = (uint32_t*)(persu + s * 65536 + (ROLE == 1 ? (tile >> 1) * 512 + (tile & 1) * 128 : tile * 256) + (l8 >> 1));
        pp[0] = r0; pp[ROLE == 1 ? 64 : 32] = r1;
    };
    const uint32_t rk0 = (h & 1) * 3, rd1 = __shfl_sync(0xffffffffu, mapa(sb, rk0 + (ROLE + 1) % 3) - sb, 0), rd2 = __shfl_sync(0xffffffffu, mapa(sb, rk0 + (ROLE + 2) % 3) - sb, 0);
    const uint32_t xo = (ROLE == 2 ? S_XV : S_X + ROLE * 2048) + warp * 256;
    const bool full = w2_full(ROLE, warp);
    const int blk = w2_block(ROLE, warp);
    const uint32_t om = blk * 2048, os = xg_side(blk);
    const uint32_t w1o = sb + w1_base(warp), w2o = sb + w2_base(warp);
    ISTAMP(2)
    if (lane == 0) mbar_arrive(sb + B_READY);
#pragma unroll 1
    for (int s = 0;; s++) {
        l8 += s & P.zero;
        uint32_t r0, r1;
        {
            uint32_t v[4][4], as[(8 - NR) * 8][4], w1a[4];
            float acc[8][4];
            const uint32_t pst = sb + S_P1 + (l8 - sb) * 16 + ((warp * 16) ^ ((l8 & 56) * 2));
#pragma unroll
            for (int i = 0; i < 4; i++) w1a[i] = w1o + (FRAG1((l8 - sb) >> 3) ^ TILE_X(i));
            auto preload = [&]() { static_for<0, PRE>([&](auto I) { load_w1<I.value, NR>(as[I.value], w1a); }); };
#pragma unroll 1
            while (true) {
                uint32_t x[4];
                if (!(PLATE >> ATT & 1)) preload();
                const uint32_t lm = opq(l8 - sb, (l8 - sb) >> 3);
                const uint8_t* pm = P.xb + xg_buf(s) + warp * 8192 + xg_lane(lm >> 3);
                const uint8_t* ps = P.xb + xg_buf(s) + XG_SIDE + warp * 2048 + (lm >> 1);
                pin_ptr(pm); pin_ptr(ps);
                mbar_wait(sb + B_RELM, s & 1);
                if (ATT ? ADELAY : BDELAY) wait_clocks(ATT ? ADELAY : BDELAY);
                PROF(10)
#pragma unroll
                for (int b = 0; b < 4; b++) { ld_relaxed4(v[b], pm + b * 2048); ld_relaxed1n(x[b], ps + (b >> 1) * 1024 + (b & 1) * 256); }
                if (PLATE >> ATT & 1) { preload(); if (PLATE >> (ATT + 2) & 1) sched_fence(); }
                project<NR, PRE, ATT ? FENCEA : FENCEB, 0, PROG>(acc, ROLE == 2, wr, as, v, x, w1a, pst, P.zero);
                const uint32_t bad = xor_or(x[0], x[1], FULL) | xor_or(x[2], x[3], FULL);
                if (tags_ok(bad, 0xffffffffu)) break;
                COUNT_RETRY(warp >> 1)
            }
            PROF(0)
            project<NR, PRE, ATT ? FENCEA : FENCEB, PROG, 64>(acc, ROLE == 2, wr, as, v, nullptr, w1a, pst, 0);
            PROF(1)
            const uint32_t isc = lds32(sb + S_ISC + (s & 1) * 4);
            const uint32_t lq = l8 + ((s >> 3) & P.zero), e1 = s == 63 ? 0 : rd1, e2 = s == 63 ? 0 : rd2;
            uint32_t x[4][4], sel[8], xd[6] = {l8 + xo, l8 + xo + e1, l8 + xo + e2, sb + B_X + e1, sb + B_X + e2, sb + S_P1 + warp * 2048 + (lq & 64) * 16 + (lq & 128) + (lq & 56) * 2};
#pragma unroll
            for (int i = 0; i < 8; i++) sel[i] = (lq & 224) == i * 32 ? 0x3F803F80u : 0u;
            pin<6>(xd); pin<8>(sel);
            if (RFENCE) sched_fence();
            bar_sync(1, 256);
#pragma unroll
            for (int i = 0; i < 4; i++) ldsm4t(x[i], xd[5] + i * 256);
            if (!ATT && l8 == sb + (warp - 3) * 1024) mbar_arrive(sb + B_P1);
            uint32_t em = warp_exp(amax(amax4(amax(amax(v[0][0], v[0][1]), amax(v[0][2], v[0][3])), v[1]), amax4(amax(amax(v[2][0], v[2][1]), amax(v[2][2], v[2][3])), v[3])));
            if (EFENCE2) sched_fence();
            reduce8(x, sel, bf_hi(isc), r0, r1);
            st_async2(xd[1], r0, r1, xd[3]);
            st_async2(xd[2], r0, r1, xd[4]);
            sts64(xd[0], r0, r1);
            if (s == 63) { persist(s, warp, r0, r1); break; }
            if (l8 == sb) sts32(sb + S_EM + warp * 4, em + (isc >> 23));
            __syncwarp();
            if (l8 == sb) mbar_arrive(sb + B_X);
            PROF(2)
        }
        uint32_t w[40][4], w2a[2], odd;
        const uint8_t *po, *pd;
        auto wo_addr = [&]() {
            const uint32_t lo = (l8 + ((s >> 2) & P.zero) - sb) >> 3;
            w2a[0] = w2o + FRAG2(lo); w2a[1] = w2o + (FRAG2(lo) ^ 32);
            po = P.xb + xg_buf(s + 1) + om + xg_lane(lo);
            pd = P.xb + xg_buf(s + 1) + os + lo * 4;
            odd = lo & 4;
            pin_ptr(po); pin_ptr(pd); pin<2>(w2a); pin<1>(&odd);
        };
        uint32_t oa = l8 * 2 + (S_OX - sb);
        if constexpr (ATT) {
            const uint32_t ln = (l8 + ((s >> 4) & P.zero) - sb) >> 3;
            const uint32_t va = sb + S_KV + 8192 + ((warp >> 1) & 1) * 4096 + ((ln & 7) + (ln >> 4) * 8) * 128 + ((((warp & 1) * 4 + ((ln >> 3) & 1)) ^ (ln & 7)) << 4);
            const uint32_t ka = sb + S_KV + (warp & 1) * 2048 + (ln & 15) * 128 + (((ln >> 4) ^ (ln & 7)) << 4);
            uint32_t ad[5] = {sb + S_SX + (ln & 3) * (8 * SROW) + (ln >> 2) * 4 + (warp < 6 ? (warp - 4) * 64 : 128 + (warp - 6) * 32), l8 + S_XV + (warp - 4) * 512,
                              l8 + S_SX + (ln >> 2) * (4 * SROW - 32), oa + (warp - 4) * 512, sb + S_ISC + (~s & 1) * 4};
            if constexpr (AB) { wo_addr(); pin<1>(&oa); }
            pin<5>(ad);
            const uint32_t sa = ad[0], sr = ad[2];
            uint32_t vf[4][4], vm[2][2], q[8][2];
            float S[4][4];
#pragma unroll
            for (int n = 0; n < 4; n++) { S[n][0] = S[n][1] = S[n][2] = S[n][3] = 0.f; }
            mbar_wait(sb + B_KVFULL, s & 1);
            if (warp < 6) {
                uint32_t kf[8][4];
#pragma unroll
                for (int k = 0; k < 8; k++) ldsm4(kf[k], (ka ^ ((k & 3) << 5)) + (k >> 2) * 4096);
#pragma unroll
                for (int i = 0; i < 4; i++) ldsm4t(vf[i], (va ^ ((i & 1) << 5)) + (i >> 1) * 2048);
                mbar_wait(sb + B_X, s & 1);
                PROF(11)
#pragma unroll
                for (int k = 0; k < 8; k++) lds64(q[k], l8 + S_X + k * 256);
#pragma unroll
                for (int k = 0; k < 8; k++) mma16816(S[k & 3], kf[k][0], kf[k][1], kf[k][2], kf[k][3], q[k][0], q[k][1]);
                sts32(sa, __float_as_uint((S[0][0] + S[1][0]) + (S[2][0] + S[3][0])));
                sts32(sa + 4 * SROW, __float_as_uint((S[0][1] + S[1][1]) + (S[2][1] + S[3][1])));
                sts32(sa + 32, __float_as_uint((S[0][2] + S[1][2]) + (S[2][2] + S[3][2])));
                sts32(sa + 4 * SROW + 32, __float_as_uint((S[0][3] + S[1][3]) + (S[2][3] + S[3][3])));
            } else {
#pragma unroll
                for (int i = 0; i < 4; i++) ldsm4t(vf[i], (va ^ ((i & 1) << 5)) + (i >> 1) * 2048);
                uint32_t xa = l8 + S_X + (warp - 6) * 1024;
                pin<1>(&xa);
                mbar_wait(sb + B_X, s & 1);
                PROF(11)
#pragma unroll
                for (int k = 0; k < 8; k++) lds64(q[k], xa + (k >> 2) * 2048 + (k & 3) * 256);
#pragma unroll
                for (int k = 0; k < 4; k++) mma16816(S[k], q[4 + (k & 2)][0], q[4 + (k & 2)][1], q[5 + (k & 2)][0], q[5 + (k & 2)][1], q[k][0], q[k][1]);
                sts32(sa, __float_as_uint((S[0][0] + S[2][0]) + (S[1][2] + S[3][2])));
                sts32(sa + 4 * SROW, __float_as_uint((S[0][1] + S[2][1]) + (S[1][3] + S[3][3])));
            }
            lds64(vm[0], ad[1]); lds64(vm[1], ad[1] + 256);
            PROF(7)
            bar_sync(2, 160);
            const float cs = 0.08838834764831845f * 1.4426950408889634f;
            float E[6][2];
#pragma unroll
            for (int i = 0; i < 6; i++) lds64f(E[(i + 4) % 6], sr + ((i + 4) % 6) * 32);
            const uint32_t isn = lds32(ad[4]);
            E[4][0] += E[5][0]; E[4][1] += E[5][1];
            float m = fmaxf(fmaxf(fmaxf(fmaxf(E[0][0], E[0][1]), fmaxf(E[1][0], E[1][1])), fmaxf(fmaxf(E[2][0], E[2][1]), fmaxf(E[3][0], E[3][1]))), fmaxf(E[4][0], E[4][1]));
            m = fmaxf(m, __shfl_xor_sync(0xffffffffu, m, 1));
            m = fmaxf(m, __shfl_xor_sync(0xffffffffu, m, 2));
            m *= cs;
            if constexpr (AB) static_for<0, PRE3>([&](auto I) { load_w2<I.value>(w[I.value], w2a); });
            uint32_t pa[5];
#pragma unroll
            for (int i = 0; i < 5; i++) { const int k = (i + 4) % 5; E[k][0] = ex2(fmaf(E[k][0], cs, -m)); E[k][1] = ex2(fmaf(E[k][1], cs, -m)); pa[k] = pack2(E[k][0], E[k][1]); }
            if (EFENCE) sched_fence();
            float O[2][4], Z[4];
#pragma unroll
            for (int i = 0; i < 4; i++) { O[0][i] = O[1][i] = Z[i] = 0.f; }
#pragma unroll
            for (int i = 0; i < 2; i++) {
                mma1688(O[i], vm[i][0], vm[i][1], pa[4]);
                mma16816(O[i], vf[i][0], vf[i][1], vf[i][2], vf[i][3], pa[0], pa[1]);
                mma16816(O[i], vf[2 + i][0], vf[2 + i][1], vf[2 + i][2], vf[2 + i][3], pa[2], pa[3]);
            }
            const float z = (((E[4][0] + E[4][1]) + (E[0][0] + E[0][1])) + ((E[1][0] + E[1][1]) + (E[2][0] + E[2][1]))) + (E[3][0] + E[3][1]);
            const float zh = __uint_as_float(__float_as_uint(z) & 0xffff0000u);
            mma1688(Z, isn, isn, pack2(zh, z - zh));
            const float i0 = rcp(Z[0]), i1 = rcp(Z[1]);
            stsm4t(ad[3], pack2(O[0][0] * i0, O[0][1] * i1), pack2(O[0][2] * i0, O[0][3] * i1), pack2(O[1][0] * i0, O[1][1] * i1), pack2(O[1][2] * i0, O[1][3] * i1));
            PROF(4)
            if constexpr (AB) wo_blocks<1, RESA, PRE3, OFENCE / 2>(w, wr + NR * 8, oa, w2a, po, pd, odd);
            else bar_arrive(3, 256);
            if (ROLE != 0) persist(s, warp, r0, r1);
            if (warp == 7 && l8 == sb) mbar_expect(sb + B_X, 4096);
        } else {
            if (ROLE != 0) persist(s, warp, r0, r1);
            wo_addr(); pin<1>(&oa);
            static_for<0, PRE2A>([&](auto I) { load_w2<I.value>(w[I.value], w2a); });
            mbar_wait(sb + B_X, s & 1);
            if (warp == 0) {
                uint32_t sc[2];
                lds64(sc, sb + S_SC);
                const int em = __reduce_max_sync(0xffffffffu, lds32(sb + S_EM + ((l8 >> 1) & 28)));
                if (l8 == sb) sts32(sb + S_ISC + (~s & 1) * 4, min(max(em - 127, (int)sc[1]) + (int)sc[0], 253) * 0x800080u);
                bar_arrive(2, 160);
            }
            wait_clocks(XDELAY - (warp == 0) * 100);
            constexpr int PRE1 = (BB - 1) * 16 - (5 - NRB) * 8 < PRE2 ? (BB - 1) * 16 - (5 - NRB) * 8 : PRE2;
            static_for<PRE2A, PRE1>([&](auto I) { load_w2<I.value>(w[I.value], w2a); });
            if (full) {
                static_for<PRE1, PRE2>([&](auto I) { load_w2<I.value>(w[I.value], w2a); });
                wo_blocks<BB, RESB, PRE2, FENCE2 * 2 + OFENCE % 2>(w, wr + NR * 8, oa, w2a, po, pd, odd);
            } else wo_blocks<BB - 1, RESB1, PRE1, FENCE2 * 2 + OFENCE % 2>(w, wr + NR * 8, oa, w2a, po, pd, odd);
        }
        PROF(5)
        if (l8 == sb) { sts32(sb + S_TO + warp * 4, gtime()); mbar_arrive(sb + B_RED); }
        if (HOLD && !(PLATE >> ATT & 1)) mbar_wait(sb + B_RED, s & 1);
        if (ROLE != 0 && (s & 3) == 3 && l8 == sb) mbar_arrive(sb + B_PERS);
        if (ROLE == 0 && s == 62) return;
    }
    __syncwarp();
    if (l8 == sb) mbar_arrive(sb + B_PERS);
}
#define IP(i)
struct Pipe { uint32_t stage, phase; };
struct Cons {
    uint32_t sb, rel;
    int wg, wq, lane, rank, pair;
    uint32_t nst;
    Pipe p;
};
__device__ __forceinline__ void pipe_next(Pipe& p) { p.stage = (p.stage + 1) & (NSTAGE - 1); p.phase ^= (p.stage == 0); }
__device__ __forceinline__ void release(const Cons& c, uint32_t stage) { if (c.lane < 2) mbar_arrive_cluster(c.rel + stage * 8); }
__device__ __forceinline__ void wait_full(const Cons& c) { mbar_wait(c.sb + B_FULL + c.p.stage * 8, c.p.phase); }

enum { PEND_NONE = 0, PEND_KVO = 1, PEND_HT = 2, PEND_OUT = 3 };
struct Pend { uint32_t pk[64]; int kind, row, col, cnt; };

__device__ __forceinline__ void staging_wait(const Cons& c) { if (c.nst) mbar_wait(c.sb + B_SFREE + c.wg * 8, (c.nst - 1) & 1); }
__device__ __forceinline__ void staging_post(Cons& c, int kind, int row, int col, int cnt) {
    __syncwarp();
    if (c.lane == 0) {
        if (c.wq == 0) { const uint32_t x[4] = {(uint32_t)kind, (uint32_t)row, (uint32_t)col, (uint32_t)cnt}; sts128(c.sb + S_DESC + c.wg * 16, x); }
        mbar_arrive(c.sb + B_SFULL + c.wg * 8);
    }
    c.nst++;
}
__device__ __forceinline__ void drain(const Params& P, Cons& c, Pend& d) {
    const uint32_t* pk = d.pk;
    if (d.kind == PEND_OUT) {
        float* o = P.out + (size_t)(d.row + c.wq * 16 + (c.lane >> 2)) * 2048 + d.col + (c.lane & 3) * 2;
#pragma unroll
        for (int j = 0; j < 16; j++) {
            st_stream2(o + j * 8, bf_lo(pk[j * 2]), bf_hi(pk[j * 2]));
            st_stream2(o + 8 * 2048 + j * 8, bf_lo(pk[j * 2 + 1]), bf_hi(pk[j * 2 + 1]));
        }
    } else {
        const bool ht = d.kind == PEND_HT;
        const int hi = (c.lane >> 3) & 1;
        const uint32_t base = c.sb + S_STG + c.wg * 16384 + ((ht ? hi * 32 + c.wq * 8 : c.wq * 16 + hi * 8) + (c.lane & 7)) * 128;
        staging_wait(c);
#pragma unroll
        for (int j = 0; j < 8; j++) {
            const int ch = (j & 3) * 2 + (c.lane >> 4);
            stsm4(base + (j >> 2) * 8192 + ((ch ^ (c.lane & 7)) << 4), pk[j * 4], pk[j * 4 + 1], pk[j * 4 + 2], pk[j * 4 + 3]);
        }
        fence_async_smem();
        staging_post(c, d.kind, d.row, d.col, (d.col & 128) ? d.cnt : -1);
    }
    if (d.col & 128) d.kind = PEND_NONE;
    d.col += 128;
#pragma unroll
    for (int i = 0; i < 32; i++) d.pk[i] = d.pk[32 + i];
}

constexpr int S_STG2 = 8 * 20480, PEND_BOTH = 8;
__device__ __forceinline__ void drain_both(Cons& c, const Pend& d) {
    const uint32_t base = c.sb + c.wg * 16384 + (c.wq * 16 + ((c.lane >> 3) & 1) * 8 + (c.lane & 7)) * 128;
#pragma unroll
    for (int j = 0; j < 16; j++)
        stsm4(base + (j < 8 ? S_STG : S_STG2) + (j >> 2 & 1) * 8192 + ((((j & 3) * 2 + (c.lane >> 4)) ^ (c.lane & 7)) << 4), d.pk[j * 4], d.pk[j * 4 + 1], d.pk[j * 4 + 2], d.pk[j * 4 + 3]);
    fence_async_smem();
    staging_post(c, PEND_KVO | PEND_BOTH, d.row, d.col, d.cnt);
}

__device__ __forceinline__ void store_warp(const Params& P, uint32_t sb, int wg, int cta) {
    if (cta < 128) {
        for (int i = 0; i < P.xd; i++) __nanosleep(1000);
        const uint32_t e1 = get_epoch(sb) + 1;
        const uint4* x = (const uint4*)P.Bx + (cta * 2 + wg) * 1024 + (threadIdx.x & 31);
        uint32_t m = 0;
#pragma unroll 4
        for (int i = 0; i < 32; i++) { const uint4 u = __ldg(x + i * 32); m = amax(amax(m, amax(u.x, u.y)), amax(u.z, u.w)); }
        m = warp_exp(m);
        if (elect_one()) { atomicMax(&g_cnt(C_XMAX), e1 << 8 | m); red_release(&g_cnt(C_XCNT)); }
        __syncwarp();
    }
    const uint32_t stg = sb + S_STG + wg * 16384;
#pragma unroll 1
    for (uint32_t n = 0;; n++) {
        mbar_wait(sb + B_SFULL + wg * 8, n & 1);
        uint32_t x[4];
        lds128(x, sb + S_DESC + wg * 16);
#pragma unroll
        for (int i = 0; i < 4; i++) x[i] = __shfl_sync(0xffffffffu, x[i], 0);
        if (x[0] == PEND_NONE) break;
        const bool ht = x[0] == PEND_HT;
        const CUtensorMap* m = &P.tm[ht ? M_HTS : M_KVO];
        const uint64_t pol = P.pol[ht ? 2 : x[1] >= 4096 ? 1 : (x[1] & 2047) < 1536 ? 0 : 10];
        if (elect_one()) {
#pragma unroll
            for (int i = 0; i < 4; i++) tma_store2d(m, x[2] + (i >> 1) * 64, x[1] + (i & 1) * (ht ? 1024 : 32), stg + i * 4096, pol);
            if (x[0] & PEND_BOTH) {
#pragma unroll 1
                for (int i = 0; i < 4; i++) tma_store2d(m, x[2] + 128 + (i >> 1) * 64, x[1] + (i & 1) * 32, stg + (S_STG2 - S_STG) + i * 4096, pol);
            }
            bulk_commit();
            bulk_wait_read();
            mbar_arrive(sb + B_SFREE + wg * 8);
            if ((int)x[3] >= 0) { bulk_wait_all(); fence_async(); red_release(&g_cnt(x[3])); }
        }
        __syncwarp();
    }
}

template <int TA, int TB, bool FIRST>
__device__ __forceinline__ void issue_ktile(float* acc, const Cons& c) {
    const uint32_t a = c.sb + c.p.stage * STAGE + c.wg * 8192, b = c.sb + c.p.stage * STAGE + 16384;
    const uint64_t da = mkdesc(a, TA ? 8192 : 16, 1024, 1), db = mkdesc(b, TB ? 8192 : 16, 1024, 1);
    wg_fence();
#pragma unroll
    for (int k = 0; k < 4; k++) {
        if (FIRST && k == 0) wgmma_ss256_first<TA, TB>(acc, da, db);
        else wgmma_ss256<TA, TB>(acc, da + (TA ? 128 : 2) * k, db + (TB ? 128 : 2) * k);
    }
    wg_commit();
}
template <bool KVONLY, bool FIRST>
__device__ __forceinline__ void issue_any(float* acc, const Cons& c, int type) {
    wait_full(c);
    if (!KVONLY && type == T_A1) issue_ktile<0, 0, FIRST>(acc, c);
    else if (!KVONLY && type == T_A2) issue_ktile<1, 0, FIRST>(acc, c);
    else issue_ktile<0, 1, FIRST>(acc, c);
}
template <bool KVONLY = false>
__device__ __forceinline__ void mainloop(float* acc, const Params& P, Cons& c, Pend& d, int type, int nk) {
    issue_any<KVONLY, true>(acc, c, type);
    if (!KVONLY) { IP(0) }
    uint32_t prev = c.p.stage;
    pipe_next(c.p);
#pragma unroll 1
    for (int kt = 1; kt < nk; kt++) {
        if (!KVONLY && d.kind != PEND_NONE && kt != 2) drain(P, c, d);
        issue_any<KVONLY, false>(acc, c, type);
        wg_wait<1>();
        release(c, prev);
        prev = c.p.stage;
        pipe_next(c.p);
    }
    d.kind = PEND_NONE;
    wg_wait<0>();
    pin<128>(acc);
    release(c, prev);
    if (!KVONLY) { IP(1) }
}
__device__ __forceinline__ void pack_half(uint32_t* pk, const float* a) {
#pragma unroll
    for (int i = 0; i < 32; i++) pk[i] = pack2(a[2 * i], a[2 * i + 1]);
}

__device__ __forceinline__ void epi_kv(const float* acc, const Cons& c, Pend& d, int mb, int nb) {
    pack_half(d.pk, acc); pack_half(d.pk + 32, acc + 64);
    d.kind = PEND_KVO; d.row = (nb >> 4) * 2048 + mb * 256 + c.rank * 128 + c.wg * 64; d.col = (nb & 15) * 256; d.cnt = C_KV + mb;
}

__device__ __forceinline__ void qa_scores(float* S, float* Sm, const uint32_t* q, Cons& c) {
    wait_full(c);
    const uint32_t st = c.sb + c.p.stage * STAGE;
    const uint64_t dk = mkdesc(st + c.wg * 8192, 16, 1024, 1), dm = mkdesc(st + 32768 + c.wg * 4096, 128, 2048, 0);
    wg_fence();
#pragma unroll
    for (int i = 0; i < 8; i++) wgmma_rs64<0>(S, q + i * 4, dk + (i >> 2) * 1024 + (i & 3) * 2, i != 0);
#pragma unroll
    for (int i = 0; i < 8; i++) wgmma_rs16<0>(Sm, q + i * 4, dm + i * 16, i != 0);
    wg_commit();
    pipe_next(c.p);
}
__device__ __forceinline__ void qa_softmax(uint32_t (*pa)[4], const float* S, const float* Sm, const Cons& c) {
    const int t = c.lane & 3, i0 = (c.wq & 1) * 16 + (c.lane >> 2) - 2 * t;
    const bool sg = c.wq >= 2;
    const float cs = 0.08838834764831845f * 1.4426950408889634f;
    float x[2][10];
#pragma unroll
    for (int r = 0; r < 2; r++) {
#pragma unroll
        for (int j = 0; j < 4; j++)
#pragma unroll
            for (int e = 0; e < 2; e++) {
                const float v = sg ? S[16 + j * 4 + r * 2 + e] : S[j * 4 + r * 2 + e];
                x[r][j * 2 + e] = (j * 8 + e - r * 8 > i0) ? -1e9f / 0.08838834764831845f : v;
            }
        x[r][8] = sg ? Sm[4 + r * 2] : Sm[r * 2];
        x[r][9] = sg ? Sm[5 + r * 2] : Sm[1 + r * 2];
        float m = fmaxf(fmaxf(fmaxf(fmaxf(x[r][0], x[r][1]), fmaxf(x[r][2], x[r][3])), fmaxf(fmaxf(x[r][4], x[r][5]), fmaxf(x[r][6], x[r][7]))), fmaxf(x[r][8], x[r][9]));
        m = fmaxf(m, __shfl_xor_sync(0xffffffffu, m, 1));
        m = fmaxf(m, __shfl_xor_sync(0xffffffffu, m, 2));
        m *= -cs;
#pragma unroll
        for (int i = 0; i < 10; i++) x[r][i] = ex2(fmaf(x[r][i], cs, m));
        float sum = (((x[r][0] + x[r][1]) + (x[r][2] + x[r][3])) + ((x[r][4] + x[r][5]) + (x[r][6] + x[r][7]))) + (x[r][8] + x[r][9]);
        sum += __shfl_xor_sync(0xffffffffu, sum, 1);
        sum += __shfl_xor_sync(0xffffffffu, sum, 2);
        const float inv = rcp(sum);
#pragma unroll
        for (int i = 0; i < 10; i++) x[r][i] *= inv;
    }
#pragma unroll
    for (int ks = 0; ks < 2; ks++)
#pragma unroll
        for (int i = 0; i < 4; i++) {
            const uint32_t p = pack2(x[i & 1][ks * 4 + (i >> 1) * 2], x[i & 1][ks * 4 + (i >> 1) * 2 + 1]);
            pa[ks][i] = sg ? 0u : p;
            pa[2 + ks][i] = sg ? p : 0u;
        }
#pragma unroll
    for (int r = 0; r < 2; r++) {
        const uint32_t p = pack2(x[r][8], x[r][9]);
        pa[4][r] = sg ? 0u : p;
        pa[4][2 + r] = sg ? p : 0u;
    }
}
__device__ __forceinline__ void qa_values(float* O, uint32_t (*pa)[4], Cons& c) {
    wait_full(c);
    const uint32_t st = c.sb + c.p.stage * STAGE;
    const uint64_t dv = mkdesc(st + c.wg * 8192, 16384, 1024, 1), dm = mkdesc(st + 32768 + c.wg * 4096, 2048, 128, 0);
    pin<20>(&pa[0][0]);
    wg_fence();
#pragma unroll
    for (int ks = 0; ks < 4; ks++) wgmma_rs128<1>(O, pa[ks], dv + ks * 128, ks != 0);
    wgmma_rs128<0>(O, pa[4], dm, 1);
    wg_commit();
    pipe_next(c.p);
}
__device__ __forceinline__ void epi_qa(const float* acc, Cons& c, Pend& d, int mb, int nb) {
    uint32_t q[64], pa[2][5][4];
    float S0[32] = {}, M0[8] = {}, S1[32] = {}, M1[8] = {}, O0[64] = {}, O1[64] = {};
    const uint32_t k0 = c.p.stage;
    pack_half(q, acc);
    pin<32>(q); pin<32>(S0); pin<8>(M0);
    qa_scores(S0, M0, q, c);
    pack_half(q + 32, acc + 64);
    pin<32>(q + 32); pin<32>(S1); pin<8>(M1);
    qa_scores(S1, M1, q + 32, c);
    wg_wait<1>();
    pin<32>(S0); pin<8>(M0);
    release(c, k0);
    qa_softmax(pa[0], S0, M0, c);
    wg_wait<0>();
    pin<32>(S1); pin<8>(M1); pin<64>(q);
    release(c, (k0 + 1) & (NSTAGE - 1));
    pin<64>(O0);
    qa_values(O0, pa[0], c);
    qa_softmax(pa[1], S1, M1, c);
    pin<64>(O1);
    qa_values(O1, pa[1], c);
    wg_wait<1>();
    pin<64>(O0); pin<20>(&pa[0][0][0]);
    release(c, (k0 + 2) & (NSTAGE - 1));
    pack_half(d.pk, O0);
    wg_wait<0>();
    pin<64>(O1); pin<20>(&pa[1][0][0]);
    release(c, (k0 + 3) & (NSTAGE - 1));
    pack_half(d.pk + 32, O1);
    d.kind = PEND_KVO; d.row = 4096 + mb * 256 + c.rank * 128 + c.wg * 64; d.col = nb * 256; d.cnt = C_O + mb;
}

__device__ __forceinline__ void epi_op(const float* acc, const Cons& c, Pend& d, int mb, int nb) {
    pack_half(d.pk, acc); pack_half(d.pk + 32, acc + 64);
    d.kind = PEND_OUT; d.row = mb * 256 + c.rank * 128 + c.wg * 64; d.col = 1024 + nb * 256;
}

__device__ __forceinline__ void epi_a2(float* acc, const Params& P, Cons& c, int mb, int col0) {
    const int g = c.lane >> 2, t = c.lane & 3;
    const int row = mb * 256 + (g >> 1) * 64 + (c.rank * 16 + c.wg * 8 + c.wq * 2) * 2 + (g & 1);
    float* o = P.out + (size_t)row * 2048 + col0 + t * 2;
#pragma unroll 1
    for (int hf = P.zero; hf < 2; hf++) {
    wait_full(c);
    const uint32_t st = c.sb + c.p.stage * STAGE, xa = st + (c.wg * 64 + c.wq * 16 + g) * 128 + t * 4 + (g << 4), da = st + 32768 + t * 4;
#pragma unroll
    for (int j = 0; j < 16; j++) {
        const float* a = acc + j * 4;
        const uint32_t ad = (xa ^ ((j & 7) << 4)) + (j >> 3) * 16384;
        const uint32_t x0 = lds32(ad), x1 = lds32(ad + 1024), dv = lds32(da + j * 16);
        const uint32_t u0 = mul_bf2(x0, dv), u1 = mul_bf2(x1, dv);
        st_stream2(o + j * 8, a[0] + bf_lo(u0), a[1] + bf_hi(u0));
        st_stream2(o + 2 * 2048 + j * 8, a[2] + bf_lo(u1), a[3] + bf_hi(u1));
    }
    __syncwarp();
    release(c, c.p.stage);
    pipe_next(c.p);
    o += 128;
#pragma unroll
    for (int i = 0; i < 64; i++) acc[i] = acc[64 + i];
    }
}

#define TSTAMP(i)
__device__ __forceinline__ float2 cmul(float2 a, float2 b) { return make_float2(fmaf(a.x, b.x, -a.y * b.y), fmaf(a.x, b.y, a.y * b.x)); }
__device__ __forceinline__ float2 cfma(float2 a, float2 b, float2 u) { return make_float2(fmaf(a.x, b.x, fmaf(-a.y, b.y, u.x)), fmaf(a.x, b.y, fmaf(a.y, b.x, u.y))); }
__device__ __forceinline__ float4 ssm_coef(float lre, float lim, float logdt) {
    const float dt = __bfloat162float(__float2bfloat16(expf(logdt)));
    const float ea = expf(dt * lre);
    float sn, cn;
    sincosf(dt * lim, &sn, &cn);
    const float br = ea * cn, bi = ea * sn, nr = br - 1.f;
    float cr, ci;
    if (fabsf(lre) >= fabsf(lim)) { const float r = lim / lre, dn = lre + lim * r; cr = (nr + bi * r) / dn; ci = (bi - nr * r) / dn; }
    else { const float r = lre / lim, dn = lre * r + lim; cr = (nr * r + bi) / dn; ci = (bi * r - nr) / dn; }
    return make_float4(br, bi, cr, ci);
}
__device__ __forceinline__ void epi_a1(const float* acc, const Params& P, const Cons& c, Pend& d, int mb, int nb) {
    const uint32_t atag = (get_epoch(c.sb) + 1) & 1;
    const int t = c.lane & 3;
    const int p = nb * 128 + c.rank * 64 + c.wg * 32 + c.wq * 8 + (c.lane >> 2);
    const float4 cf = __ldcg(&g_coef[p]);
    const float2 lam = make_float2(cf.x, P.swap_ri ? -cf.y : cf.y);
    const float a0 = P.swap_ri ? -2.f * cf.w : 2.f * cf.z, a1 = P.swap_ri ? 2.f * cf.z : -2.f * cf.w;
    const float b0 = P.swap_ri ? -2.f * cf.z : -2.f * cf.w, b1 = P.swap_ri ? -2.f * cf.w : -2.f * cf.z;
    float2 h = make_float2(0.f, 0.f);
#pragma unroll
    for (int round = 0; round < 2; round++) {
#pragma unroll
        for (int j = 0; j < 32; j++) {
            h = cfma(lam, h, make_float2(acc[j * 4], acc[j * 4 + 2]));
            const float r0 = fmaf(a0, h.x, a1 * h.y), m0 = fmaf(b0, h.x, b1 * h.y);
            h = cfma(lam, h, make_float2(acc[j * 4 + 1], acc[j * 4 + 3]));
            d.pk[j * 2] = pack2(r0, fmaf(a0, h.x, a1 * h.y));
            d.pk[j * 2 + 1] = pack2(m0, fmaf(b0, h.x, b1 * h.y));
        }
        if (round) break;
        float2 l64 = lam;
#pragma unroll
        for (int i = 0; i < 6; i++) l64 = cmul(l64, l64);
        const float2 l128 = cmul(l64, l64), l256 = cmul(l128, l128);
        float2 o = make_float2(__shfl_up_sync(0xffffffffu, h.x, 1), __shfl_up_sync(0xffffffffu, h.y, 1));
        if (t >= 1) h = cfma(l64, o, h);
        o = make_float2(__shfl_up_sync(0xffffffffu, h.x, 2), __shfl_up_sync(0xffffffffu, h.y, 2));
        if (t >= 2) h = cfma(l128, o, h);
        IP(2)
        if (t == 3) st_relaxed2(&g_agg[mb * 1024 + p], (__float_as_uint(h.x) & ~1u) | atag, __float_as_uint(h.y));
        h = make_float2(__shfl_up_sync(0xffffffffu, h.x, 1), __shfl_up_sync(0xffffffffu, h.y, 1));
        if (t == 0) h = make_float2(0.f, 0.f);
        uint32_t ax[7], ay[7];
        while (true) {
            uint32_t bad = 0;
#pragma unroll
            for (int j = 0; j < 7; j++) { ax[j] = atag; ay[j] = 0; ld_relaxed2_if(ax[j], ay[j], &g_agg[j * 1024 + p], j < mb); }
#pragma unroll
            for (int j = 0; j < 7; j++) bad |= ax[j] ^ atag;
            if (tags_ok(bad)) break;
            __nanosleep(2 * POLLNS);
        }
        float2 carry = make_float2(0.f, 0.f);
#pragma unroll
        for (int j = 0; j < 7; j++) if (j < mb) carry = cfma(l256, carry, make_float2(__uint_as_float(ax[j]), __uint_as_float(ay[j])));
        float2 w = (t & 1) ? l64 : make_float2(1.f, 0.f);
        if (t & 2) w = cmul(w, l128);
        h = cfma(w, carry, h);
        IP(3)
    }
    IP(4)
    d.kind = PEND_HT; d.row = nb * 128 + c.rank * 64 + c.wg * 32; d.col = mb * 256; d.cnt = C_HT + mb;
}

__device__ __forceinline__ uint32_t fresh_tid() { uint32_t t; asm volatile("mov.u32 %0, %%tid.x;" : "=r"(t)); return t; }
__device__ __forceinline__ uint32_t acquire_stage(uint32_t sb, Pipe& p, uint32_t bytes) {
    mbar_wait(sb + B_EMPTY + p.stage * 8, p.phase ^ 1);
    mbar_expect_e(sb + B_FULL + p.stage * 8, bytes);
    return p.stage;
}
__device__ __forceinline__ void producer(const Params& P, const uint32_t sb, const int cta, const uint32_t epoch) {
    Pipe p = {0, 0};
    uint32_t resume = 1;
    const uint32_t e1 = epoch + 1;
    const int rank = cta & 1;
    const uint16_t both = 3 << (__shfl_sync(0xffffffffu, cluster_rank(), 0) & ~1u);
    for (int it = ITEM_OFF(cta >> 1); it < ITEM_OFF((cta >> 1) + 1); it++) {
        const int item = ITEM(it), type = (item >> 8) & 7, mb = (item >> 5) & 7, nb = item & 31, half = item >> 12 & 1, hw = item >> 13;
        if (type == T_CHAIN) {
            const int h = cta / 3, role = cta - h * 3;
#pragma unroll 1
            for (int w = 0; w < 8; w++) {
                mbar_wait(sb + B_EMPTY + (w * 20480 + 20479) / STAGE * 8, 1);
                chain_load(P, sb, cta, w, threadIdx.x & 31, 0);
            }
            uint32_t* flag = &g_cnt(C_FLAG + (role == 2 ? 32 : 0) + h);
            if (role) { wait_count(&g_cnt(C_KV), e1 * 128); fence_async(); }
#pragma unroll 1
            for (int s = 0; s < 64 && role != 0; s++) {
                if (s < 63) {
                    mbar_wait(sb + B_GO, s & 1);
                    tma3d_mc_e(sb + S_KV + (role - 1) * 8192, &P.tm[M_SEG], 0, (role - 1) * 2048 + s * 32, h * 2, sb + B_KVFULL, 7 << ((h & 1) * 3), P.pol[s < 48 ? 8 : 11]);
                    if ((s & 7) == 7) { wait_count(&g_cnt(C_KV + 1 + (s >> 3)), e1 * 128); fence_async(); }
                    tma_prefetch3d_e(&P.tm[M_SEG], 0, (role - 1) * 2048 + s * 32 + 32, h * 2);
                }
                if (s > 0 && ((s & 3) == 0 || s == 63)) {
                    const int i = (s - 1) >> 2;
                    mbar_wait(sb + B_PERS, i & 1);
                    asm volatile("{\n.reg .pred E;\nelect.sync _|E, 0xffffffff;\n@E st.release.gpu.global.u32 [%0], %1;\n}" ::"l"(flag), "r"(epoch * 64 + i * 4 + 4) : "memory");
                }
            }
            if (role == 0) {
                const int lane = threadIdx.x & 31;
                if (lane == 0) mbar_arrive(sb + B_RELM);
#pragma unroll 1
                for (int s = 0; s < 63; s++) {
                    mbar_wait(sb + B_P1, s & 1);
                    if (s > 0) {
                        st_relaxed4(P.xb + xg_buf(s - 1) + h * 2048 + xg_lane(lane), 0, 0, 0, 0);
                        st_relaxed1(P.xb + xg_buf(s - 1) + xg_side(h) + lane * 4, 0);
                        __threadfence();
                    }
                    __syncwarp();
                    if (lane == 0) mbar_arrive(sb + B_RELM);
                }
            }
            if ((threadIdx.x & 31) < M_C1 - 1) asm volatile("prefetch.tensormap [%0];" ::"l"(&P.tm[1 + (threadIdx.x & 31)]) : "memory");
            resume = 0;
            continue;
        }
        const int m0 = mb * 256 + rank * 128, ssm = type >= T_A1;
        const CUtensorMap* ma = &P.tm[max(type, 1) + half * M_HALF];
        const CUtensorMap* mw = &P.tm[type ? M_WV + type : M_WK + (nb >> 4)];
        const int nk = type == T_OP ? 64 : type == T_A2 ? 32 : 16;
        const int a3 = type == T_A1 ? nb * 16 + rank * 8 + hw * 4 : type == T_A2 ? mb * 4 + rank * 2 + hw : (type == T_OP ? 4096 : 0) + m0 + hw * 64;
        const int b3 = type == T_A1 ? mb * 128 + rank * 16 : type == T_A2 ? (nb * 2 + rank) * 128 : (nb & 15) * 4 + rank * 2;
        if (type) {
            wait_count(&g_cnt(type == T_A1 ? C_COEF : (type >> 1) * 8 + mb), e1 * (type == T_A1 ? 4 : 128 >> (type >> 1)));
            fence_async();
        }
        if (type == T_A1) l2_prefetch_e(g_coef + nb * 128 + rank * 64, 1024);
        auto arrived = [&]() {
            const uint32_t t = fresh_tid();
            return __all_sync(0xffffffffu, (int32_t)(ld_acquire(&g_cnt(C_FLAG + (t & 2) * 16 + nb * 2 + (t & 1))) - (epoch * 64 + mb * 8 + rank * 4 + 4)) >= 0);
        };
        bool passed = false;
        mbar_wait(sb + B_RESUME, resume);
#pragma unroll 1
        for (int kt = 0; kt < nk; kt++) {
            if (type == T_QA && kt == 9) passed = arrived();
            const uint32_t st = acquire_stage(sb, p, STAGE - half * 8192), bar = sb + B_FULL + st * 8;
            const int a1 = type == T_A2 ? kt * 64 : 0, b0 = ssm ? (kt & 15) * 64 : 0;
            tma4d_e(sb + st * STAGE + hw * 8192, ma, kt * 64 - a1, a1, a3, bar, P.pol[11]);
            tma4d_mc_e(sb + st * STAGE + 16384 + rank * 16384, mw + (ssm & kt >> 4), b0, ssm ? 0 : kt * 64, b3, bar, both, P.pol[item == (item & 31) + 224 ? 9 : 11]);
            if (type == T_QA && kt < 8) tma_prefetch4d_e(&P.tm[M_OA], nb * 256 + (kt & 3) * 64, (kt >> 2) * 2048 + m0);
            pipe_next(p);
        }
        if (type == T_QA) {
            while (!passed) { passed = arrived(); if (!passed) __nanosleep(POLLNS); }
            fence_async();
        }
        const int q = type == T_QA;
#pragma unroll 1
        for (int e = 0; e < (q ? 4 : type == T_A2 ? 2 : 0); e++) {
            const uint32_t st = acquire_stage(sb, p, q ? 40960 : 32768 + 256), bar = sb + B_FULL + st * 8, dst = sb + st * STAGE;
#pragma unroll 1
            for (int i = 0; i < 2; i++) tma4d_e(dst + i * 16384, &P.tm[q ? M_OA : M_AX], nb * 256 + (e & 1) * 128 + i * 64, 0, q ? (e >> 1) * 2048 + m0 : mb * 128 + rank * 16, bar, P.pol[q ? 3 : 11]);
            const uint8_t* src = q ? (const uint8_t*)(((e >> 1) ? g_vmt : g_km) + ((mb * 8 + rank * 4) * 32 + nb * 2 + (e & 1)) * 512) : (const uint8_t*)(P.Dskip + nb * 256 + e * 128);
#pragma unroll 1
            for (int i = 0; i < (q ? 4 : 1); i++) bulk_g2s_e(dst + 32768 + i * 2048, src + i * 65536, q ? 2048 : 256, bar);
            pipe_next(p);
        }
    }
}

__device__ __forceinline__ uint32_t fresh_ctaid() { uint32_t t; asm volatile("mov.u32 %0, %%ctaid.x;" : "=r"(t)); return t; }
__device__ __forceinline__ void reset_state(const Params& P, Cons& c, Pend& d, uint32_t sb, bool resumed) {
    const uint32_t t = fresh_tid(), b = fresh_ctaid() + P.cta0;
    const int w = __shfl_sync(0xffffffffu, t >> 5, 0);
    c.sb = sb; c.wg = w >> 2; c.wq = w & 3; c.lane = t & 31;
    c.rank = __shfl_sync(0xffffffffu, b & 1, 0); c.pair = __shfl_sync(0xffffffffu, b >> 1, 0);
    c.rel = mapa(sb + B_EMPTY, cluster_rank() ^ (c.lane & 1));
    c.p.stage = 0; c.p.phase = 0;
    c.nst = resumed && c.pair < NCHAIN;
    d = Pend{};
}
#define PROF_ITEM(i, item)

__global__ void __launch_bounds__(384, 1) fused_kernel(const __grid_constant__ Params P) {
    extern __shared__ __align__(1024) uint8_t smem[];
    const uint32_t sb = smem_u32(smem);
    asm volatile("griddepcontrol.launch_dependents;");
    declare_fence(P.zero);
    const int tid = threadIdx.x, lane = tid & 31;
    const int warp = __shfl_sync(0xffffffffu, tid >> 5, 0);
    const int cta = __shfl_sync(0xffffffffu, blockIdx.x + P.cta0, 0), pair = cta >> 1, rank = cta & 1;
    if (tid == 0) {
        if (sb & 1023) spin_fault();
        for (int i = 0; i < NSTAGE; i++) { mbar_init(sb + B_FULL + i * 8, 1); mbar_init(sb + B_EMPTY + i * 8, 16); }
        mbar_init(sb + B_RESUME, 2);
        mbar_init(sb + B_KVFULL, 1);
        mbar_init(sb + B_GO, 3); mbar_init(sb + B_RED, 8); mbar_init(sb + B_P1, 1); mbar_init(sb + B_EPOCH, 1); mbar_init(sb + B_PERS, 8); mbar_init(sb + B_INIT, 8); mbar_init(sb + B_INIT2, 8);
        mbar_init(sb + B_READY, 8);
        for (int i = 0; i < 2; i++) { mbar_init(sb + B_SFULL + i * 8, 4); mbar_init(sb + B_SFREE + i * 8, 1); }
        mbar_init(sb + B_RELM, cta % 3 ? 1 : 2); mbar_init(sb + B_X, 9);
        mbar_init(sb + B_DONE, 2);
        mbar_expect(sb + B_X, 4096);
        sts64(sb + S_EV, 0, 0);
        asm volatile("fence.mbarrier_init.release.cluster;" ::: "memory");
    }
    __syncthreads();
    cluster_sync();
    if (warp >= 8) {
        asm volatile("setmaxnreg.dec.sync.aligned.u32 24;");
        if (warp == 8) {
            producer(P, sb, cta, get_epoch(sb));
            cluster_sync();
        } else if (warp == 9) {
            const uint32_t epoch = __shfl_sync(0xffffffffu, ld_acquire(&g_cnt(C_EPOCH)), 0);
            if (lane == 0) { sts32(sb + S_EPOCH, epoch); mbar_arrive(sb + B_EPOCH); red_release(&g_cnt(C_READ)); }
            __syncwarp();
            if (pair < NCHAIN) pacer(P, sb, cta, lane, epoch);
            if (cta == 0 && lane == 0) {
                for (int n = 0; (int32_t)(ld_acquire(&g_cnt(C_READ)) - (epoch + 1) * (NPAIR * 2)) < 0; n++) if (n > SPIN_LIMIT) spin_fault();
                st_relaxed1(&g_cnt(C_EPOCH), epoch + 1);
            }
            __syncwarp();
            mbar_wait_bounded(sb + B_DONE, 0);
        } else {
            store_warp(P, sb, warp - 10, cta);
        }
    } else {
        asm volatile("setmaxnreg.inc.sync.aligned.u32 240;");
        Cons c;
        Pend d;
        if (pair < NCHAIN) {
            reset_state(P, c, d, sb, false);
            {
                const int item = ITEM(ITEM_OFF(pair));
                PROF_ITEM(0, item)
                float acc[128];
                mainloop<true>(acc, P, c, d, T_KV, 16);
                ISTAMP(4)
                epi_kv(acc, c, d, (item >> 5) & 7, item & 31);
            }
            ISTAMP(9)
            mbar_wait(sb + B_EMPTY + 3 * 8, 1);
            drain_both(c, d);
            ISTAMP(10)
            uint32_t wr[40][4];
            chain_fetch(P, sb, cta, warp, lane, wr);
            PROF_ITEM(1, T_CHAIN << 8)
            chain_bounds(sb, cta, warp, lane, wr);
            ISTAMP(11)
            if (warp < 4) chain_role<false>(P, sb, cta, warp, lane, wr);
            else chain_role<true>(P, sb, cta, warp, lane, wr);
            fence_async_smem();
            bar_sync(1, 256);
            const uint32_t t2 = fresh_tid();
            if (t2 < 2) mbar_arrive_cluster(mapa(sb + B_RESUME, cluster_rank() ^ t2));
        } else if (pair >= NPAIR - 2) {
            const int ch = (pair - (NPAIR - 2)) * 512 + rank * 256 + tid;
            g_coef[ch] = ssm_coef(__bfloat162float(P.Lre[ch]), __bfloat162float(P.Lim[ch]), __bfloat162float(P.logdt[ch]));
            bar_sync(1, 256);
            if (tid == 0) red_release(&g_cnt(C_COEF));
        }
        reset_state(P, c, d, sb, true);
        int it = ITEM_OFF(c.pair) + (c.pair < NCHAIN ? 2 : 0);
        const int end = ITEM_OFF(c.pair + 1);
        for (;; it++) {
            const bool last = it == end;
            const int item = ITEM(it), type = (item >> 8) & 7, mb = (item >> 5) & 7, nb = item & 31;
            const bool idle = (item >> 12) == 3 - 2 * c.wg;
            if (d.kind != PEND_NONE && (last || idle || (ITEM(it - 1) & URGENT) || !bar_and(5 + c.wg, mbar_try(sb + B_FULL + c.p.stage * 8, c.p.phase)))) {
#pragma unroll 1
                while (d.kind != PEND_NONE) drain(P, c, d);
            }
            if (last) break;
            const int nk = type == T_OP ? 64 : type == T_A2 ? 32 : 16;
            PROF_ITEM(it - ITEM_OFF(c.pair), item)
            if (idle) {
#pragma unroll 1
                for (int kt = nk + (type == T_A2 ? 2 : type == T_QA ? 4 : 0); kt > 0; kt--) { wait_full(c); release(c, c.p.stage); pipe_next(c.p); }
                continue;
            }
            float acc[128];
            mainloop(acc, P, c, d, type, nk);
            if (type == T_KV) epi_kv(acc, c, d, mb, nb);
            else if (type == T_QA) epi_qa(acc, c, d, mb, nb);
            else if (type == T_OP) epi_op(acc, c, d, mb, nb);
            else if (type == T_A1) epi_a1(acc, P, c, d, mb, nb);
            else epi_a2(acc, P, c, mb, nb * 256);
        }
        staging_wait(c);
        staging_post(c, PEND_NONE, 0, 0, 0);
        if (c.wq == 0 && c.lane == 0) mbar_arrive(sb + B_DONE);
        cluster_sync();
    }
}

typedef CUresult (*EncodeFn)(CUtensorMap*, CUtensorMapDataType, cuuint32_t, void*, const cuuint64_t*, const cuuint64_t*, const cuuint32_t*, const cuuint32_t*,
                             CUtensorMapInterleave, CUtensorMapSwizzle, CUtensorMapL2promotion, CUtensorMapFloatOOBfill);
void encode(EncodeFn fn, CUtensorMap* m, const void* base, int rank, const uint64_t* dims, const uint64_t* strides, const uint32_t* box, CUtensorMapSwizzle swz = CU_TENSOR_MAP_SWIZZLE_128B) {
    cuuint64_t d[5], s[5]; cuuint32_t b[5], e[5];
    for (int i = 0; i < rank; i++) { d[i] = dims[i]; b[i] = box[i]; e[i] = 1; if (i) s[i - 1] = strides[i - 1]; }
    fn(m, CU_TENSOR_MAP_DATA_TYPE_BFLOAT16, rank, (void*)base, d, s, b, e, CU_TENSOR_MAP_INTERLEAVE_NONE, swz,
       CU_TENSOR_MAP_L2_PROMOTION_L2_256B, CU_TENSOR_MAP_FLOAT_OOB_FILL_NONE);
}
void map_kmajor(EncodeFn fn, CUtensorMap* m, const void* base, uint64_t rows, uint64_t cols, uint32_t box_rows) {
    const uint64_t d[4] = {cols, 1, 1, rows}, s[3] = {cols * 2, cols * 2, cols * 2}; const uint32_t b[4] = {64, 1, 1, box_rows};
    encode(fn, m, base, 4, d, s, b);
}
void map_mnmajor(EncodeFn fn, CUtensorMap* m, const void* base, uint64_t krows, uint64_t cols, uint32_t groups = 2) {
    const uint64_t d[4] = {64, krows, 1, cols / 64}, s[3] = {cols * 2, 128, 128}; const uint32_t b[4] = {64, 64, 1, groups};
    encode(fn, m, base, 4, d, s, b);
}
void map_store(EncodeFn fn, CUtensorMap* m, const void* base, uint64_t rows, uint64_t cols) {
    const uint64_t d[2] = {cols, rows}, s[1] = {cols * 2}; const uint32_t b[2] = {64, 32};
    encode(fn, m, base, 2, d, s, b);
}

}

extern "C" void kernel_launch(void* const* d_in, const int* in_sizes, int n_in, void* d_out, int out_size) {
    static Params P;
    static EncodeFn fn = nullptr;
    if (!fn) {
        cudaDriverEntryPointQueryResult q;
        cudaGetDriverEntryPoint("cuTensorMapEncodeTiled", (void**)&fn, cudaEnableDefault, &q);
        cudaFuncSetAttribute(fused_kernel, cudaFuncAttributeMaxDynamicSharedMemorySize, S_TOTAL);
    }
    const bf16* in[15];
    for (int i = 0; i < 15; i++) in[i] = (const bf16*)d_in[i];
    void *kvo, *ht;
    cudaGetSymbolAddress(&kvo, g_kvo);
    cudaGetSymbolAddress(&ht, g_ht);
    map_kmajor(fn, &P.tm[M_BX], in[9], 2048, 1024, 128);
    map_mnmajor(fn, &P.tm[M_WQ], in[11], 1024, 4096);
    map_mnmajor(fn, &P.tm[M_WK], in[12], 1024, 4096);
    map_mnmajor(fn, &P.tm[M_WV], in[13], 1024, 4096);
    map_mnmajor(fn, &P.tm[M_WO], in[14], 4096, 1024);
    map_kmajor(fn, &P.tm[M_OA], kvo, 3 * 2048, 4096, 128);
    P.swap_ri = in[4] < in[3];
    {
        const bf16* lo = P.swap_ri ? in[4] : in[3];
        const uint64_t diff = (uint64_t)((const char*)(P.swap_ri ? in[3] : in[4]) - (const char*)lo);
        const uint64_t d[4] = {1024, 8, 2, 128}, s[3] = {2048, diff, 16384}; const uint32_t b[4] = {64, 8, 2, 8}, bh[4] = {64, 8, 2, 4};
        encode(fn, &P.tm[M_AB], lo, 4, d, s, b);
        encode(fn, &P.tm[M_AB + M_HALF], lo, 4, d, s, bh);
    }
    {
        const uint64_t d[4] = {1024, 2, 4, 1024}, s[3] = {2048, 64 * 2048, 4096}; const uint32_t b[4] = {64, 2, 4, 16};
        encode(fn, &P.tm[M_AX], in[0], 4, d, s, b);
    }
    map_mnmajor(fn, &P.tm[M_HT], ht, 2048, 2048);
    map_kmajor(fn, &P.tm[M_CRE], in[5], 1024, 1024, 128);
    map_kmajor(fn, &P.tm[M_CIM], in[6], 1024, 1024, 128);
    map_store(fn, &P.tm[M_KVO], kvo, 3 * 2048, 4096);
    map_store(fn, &P.tm[M_HTS], ht, 2048, 2048);
    map_kmajor(fn, &P.tm[M_BX + M_HALF], in[9], 2048, 1024, 64);
    map_kmajor(fn, &P.tm[M_OA + M_HALF], kvo, 3 * 2048, 4096, 64);
    map_mnmajor(fn, &P.tm[M_HT + M_HALF], ht, 2048, 2048, 1);
    for (int i = 0; i < 3; i++) {
        const uint64_t d[3] = {64, 1024, 64}, s[2] = {8192, 128}; const uint32_t b[3] = {64, 16, 2};
        encode(fn, &P.tm[M_C1 + i], in[11 + i], 3, d, s, b);
    }
    {
        const uint64_t d[2] = {1024, 4096}, s[1] = {2048}; const uint32_t b[2] = {32, 32};
        encode(fn, &P.tm[M_CO], in[14], 2, d, s, b, CU_TENSOR_MAP_SWIZZLE_64B);
    }
    {
        const uint64_t d[3] = {64, 3 * 2048, 64}, s[2] = {8192, 128}; const uint32_t b[3] = {64, 32, 2};
        encode(fn, &P.tm[M_SEG], kvo, 3, d, s, b);
    }
    void* xs;
    cudaGetSymbolAddress(&xs, g_x);
    P.xb = (uint8_t*)(((uintptr_t)xs + (2u << 20) - 1) & ~(uintptr_t)((2u << 20) - 1));
    P.Wq = in[11]; P.Wk = in[12]; P.Wv = in[13]; P.Wo = in[14]; P.mem0 = in[10]; P.Bx = in[9];
    P.Ax = in[0]; P.Lre = in[1]; P.Lim = in[2]; P.logdt = in[7]; P.Dskip = in[8];
    P.out = (float*)d_out;
    int pv[10] = {1300, 0, 110, 0, 330, 0, 32, 32, 0, 0};
    int ef = 779;
    for (int i = 0; i < 12; i++) P.pol[i] = (ef >> i & 1) ? 0x12F0000000000000ull : 0x1000000000000000ull;
    P.dly = pv[0]; P.mrg = pv[2];
    P.rd = pv[4]; P.guard = pv[5]; P.clampv = pv[6]; P.clamp0 = pv[7]; P.kvd = pv[9]; P.xd = pv[8];
    cudaLaunchConfig_t cfg = {};
    cudaLaunchAttribute at[2];
    cfg.blockDim = dim3(384); cfg.dynamicSmemBytes = S_TOTAL; cfg.stream = cudaStreamPerThread; cfg.attrs = at;
    at[0].id = cudaLaunchAttributeClusterDimension;
    at[0].val.clusterDim.y = at[0].val.clusterDim.z = 1;
    at[1].id = cudaLaunchAttributeProgrammaticStreamSerialization;
    at[1].val.programmaticStreamSerializationAllowed = 1;
    for (int i = 0; i < 2; i++) {
        P.cta0 = i ? 2 * NCHAIN : 0;
        cfg.gridDim = dim3(i ? 2 * (NPAIR - NCHAIN) : 2 * NCHAIN);
        at[0].val.clusterDim.x = i ? 2 : 6;
        cfg.numAttrs = 1 + i;
        cudaLaunchKernelEx(&cfg, fused_kernel, P);
    }
}
```

```cpp
#include <cuda_runtime.h>
#include <cuda_bf16.h>
#include <cuda.h>
#include <stdint.h>
#include <string.h>

typedef __nv_bfloat16 bf16;

namespace {

constexpr int SPIN_LIMIT = 1 << 22;
#define POLLNS 100
constexpr int NPAIR = 66;
constexpr int NCHAIN = 48;
enum { T_KV = 0, T_QA = 1, T_OP = 2, T_A1 = 3, T_A2 = 4, T_CHAIN = 5 };
constexpr int URGENT = 2048;
constexpr int HALF = 4096;
enum { M_BX = 1, M_OA, M_AB, M_HT, M_HALF = 4, M_WK = 9, M_WV, M_WQ, M_WO, M_AX, M_CRE, M_CIM, M_KVO, M_HTS, M_C1, M_CO = M_C1 + 3, M_SEG, M_COUNT };
enum { C_KV = 0, C_O = 8, C_HT = 16, C_READ = 24, C_EPOCH = 25, C_COEF = 26, C_XMAX = 27, C_XCNT = 28, C_FLAG = 32 };

struct Params {
    CUtensorMap tm[M_COUNT];
    const bf16 *Wq, *Wk, *Wv, *Wo, *mem0, *Bx, *Ax, *Lre, *Lim, *logdt, *Dskip;
    float* out;
    uint8_t* xb;
    int swap_ri, zero;
    int dly, mrg, rd, guard, clampv, clamp0, kvd, xd;
    uint64_t pol[12];
    uint16_t cta0;
};

__constant__ uint16_t c_off[67] = {0, 4, 8, 12, 17, 21, 25, 29, 33, 38, 43, 48, 53, 58, 63, 68, 72, 76, 81, 86, 90, 94, 98, 102, 106, 110, 114, 118, 122, 127, 131, 135, 139, 144, 149, 153, 157, 162, 166, 170, 174, 179, 183, 188, 192, 196, 201, 206, 211, 231, 251, 270, 289, 308, 328, 347, 365, 385, 405, 425, 445, 465, 485, 505, 524, 543, 562};
__constant__ uint16_t c_items[700] = {
    0, 1280, 2473, 642, 16, 1280, 2474, 514, 32, 1280, 2476, 611, 1, 1280, 486, 2823, 1089, 17, 1280, 495, 675, 33, 1280, 417,
    544, 2, 1280, 773, 578, 18, 1280, 870, 739, 34, 1280, 806, 807, 1187, 3, 1280, 2504, 2979, 12962, 19, 1280, 2503, 2945, 1121,
    35, 1280, 2529, 3043, 4770, 4, 1280, 2502, 770, 1056, 20, 1280, 2539, 932, 1153, 36, 1280, 2509, 2946, 1027, 5, 1280, 482, 547,
    21, 1280, 2475, 512, 37, 1280, 2471, 2919, 1088, 6, 1280, 2510, 834, 1123, 22, 1280, 489, 609, 38, 1280, 2469, 705, 7, 1280,
    2820, 515, 23, 1280, 833, 737, 39, 1280, 774, 704, 8, 1280, 483, 576, 24, 1280, 488, 706, 40, 1280, 453, 738, 9, 1280,
    449, 608, 25, 1280, 2506, 963, 1025, 41, 1280, 492, 641, 10, 1280, 451, 513, 26, 1280, 416, 545, 42, 1280, 2532, 866, 1184,
    11, 1280, 459, 802, 1250, 27, 1280, 2538, 577, 43, 1280, 448, 643, 12, 1280, 2508, 2948, 4832, 28, 1280, 2498, 672, 44, 1280,
    431, 707, 13, 1280, 2511, 640, 29, 1280, 2466, 934, 1248, 45, 1280, 424, 546, 14, 1280, 494, 868, 1154, 30, 1280, 430, 610,
    46, 1280, 2528, 579, 15, 1280, 838, 839, 1217, 31, 1280, 804, 2951, 1026, 47, 1280, 836, 2977, 1122, 48, 66, 84, 102, 256,
    124, 142, 160, 175, 191, 207, 224, 239, 230, 328, 386, 331, 928, 3010, 1120, 49, 67, 85, 103, 257, 125, 143, 161, 176,
    192, 208, 225, 240, 241, 399, 354, 335, 835, 998, 1090, 50, 68, 86, 104, 258, 126, 144, 162, 177, 193, 209, 226, 2350,
    388, 2412, 2819, 803, 2983, 1058, 51, 69, 87, 105, 259, 127, 145, 163, 178, 194, 210, 2438, 2446, 385, 355, 391, 899, 997,
    1216, 52, 70, 88, 106, 260, 128, 146, 164, 179, 195, 211, 329, 298, 2817, 395, 367, 2913, 3041, 1024, 53, 71, 89, 107,
    261, 129, 147, 165, 180, 196, 212, 229, 244, 245, 330, 297, 397, 837, 3008, 1185, 54, 72, 90, 108, 262, 130, 148, 166,
    181, 197, 213, 321, 394, 396, 326, 2370, 902, 2981, 1155, 55, 73, 91, 109, 263, 131, 149, 167, 182, 198, 214, 231, 327,
    362, 387, 299, 487, 673, 56, 74, 92, 110, 264, 132, 150, 168, 183, 199, 215, 232, 247, 227, 323, 358, 366, 800, 3047,
    1251, 57, 75, 93, 111, 265, 133, 151, 169, 184, 200, 216, 233, 248, 254, 359, 334, 360, 896, 965, 1152, 58, 76, 94,
    112, 266, 134, 152, 170, 185, 201, 217, 234, 249, 243, 352, 332, 384, 901, 992, 1218, 59, 77, 95, 113, 267, 135, 153,
    171, 186, 202, 218, 235, 250, 255, 420, 356, 320, 832, 3009, 1091, 60, 78, 96, 114, 268, 136, 154, 172, 187, 203, 219,
    236, 251, 246, 419, 452, 361, 805, 3014, 1186, 61, 79, 97, 115, 269, 137, 155, 173, 188, 204, 220, 237, 252, 242, 392,
    457, 485, 864, 3015, 1057, 62, 80, 98, 116, 270, 138, 156, 174, 189, 205, 221, 238, 253, 228, 2349, 333, 295, 867, 3044,
    1059, 63, 81, 99, 117, 271, 139, 157, 288, 190, 292, 293, 296, 300, 429, 303, 493, 869, 3042, 1249, 64, 82, 100, 118,
    120, 122, 140, 158, 289, 206, 222, 294, 393, 422, 2413, 363, 801, 930, 1219, 65, 83, 101, 119, 121, 123, 141, 159, 290,
    291, 223, 389, 353, 2405, 324, 325, 768, 3012, 13024,
};
#define ITEM_OFF(p) c_off[p]
#define ITEM(i) c_items[i]

__device__ __align__(1024) bf16 g_kvo[3 * 2048 * 4096];
__device__ __align__(1024) bf16 g_ht[2048 * 2048];
__device__ __align__(1024) uint8_t g_x[4 << 20];
__device__ __align__(1024) uint32_t g_km[64 * 32 * 512];
__device__ __align__(1024) uint32_t g_vmt[64 * 32 * 512];
__device__ __align__(1024) float2 g_agg[8 * 1024];
__device__ __align__(1024) float4 g_coef[1024];
__device__ __align__(1024) uint32_t g_cntl[128 * 32];
#define g_cnt(i) g_cntl[(i) * 32]
__device__ __align__(1024) uint32_t g_hint[96 * 32];
#define PROF(i)
#define PROFDUMP()
#define PROFP(i)
constexpr int XG_SIDE = 65536, XG_T = 98304;
__device__ __forceinline__ uint32_t xg_buf(int b) { return (b & 1) * 128 + (b & 2) * 256 + (b & 4) * 32768; }
__device__ __forceinline__ uint32_t xg_lane(uint32_t lane) { return (lane >> 4) * 1024 + (lane & 8) * 32 + (lane & 7) * 16; }
__device__ __forceinline__ uint32_t xg_side(int b) { return XG_SIDE + (b >> 1) * 1024 + (b & 1) * 256; }

constexpr int STAGE = 49152, NSTAGE = 4;
constexpr int S_STG = NSTAGE * STAGE;
constexpr int S_BAR = S_STG + 32768;
constexpr int B_FULL = S_BAR, B_EMPTY = S_BAR + 32, B_RESUME = S_BAR + 64, B_KVFULL = S_BAR + 72, B_GO = S_BAR + 88, B_X = S_BAR + 96, B_PERS = S_BAR + 104,
              B_INIT = S_BAR + 112, B_RELM = S_BAR + 120, B_READY = S_BAR + 136, B_SFULL = S_BAR + 144, B_SFREE = S_BAR + 160, S_DESC = S_BAR + 176, B_RED = S_BAR + 216;
constexpr int S_EV = S_BAR + 80, S_EO = S_BAR + 84, B_INIT2 = S_BAR + 128, S_SC = S_BAR + 208, S_ISC = S_EV;
constexpr int S_XV = S_BAR + 256, S_LOG = S_XV + 2048;
constexpr int S_TOTAL = S_LOG + 768;
#define NRA 5
#define NRB 3
constexpr int S_W1 = 0;
constexpr int S_W2 = 4 * 4096 * (16 - NRA - NRB);
constexpr int S_KV = 188416;
constexpr int S_P1 = S_KV + 16384;
constexpr int S_X = S_P1 + 16384;
constexpr int S_SX = S_P1, S_OX = S_P1 + 2048;
constexpr int S_EM = S_X + 4096, S_TO = S_EM + 32, B_DONE = S_BAR + 224, B_P1 = S_BAR + 232, B_EPOCH = S_BAR + 240, S_EPOCH = S_BAR + 248;
static_assert(S_TO + 32 <= S_BAR && S_KV % 1024 == 0 && S_TOTAL <= 232448, "chain smem layout");

template <int V> struct IC { static constexpr int value = V; };
template <int B, int E, typename F> __device__ __forceinline__ void static_for(F&& f) { if constexpr (B < E) { f(IC<B>{}); static_for<B + 1, E>(f); } }
__device__ __forceinline__ uint32_t cluster_rank() { uint32_t r; asm volatile("mov.u32 %0, %%cluster_ctarank;" : "=r"(r)); return r; }
__device__ __forceinline__ void spin_fault() { asm volatile("st.global.u32 [%0], 0;" ::"l"(0ull) : "memory"); }
__device__ __forceinline__ uint32_t smem_u32(const void* p) { return (uint32_t)__cvta_generic_to_shared(p); }
__device__ __forceinline__ uint32_t opq(uint32_t x, int lane) { return __shfl_sync(0xffffffffu, x, lane); }
__device__ __forceinline__ uint32_t mapa(uint32_t a, uint32_t r) { uint32_t d; asm volatile("mapa.shared::cluster.u32 %0, %1, %2;" : "=r"(d) : "r"(a), "r"(r)); return d; }
__device__ __forceinline__ void mma16816(float* d, uint32_t a0, uint32_t a1, uint32_t a2, uint32_t a3, uint32_t b0, uint32_t b1) {
    asm("mma.sync.aligned.m16n8k16.row.col.f32.bf16.bf16.f32 {%0,%1,%2,%3}, {%4,%5,%6,%7}, {%8,%9}, {%0,%1,%2,%3};"
        : "+f"(d[0]), "+f"(d[1]), "+f"(d[2]), "+f"(d[3]) : "r"(a0), "r"(a1), "r"(a2), "r"(a3), "r"(b0), "r"(b1));
}
__device__ __forceinline__ void mma1688(float* d, uint32_t a0, uint32_t a1, uint32_t b0) {
    asm("mma.sync.aligned.m16n8k8.row.col.f32.bf16.bf16.f32 {%0,%1,%2,%3}, {%4,%5}, {%6}, {%0,%1,%2,%3};"
        : "+f"(d[0]), "+f"(d[1]), "+f"(d[2]), "+f"(d[3]) : "r"(a0), "r"(a1), "r"(b0));
}
__device__ __forceinline__ void ldsm4(uint32_t* r, uint32_t a) {
    asm volatile("ldmatrix.sync.aligned.m8n8.x4.shared.b16 {%0,%1,%2,%3}, [%4];" : "=r"(r[0]), "=r"(r[1]), "=r"(r[2]), "=r"(r[3]) : "r"(a));
}
__device__ __forceinline__ void ldsm4t(uint32_t* r, uint32_t a) {
    asm volatile("ldmatrix.sync.aligned.m8n8.x4.trans.shared.b16 {%0,%1,%2,%3}, [%4];" : "=r"(r[0]), "=r"(r[1]), "=r"(r[2]), "=r"(r[3]) : "r"(a));
}
__device__ __forceinline__ void stsm4(uint32_t a, uint32_t r0, uint32_t r1, uint32_t r2, uint32_t r3) {
    asm volatile("stmatrix.sync.aligned.m8n8.x4.shared.b16 [%0], {%1,%2,%3,%4};" ::"r"(a), "r"(r0), "r"(r1), "r"(r2), "r"(r3) : "memory");
}
__device__ __forceinline__ void stsm4t(uint32_t a, uint32_t r0, uint32_t r1, uint32_t r2, uint32_t r3) {
    asm volatile("stmatrix.sync.aligned.m8n8.x4.trans.shared.b16 [%0], {%1,%2,%3,%4};" ::"r"(a), "r"(r0), "r"(r1), "r"(r2), "r"(r3) : "memory");
}
__device__ __forceinline__ uint32_t movm(uint32_t a) { uint32_t d; asm volatile("movmatrix.sync.aligned.m8n8.trans.b16 %0, %1;" : "=r"(d) : "r"(a)); return d; }
__device__ __forceinline__ uint32_t pack2(float lo, float hi) { uint32_t d; asm("cvt.rn.bf16x2.f32 %0, %1, %2;" : "=r"(d) : "f"(hi), "f"(lo)); return d; }
__device__ __forceinline__ uint32_t prmt(uint32_t a, uint32_t b, uint32_t s) { uint32_t d; asm("prmt.b32 %0, %1, %2, %3;" : "=r"(d) : "r"(a), "r"(b), "r"(s)); return d; }
__device__ __forceinline__ uint32_t pack2h(float lo, float hi) { uint32_t d; asm("cvt.rn.f16x2.f32 %0, %1, %2;" : "=r"(d) : "f"(hi), "f"(lo)); return d; }
__device__ __forceinline__ uint32_t h2bf(uint32_t a, uint32_t b) {
    uint32_t d;
    asm("{\n.reg .b16 l, h, u;\n.reg .f32 x, y;\nmov.b32 {l, u}, %1;\ncvt.f32.f16 x, l;\nmov.b32 {u, h}, %2;\ncvt.f32.f16 y, h;\ncvt.rn.bf16x2.f32 %0, y, x;\n}" : "=r"(d) : "r"(a), "r"(b));
    return d;
}
__device__ __forceinline__ void cvt_block(uint32_t* u, uint32_t& x, uint32_t sel) {
    const uint32_t a = prmt(u[0], u[0], sel), b = prmt(u[1], u[1], sel), c = prmt(u[2], u[2], sel), d = prmt(u[3], x, sel);
    x ^= u[3] ^ d;
    u[0] = h2bf(a, a); u[1] = h2bf(b, b); u[2] = h2bf(c, c); u[3] = h2bf(d, d);
}
__device__ __forceinline__ uint32_t amax(uint32_t a, uint32_t b) { uint32_t d; asm("max.xorsign.abs.bf16x2 %0, %1, %2;" : "=r"(d) : "r"(a), "r"(b)); return d; }
__device__ __forceinline__ uint32_t amax4(uint32_t m, const uint32_t* v) { return amax(amax(m, amax(v[0], v[1])), amax(v[2], v[3])); }
__device__ __forceinline__ uint32_t warp_exp(uint32_t m) { return __reduce_max_sync(0xffffffffu, max(m & 0x7f80u, (m >> 16) & 0x7f80u)) >> 7; }
__device__ __forceinline__ void red_max_shared(uint32_t a, uint32_t x) { asm volatile("red.shared.max.u32 [%0], %1;" ::"r"(a), "r"(x) : "memory"); }
__device__ __forceinline__ uint32_t mul_bf2(uint32_t a, uint32_t b) { uint32_t d; asm("mul.rn.bf16x2 %0, %1, %2;" : "=r"(d) : "r"(a), "r"(b)); return d; }
__device__ __forceinline__ float bf_lo(uint32_t u) { return __uint_as_float(u << 16); }
__device__ __forceinline__ float bf_hi(uint32_t u) { return __uint_as_float(u & 0xffff0000u); }
__device__ __forceinline__ float ex2(float x) { float y; asm("ex2.approx.ftz.f32 %0, %1;" : "=f"(y) : "f"(x)); return y; }
__device__ __forceinline__ float rcp(float x) { float y; asm("rcp.approx.ftz.f32 %0, %1;" : "=f"(y) : "f"(x)); return y; }
__device__ __forceinline__ void st_relaxed4(const void* p, uint32_t a, uint32_t b, uint32_t c, uint32_t d) {
    asm volatile("{\n.reg .b128 t;\nmov.b128 t, {%1,%2,%3,%4};\nst.relaxed.gpu.global.b128 [%0], t;\n}" ::"l"(p), "r"(a), "r"(b), "r"(c), "r"(d) : "memory");
}
__device__ __forceinline__ void st_relaxed2(const void* p, uint32_t a, uint32_t b) {
    asm volatile("{\n.reg .b64 t;\nmov.b64 t, {%1,%2};\nst.relaxed.gpu.global.b64 [%0], t;\n}" ::"l"(p), "r"(a), "r"(b) : "memory");
}
__device__ __forceinline__ void ld_relaxed2_if(uint32_t& a, uint32_t& b, const void* p, bool on) {
    asm volatile("{\n.reg .pred P;\n.reg .b64 t;\nsetp.ne.u32 P, %3, 0;\nmov.b64 t, {%0,%1};\n@P ld.relaxed.gpu.global.b64 t, [%2];\nmov.b64 {%0,%1}, t;\n}" : "+r"(a), "+r"(b) : "l"(p), "r"((uint32_t)on) : "memory");
}
__device__ __forceinline__ void ld_relaxed4(uint32_t* v, const void* p) {
    asm volatile("ld.relaxed.gpu.global.L1::no_allocate.v4.b32 {%0,%1,%2,%3}, [%4];" : "=r"(v[0]), "=r"(v[1]), "=r"(v[2]), "=r"(v[3]) : "l"(p) : "memory");
}
__device__ __forceinline__ void ld_relaxed1n(uint32_t& v, const void* p) { asm volatile("ld.relaxed.gpu.global.L1::no_allocate.b32 %0, [%1];" : "=r"(v) : "l"(p) : "memory"); }
__device__ __forceinline__ void red_add4(const void* p, uint32_t a, uint32_t b, uint32_t c, uint32_t d) {
    asm volatile("red.relaxed.gpu.global.add.noftz.v4.f16x2 [%0], {%1,%2,%3,%4};" ::"l"(p), "r"(a), "r"(b), "r"(c), "r"(d) : "memory");
}
__device__ __forceinline__ void red_add1(const void* p, uint32_t a) { asm volatile("red.relaxed.gpu.global.add.noftz.f16x2 [%0], %1;" ::"l"(p), "r"(a) : "memory"); }
__device__ __forceinline__ void ld_relaxed2(uint32_t* v, const void* p) {
    asm volatile("{\n.reg .b64 t;\nld.relaxed.gpu.global.L1::no_allocate.b64 t, [%2];\nmov.b64 {%0,%1}, t;\n}" : "=r"(v[0]), "=r"(v[1]) : "l"(p) : "memory");
}
__device__ __forceinline__ uint32_t ld_relaxed1(const void* p) { uint32_t v; asm volatile("ld.relaxed.gpu.global.u32 %0, [%1];" : "=r"(v) : "l"(p) : "memory"); return v; }
__device__ __forceinline__ void st_relaxed1(const void* p, uint32_t v) { asm volatile("st.relaxed.gpu.global.u32 [%0], %1;" ::"l"(p), "r"(v) : "memory"); }
__device__ __forceinline__ uint32_t ld_acquire(const void* p) { uint32_t v; asm volatile("ld.acquire.gpu.global.u32 %0, [%1];" : "=r"(v) : "l"(p) : "memory"); return v; }
__device__ __forceinline__ void red_relaxed(void* p) { asm volatile("red.relaxed.gpu.global.add.u32 [%0], 1;" ::"l"(p) : "memory"); }
__device__ __forceinline__ void red_release(void* p) { asm volatile("red.release.gpu.global.add.u32 [%0], 1;" ::"l"(p) : "memory"); }
__device__ __forceinline__ void st_stream2(float* p, float a, float b) { asm volatile("st.global.cs.v2.f32 [%0], {%1, %2};" ::"l"(p), "f"(a), "f"(b) : "memory"); }
__device__ __forceinline__ void fence_async() { asm volatile("fence.proxy.async.global;" ::: "memory"); }
__device__ __forceinline__ void fence_async_smem() { asm volatile("fence.proxy.async.shared::cta;" ::: "memory"); }
__device__ __forceinline__ void wait_count(const uint32_t* p, uint32_t target) {
    while ((int32_t)(ld_acquire(p) - target) < 0) __nanosleep(POLLNS);
}
__device__ __forceinline__ void bar_sync(int id, int n) { asm volatile("bar.sync %0, %1;" ::"r"(id), "r"(n) : "memory"); }
__device__ __forceinline__ bool bar_and(int id, bool v) {
    uint32_t r;
    asm volatile("{\n.reg .pred P, Q;\nsetp.ne.u32 Q, %2, 0;\nbar.red.and.pred P, %1, 128, Q;\nselp.u32 %0, 1, 0, P;\n}" : "=r"(r) : "r"(id), "r"((uint32_t)v) : "memory");
    return r;
}
__device__ __forceinline__ void bar_arrive(int id, int n) { asm volatile("bar.arrive %0, %1;" ::"r"(id), "r"(n) : "memory"); }
__device__ __forceinline__ void lds128(uint32_t* v, uint32_t a) { asm volatile("ld.shared.v4.b32 {%0,%1,%2,%3}, [%4];" : "=r"(v[0]), "=r"(v[1]), "=r"(v[2]), "=r"(v[3]) : "r"(a) : "memory"); }
__device__ __forceinline__ uint32_t lds32(uint32_t a) { uint32_t v; asm volatile("ld.shared.b32 %0, [%1];" : "=r"(v) : "r"(a) : "memory"); return v; }
__device__ __forceinline__ void lds64(uint32_t* v, uint32_t a) { asm volatile("ld.shared.v2.b32 {%0,%1}, [%2];" : "=r"(v[0]), "=r"(v[1]) : "r"(a) : "memory"); }
__device__ __forceinline__ void lds64f(float* v, uint32_t a) { asm volatile("ld.shared.v2.f32 {%0,%1}, [%2];" : "=f"(v[0]), "=f"(v[1]) : "r"(a) : "memory"); }
__device__ __forceinline__ void sts128(uint32_t a, const uint32_t* v) { asm volatile("st.shared.v4.b32 [%0], {%1,%2,%3,%4};" ::"r"(a), "r"(v[0]), "r"(v[1]), "r"(v[2]), "r"(v[3]) : "memory"); }
__device__ __forceinline__ void sts64(uint32_t a, uint32_t x, uint32_t y) { asm volatile("st.shared.v2.b32 [%0], {%1,%2};" ::"r"(a), "r"(x), "r"(y) : "memory"); }
__device__ __forceinline__ void sts32(uint32_t a, uint32_t x) { asm volatile("st.shared.b32 [%0], %1;" ::"r"(a), "r"(x) : "memory"); }
__device__ __forceinline__ bool mbar_try(uint32_t b, uint32_t par) {
    uint32_t ok;
    asm volatile("{\n.reg .pred P;\nmbarrier.test_wait.parity.shared::cta.b64 P, [%1], %2;\nselp.u32 %0, 1, 0, P;\n}" : "=r"(ok) : "r"(b), "r"(par) : "memory");
    return ok;
}
__device__ __forceinline__ void mbar_wait(uint32_t b, uint32_t par) {
    asm volatile("{\n.reg .pred P;\nW: mbarrier.try_wait.parity.shared::cta.b64 P, [%0], %1;\n@!P bra W;\n}" ::"r"(b), "r"(par) : "memory");
}
__device__ __forceinline__ void mbar_wait_bounded(uint32_t b, uint32_t par) {
    asm volatile("{\n.reg .pred P, Q;\n.reg .u32 t, u;\nmov.u32 t, %%globaltimer_lo;\nW: mbarrier.try_wait.parity.shared::cta.b64 P, [%0], %1;\n"
                 "mov.u32 u, %%globaltimer_lo;\nsub.u32 u, u, t;\nsetp.gt.u32 Q, u, 2000000000;\n@Q st.global.u32 [%2], 0;\n@!P bra W;\n}" ::"r"(b), "r"(par), "l"(0ull) : "memory");
}
__device__ __forceinline__ void declare_fence(int zero) { asm volatile(".reg .pred PNEVER;\nsetp.ne.u32 PNEVER, %0, 0;" ::"r"(zero)); }
__device__ __forceinline__ void sched_fence() { asm volatile("{\n.reg .pred Q;\n.reg .u32 x;\n@!PNEVER bra D;\nF: ld.volatile.global.u32 x, [%0];\nsetp.ne.u32 Q, x, 0;\n@Q bra F;\nD:\n}" ::"l"(0ull) : "memory"); }
__device__ __forceinline__ void mbar_init(uint32_t b, uint32_t n) { asm volatile("mbarrier.init.shared::cta.b64 [%0], %1;" ::"r"(b), "r"(n) : "memory"); }
__device__ __forceinline__ void mbar_expect(uint32_t b, uint32_t bytes) { asm volatile("mbarrier.arrive.expect_tx.shared::cta.b64 _, [%0], %1;" ::"r"(b), "r"(bytes) : "memory"); }
__device__ __forceinline__ void mbar_arrive(uint32_t b) { asm volatile("mbarrier.arrive.shared::cta.b64 _, [%0];" ::"r"(b) : "memory"); }
__device__ __forceinline__ void mbar_arrive_cluster(uint32_t b) { asm volatile("mbarrier.arrive.shared::cluster.b64 _, [%0];" ::"r"(b) : "memory"); }
__device__ __forceinline__ void cluster_sync() { asm volatile("barrier.cluster.arrive.relaxed.aligned;\nbarrier.cluster.wait.aligned;" ::: "memory"); }
__device__ __forceinline__ uint32_t get_epoch(uint32_t sb) { mbar_wait(sb + B_EPOCH, 0); return __shfl_sync(0xffffffffu, lds32(sb + S_EPOCH), 0); }
__device__ __forceinline__ void tma2d(uint32_t dst, const CUtensorMap* m, int c0, int c1, uint32_t bar) {
    asm volatile("cp.async.bulk.tensor.2d.shared::cluster.global.mbarrier::complete_tx::bytes [%0], [%1, {%2, %3}], [%4];" ::"r"(dst), "l"(m), "r"(c0), "r"(c1), "r"(bar) : "memory");
}
__device__ __forceinline__ void tma3d(uint32_t dst, const CUtensorMap* m, int c0, int c1, int c2, uint32_t bar) {
    asm volatile("cp.async.bulk.tensor.3d.shared::cluster.global.mbarrier::complete_tx::bytes [%0], [%1, {%2, %3, %4}], [%5];" ::"r"(dst), "l"(m), "r"(c0), "r"(c1), "r"(c2), "r"(bar) : "memory");
}
__device__ __forceinline__ void l2_prefetch(const void* src, uint32_t bytes) { asm volatile("cp.async.bulk.prefetch.L2.global [%0], %1;" ::"l"(src), "r"(bytes) : "memory"); }
__device__ __forceinline__ void mbar_expect_e(uint32_t b, uint32_t bytes) {
    asm volatile("{\n.reg .pred E;\nelect.sync _|E, 0xffffffff;\n@E mbarrier.arrive.expect_tx.shared::cta.b64 _, [%0], %1;\n}" ::"r"(b), "r"(bytes) : "memory");
}
__device__ __forceinline__ void tma3d_mc_e(uint32_t dst, const CUtensorMap* m, int c0, int c1, int c2, uint32_t bar, uint16_t mask, uint64_t pol) {
    asm volatile("{\n.reg .pred E;\nelect.sync _|E, 0xffffffff;\n@E cp.async.bulk.tensor.3d.shared::cluster.global.mbarrier::complete_tx::bytes.multicast::cluster.L2::cache_hint [%0], [%1, {%2, %3, %4}], [%5], %6, %7;\n}" ::"r"(dst), "l"(m), "r"(c0), "r"(c1), "r"(c2), "r"(bar), "h"(mask), "l"(pol) : "memory");
}
__device__ __forceinline__ void tma4d_e(uint32_t dst, const CUtensorMap* m, int c0, int c1, int c3, uint32_t bar, uint64_t pol) {
    asm volatile("{\n.reg .pred E;\nelect.sync _|E, 0xffffffff;\n@E cp.async.bulk.tensor.4d.shared::cluster.global.mbarrier::complete_tx::bytes.L2::cache_hint [%0], [%1, {%2, %3, 0, %4}], [%5], %6;\n}" ::"r"(dst), "l"(m), "r"(c0), "r"(c1), "r"(c3), "r"(bar), "l"(pol) : "memory");
}
__device__ __forceinline__ void tma4d_mc_e(uint32_t dst, const CUtensorMap* m, int c0, int c1, int c3, uint32_t bar, uint16_t mask, uint64_t pol) {
    asm volatile("{\n.reg .pred E;\nelect.sync _|E, 0xffffffff;\n@E cp.async.bulk.tensor.4d.shared::cluster.global.mbarrier::complete_tx::bytes.multicast::cluster.L2::cache_hint [%0], [%1, {%2, %3, 0, %4}], [%5], %6, %7;\n}" ::"r"(dst), "l"(m), "r"(c0), "r"(c1), "r"(c3), "r"(bar), "h"(mask), "l"(pol) : "memory");
}
__device__ __forceinline__ void tma_prefetch4d_e(const CUtensorMap* m, int c0, int c3) {
    asm volatile("{\n.reg .pred E;\nelect.sync _|E, 0xffffffff;\n@E cp.async.bulk.prefetch.tensor.4d.L2.global [%0, {%1, 0, 0, %2}];\n}" ::"l"(m), "r"(c0), "r"(c3) : "memory");
}
__device__ __forceinline__ void tma_prefetch3d_e(const CUtensorMap* m, int c0, int c1, int c2) {
    asm volatile("{\n.reg .pred E;\nelect.sync _|E, 0xffffffff;\n@E cp.async.bulk.prefetch.tensor.3d.L2.global [%0, {%1, %2, %3}];\n}" ::"l"(m), "r"(c0), "r"(c1), "r"(c2) : "memory");
}
__device__ __forceinline__ void l2_prefetch_e(const void* src, uint32_t bytes) {
    asm volatile("{\n.reg .pred E;\nelect.sync _|E, 0xffffffff;\n@E cp.async.bulk.prefetch.L2.global [%0], %1;\n}" ::"l"(src), "r"(bytes) : "memory");
}
__device__ __forceinline__ void bulk_g2s_e(uint32_t dst, const void* src, uint32_t bytes, uint32_t bar) {
    asm volatile("{\n.reg .pred E;\nelect.sync _|E, 0xffffffff;\n@E cp.async.bulk.shared::cluster.global.mbarrier::complete_tx::bytes [%0], [%1], %2, [%3];\n}" ::"r"(dst), "l"(src), "r"(bytes), "r"(bar) : "memory");
}
__device__ __forceinline__ bool elect_one() {
    uint32_t r;
    asm volatile("{\n.reg .pred E;\nelect.sync _|E, 0xffffffff;\nselp.u32 %0, 1, 0, E;\n}" : "=r"(r));
    return r;
}
__device__ __forceinline__ void tma_store2d(const CUtensorMap* m, int c0, int c1, uint32_t src, uint64_t pol) {
    asm volatile("cp.async.bulk.tensor.2d.global.shared::cta.bulk_group.L2::cache_hint [%0, {%1, %2}], [%3], %4;" ::"l"(m), "r"(c0), "r"(c1), "r"(src), "l"(pol) : "memory");
}
__device__ __forceinline__ void bulk_commit() { asm volatile("cp.async.bulk.commit_group;" ::: "memory"); }
__device__ __forceinline__ void bulk_wait_read() { asm volatile("cp.async.bulk.wait_group.read 0;" ::: "memory"); }
__device__ __forceinline__ void bulk_wait_all() { asm volatile("cp.async.bulk.wait_group 0;" ::: "memory"); }
__device__ __forceinline__ uint64_t mkdesc(uint32_t addr, uint32_t lbo, uint32_t sbo, uint32_t swz) {
    return (uint64_t)((addr & 0x3FFFF) >> 4) | ((uint64_t)(lbo >> 4) << 16) | ((uint64_t)(sbo >> 4) << 32) | ((uint64_t)swz << 62);
}
__device__ __forceinline__ void wg_fence() { asm volatile("wgmma.fence.sync.aligned;" ::: "memory"); }
__device__ __forceinline__ void wg_commit() { asm volatile("wgmma.commit_group.sync.aligned;" ::: "memory"); }
template <int N> __device__ __forceinline__ void wg_wait() { asm volatile("wgmma.wait_group.sync.aligned %0;" ::"n"(N) : "memory"); }
template <typename T> __device__ __forceinline__ void pin_ptr(T*& p) { asm volatile("" : "+l"(p)); }
template <int N> __device__ __forceinline__ void pin(uint32_t* d) {
#pragma unroll
    for (int i = 0; i < N; i++) asm volatile("" : "+r"(d[i])::"memory");
}
template <int N> __device__ __forceinline__ void pin(float* d) {
#pragma unroll
    for (int i = 0; i < N; i++) asm volatile("" : "+f"(d[i])::"memory");
}

template <int TA, int TB>
__device__ __forceinline__ void wgmma_ss256(float* d, uint64_t da, uint64_t db) {
    asm volatile("wgmma.mma_async.sync.aligned.m64n256k16.f32.bf16.bf16 "
        "{%0, %1, %2, %3, %4, %5, %6, %7, %8, %9, %10, %11, %12, %13, %14, %15, %16, %17, %18, %19, %20, %21, %22, %23, %24, %25, %26, %27, %28, %29, %30, %31, %32, %33, %34, %35, %36, %37, %38, %39, %40, %41, %42, %43, %44, %45, %46, %47, %48, %49, %50, %51, %52, %53, %54, %55, %56, %57, %58, %59, %60, %61, %62, %63, %64, %65, %66, %67, %68, %69, %70, %71, %72, %73, %74, %75, %76, %77, %78, %79, %80, %81, %82, %83, %84, %85, %86, %87, %88, %89, %90, %91, %92, %93, %94, %95, %96, %97, %98, %99, %100, %101, %102, %103, %104, %105, %106, %107, %108, %109, %110, %111, %112, %113, %114, %115, %116, %117, %118, %119, %120, %121, %122, %123, %124, %125, %126, %127}, %128, %129, 1, 1, 1, %130, %131;"
        : "+f"(d[0]), "+f"(d[1]), "+f"(d[2]), "+f"(d[3]), "+f"(d[4]), "+f"(d[5]), "+f"(d[6]), "+f"(d[7]), "+f"(d[8]), "+f"(d[9]), "+f"(d[10]), "+f"(d[11]), "+f"(d[12]), "+f"(d[13]), "+f"(d[14]), "+f"(d[15]), "+f"(d[16]), "+f"(d[17]), "+f"(d[18]), "+f"(d[19]), "+f"(d[20]), "+f"(d[21]), "+f"(d[22]), "+f"(d[23]), "+f"(d[24]), "+f"(d[25]), "+f"(d[26]), "+f"(d[27]), "+f"(d[28]), "+f"(d[29]), "+f"(d[30]), "+f"(d[31]), "+f"(d[32]), "+f"(d[33]), "+f"(d[34]), "+f"(d[35]), "+f"(d[36]), "+f"(d[37]), "+f"(d[38]), "+f"(d[39]), "+f"(d[40]), "+f"(d[41]), "+f"(d[42]), "+f"(d[43]), "+f"(d[44]), "+f"(d[45]), "+f"(d[46]), "+f"(d[47]), "+f"(d[48]), "+f"(d[49]), "+f"(d[50]), "+f"(d[51]), "+f"(d[52]), "+f"(d[53]), "+f"(d[54]), "+f"(d[55]), "+f"(d[56]), "+f"(d[57]), "+f"(d[58]), "+f"(d[59]), "+f"(d[60]), "+f"(d[61]), "+f"(d[62]), "+f"(d[63]), "+f"(d[64]), "+f"(d[65]), "+f"(d[66]), "+f"(d[67]), "+f"(d[68]), "+f"(d[69]), "+f"(d[70]), "+f"(d[71]), "+f"(d[72]), "+f"(d[73]), "+f"(d[74]), "+f"(d[75]), "+f"(d[76]), "+f"(d[77]), "+f"(d[78]), "+f"(d[79]), "+f"(d[80]), "+f"(d[81]), "+f"(d[82]), "+f"(d[83]), "+f"(d[84]), "+f"(d[85]), "+f"(d[86]), "+f"(d[87]), "+f"(d[88]), "+f"(d[89]), "+f"(d[90]), "+f"(d[91]), "+f"(d[92]), "+f"(d[93]), "+f"(d[94]), "+f"(d[95]), "+f"(d[96]), "+f"(d[97]), "+f"(d[98]), "+f"(d[99]), "+f"(d[100]), "+f"(d[101]), "+f"(d[102]), "+f"(d[103]), "+f"(d[104]), "+f"(d[105]), "+f"(d[106]), "+f"(d[107]), "+f"(d[108]), "+f"(d[109]), "+f"(d[110]), "+f"(d[111]), "+f"(d[112]), "+f"(d[113]), "+f"(d[114]), "+f"(d[115]), "+f"(d[116]), "+f"(d[117]), "+f"(d[118]), "+f"(d[119]), "+f"(d[120]), "+f"(d[121]), "+f"(d[122]), "+f"(d[123]), "+f"(d[124]), "+f"(d[125]), "+f"(d[126]), "+f"(d[127])
        : "l"(da), "l"(db), "n"(TA), "n"(TB));
}
template <int TA, int TB>
__device__ __forceinline__ void wgmma_ss256_first(float* d, uint64_t da, uint64_t db) {
    asm volatile("wgmma.mma_async.sync.aligned.m64n256k16.f32.bf16.bf16 "
        "{%0, %1, %2, %3, %4, %5, %6, %7, %8, %9, %10, %11, %12, %13, %14, %15, %16, %17, %18, %19, %20, %21, %22, %23, %24, %25, %26, %27, %28, %29, %30, %31, %32, %33, %34, %35, %36, %37, %38, %39, %40, %41, %42, %43, %44, %45, %46, %47, %48, %49, %50, %51, %52, %53, %54, %55, %56, %57, %58, %59, %60, %61, %62, %63, %64, %65, %66, %67, %68, %69, %70, %71, %72, %73, %74, %75, %76, %77, %78, %79, %80, %81, %82, %83, %84, %85, %86, %87, %88, %89, %90, %91, %92, %93, %94, %95, %96, %97, %98, %99, %100, %101, %102, %103, %104, %105, %106, %107, %108, %109, %110, %111, %112, %113, %114, %115, %116, %117, %118, %119, %120, %121, %122, %123, %124, %125, %126, %127}, %128, %129, 0, 1, 1, %130, %131;"
        : "=f"(d[0]), "=f"(d[1]), "=f"(d[2]), "=f"(d[3]), "=f"(d[4]), "=f"(d[5]), "=f"(d[6]), "=f"(d[7]), "=f"(d[8]), "=f"(d[9]), "=f"(d[10]), "=f"(d[11]), "=f"(d[12]), "=f"(d[13]), "=f"(d[14]), "=f"(d[15]), "=f"(d[16]), "=f"(d[17]), "=f"(d[18]), "=f"(d[19]), "=f"(d[20]), "=f"(d[21]), "=f"(d[22]), "=f"(d[23]), "=f"(d[24]), "=f"(d[25]), "=f"(d[26]), "=f"(d[27]), "=f"(d[28]), "=f"(d[29]), "=f"(d[30]), "=f"(d[31]), "=f"(d[32]), "=f"(d[33]), "=f"(d[34]), "=f"(d[35]), "=f"(d[36]), "=f"(d[37]), "=f"(d[38]), "=f"(d[39]), "=f"(d[40]), "=f"(d[41]), "=f"(d[42]), "=f"(d[43]), "=f"(d[44]), "=f"(d[45]), "=f"(d[46]), "=f"(d[47]), "=f"(d[48]), "=f"(d[49]), "=f"(d[50]), "=f"(d[51]), "=f"(d[52]), "=f"(d[53]), "=f"(d[54]), "=f"(d[55]), "=f"(d[56]), "=f"(d[57]), "=f"(d[58]), "=f"(d[59]), "=f"(d[60]), "=f"(d[61]), "=f"(d[62]), "=f"(d[63]), "=f"(d[64]), "=f"(d[65]), "=f"(d[66]), "=f"(d[67]), "=f"(d[68]), "=f"(d[69]), "=f"(d[70]), "=f"(d[71]), "=f"(d[72]), "=f"(d[73]), "=f"(d[74]), "=f"(d[75]), "=f"(d[76]), "=f"(d[77]), "=f"(d[78]), "=f"(d[79]), "=f"(d[80]), "=f"(d[81]), "=f"(d[82]), "=f"(d[83]), "=f"(d[84]), "=f"(d[85]), "=f"(d[86]), "=f"(d[87]), "=f"(d[88]), "=f"(d[89]), "=f"(d[90]), "=f"(d[91]), "=f"(d[92]), "=f"(d[93]), "=f"(d[94]), "=f"(d[95]), "=f"(d[96]), "=f"(d[97]), "=f"(d[98]), "=f"(d[99]), "=f"(d[100]), "=f"(d[101]), "=f"(d[102]), "=f"(d[103]), "=f"(d[104]), "=f"(d[105]), "=f"(d[106]), "=f"(d[107]), "=f"(d[108]), "=f"(d[109]), "=f"(d[110]), "=f"(d[111]), "=f"(d[112]), "=f"(d[113]), "=f"(d[114]), "=f"(d[115]), "=f"(d[116]), "=f"(d[117]), "=f"(d[118]), "=f"(d[119]), "=f"(d[120]), "=f"(d[121]), "=f"(d[122]), "=f"(d[123]), "=f"(d[124]), "=f"(d[125]), "=f"(d[126]), "=f"(d[127])
        : "l"(da), "l"(db), "n"(TA), "n"(TB));
}
template <int TB>
__device__ __forceinline__ void wgmma_rs128(float* d, const uint32_t* a, uint64_t db, uint32_t acc) {
    asm volatile("{\n.reg .pred P;\nsetp.ne.u32 P, %69, 0;\nwgmma.mma_async.sync.aligned.m64n128k16.f32.bf16.bf16 "
        "{%0, %1, %2, %3, %4, %5, %6, %7, %8, %9, %10, %11, %12, %13, %14, %15, %16, %17, %18, %19, %20, %21, %22, %23, %24, %25, %26, %27, %28, %29, %30, %31, %32, %33, %34, %35, %36, %37, %38, %39, %40, %41, %42, %43, %44, %45, %46, %47, %48, %49, %50, %51, %52, %53, %54, %55, %56, %57, %58, %59, %60, %61, %62, %63}, {%64, %65, %66, %67}, %68, P, 1, 1, %70;\n}"
        : "+f"(d[0]), "+f"(d[1]), "+f"(d[2]), "+f"(d[3]), "+f"(d[4]), "+f"(d[5]), "+f"(d[6]), "+f"(d[7]), "+f"(d[8]), "+f"(d[9]), "+f"(d[10]), "+f"(d[11]), "+f"(d[12]), "+f"(d[13]), "+f"(d[14]), "+f"(d[15]), "+f"(d[16]), "+f"(d[17]), "+f"(d[18]), "+f"(d[19]), "+f"(d[20]), "+f"(d[21]), "+f"(d[22]), "+f"(d[23]), "+f"(d[24]), "+f"(d[25]), "+f"(d[26]), "+f"(d[27]), "+f"(d[28]), "+f"(d[29]), "+f"(d[30]), "+f"(d[31]), "+f"(d[32]), "+f"(d[33]), "+f"(d[34]), "+f"(d[35]), "+f"(d[36]), "+f"(d[37]), "+f"(d[38]), "+f"(d[39]), "+f"(d[40]), "+f"(d[41]), "+f"(d[42]), "+f"(d[43]), "+f"(d[44]), "+f"(d[45]), "+f"(d[46]), "+f"(d[47]), "+f"(d[48]), "+f"(d[49]), "+f"(d[50]), "+f"(d[51]), "+f"(d[52]), "+f"(d[53]), "+f"(d[54]), "+f"(d[55]), "+f"(d[56]), "+f"(d[57]), "+f"(d[58]), "+f"(d[59]), "+f"(d[60]), "+f"(d[61]), "+f"(d[62]), "+f"(d[63])
        : "r"(a[0]), "r"(a[1]), "r"(a[2]), "r"(a[3]), "l"(db), "r"(acc), "n"(TB));
}
template <int TB>
__device__ __forceinline__ void wgmma_rs64(float* d, const uint32_t* a, uint64_t db, uint32_t acc) {
    asm volatile("{\n.reg .pred P;\nsetp.ne.u32 P, %37, 0;\nwgmma.mma_async.sync.aligned.m64n64k16.f32.bf16.bf16 "
        "{%0, %1, %2, %3, %4, %5, %6, %7, %8, %9, %10, %11, %12, %13, %14, %15, %16, %17, %18, %19, %20, %21, %22, %23, %24, %25, %26, %27, %28, %29, %30, %31}, {%32, %33, %34, %35}, %36, P, 1, 1, %38;\n}"
        : "+f"(d[0]), "+f"(d[1]), "+f"(d[2]), "+f"(d[3]), "+f"(d[4]), "+f"(d[5]), "+f"(d[6]), "+f"(d[7]), "+f"(d[8]), "+f"(d[9]), "+f"(d[10]), "+f"(d[11]), "+f"(d[12]), "+f"(d[13]), "+f"(d[14]), "+f"(d[15]), "+f"(d[16]), "+f"(d[17]), "+f"(d[18]), "+f"(d[19]), "+f"(d[20]), "+f"(d[21]), "+f"(d[22]), "+f"(d[23]), "+f"(d[24]), "+f"(d[25]), "+f"(d[26]), "+f"(d[27]), "+f"(d[28]), "+f"(d[29]), "+f"(d[30]), "+f"(d[31])
        : "r"(a[0]), "r"(a[1]), "r"(a[2]), "r"(a[3]), "l"(db), "r"(acc), "n"(TB));
}
template <int TB>
__device__ __forceinline__ void wgmma_rs16(float* d, const uint32_t* a, uint64_t db, uint32_t acc) {
    asm volatile("{\n.reg .pred P;\nsetp.ne.u32 P, %13, 0;\nwgmma.mma_async.sync.aligned.m64n16k16.f32.bf16.bf16 "
        "{%0, %1, %2, %3, %4, %5, %6, %7}, {%8, %9, %10, %11}, %12, P, 1, 1, %14;\n}"
        : "+f"(d[0]), "+f"(d[1]), "+f"(d[2]), "+f"(d[3]), "+f"(d[4]), "+f"(d[5]), "+f"(d[6]), "+f"(d[7])
        : "r"(a[0]), "r"(a[1]), "r"(a[2]), "r"(a[3]), "l"(db), "r"(acc), "n"(TB));
}

__device__ __forceinline__ uint32_t delay_loop(int n, uint32_t x0) {
    uint32_t z;
    asm volatile("{\n.reg .pred P;\n.reg .u32 c, x;\nmov.u32 c, %1;\nmov.u32 x, %2;\nDL: mad.lo.u32 x, x, 1664525, 1013904223;\nadd.u32 c, c, -1;\nsetp.gt.s32 P, c, 0;\n@P bra DL;\n"
                 "setp.eq.u32 P, x, 0x7fffffff;\nselp.u32 %0, 16, 0, P;\n}" : "=r"(z) : "r"(n), "r"(x0) : "memory");
    return z;
}
__device__ __forceinline__ void wait_clocks(uint32_t n) {
    asm volatile("{\n.reg .pred P;\n.reg .u32 a, b;\nmov.u32 a, %%clock;\nW: mov.u32 b, %%clock;\nsub.u32 b, b, a;\nsetp.lt.u32 P, b, %0;\n@P bra W;\n}" ::"r"(n) : "memory");
}
__device__ __forceinline__ uint32_t gtime() { uint32_t t; asm volatile("mov.u32 %0, %%globaltimer_lo;" : "=r"(t)); return t; }
#define COUNT_RETRY(i)
__device__ __forceinline__ uint32_t stamp_word(uint32_t seq) { return (gtime() & ~31u) | (seq & 31u); }
__device__ __forceinline__ void wait_time(uint32_t t, uint32_t sb) { while ((int32_t)(gtime() - t) < 0) {} }
#define NAPMODE 1
__device__ __forceinline__ void nap(uint32_t ns) { if (NAPMODE) wait_clocks(ns * 7 / 4); else __nanosleep(ns); }
template <int STRIDE>
__device__ __forceinline__ uint32_t latest_stamp(const uint32_t* p, uint32_t seq, uint32_t ref, uint32_t sb) {
#pragma unroll 1
    for (int n = opq(0, 0);; n++) {
        uint32_t bad = 0; int32_t m = INT32_MIN;
#pragma unroll
        for (int i = 0; i < 3; i++) { const uint32_t v = ld_relaxed1(p + i * STRIDE); bad |= (v ^ seq) & 31u; m = max(m, (int32_t)((v & ~31u) - ref)); }
        if (__all_sync(0xffffffffu, bad == 0)) return ref + __reduce_max_sync(0xffffffffu, m);
        nap(100);
        if (n > SPIN_LIMIT) spin_fault();
    }
}
constexpr uint32_t ONES = 0x3C003C00u, FULL = 0x50005000u;
__device__ __forceinline__ void pacer(const Params& P, const uint32_t sb, const int cta, const int lane, const uint32_t epoch) {
    uint8_t* const zp = P.xb + cta * 2048 + xg_lane(lane);
    if (lane < 3) asm volatile("prefetch.tensormap [%0];" ::"l"(&P.tm[lane == 0 ? M_C1 + cta % 3 : lane == 1 ? M_CO : M_SEG]) : "memory");
    uint32_t e0 = 0;
#pragma unroll 2
    for (int i = 0; i < 32; i++) { const uint4 u = __ldg((const uint4*)P.mem0 + i * 32 + lane); e0 = amax(amax(e0, amax(u.x, u.y)), amax(u.z, u.w)); }
    e0 = min(max(warp_exp(e0), 31u), 253u) - 14;
    if (cta < 32) {
        const uint32_t* m = (const uint32_t*)(P.mem0 + (lane >> 2) * 1024 + cta * 32 + (lane & 3) * 2);
        const float sc = __uint_as_float((254 - e0) << 23);
        auto cv = [&](uint32_t u) { return pack2h(bf_lo(u) * sc, bf_hi(u) * sc); };
        const uint32_t y = cv(m[12]);
        st_relaxed4(zp, cv(m[0]), cv(m[4]), cv(m[8]), prmt(y, FULL, 0x7610));
        st_relaxed1(P.xb + xg_side(cta) + lane * 4, prmt(y, FULL, 0x3254));
    }
    if (cta < 40) {
#pragma unroll 1
        for (int b = 1; b < 8; b++) st_relaxed4(zp + xg_buf(b), 0, 0, 0, 0);
    }
    __threadfence();
    const uint32_t* ts = (const uint32_t*)(P.xb + XG_T) + lane;
    int32_t d0 = P.dly;
    const uint32_t go = mapa(sb + B_GO, (cta / 3 & 1) * 3 + 1 + (lane & 1));
    auto free_segment = [&]() { if (lane == 0) mbar_expect(sb + B_KVFULL, 16384); __syncwarp(); if (lane < 2) mbar_arrive_cluster(go); };
    for (int n = 0; (int32_t)(ld_acquire(&g_cnt(C_XCNT)) - (epoch + 1) * 256) < 0; n++) { __nanosleep(500); if (n > SPIN_LIMIT) spin_fault(); }
    const uint32_t ex = max(ld_relaxed1(&g_cnt(C_XMAX)) & 255, 67u);
    mbar_wait_bounded(sb + B_READY, 0);
    free_segment();
    if (lane == 0) st_relaxed2(g_hint + cta * 32, stamp_word(epoch + 1), lds32(sb + S_EV) | lds32(sb + S_EO) << 16);
    uint32_t a = gtime();
    for (int n = 0;; n++) {
        uint32_t bad = 0, e = 0; int32_t m = INT32_MIN;
#pragma unroll
        for (int i = 0; i < 3; i++) {
            uint32_t v[2];
            ld_relaxed2(v, g_hint + lane * 32 + i * 1024);
            bad |= (v[0] ^ (epoch + 1)) & 31u; m = max(m, (int32_t)((v[0] & ~31u) - a)); e = __vmaxu2(e, v[1]);
        }
        if (__all_sync(0xffffffffu, bad == 0)) {
            a += __reduce_max_sync(0xffffffffu, m);
            const uint32_t ev = __reduce_max_sync(0xffffffffu, e & 255), eo = __reduce_max_sync(0xffffffffu, e >> 16);
            if (lane == 0) { sts64(sb + S_SC, max(ev, 97u) + max(eo, 97u) - 244, ex); sts32(sb + S_ISC, e0 * 0x800080u); }
            break;
        }
        wait_clocks(100);
        if (n > SPIN_LIMIT) spin_fault();
    }
    wait_time(a, sb);
    if (lane == 0) mbar_arrive(sb + B_RELM);
#pragma unroll 1
    for (int s = 0; s < 63; s++) {
        const uint32_t seq = epoch * 63 + s + 1;
        mbar_wait_bounded(sb + B_P1, s & 1);
        const uint32_t tx = gtime();
        if (lane == 0) st_relaxed1(ts + (s & 1) * 256 + cta, (tx & ~31u) | (seq & 31u));
        { const uint32_t t = tx; PROFP(3) }
        if (s > 0) {
            const int32_t e0 = latest_stamp<32>(ts + (~s & 1) * 256 + 128, seq - 1, a, sb) + P.mrg - a;
            d0 += s < 3 ? e0 : min(max(e0, -P.clamp0), P.clampv) / 2;
        }
        while ((int32_t)(gtime() - tx) < P.rd) nap(20);
        a = latest_stamp<32>(ts + (s & 1) * 256, seq, tx, sb) + d0;
        { const uint32_t t = gtime(); PROFP(0) }
        while ((int32_t)(a - gtime()) > 250) nap(40);
        wait_time(a, sb);
        if (lane == 0) mbar_arrive(sb + B_RELM);
        { const uint32_t t = a; PROFP(2) }
        mbar_wait_bounded(sb + B_RED, s & 1);
        { const uint32_t t = gtime(); PROFP(1) }
        const uint32_t g = tx + __reduce_max_sync(0xffffffffu, lds32(sb + S_TO + (lane & 7) * 4) - tx);
        if (lane == 0) st_relaxed1(ts + (s & 1) * 256 + 128 + cta, (g & ~31u) | (seq & 31u));
        if (s < 62) { if (P.kvd) nap(P.kvd); free_segment(); }
    }
}
__device__ __forceinline__ void st_async2(uint32_t a, uint32_t x, uint32_t y, uint32_t bar) {
    asm volatile("st.async.weak.shared::cluster.mbarrier::complete_tx::bytes.v2.b32 [%0], {%1,%2}, [%3];" ::"r"(a), "r"(x), "r"(y), "r"(bar) : "memory");
}
__device__ __forceinline__ uint32_t xor_or(uint32_t a, uint32_t b, uint32_t t) { uint32_t d; asm("lop3.b32 %0, %1, %2, %3, 0x7E;" : "=r"(d) : "r"(a), "r"(b), "r"(t)); return d; }
__device__ __forceinline__ uint32_t or3(uint32_t a, uint32_t b, uint32_t c) { uint32_t d; asm("lop3.b32 %0, %1, %2, %3, 0xFE;" : "=r"(d) : "r"(a), "r"(b), "r"(c)); return d; }
__device__ __forceinline__ bool tags_ok(uint32_t bad, uint32_t mask = 1) {
    uint32_t r;
    asm volatile("{\n.reg .pred P;\n.reg .b32 x;\nand.b32 x, %1, %2;\nsetp.ne.b32 P, x, 0;\nvote.sync.any.pred P, P, 0xffffffff;\nselp.u32 %0, 0, 1, P;\n}" : "=r"(r) : "r"(bad), "r"(mask));
    return r;
}
constexpr int SROW = 56;
#define PREA 8
#define PREB 9
#define RING1 6
#define RING2 7
#define RING3 8
#define PRE2 10
#define PRE2A 0
#define PRE3 0
#define EFENCE 0
#define RFENCE 1
#define PROG 16
#define EARLY 0
#define PLATE 1
#define NDEP 0
#define EFENCE2 0
#define LAG2 8
#define LAG 4
#define PUT1 33
#define DEPS 3
#define ADELAY 120
#define BDELAY 0
#define HOLD 1
#define XDELAY 330
#define FENCEA 0x80
#define FENCEB 0x80
#define FENCE2 0x220
#define OFENCE 0
#define MASK3 0x57
#define MASK4 0x55
#define MASK5 0x25
#define OFF3 0x5320
#define OFF4 0x6420
#define OFF5 0x0520
#define RESA (NRA == 3 ? 15 : NRA == 4 ? 3 : 0)
#define RESB (NRB == 3 ? 0xcc : NRB == 4 ? 0x30 : 0)
#define RESB1 (NRB == 3 ? 0xcc : NRB == 4 ? 0xc : 0)
__host__ __device__ constexpr int smem_mask(int NR) { return NR == 3 ? MASK3 : NR == 4 ? MASK4 : MASK5; }
__host__ __device__ constexpr bool round_smem(int r, int NR) { return smem_mask(NR) >> r & 1; }
__host__ __device__ constexpr int kord(int r, int NR) { int c = 0; for (int i = 0; i < r; i++) c += round_smem(i, NR) == round_smem(r, NR); return round_smem(r, NR) ? NR + c : c; }
__host__ __device__ constexpr int slot_r(int n, int NR) { return n < 32 ? n >> 2 : (((n & 31) >> 2) + ((NR == 3 ? OFF3 : NR == 4 ? OFF4 : OFF5) >> (n & 3) * 4)) & 7; }
__host__ __device__ constexpr int slot_k(int n, int NR) { return kord(slot_r(n, NR), NR); }
__host__ __device__ constexpr int slot_sord(int n, int NR) { int c = 0; for (int i = 0; i < n; i++) c += slot_k(i, NR) >= NR; return c; }
__host__ __device__ constexpr int sfrag_slot(int q, int NR) { for (int n = 0; n < 64; n++) if (slot_k(n, NR) >= NR && slot_sord(n, NR) == q) return n; return -1; }
__host__ __device__ constexpr int w1_loaded(int n, int NR, int PRE) {
    int q = PRE;
    for (int i = 0; i <= n; i++) q += q < (8 - NR) * 8 && q - slot_sord(i + 1, NR) < (i < 32 ? RING1 : RING2);
    return q;
}
template <int Q, int NR>
__device__ __forceinline__ void load_w1(uint32_t* w, const uint32_t* a) {
    constexpr int n = sfrag_slot(Q, NR);
    ldsm4t(w, a[n & 3] + ((slot_k(n, NR) - NR) * 2 + (n >> 5)) * 2048);
}
constexpr int AB = NRA < 5, BB = 3 - AB;
__device__ __forceinline__ bool w2_full(int role, int warp) { return warp < (role == 2 ? 2 : 3); }
__device__ __forceinline__ int w2_nblk(int role, int warp) { return warp < 4 ? BB - !w2_full(role, warp) : AB; }
__host__ __device__ constexpr int w2_step(bool full, int i) { return AB ? (full ? 2 * i : 0) : full ? (i == 0 ? 0 : i == 1 ? 16 - 2 * EARLY : 18 - 2 * EARLY) : i; }
__device__ __forceinline__ int w2_block(int role, int warp) {
    const int f = role * 3 + warp, g = role == 2 ? warp : role;
    if (AB) return (warp >= 4 ? role * 4 + (warp - 4) : w2_full(role, warp) ? 16 + 4 * (f >> 1) + (f & 1) : 12 + g) ^ EARLY;
    return w2_full(role, warp) ? EARLY + 4 * (f >> 1) + (f & 1) : EARLY + 2 + 4 * g;
}
__device__ __forceinline__ int w2_res(int role, int warp) { return warp >= 4 ? RESA : w2_full(role, warp) ? RESB : RESB1; }
__device__ __forceinline__ int w2_units(int role, int warp) { return w2_nblk(role, warp) * 4 - (5 - (warp < 4 ? NRB : NRA)) * 2; }
constexpr int W2B = (BB * 4 - (5 - NRB) * 2) * 2048, W2A = (AB * 4 - (5 - NRA) * 2) * 2048;
static_assert(S_W2 + 4 * W2B - 8192 + 4 * W2A == S_KV, "weights");
__device__ __forceinline__ int w1_base(int warp) { return S_W1 + (warp < 4 ? warp * (8 - NRB) : 4 * (8 - NRB) + (warp - 4) * (8 - NRA)) * 4096; }
__device__ __forceinline__ int w2_base(int warp) { return S_W2 + (warp < 4 ? warp * W2B : 4 * W2B - 8192 + (warp - 4) * W2A); }
__device__ __forceinline__ void chain_load(const Params& P, uint32_t sb, int cta, int warp, int lane, int round) {
    const int role = cta % 3, h = cta / 3;
    mbar_expect_e(sb + B_INIT, round ? (8 - (warp < 4 ? NRB : NRA)) * 4096 : 20480);
    if (round) mbar_expect_e(sb + B_INIT2, w2_units(role, warp) * 2048);
    __syncwarp();
    const int m1 = (warp < 4 ? smem_mask(NRB) : smem_mask(NRA)) ^ (round ? 0 : 255), below = (1 << lane) - 1;
    const int m2 = (w2_res(role, warp) ^ (round ? 0xfff : 0)) & ((1 << w2_nblk(role, warp) * 4) - 1);
    const uint32_t d1 = sb + (round ? w1_base(warp) : warp * 20480), d2 = round ? sb + w2_base(warp) : d1 + __popc(m1) * 4096;
    if (m1 >> lane & 1) tma3d(d1 + __popc(m1 & below) * 4096, &P.tm[M_C1 + role], 0, warp * 128 + lane * 16, h * 2, sb + B_INIT);
    __syncwarp();
    if (m2 >> lane & 1)
        tma2d(d2 + __popc(m2 & below) * 2048, &P.tm[M_CO], (w2_block(role, warp) + w2_step(w2_full(role, warp), lane >> 2)) * 32, h * 128 + (lane & 3) * 32, sb + (round ? B_INIT2 : B_INIT));
    __syncwarp();
}

__device__ __forceinline__ void put_partials(bool TR, uint32_t a, const float* x, const float* y) {
    if (TR) stsm4t(a, pack2(x[0], x[1]), pack2(x[2], x[3]), pack2(y[0], y[1]), pack2(y[2], y[3]));
    else stsm4(a, pack2(x[0], x[1]), pack2(x[2], x[3]), pack2(y[0], y[1]), pack2(y[2], y[3]));
}
template <int NR, int PRE, int FM, int B, int E>
__device__ __forceinline__ void project(float (*acc)[4], bool TR, const uint32_t (*wr)[4], uint32_t (*as)[4], uint32_t (*v)[4], uint32_t* x, const uint32_t* w1a, uint32_t pp, uint32_t zero) {
    static_for<B, E>([&](auto I) {
        constexpr int n = I.value, kk = slot_k(n, NR), T = (n >> 5) * 4 + (n & 3), so = slot_sord(n, NR), q = w1_loaded(n - 1, NR, PRE);
        constexpr bool sm = kk >= NR;
        const uint32_t* w = sm ? as[so] : wr[sm ? 0 : (kk * 2 + (n >> 5)) * 4 + (n & 3)];
        if constexpr (n == 32 && PUT1 < 32) { put_partials(TR, pp, acc[0], acc[1]); put_partials(TR, pp + 4096, acc[2], acc[3]); }
        if constexpr (n == 0) {
            const uint32_t c = prmt(v[0][3], x[0], 0x3254);
            v[0][0] = h2bf(v[0][0], v[0][0]); v[0][1] = h2bf(v[0][1], v[0][1]); v[0][2] = h2bf(v[0][2], v[0][2]); v[0][3] = h2bf(v[0][3], x[0]);
            x[0] = c;
        }
        if constexpr ((n & 31) < 4) acc[T][0] = acc[T][1] = acc[T][2] = acc[T][3] = 0.f;
        mma16816(acc[T], w[0], w[1], w[2], w[3], v[slot_r(n, NR) >> 1][(slot_r(n, NR) & 1) * 2], v[slot_r(n, NR) >> 1][(slot_r(n, NR) & 1) * 2 + 1]);
        if constexpr (n == DEPS) {
            const uint32_t sel = __float_as_uint(acc[T][0]) * zero + 0x7610;
#pragma unroll
            for (int b = 1; b < 4; b++) {
                if (b <= NDEP) cvt_block(v[b], x[b], sel);
                else {
                    const uint32_t c = prmt(v[b][3], x[b], 0x3254);
                    v[b][0] = h2bf(v[b][0], v[b][0]); v[b][1] = h2bf(v[b][1], v[b][1]); v[b][2] = h2bf(v[b][2], v[b][2]); v[b][3] = h2bf(v[b][3], x[b]);
                    x[b] = c;
                }
            }
        }
        if constexpr (w1_loaded(n, NR, PRE) > q) load_w1<q, NR>(as[q], w1a);
        if constexpr (n == PUT1 && n >= 32) { put_partials(TR, pp, acc[0], acc[1]); put_partials(TR, pp + 4096, acc[2], acc[3]); }
        if constexpr (n % 4 == 3 && (FM >> (n / 4) & 1) && n != E - 1) sched_fence();
    });
    if constexpr (E == 64) { put_partials(TR, pp + 8192, acc[4], acc[5]); put_partials(TR, pp + 12288, acc[6], acc[7]); }
}
__device__ __forceinline__ void reduce8(const uint32_t (*x)[4], const uint32_t* sel, float sc, uint32_t& r0, uint32_t& r1) {
    float d[4][4];
#pragma unroll
    for (int i = 0; i < 4; i++) {
        d[i][0] = d[i][1] = d[i][2] = d[i][3] = 0.f;
        mma16816(d[i], x[i][0], x[i][1], x[i][2], x[i][3], sel[2 * i], sel[2 * i + 1]);
    }
    r0 = pack2(((d[0][0] + d[1][0]) + (d[2][0] + d[3][0])) * sc, ((d[0][1] + d[1][1]) + (d[2][1] + d[3][1])) * sc);
    r1 = pack2(((d[0][2] + d[1][2]) + (d[2][2] + d[3][2])) * sc, ((d[0][3] + d[1][3]) + (d[2][3] + d[3][3])) * sc);
}

#define ISTAMP(i)
__host__ __device__ constexpr int wo_count(int n, int RES, bool res) { int c = 0; for (int i = 0; i < n; i++) c += (RES >> (i >> 2) & 1) == res; return c; }
__host__ __device__ constexpr int wo_loaded(int n, int RES, int PRE, int end) { int q = PRE; for (int i = 0; i <= n; i++) q += q < end && q - wo_count(i + 1, RES, false) < RING3; return q; }
template <int Q>
__device__ __forceinline__ void load_w2(uint32_t* w, const uint32_t* a) { ldsm4t(w, a[Q & 1] + (Q >> 1) * 1024); }
template <int NB, int RES, int PRE, int FM>
__device__ __forceinline__ void wo_blocks(uint32_t (*w)[4], const uint32_t (*wp)[4], uint32_t oa, const uint32_t* wa, const uint8_t* dst, const uint8_t* dsd, bool odd) {
    float a[NB][4][4];
    uint32_t o[4][4], r[5];
    bar_sync(3, 256);
#pragma unroll
    for (int i = 0; i < 4; i++) ldsm4(o[i], oa + i * 512);
    if (FM & 1) sched_fence();
    static_for<0, NB * 16>([&](auto I) {
        constexpr int n = I.value, i = n & 15, end = wo_count(NB * 16, RES, false), q = wo_loaded(n - 1, RES, PRE, end);
        constexpr bool res = RES >> (n >> 2) & 1;
        const uint32_t* b = o[i >> 2] + (i & 2);
        const uint32_t* x = res ? wp[wo_count(n, RES, true)] : w[wo_count(n, RES, false)];
        float* d = a[n >> 4][i & 3];
        if constexpr (i < 4) d[0] = d[1] = d[2] = d[3] = 0.f;
        mma16816(d, x[0], x[1], x[2], x[3], b[0], b[1]);
        if constexpr (wo_loaded(n, RES, PRE, end) > q) load_w2<q>(w[q], wa);
        if constexpr (n == NB * 16 - 1 || (n >= 16 && i == LAG - 1)) {
            const float (*e)[4] = a[n == NB * 16 - 1 ? NB - 1 : (n >> 4) - 1];
            const uint32_t y = pack2h(e[1][2] + e[3][2], e[1][3] + e[3][3]);
            r[0] = movm(pack2h(e[0][0] + e[2][0], e[0][1] + e[2][1])); r[1] = movm(pack2h(e[0][2] + e[2][2], e[0][3] + e[2][3]));
            r[2] = movm(pack2h(e[1][0] + e[3][0], e[1][1] + e[3][1])); r[3] = movm(odd ? ONES : y); r[4] = movm(odd ? y : ONES);
        }
        if constexpr (n == NB * 16 - 1 || (n >= 16 && i == LAG2 - 1)) {
            constexpr int bs = w2_step(NB == BB, n == NB * 16 - 1 ? NB - 1 : (n >> 4) - 1);
            red_add4(dst + bs * 2048, r[0], r[1], r[2], r[3]);
            red_add1(dsd + (bs >> 1) * 1024 + (bs & 1) * 256, r[4]);
        }
        if constexpr (((FM >> (n / 4 + 1)) & 1) && (n & 3) == 3 && n != NB * 16 - 1) sched_fence();
    });
}
#define FRAG1(ln) ((((ln) & 7) + ((ln) >> 4) * 8) * 128 + ((((((ln) >> 3) & 1) << (ROLE == 1)) ^ ((ln) & 7)) << 4))
#define FRAG2(ln) ((((ln) & 7) + ((ln) >> 4) * 8) * 64 + (((((ln) >> 3) & 1) ^ (((ln) >> 1) & 3)) << 4))
#define TILE_X(i) (ROLE == 1 ? (((i) >> 1) << 6) | (((i) & 1) << 4) : (i) << 5)
__device__ __forceinline__ void chain_fetch(const Params& P, const uint32_t sb, const int cta, const int warp, const int lane, uint32_t (*wr)[4]) {
    const int ROLE = cta % 3, nr = warp < 4 ? NRB : NRA;
    mbar_wait(sb + B_INIT, 0);
    ISTAMP(0)
#pragma unroll
    for (int f = 0; f < 40; f++) {
        const bool w1 = f < (NRA < NRB ? NRA : NRB) * 8 || f < nr * 8;
        ldsm4t(wr[f], sb + warp * 20480 + (f >> 2) * 2048 + (w1 ? FRAG1(lane) ^ TILE_X(f & 3) : (f & 2) * 512 + (FRAG2(lane) ^ ((f & 1) << 5))));
    }
    fence_async_smem();
    mbar_wait(sb + B_SFREE + (warp >> 2) * 8, 0);
    bar_sync(1, 256);
    chain_load(P, sb, cta, warp, lane, 1);
    ISTAMP(1)
}
__device__ __forceinline__ void chain_bounds(const uint32_t sb, const int cta, const int warp, const int lane, const uint32_t (*wr)[4]) {
    const int ROLE = cta % 3, nr = warp < 4 ? NRB : NRA;
    uint32_t m[6] = {}, u[4];
#pragma unroll
    for (int f = 0; f < 40; f++) m[f < 24 ? 0 : f >> 3] = amax4(m[f < 24 ? 0 : f >> 3], wr[f]);
    uint32_t m1 = amax(m[0], amax(nr > 3 ? m[3] : 0, nr > 4 ? m[4] : 0)), m2 = amax(nr > 3 ? 0 : m[3], nr > 4 ? 0 : m[4]);
    ISTAMP(5)
    mbar_wait(sb + B_INIT, 1);
    ISTAMP(3)
    if (ROLE == 2) {
#pragma unroll 4
        for (int i = 0; i < S_W2 / 4096; i++) { lds128(u, sb + S_W1 + warp * (S_W2 / 8) + i * 512 + lane * 16); m1 = amax4(m1, u); }
    }
    mbar_wait(sb + B_INIT2, 0);
    ISTAMP(7)
    const int n = w2_units(ROLE, warp) * 4;
#pragma unroll 4
    for (int i = 0; i < n; i++) { lds128(u, sb + w2_base(warp) + i * 512 + lane * 16); m2 = amax4(m2, u); }
    m1 = warp_exp(m1); m2 = warp_exp(m2);
    if (lane == 0) { if (ROLE == 2) red_max_shared(sb + S_EV, m1); red_max_shared(sb + S_EO, m2); }
}
template <bool ATT>
__device__ __forceinline__ void chain_role(const Params& P, const uint32_t sb, const int cta, const int warp, const int lane, const uint32_t (*wr)[4]) {
    constexpr int NR = ATT ? NRA : NRB, PRE = ATT ? PREA : PREB;
    const int h = cta / 3, ROLE = cta - h * 3;
    ISTAMP(6)
    uint32_t l8 = opq(sb + lane * 8, lane);
    const uint8_t* persu = (const uint8_t*)((ROLE == 1 ? g_km : g_vmt) + h * 512) - (sb >> 1);
    auto persist = [&](int s, int tile, uint32_t r0, uint32_t r1) {
        uint32_t* pp = (uint32_t*)(persu + s * 65536 + (ROLE == 1 ? (tile >> 1) * 512 + (tile & 1) * 128 : tile * 256) + (l8 >> 1));
        pp[0] = r0; pp[ROLE == 1 ? 64 : 32] = r1;
    };
    const uint32_t rk0 = (h & 1) * 3, rd1 = __shfl_sync(0xffffffffu, mapa(sb, rk0 + (ROLE + 1) % 3) - sb, 0), rd2 = __shfl_sync(0xffffffffu, mapa(sb, rk0 + (ROLE + 2) % 3) - sb, 0);
    const uint32_t xo = (ROLE == 2 ? S_XV : S_X + ROLE * 2048) + warp * 256;
    const bool full = w2_full(ROLE, warp);
    const int blk = w2_block(ROLE, warp);
    const uint32_t om = blk * 2048, os = xg_side(blk);
    const uint32_t w1o = sb + w1_base(warp), w2o = sb + w2_base(warp);
    ISTAMP(2)
    if (lane == 0) mbar_arrive(sb + B_READY);
#pragma unroll 1
    for (int s = 0;; s++) {
        l8 += s & P.zero;
        uint32_t r0, r1;
        {
            uint32_t v[4][4], as[(8 - NR) * 8][4], w1a[4];
            float acc[8][4];
            const uint32_t pst = sb + S_P1 + (l8 - sb) * 16 + ((warp * 16) ^ ((l8 & 56) * 2));
#pragma unroll
            for (int i = 0; i < 4; i++) w1a[i] = w1o + (FRAG1((l8 - sb) >> 3) ^ TILE_X(i));
            auto preload = [&]() { static_for<0, PRE>([&](auto I) { load_w1<I.value, NR>(as[I.value], w1a); }); };
#pragma unroll 1
            while (true) {
                uint32_t x[4];
                if (!(PLATE >> ATT & 1)) preload();
                const uint32_t lm = opq(l8 - sb, (l8 - sb) >> 3);
                const uint8_t* pm = P.xb + xg_buf(s) + warp * 8192 + xg_lane(lm >> 3);
                const uint8_t* ps = P.xb + xg_buf(s) + XG_SIDE + warp * 2048 + (lm >> 1);
                pin_ptr(pm); pin_ptr(ps);
                mbar_wait(sb + B_RELM, s & 1);
                if (ATT ? ADELAY : BDELAY) wait_clocks(ATT ? ADELAY : BDELAY);
                PROF(10)
#pragma unroll
                for (int b = 0; b < 4; b++) { ld_relaxed4(v[b], pm + b * 2048); ld_relaxed1n(x[b], ps + (b >> 1) * 1024 + (b & 1) * 256); }
                if (PLATE >> ATT & 1) { preload(); if (PLATE >> (ATT + 2) & 1) sched_fence(); }
                project<NR, PRE, ATT ? FENCEA : FENCEB, 0, PROG>(acc, ROLE == 2, wr, as, v, x, w1a, pst, P.zero);
                const uint32_t bad = xor_or(x[0], x[1], FULL) | xor_or(x[2], x[3], FULL);
                if (tags_ok(bad, 0xffffffffu)) break;
                COUNT_RETRY(warp >> 1)
            }
            PROF(0)
            project<NR, PRE, ATT ? FENCEA : FENCEB, PROG, 64>(acc, ROLE == 2, wr, as, v, nullptr, w1a, pst, 0);
            PROF(1)
            const uint32_t isc = lds32(sb + S_ISC + (s & 1) * 4);
            const uint32_t lq = l8 + ((s >> 3) & P.zero), e1 = s == 63 ? 0 : rd1, e2 = s == 63 ? 0 : rd2;
            uint32_t x[4][4], sel[8], xd[6] = {l8 + xo, l8 + xo + e1, l8 + xo + e2, sb + B_X + e1, sb + B_X + e2, sb + S_P1 + warp * 2048 + (lq & 64) * 16 + (lq & 128) + (lq & 56) * 2};
#pragma unroll
            for (int i = 0; i < 8; i++) sel[i] = (lq & 224) == i * 32 ? 0x3F803F80u : 0u;
            pin<6>(xd); pin<8>(sel);
            if (RFENCE) sched_fence();
            bar_sync(1, 256);
#pragma unroll
            for (int i = 0; i < 4; i++) ldsm4t(x[i], xd[5] + i * 256);
            if (!ATT && l8 == sb + (warp - 3) * 1024) mbar_arrive(sb + B_P1);
            uint32_t em = warp_exp(amax(amax4(amax(amax(v[0][0], v[0][1]), amax(v[0][2], v[0][3])), v[1]), amax4(amax(amax(v[2][0], v[2][1]), amax(v[2][2], v[2][3])), v[3])));
            if (EFENCE2) sched_fence();
            reduce8(x, sel, bf_hi(isc), r0, r1);
            st_async2(xd[1], r0, r1, xd[3]);
            st_async2(xd[2], r0, r1, xd[4]);
            sts64(xd[0], r0, r1);
            if (s == 63) { persist(s, warp, r0, r1); break; }
            if (l8 == sb) sts32(sb + S_EM + warp * 4, em + (isc >> 23));
            __syncwarp();
            if (l8 == sb) mbar_arrive(sb + B_X);
            PROF(2)
        }
        uint32_t w[40][4], w2a[2], odd;
        const uint8_t *po, *pd;
        auto wo_addr = [&]() {
            const uint32_t lo = (l8 + ((s >> 2) & P.zero) - sb) >> 3;
            w2a[0] = w2o + FRAG2(lo); w2a[1] = w2o + (FRAG2(lo) ^ 32);
            po = P.xb + xg_buf(s + 1) + om + xg_lane(lo);
            pd = P.xb + xg_buf(s + 1) + os + lo * 4;
            odd = lo & 4;
            pin_ptr(po); pin_ptr(pd); pin<2>(w2a); pin<1>(&odd);
        };
        uint32_t oa = l8 * 2 + (S_OX - sb);
        if constexpr (ATT) {
            const uint32_t ln = (l8 + ((s >> 4) & P.zero) - sb) >> 3;
            const uint32_t va = sb + S_KV + 8192 + ((warp >> 1) & 1) * 4096 + ((ln & 7) + (ln >> 4) * 8) * 128 + ((((warp & 1) * 4 + ((ln >> 3) & 1)) ^ (ln & 7)) << 4);
            const uint32_t ka = sb + S_KV + (warp & 1) * 2048 + (ln & 15) * 128 + (((ln >> 4) ^ (ln & 7)) << 4);
            uint32_t ad[5] = {sb + S_SX + (ln & 3) * (8 * SROW) + (ln >> 2) * 4 + (warp < 6 ? (warp - 4) * 64 : 128 + (warp - 6) * 32), l8 + S_XV + (warp - 4) * 512,
                              l8 + S_SX + (ln >> 2) * (4 * SROW - 32), oa + (warp - 4) * 512, sb + S_ISC + (~s & 1) * 4};
            if constexpr (AB) { wo_addr(); pin<1>(&oa); }
            pin<5>(ad);
            const uint32_t sa = ad[0], sr = ad[2];
            uint32_t vf[4][4], vm[2][2], q[8][2];
            float S[4][4];
#pragma unroll
            for (int n = 0; n < 4; n++) { S[n][0] = S[n][1] = S[n][2] = S[n][3] = 0.f; }
            mbar_wait(sb + B_KVFULL, s & 1);
            if (warp < 6) {
                uint32_t kf[8][4];
#pragma unroll
                for (int k = 0; k < 8; k++) ldsm4(kf[k], (ka ^ ((k & 3) << 5)) + (k >> 2) * 4096);
#pragma unroll
                for (int i = 0; i < 4; i++) ldsm4t(vf[i], (va ^ ((i & 1) << 5)) + (i >> 1) * 2048);
                mbar_wait(sb + B_X, s & 1);
                PROF(11)
#pragma unroll
                for (int k = 0; k < 8; k++) lds64(q[k], l8 + S_X + k * 256);
#pragma unroll
                for (int k = 0; k < 8; k++) mma16816(S[k & 3], kf[k][0], kf[k][1], kf[k][2], kf[k][3], q[k][0], q[k][1]);
                sts32(sa, __float_as_uint((S[0][0] + S[1][0]) + (S[2][0] + S[3][0])));
                sts32(sa + 4 * SROW, __float_as_uint((S[0][1] + S[1][1]) + (S[2][1] + S[3][1])));
                sts32(sa + 32, __float_as_uint((S[0][2] + S[1][2]) + (S[2][2] + S[3][2])));
                sts32(sa + 4 * SROW + 32, __float_as_uint((S[0][3] + S[1][3]) + (S[2][3] + S[3][3])));
            } else {
#pragma unroll
                for (int i = 0; i < 4; i++) ldsm4t(vf[i], (va ^ ((i & 1) << 5)) + (i >> 1) * 2048);
                uint32_t xa = l8 + S_X + (warp - 6) * 1024;
                pin<1>(&xa);
                mbar_wait(sb + B_X, s & 1);
                PROF(11)
#pragma unroll
                for (int k = 0; k < 8; k++) lds64(q[k], xa + (k >> 2) * 2048 + (k & 3) * 256);
#pragma unroll
                for (int k = 0; k < 4; k++) mma16816(S[k], q[4 + (k & 2)][0], q[4 + (k & 2)][1], q[5 + (k & 2)][0], q[5 + (k & 2)][1], q[k][0], q[k][1]);
                sts32(sa, __float_as_uint((S[0][0] + S[2][0]) + (S[1][2] + S[3][2])));
                sts32(sa + 4 * SROW, __float_as_uint((S[0][1] + S[2][1]) + (S[1][3] + S[3][3])));
            }
            lds64(vm[0], ad[1]); lds64(vm[1], ad[1] + 256);
            PROF(7)
            bar_sync(2, 160);
            const float cs = 0.08838834764831845f * 1.4426950408889634f;
            float E[6][2];
#pragma unroll
            for (int i = 0; i < 6; i++) lds64f(E[(i + 4) % 6], sr + ((i + 4) % 6) * 32);
            const uint32_t isn = lds32(ad[4]);
            E[4][0] += E[5][0]; E[4][1] += E[5][1];
            float m = fmaxf(fmaxf(fmaxf(fmaxf(E[0][0], E[0][1]), fmaxf(E[1][0], E[1][1])), fmaxf(fmaxf(E[2][0], E[2][1]), fmaxf(E[3][0], E[3][1]))), fmaxf(E[4][0], E[4][1]));
            m = fmaxf(m, __shfl_xor_sync(0xffffffffu, m, 1));
            m = fmaxf(m, __shfl_xor_sync(0xffffffffu, m, 2));
            m *= cs;
            if constexpr (AB) static_for<0, PRE3>([&](auto I) { load_w2<I.value>(w[I.value], w2a); });
            uint32_t pa[5];
#pragma unroll
            for (int i = 0; i < 5; i++) { const int k = (i + 4) % 5; E[k][0] = ex2(fmaf(E[k][0], cs, -m)); E[k][1] = ex2(fmaf(E[k][1], cs, -m)); pa[k] = pack2(E[k][0], E[k][1]); }
            if (EFENCE) sched_fence();
            float O[2][4], Z[4];
#pragma unroll
            for (int i = 0; i < 4; i++) { O[0][i] = O[1][i] = Z[i] = 0.f; }
#pragma unroll
            for (int i = 0; i < 2; i++) {
                mma1688(O[i], vm[i][0], vm[i][1], pa[4]);
                mma16816(O[i], vf[i][0], vf[i][1], vf[i][2], vf[i][3], pa[0], pa[1]);
                mma16816(O[i], vf[2 + i][0], vf[2 + i][1], vf[2 + i][2], vf[2 + i][3], pa[2], pa[3]);
            }
            const float z = (((E[4][0] + E[4][1]) + (E[0][0] + E[0][1])) + ((E[1][0] + E[1][1]) + (E[2][0] + E[2][1]))) + (E[3][0] + E[3][1]);
            const float zh = __uint_as_float(__float_as_uint(z) & 0xffff0000u);
            mma1688(Z, isn, isn, pack2(zh, z - zh));
            const float i0 = rcp(Z[0]), i1 = rcp(Z[1]);
            stsm4t(ad[3], pack2(O[0][0] * i0, O[0][1] * i1), pack2(O[0][2] * i0, O[0][3] * i1), pack2(O[1][0] * i0, O[1][1] * i1), pack2(O[1][2] * i0, O[1][3] * i1));
            PROF(4)
            if constexpr (AB) wo_blocks<1, RESA, PRE3, OFENCE / 2>(w, wr + NR * 8, oa, w2a, po, pd, odd);
            else bar_arrive(3, 256);
            if (ROLE != 0) persist(s, warp, r0, r1);
            if (warp == 7 && l8 == sb) mbar_expect(sb + B_X, 4096);
        } else {
            if (ROLE != 0) persist(s, warp, r0, r1);
            wo_addr(); pin<1>(&oa);
            static_for<0, PRE2A>([&](auto I) { load_w2<I.value>(w[I.value], w2a); });
            mbar_wait(sb + B_X, s & 1);
            if (warp == 0) {
                uint32_t sc[2];
                lds64(sc, sb + S_SC);
                const int em = __reduce_max_sync(0xffffffffu, lds32(sb + S_EM + ((l8 >> 1) & 28)));
                if (l8 == sb) sts32(sb + S_ISC + (~s & 1) * 4, min(max(em - 127, (int)sc[1]) + (int)sc[0], 253) * 0x800080u);
                bar_arrive(2, 160);
            }
            wait_clocks(XDELAY - (warp == 0) * 100);
            constexpr int PRE1 = (BB - 1) * 16 - (5 - NRB) * 8 < PRE2 ? (BB - 1) * 16 - (5 - NRB) * 8 : PRE2;
            static_for<PRE2A, PRE1>([&](auto I) { load_w2<I.value>(w[I.value], w2a); });
            if (full) {
                static_for<PRE1, PRE2>([&](auto I) { load_w2<I.value>(w[I.value], w2a); });
                wo_blocks<BB, RESB, PRE2, FENCE2 * 2 + OFENCE % 2>(w, wr + NR * 8, oa, w2a, po, pd, odd);
            } else wo_blocks<BB - 1, RESB1, PRE1, FENCE2 * 2 + OFENCE % 2>(w, wr + NR * 8, oa, w2a, po, pd, odd);
        }
        PROF(5)
        if (l8 == sb) { sts32(sb + S_TO + warp * 4, gtime()); mbar_arrive(sb + B_RED); }
        if (HOLD && !(PLATE >> ATT & 1)) mbar_wait(sb + B_RED, s & 1);
        if (ROLE != 0 && (s & 3) == 3 && l8 == sb) mbar_arrive(sb + B_PERS);
        if (ROLE == 0 && s == 62) return;
    }
    __syncwarp();
    if (l8 == sb) mbar_arrive(sb + B_PERS);
}
#define IP(i)
struct Pipe { uint32_t stage, phase; };
struct Cons {
    uint32_t sb, rel;
    int wg, wq, lane, rank, pair;
    uint32_t nst;
    Pipe p;
};
__device__ __forceinline__ void pipe_next(Pipe& p) { p.stage = (p.stage + 1) & (NSTAGE - 1); p.phase ^= (p.stage == 0); }
__device__ __forceinline__ void release(const Cons& c, uint32_t stage) { if (c.lane < 2) mbar_arrive_cluster(c.rel + stage * 8); }
__device__ __forceinline__ void wait_full(const Cons& c) { mbar_wait(c.sb + B_FULL + c.p.stage * 8, c.p.phase); }

enum { PEND_NONE = 0, PEND_KVO = 1, PEND_HT = 2, PEND_OUT = 3 };
struct Pend { uint32_t pk[64]; int kind, row, col, cnt; };

__device__ __forceinline__ void staging_wait(const Cons& c) { if (c.nst) mbar_wait(c.sb + B_SFREE + c.wg * 8, (c.nst - 1) & 1); }
__device__ __forceinline__ void staging_post(Cons& c, int kind, int row, int col, int cnt) {
    __syncwarp();
    if (c.lane == 0) {
        if (c.wq == 0) { const uint32_t x[4] = {(uint32_t)kind, (uint32_t)row, (uint32_t)col, (uint32_t)cnt}; sts128(c.sb + S_DESC + c.wg * 16, x); }
        mbar_arrive(c.sb + B_SFULL + c.wg * 8);
    }
    c.nst++;
}
__device__ __forceinline__ void drain(const Params& P, Cons& c, Pend& d) {
    const uint32_t* pk = d.pk;
    if (d.kind == PEND_OUT) {
        float* o = P.out + (size_t)(d.row + c.wq * 16 + (c.lane >> 2)) * 2048 + d.col + (c.lane & 3) * 2;
#pragma unroll
        for (int j = 0; j < 16; j++) {
            st_stream2(o + j * 8, bf_lo(pk[j * 2]), bf_hi(pk[j * 2]));
            st_stream2(o + 8 * 2048 + j * 8, bf_lo(pk[j * 2 + 1]), bf_hi(pk[j * 2 + 1]));
        }
    } else {
        const bool ht = d.kind == PEND_HT;
        const int hi = (c.lane >> 3) & 1;
        const uint32_t base = c.sb + S_STG + c.wg * 16384 + ((ht ? hi * 32 + c.wq * 8 : c.wq * 16 + hi * 8) + (c.lane & 7)) * 128;
        staging_wait(c);
#pragma unroll
        for (int j = 0; j < 8; j++) {
            const int ch = (j & 3) * 2 + (c.lane >> 4);
            stsm4(base + (j >> 2) * 8192 + ((ch ^ (c.lane & 7)) << 4), pk[j * 4], pk[j * 4 + 1], pk[j * 4 + 2], pk[j * 4 + 3]);
        }
        fence_async_smem();
        staging_post(c, d.kind, d.row, d.col, (d.col & 128) ? d.cnt : -1);
    }
    if (d.col & 128) d.kind = PEND_NONE;
    d.col += 128;
#pragma unroll
    for (int i = 0; i < 32; i++) d.pk[i] = d.pk[32 + i];
}

constexpr int S_STG2 = 8 * 20480, PEND_BOTH = 8;
__device__ __forceinline__ void drain_both(Cons& c, const Pend& d) {
    const uint32_t base = c.sb + c.wg * 16384 + (c.wq * 16 + ((c.lane >> 3) & 1) * 8 + (c.lane & 7)) * 128;
#pragma unroll
    for (int j = 0; j < 16; j++)
        stsm4(base + (j < 8 ? S_STG : S_STG2) + (j >> 2 & 1) * 8192 + ((((j & 3) * 2 + (c.lane >> 4)) ^ (c.lane & 7)) << 4), d.pk[j * 4], d.pk[j * 4 + 1], d.pk[j * 4 + 2], d.pk[j * 4 + 3]);
    fence_async_smem();
    staging_post(c, PEND_KVO | PEND_BOTH, d.row, d.col, d.cnt);
}

__device__ __forceinline__ void store_warp(const Params& P, uint32_t sb, int wg, int cta) {
    if (cta < 128) {
        for (int i = 0; i < P.xd; i++) __nanosleep(1000);
        const uint32_t e1 = get_epoch(sb) + 1;
        const uint4* x = (const uint4*)P.Bx + (cta * 2 + wg) * 1024 + (threadIdx.x & 31);
        uint32_t m = 0;
#pragma unroll 4
        for (int i = 0; i < 32; i++) { const uint4 u = __ldg(x + i * 32); m = amax(amax(m, amax(u.x, u.y)), amax(u.z, u.w)); }
        m = warp_exp(m);
        if (elect_one()) { atomicMax(&g_cnt(C_XMAX), e1 << 8 | m); red_release(&g_cnt(C_XCNT)); }
        __syncwarp();
    }
    const uint32_t stg = sb + S_STG + wg * 16384;
#pragma unroll 1
    for (uint32_t n = 0;; n++) {
        mbar_wait(sb + B_SFULL + wg * 8, n & 1);
        uint32_t x[4];
        lds128(x, sb + S_DESC + wg * 16);
#pragma unroll
        for (int i = 0; i < 4; i++) x[i] = __shfl_sync(0xffffffffu, x[i], 0);
        if (x[0] == PEND_NONE) break;
        const bool ht = x[0] == PEND_HT;
        const CUtensorMap* m = &P.tm[ht ? M_HTS : M_KVO];
        const uint64_t pol = P.pol[ht ? 2 : x[1] >= 4096 ? 1 : (x[1] & 2047) < 1536 ? 0 : 10];
        if (elect_one()) {
#pragma unroll
            for (int i = 0; i < 4; i++) tma_store2d(m, x[2] + (i >> 1) * 64, x[1] + (i & 1) * (ht ? 1024 : 32), stg + i * 4096, pol);
            if (x[0] & PEND_BOTH) {
#pragma unroll 1
                for (int i = 0; i < 4; i++) tma_store2d(m, x[2] + 128 + (i >> 1) * 64, x[1] + (i & 1) * 32, stg + (S_STG2 - S_STG) + i * 4096, pol);
            }
            bulk_commit();
            bulk_wait_read();
            mbar_arrive(sb + B_SFREE + wg * 8);
            if ((int)x[3] >= 0) { bulk_wait_all(); fence_async(); red_relaxed(&g_cnt(x[3])); }
        }
        __syncwarp();
    }
}

template <int TA, int TB, bool FIRST>
__device__ __forceinline__ void issue_ktile(float* acc, const Cons& c) {
    const uint32_t a = c.sb + c.p.stage * STAGE + c.wg * 8192, b = c.sb + c.p.stage * STAGE + 16384;
    const uint64_t da = mkdesc(a, TA ? 8192 : 16, 1024, 1), db = mkdesc(b, TB ? 8192 : 16, 1024, 1);
    wg_fence();
#pragma unroll
    for (int k = 0; k < 4; k++) {
        if (FIRST && k == 0) wgmma_ss256_first<TA, TB>(acc, da, db);
        else wgmma_ss256<TA, TB>(acc, da + (TA ? 128 : 2) * k, db + (TB ? 128 : 2) * k);
    }
    wg_commit();
}
template <bool KVONLY, bool FIRST>
__device__ __forceinline__ void issue_any(float* acc, const Cons& c, int type) {
    wait_full(c);
    if (!KVONLY && type == T_A1) issue_ktile<0, 0, FIRST>(acc, c);
    else if (!KVONLY && type == T_A2) issue_ktile<1, 0, FIRST>(acc, c);
    else issue_ktile<0, 1, FIRST>(acc, c);
}
template <bool KVONLY = false>
__device__ __forceinline__ void mainloop(float* acc, const Params& P, Cons& c, Pend& d, int type, int nk) {
    issue_any<KVONLY, true>(acc, c, type);
    if (!KVONLY) { IP(0) }
    uint32_t prev = c.p.stage;
    pipe_next(c.p);
#pragma unroll 1
    for (int kt = 1; kt < nk; kt++) {
        if (!KVONLY && d.kind != PEND_NONE && kt != 2) drain(P, c, d);
        issue_any<KVONLY, false>(acc, c, type);
        wg_wait<1>();
        release(c, prev);
        prev = c.p.stage;
        pipe_next(c.p);
    }
    d.kind = PEND_NONE;
    wg_wait<0>();
    pin<128>(acc);
    release(c, prev);
    if (!KVONLY) { IP(1) }
}
__device__ __forceinline__ void pack_half(uint32_t* pk, const float* a) {
#pragma unroll
    for (int i = 0; i < 32; i++) pk[i] = pack2(a[2 * i], a[2 * i + 1]);
}

__device__ __forceinline__ void epi_kv(const float* acc, const Cons& c, Pend& d, int mb, int nb) {
    pack_half(d.pk, acc); pack_half(d.pk + 32, acc + 64);
    d.kind = PEND_KVO; d.row = (nb >> 4) * 2048 + mb * 256 + c.rank * 128 + c.wg * 64; d.col = (nb & 15) * 256; d.cnt = C_KV + mb;
}

__device__ __forceinline__ void qa_scores(float* S, float* Sm, const uint32_t* q, Cons& c) {
    wait_full(c);
    const uint32_t st = c.sb + c.p.stage * STAGE;
    const uint64_t dk = mkdesc(st + c.wg * 8192, 16, 1024, 1), dm = mkdesc(st + 32768 + c.wg * 4096, 128, 2048, 0);
    wg_fence();
#pragma unroll
    for (int i = 0; i < 8; i++) wgmma_rs64<0>(S, q + i * 4, dk + (i >> 2) * 1024 + (i & 3) * 2, i != 0);
#pragma unroll
    for (int i = 0; i < 8; i++) wgmma_rs16<0>(Sm, q + i * 4, dm + i * 16, i != 0);
    wg_commit();
    pipe_next(c.p);
}
__device__ __forceinline__ void qa_softmax(uint32_t (*pa)[4], const float* S, const float* Sm, const Cons& c) {
    const int t = c.lane & 3, i0 = (c.wq & 1) * 16 + (c.lane >> 2) - 2 * t;
    const bool sg = c.wq >= 2;
    const float cs = 0.08838834764831845f * 1.4426950408889634f;
    float x[2][10];
#pragma unroll
    for (int r = 0; r < 2; r++) {
#pragma unroll
        for (int j = 0; j < 4; j++)
#pragma unroll
            for (int e = 0; e < 2; e++) {
                const float v = sg ? S[16 + j * 4 + r * 2 + e] : S[j * 4 + r * 2 + e];
                x[r][j * 2 + e] = (j * 8 + e - r * 8 > i0) ? -1e9f / 0.08838834764831845f : v;
            }
        x[r][8] = sg ? Sm[4 + r * 2] : Sm[r * 2];
        x[r][9] = sg ? Sm[5 + r * 2] : Sm[1 + r * 2];
        float m = fmaxf(fmaxf(fmaxf(fmaxf(x[r][0], x[r][1]), fmaxf(x[r][2], x[r][3])), fmaxf(fmaxf(x[r][4], x[r][5]), fmaxf(x[r][6], x[r][7]))), fmaxf(x[r][8], x[r][9]));
        m = fmaxf(m, __shfl_xor_sync(0xffffffffu, m, 1));
        m = fmaxf(m, __shfl_xor_sync(0xffffffffu, m, 2));
        m *= -cs;
#pragma unroll
        for (int i = 0; i < 10; i++) x[r][i] = ex2(fmaf(x[r][i], cs, m));
        float sum = (((x[r][0] + x[r][1]) + (x[r][2] + x[r][3])) + ((x[r][4] + x[r][5]) + (x[r][6] + x[r][7]))) + (x[r][8] + x[r][9]);
        sum += __shfl_xor_sync(0xffffffffu, sum, 1);
        sum += __shfl_xor_sync(0xffffffffu, sum, 2);
        const float inv = rcp(sum);
#pragma unroll
        for (int i = 0; i < 10; i++) x[r][i] *= inv;
    }
#pragma unroll
    for (int ks = 0; ks < 2; ks++)
#pragma unroll
        for (int i = 0; i < 4; i++) {
            const uint32_t p = pack2(x[i & 1][ks * 4 + (i >> 1) * 2], x[i & 1][ks * 4 + (i >> 1) * 2 + 1]);
            pa[ks][i] = sg ? 0u : p;
            pa[2 + ks][i] = sg ? p : 0u;
        }
#pragma unroll
    for (int r = 0; r < 2; r++) {
        const uint32_t p = pack2(x[r][8], x[r][9]);
        pa[4][r] = sg ? 0u : p;
        pa[4][2 + r] = sg ? p : 0u;
    }
}
__device__ __forceinline__ void qa_values(float* O, uint32_t (*pa)[4], Cons& c) {
    wait_full(c);
    const uint32_t st = c.sb + c.p.stage * STAGE;
    const uint64_t dv = mkdesc(st + c.wg * 8192, 16384, 1024, 1), dm = mkdesc(st + 32768 + c.wg * 4096, 2048, 128, 0);
    pin<20>(&pa[0][0]);
    wg_fence();
#pragma unroll
    for (int ks = 0; ks < 4; ks++) wgmma_rs128<1>(O, pa[ks], dv + ks * 128, ks != 0);
    wgmma_rs128<0>(O, pa[4], dm, 1);
    wg_commit();
    pipe_next(c.p);
}
__device__ __forceinline__ void epi_qa(const float* acc, Cons& c, Pend& d, int mb, int nb) {
    uint32_t q[64], pa[2][5][4];
    float S0[32] = {}, M0[8] = {}, S1[32] = {}, M1[8] = {}, O0[64] = {}, O1[64] = {};
    const uint32_t k0 = c.p.stage;
    pack_half(q, acc);
    pin<32>(q); pin<32>(S0); pin<8>(M0);
    qa_scores(S0, M0, q, c);
    pack_half(q + 32, acc + 64);
    pin<32>(q + 32); pin<32>(S1); pin<8>(M1);
    qa_scores(S1, M1, q + 32, c);
    wg_wait<1>();
    pin<32>(S0); pin<8>(M0);
    release(c, k0);
    qa_softmax(pa[0], S0, M0, c);
    wg_wait<0>();
    pin<32>(S1); pin<8>(M1); pin<64>(q);
    release(c, (k0 + 1) & (NSTAGE - 1));
    pin<64>(O0);
    qa_values(O0, pa[0], c);
    qa_softmax(pa[1], S1, M1, c);
    pin<64>(O1);
    qa_values(O1, pa[1], c);
    wg_wait<1>();
    pin<64>(O0); pin<20>(&pa[0][0][0]);
    release(c, (k0 + 2) & (NSTAGE - 1));
    pack_half(d.pk, O0);
    wg_wait<0>();
    pin<64>(O1); pin<20>(&pa[1][0][0]);
    release(c, (k0 + 3) & (NSTAGE - 1));
    pack_half(d.pk + 32, O1);
    d.kind = PEND_KVO; d.row = 4096 + mb * 256 + c.rank * 128 + c.wg * 64; d.col = nb * 256; d.cnt = C_O + mb;
}

__device__ __forceinline__ void epi_op(const float* acc, const Cons& c, Pend& d, int mb, int nb) {
    pack_half(d.pk, acc); pack_half(d.pk + 32, acc + 64);
    d.kind = PEND_OUT; d.row = mb * 256 + c.rank * 128 + c.wg * 64; d.col = 1024 + nb * 256;
}

__device__ __forceinline__ void epi_a2(float* acc, const Params& P, Cons& c, int mb, int col0) {
    const int g = c.lane >> 2, t = c.lane & 3;
    const int row = mb * 256 + (g >> 1) * 64 + (c.rank * 16 + c.wg * 8 + c.wq * 2) * 2 + (g & 1);
    float* o = P.out + (size_t)row * 2048 + col0 + t * 2;
#pragma unroll 1
    for (int hf = P.zero; hf < 2; hf++) {
    wait_full(c);
    const uint32_t st = c.sb + c.p.stage * STAGE, xa = st + (c.wg * 64 + c.wq * 16 + g) * 128 + t * 4 + (g << 4), da = st + 32768 + t * 4;
#pragma unroll
    for (int j = 0; j < 16; j++) {
        const float* a = acc + j * 4;
        const uint32_t ad = (xa ^ ((j & 7) << 4)) + (j >> 3) * 16384;
        const uint32_t x0 = lds32(ad), x1 = lds32(ad + 1024), dv = lds32(da + j * 16);
        const uint32_t u0 = mul_bf2(x0, dv), u1 = mul_bf2(x1, dv);
        st_stream2(o + j * 8, a[0] + bf_lo(u0), a[1] + bf_hi(u0));
        st_stream2(o + 2 * 2048 + j * 8, a[2] + bf_lo(u1), a[3] + bf_hi(u1));
    }
    __syncwarp();
    release(c, c.p.stage);
    pipe_next(c.p);
    o += 128;
#pragma unroll
    for (int i = 0; i < 64; i++) acc[i] = acc[64 + i];
    }
}

#define TSTAMP(i)
__device__ __forceinline__ float2 cmul(float2 a, float2 b) { return make_float2(fmaf(a.x, b.x, -a.y * b.y), fmaf(a.x, b.y, a.y * b.x)); }
__device__ __forceinline__ float2 cfma(float2 a, float2 b, float2 u) { return make_float2(fmaf(a.x, b.x, fmaf(-a.y, b.y, u.x)), fmaf(a.x, b.y, fmaf(a.y, b.x, u.y))); }
__device__ __forceinline__ float4 ssm_coef(float lre, float lim, float logdt) {
    const float dt = __bfloat162float(__float2bfloat16(expf(logdt)));
    const float ea = expf(dt * lre);
    float sn, cn;
    sincosf(dt * lim, &sn, &cn);
    const float br = ea * cn, bi = ea * sn, nr = br - 1.f;
    const bool sw = fabsf(lre) < fabsf(lim);
    const float big = sw ? lim : lre, r = __fdividef(sw ? lre : lim, big), inv = __fdividef(1.f, fmaf(sw ? lre : lim, r, big));
    const float cr = (sw ? fmaf(nr, r, bi) : fmaf(bi, r, nr)) * inv, ci = (sw ? fmaf(bi, r, -nr) : fmaf(-nr, r, bi)) * inv;
    return make_float4(br, bi, cr, ci);
}
__device__ __forceinline__ void epi_a1(const float* acc, const Params& P, const Cons& c, Pend& d, int mb, int nb) {
    const uint32_t atag = (get_epoch(c.sb) + 1) & 1;
    const int t = c.lane & 3;
    const int p = nb * 128 + c.rank * 64 + c.wg * 32 + c.wq * 8 + (c.lane >> 2);
    const float4 cf = __ldcg(&g_coef[p]);
    const float2 lam = make_float2(cf.x, P.swap_ri ? -cf.y : cf.y);
    const float a0 = P.swap_ri ? -2.f * cf.w : 2.f * cf.z, a1 = P.swap_ri ? 2.f * cf.z : -2.f * cf.w;
    const float b0 = P.swap_ri ? -2.f * cf.z : -2.f * cf.w, b1 = P.swap_ri ? -2.f * cf.w : -2.f * cf.z;
    float2 h = make_float2(0.f, 0.f);
#pragma unroll
    for (int round = 0; round < 2; round++) {
#pragma unroll
        for (int j = 0; j < 32; j++) {
            h = cfma(lam, h, make_float2(acc[j * 4], acc[j * 4 + 2]));
            const float r0 = fmaf(a0, h.x, a1 * h.y), m0 = fmaf(b0, h.x, b1 * h.y);
            h = cfma(lam, h, make_float2(acc[j * 4 + 1], acc[j * 4 + 3]));
            d.pk[j * 2] = pack2(r0, fmaf(a0, h.x, a1 * h.y));
            d.pk[j * 2 + 1] = pack2(m0, fmaf(b0, h.x, b1 * h.y));
        }
        if (round) break;
        float2 l64 = lam;
#pragma unroll
        for (int i = 0; i < 6; i++) l64 = cmul(l64, l64);
        const float2 l128 = cmul(l64, l64), l256 = cmul(l128, l128);
        float2 o = make_float2(__shfl_up_sync(0xffffffffu, h.x, 1), __shfl_up_sync(0xffffffffu, h.y, 1));
        if (t >= 1) h = cfma(l64, o, h);
        o = make_float2(__shfl_up_sync(0xffffffffu, h.x, 2), __shfl_up_sync(0xffffffffu, h.y, 2));
        if (t >= 2) h = cfma(l128, o, h);
        IP(2)
        if (t == 3) st_relaxed2(&g_agg[mb * 1024 + p], (__float_as_uint(h.x) & ~1u) | atag, __float_as_uint(h.y));
        h = make_float2(__shfl_up_sync(0xffffffffu, h.x, 1), __shfl_up_sync(0xffffffffu, h.y, 1));
        if (t == 0) h = make_float2(0.f, 0.f);
        uint32_t ax[7], ay[7];
        while (true) {
            uint32_t bad = 0;
#pragma unroll
            for (int j = 0; j < 7; j++) { ax[j] = atag; ay[j] = 0; ld_relaxed2_if(ax[j], ay[j], &g_agg[j * 1024 + p], j < mb); }
#pragma unroll
            for (int j = 0; j < 7; j++) bad |= ax[j] ^ atag;
            if (tags_ok(bad)) break;
            __nanosleep(2 * POLLNS);
        }
        float2 carry = make_float2(0.f, 0.f);
#pragma unroll
        for (int j = 0; j < 7; j++) if (j < mb) carry = cfma(l256, carry, make_float2(__uint_as_float(ax[j]), __uint_as_float(ay[j])));
        float2 w = (t & 1) ? l64 : make_float2(1.f, 0.f);
        if (t & 2) w = cmul(w, l128);
        h = cfma(w, carry, h);
        IP(3)
    }
    IP(4)
    d.kind = PEND_HT; d.row = nb * 128 + c.rank * 64 + c.wg * 32; d.col = mb * 256; d.cnt = C_HT + mb;
}

__device__ __forceinline__ uint32_t fresh_tid() { uint32_t t; asm volatile("mov.u32 %0, %%tid.x;" : "=r"(t)); return t; }
__device__ __forceinline__ uint32_t acquire_stage(uint32_t sb, Pipe& p, uint32_t bytes) {
    mbar_wait(sb + B_EMPTY + p.stage * 8, p.phase ^ 1);
    mbar_expect_e(sb + B_FULL + p.stage * 8, bytes);
    return p.stage;
}
__device__ __forceinline__ void producer(const Params& P, const uint32_t sb, const int cta, const uint32_t epoch) {
    Pipe p = {0, 0};
    uint32_t resume = 1;
    const uint32_t e1 = epoch + 1;
    const int rank = cta & 1;
    const uint16_t both = 3 << (__shfl_sync(0xffffffffu, cluster_rank(), 0) & ~1u);
    for (int it = ITEM_OFF(cta >> 1); it < ITEM_OFF((cta >> 1) + 1); it++) {
        const int item = ITEM(it), type = (item >> 8) & 7, mb = (item >> 5) & 7, nb = item & 31, half = item >> 12 & 1, hw = item >> 13;
        if (type == T_CHAIN) {
            const int h = cta / 3, role = cta - h * 3;
#pragma unroll 1
            for (int w = 0; w < 8; w++) {
                mbar_wait(sb + B_EMPTY + (w * 20480 + 20479) / STAGE * 8, 1);
                chain_load(P, sb, cta, w, threadIdx.x & 31, 0);
            }
            uint32_t* flag = &g_cnt(C_FLAG + (role == 2 ? 32 : 0) + h);
            if (role) { wait_count(&g_cnt(C_KV), e1 * 128); fence_async(); }
#pragma unroll 1
            for (int s = 0; s < 64 && role != 0; s++) {
                if (s < 63) {
                    mbar_wait(sb + B_GO, s & 1);
                    tma3d_mc_e(sb + S_KV + (role - 1) * 8192, &P.tm[M_SEG], 0, (role - 1) * 2048 + s * 32, h * 2, sb + B_KVFULL, 7 << ((h & 1) * 3), P.pol[s < 48 ? 8 : 11]);
                    if ((s & 7) == 7) { wait_count(&g_cnt(C_KV + 1 + (s >> 3)), e1 * 128); fence_async(); }
                    tma_prefetch3d_e(&P.tm[M_SEG], 0, (role - 1) * 2048 + s * 32 + 32, h * 2);
                }
                if (s > 0 && ((s & 3) == 0 || s == 63)) {
                    const int i = (s - 1) >> 2;
                    mbar_wait(sb + B_PERS, i & 1);
                    asm volatile("{\n.reg .pred E;\nelect.sync _|E, 0xffffffff;\n@E st.release.gpu.global.u32 [%0], %1;\n}" ::"l"(flag), "r"(epoch * 64 + i * 4 + 4) : "memory");
                }
            }
            if (role == 0) {
                const int lane = threadIdx.x & 31;
                if (lane == 0) mbar_arrive(sb + B_RELM);
#pragma unroll 1
                for (int s = 0; s < 63; s++) {
                    mbar_wait(sb + B_P1, s & 1);
                    if (s > 0) {
                        st_relaxed4(P.xb + xg_buf(s - 1) + h * 2048 + xg_lane(lane), 0, 0, 0, 0);
                        st_relaxed1(P.xb + xg_buf(s - 1) + xg_side(h) + lane * 4, 0);
                        __threadfence();
                    }
                    __syncwarp();
                    if (lane == 0) mbar_arrive(sb + B_RELM);
                }
            }
            if ((threadIdx.x & 31) < M_C1 - 1) asm volatile("prefetch.tensormap [%0];" ::"l"(&P.tm[1 + (threadIdx.x & 31)]) : "memory");
            resume = 0;
            continue;
        }
        const int m0 = mb * 256 + rank * 128, ssm = type >= T_A1;
        const CUtensorMap* ma = &P.tm[max(type, 1) + half * M_HALF];
        const CUtensorMap* mw = &P.tm[type ? M_WV + type : M_WK + (nb >> 4)];
        const int nk = type == T_OP ? 64 : type == T_A2 ? 32 : 16;
        const int a3 = type == T_A1 ? nb * 16 + rank * 8 + hw * 4 : type == T_A2 ? mb * 4 + rank * 2 + hw : (type == T_OP ? 4096 : 0) + m0 + hw * 64;
        const int b3 = type == T_A1 ? mb * 128 + rank * 16 : type == T_A2 ? (nb * 2 + rank) * 128 : (nb & 15) * 4 + rank * 2;
        if (type) {
            wait_count(&g_cnt(type == T_A1 ? C_COEF : (type >> 1) * 8 + mb), e1 * (type == T_A1 ? 4 : 128 >> (type >> 1)));
            fence_async();
        }
        if (type == T_A1) l2_prefetch_e(g_coef + nb * 128 + rank * 64, 1024);
        auto arrived = [&]() {
            const uint32_t t = fresh_tid();
            return __all_sync(0xffffffffu, (int32_t)(ld_acquire(&g_cnt(C_FLAG + (t & 2) * 16 + nb * 2 + (t & 1))) - (epoch * 64 + mb * 8 + rank * 4 + 4)) >= 0);
        };
        bool passed = false;
        mbar_wait(sb + B_RESUME, resume);
#pragma unroll 1
        for (int kt = 0; kt < nk; kt++) {
            if (type == T_QA && kt == 9) passed = arrived();
            const uint32_t st = acquire_stage(sb, p, STAGE - half * 8192), bar = sb + B_FULL + st * 8;
            const int a1 = type == T_A2 ? kt * 64 : 0, b0 = ssm ? (kt & 15) * 64 : 0;
            tma4d_e(sb + st * STAGE + hw * 8192, ma, kt * 64 - a1, a1, a3, bar, P.pol[11]);
            tma4d_mc_e(sb + st * STAGE + 16384 + rank * 16384, mw + (ssm & kt >> 4), b0, ssm ? 0 : kt * 64, b3, bar, both, P.pol[item == (item & 31) + 224 ? 9 : 11]);
            if (type == T_QA && kt < 8) tma_prefetch4d_e(&P.tm[M_OA], nb * 256 + (kt & 3) * 64, (kt >> 2) * 2048 + m0);
            pipe_next(p);
        }
        if (type == T_QA) {
            while (!passed) { passed = arrived(); if (!passed) __nanosleep(POLLNS); }
            fence_async();
        }
        const int q = type == T_QA;
#pragma unroll 1
        for (int e = 0; e < (q ? 4 : type == T_A2 ? 2 : 0); e++) {
            const uint32_t st = acquire_stage(sb, p, q ? 40960 : 32768 + 256), bar = sb + B_FULL + st * 8, dst = sb + st * STAGE;
#pragma unroll 1
            for (int i = 0; i < 2; i++) tma4d_e(dst + i * 16384, &P.tm[q ? M_OA : M_AX], nb * 256 + (e & 1) * 128 + i * 64, 0, q ? (e >> 1) * 2048 + m0 : mb * 128 + rank * 16, bar, P.pol[q ? 3 : 11]);
            const uint8_t* src = q ? (const uint8_t*)(((e >> 1) ? g_vmt : g_km) + ((mb * 8 + rank * 4) * 32 + nb * 2 + (e & 1)) * 512) : (const uint8_t*)(P.Dskip + nb * 256 + e * 128);
#pragma unroll 1
            for (int i = 0; i < (q ? 4 : 1); i++) bulk_g2s_e(dst + 32768 + i * 2048, src + i * 65536, q ? 2048 : 256, bar);
            pipe_next(p);
        }
    }
}

__device__ __forceinline__ uint32_t fresh_ctaid() { uint32_t t; asm volatile("mov.u32 %0, %%ctaid.x;" : "=r"(t)); return t; }
__device__ __forceinline__ void reset_state(const Params& P, Cons& c, Pend& d, uint32_t sb, bool resumed) {
    const uint32_t t = fresh_tid(), b = fresh_ctaid() + P.cta0;
    const int w = __shfl_sync(0xffffffffu, t >> 5, 0);
    c.sb = sb; c.wg = w >> 2; c.wq = w & 3; c.lane = t & 31;
    c.rank = __shfl_sync(0xffffffffu, b & 1, 0); c.pair = __shfl_sync(0xffffffffu, b >> 1, 0);
    c.rel = mapa(sb + B_EMPTY, cluster_rank() ^ (c.lane & 1));
    c.p.stage = 0; c.p.phase = 0;
    c.nst = resumed && c.pair < NCHAIN;
    d = Pend{};
}
#define PROF_ITEM(i, item)

__global__ void __launch_bounds__(384, 1) fused_kernel(const __grid_constant__ Params P) {
    extern __shared__ __align__(1024) uint8_t smem[];
    const uint32_t sb = smem_u32(smem);
    asm volatile("griddepcontrol.launch_dependents;");
    declare_fence(P.zero);
    const int tid = threadIdx.x, lane = tid & 31;
    const int warp = __shfl_sync(0xffffffffu, tid >> 5, 0);
    const int cta = __shfl_sync(0xffffffffu, blockIdx.x + P.cta0, 0), pair = cta >> 1, rank = cta & 1;
    if (tid == 0) {
        if (sb & 1023) spin_fault();
        for (int i = 0; i < NSTAGE; i++) { mbar_init(sb + B_FULL + i * 8, 1); mbar_init(sb + B_EMPTY + i * 8, 16); }
        mbar_init(sb + B_RESUME, 2);
        mbar_init(sb + B_KVFULL, 1);
        mbar_init(sb + B_GO, 3); mbar_init(sb + B_RED, 8); mbar_init(sb + B_P1, 1); mbar_init(sb + B_EPOCH, 1); mbar_init(sb + B_PERS, 8); mbar_init(sb + B_INIT, 8); mbar_init(sb + B_INIT2, 8);
        mbar_init(sb + B_READY, 8);
        for (int i = 0; i < 2; i++) { mbar_init(sb + B_SFULL + i * 8, 4); mbar_init(sb + B_SFREE + i * 8, 1); }
        mbar_init(sb + B_RELM, cta % 3 ? 1 : 2); mbar_init(sb + B_X, 9);
        mbar_init(sb + B_DONE, 2);
        mbar_expect(sb + B_X, 4096);
        sts64(sb + S_EV, 0, 0);
        asm volatile("fence.mbarrier_init.release.cluster;" ::: "memory");
    }
    __syncthreads();
    cluster_sync();
    if (warp >= 8) {
        asm volatile("setmaxnreg.dec.sync.aligned.u32 24;");
        if (warp == 8) {
            producer(P, sb, cta, get_epoch(sb));
            cluster_sync();
        } else if (warp == 9) {
            const uint32_t epoch = __shfl_sync(0xffffffffu, ld_acquire(&g_cnt(C_EPOCH)), 0);
            if (lane == 0) { sts32(sb + S_EPOCH, epoch); mbar_arrive(sb + B_EPOCH); red_release(&g_cnt(C_READ)); }
            __syncwarp();
            if (pair < NCHAIN) pacer(P, sb, cta, lane, epoch);
            if (cta == 0 && lane == 0) {
                for (int n = 0; (int32_t)(ld_acquire(&g_cnt(C_READ)) - (epoch + 1) * (NPAIR * 2)) < 0; n++) if (n > SPIN_LIMIT) spin_fault();
                st_relaxed1(&g_cnt(C_EPOCH), epoch + 1);
            }
            __syncwarp();
            mbar_wait_bounded(sb + B_DONE, 0);
        } else {
            store_warp(P, sb, warp - 10, cta);
        }
    } else {
        asm volatile("setmaxnreg.inc.sync.aligned.u32 240;");
        Cons c;
        Pend d;
        if (pair < NCHAIN) {
            reset_state(P, c, d, sb, false);
            {
                const int item = ITEM(ITEM_OFF(pair));
                PROF_ITEM(0, item)
                float acc[128];
                mainloop<true>(acc, P, c, d, T_KV, 16);
                ISTAMP(4)
                epi_kv(acc, c, d, (item >> 5) & 7, item & 31);
            }
            ISTAMP(9)
            mbar_wait(sb + B_EMPTY + 3 * 8, 1);
            drain_both(c, d);
            ISTAMP(10)
            uint32_t wr[40][4];
            chain_fetch(P, sb, cta, warp, lane, wr);
            PROF_ITEM(1, T_CHAIN << 8)
            chain_bounds(sb, cta, warp, lane, wr);
            ISTAMP(11)
            if (warp < 4) chain_role<false>(P, sb, cta, warp, lane, wr);
            else chain_role<true>(P, sb, cta, warp, lane, wr);
            fence_async_smem();
            bar_sync(1, 256);
            const uint32_t t2 = fresh_tid();
            if (t2 < 2) mbar_arrive_cluster(mapa(sb + B_RESUME, cluster_rank() ^ t2));
        } else if (pair >= NPAIR - 2) {
            const int ch = (pair - (NPAIR - 2)) * 512 + rank * 256 + tid;
            g_coef[ch] = ssm_coef(__bfloat162float(P.Lre[ch]), __bfloat162float(P.Lim[ch]), __bfloat162float(P.logdt[ch]));
            bar_sync(1, 256);
            if (tid == 0) red_release(&g_cnt(C_COEF));
        }
        reset_state(P, c, d, sb, true);
        int it = ITEM_OFF(c.pair) + (c.pair < NCHAIN ? 2 : 0);
        const int end = ITEM_OFF(c.pair + 1);
        for (;; it++) {
            const bool last = it == end;
            const int item = ITEM(it), type = (item >> 8) & 7, mb = (item >> 5) & 7, nb = item & 31;
            const bool idle = (item >> 12) == 3 - 2 * c.wg;
            if (d.kind != PEND_NONE && (last || idle || (ITEM(it - 1) & URGENT) || !bar_and(5 + c.wg, mbar_try(sb + B_FULL + c.p.stage * 8, c.p.phase)))) {
#pragma unroll 1
                while (d.kind != PEND_NONE) drain(P, c, d);
            }
            if (last) break;
            const int nk = type == T_OP ? 64 : type == T_A2 ? 32 : 16;
            PROF_ITEM(it - ITEM_OFF(c.pair), item)
            if (idle) {
#pragma unroll 1
                for (int kt = nk + (type == T_A2 ? 2 : type == T_QA ? 4 : 0); kt > 0; kt--) { wait_full(c); release(c, c.p.stage); pipe_next(c.p); }
                continue;
            }
            float acc[128];
            mainloop(acc, P, c, d, type, nk);
            if (type == T_KV) epi_kv(acc, c, d, mb, nb);
            else if (type == T_QA) epi_qa(acc, c, d, mb, nb);
            else if (type == T_OP) epi_op(acc, c, d, mb, nb);
            else if (type == T_A1) epi_a1(acc, P, c, d, mb, nb);
            else epi_a2(acc, P, c, mb, nb * 256);
        }
        staging_wait(c);
        staging_post(c, PEND_NONE, 0, 0, 0);
        if (c.wq == 0 && c.lane == 0) mbar_arrive(sb + B_DONE);
        cluster_sync();
    }
}

typedef CUresult (*EncodeFn)(CUtensorMap*, CUtensorMapDataType, cuuint32_t, void*, const cuuint64_t*, const cuuint64_t*, const cuuint32_t*, const cuuint32_t*,
                             CUtensorMapInterleave, CUtensorMapSwizzle, CUtensorMapL2promotion, CUtensorMapFloatOOBfill);
void encode(EncodeFn fn, CUtensorMap* m, const void* base, int rank, const uint64_t* dims, const uint64_t* strides, const uint32_t* box, CUtensorMapSwizzle swz = CU_TENSOR_MAP_SWIZZLE_128B) {
    cuuint64_t d[5], s[5]; cuuint32_t b[5], e[5];
    for (int i = 0; i < rank; i++) { d[i] = dims[i]; b[i] = box[i]; e[i] = 1; if (i) s[i - 1] = strides[i - 1]; }
    fn(m, CU_TENSOR_MAP_DATA_TYPE_BFLOAT16, rank, (void*)base, d, s, b, e, CU_TENSOR_MAP_INTERLEAVE_NONE, swz,
       CU_TENSOR_MAP_L2_PROMOTION_L2_256B, CU_TENSOR_MAP_FLOAT_OOB_FILL_NONE);
}
void map_kmajor(EncodeFn fn, CUtensorMap* m, const void* base, uint64_t rows, uint64_t cols, uint32_t box_rows) {
    const uint64_t d[4] = {cols, 1, 1, rows}, s[3] = {cols * 2, cols * 2, cols * 2}; const uint32_t b[4] = {64, 1, 1, box_rows};
    encode(fn, m, base, 4, d, s, b);
}
void map_mnmajor(EncodeFn fn, CUtensorMap* m, const void* base, uint64_t krows, uint64_t cols, uint32_t groups = 2) {
    const uint64_t d[4] = {64, krows, 1, cols / 64}, s[3] = {cols * 2, 128, 128}; const uint32_t b[4] = {64, 64, 1, groups};
    encode(fn, m, base, 4, d, s, b);
}
void map_store(EncodeFn fn, CUtensorMap* m, const void* base, uint64_t rows, uint64_t cols) {
    const uint64_t d[2] = {cols, rows}, s[1] = {cols * 2}; const uint32_t b[2] = {64, 32};
    encode(fn, m, base, 2, d, s, b);
}

}

extern "C" void kernel_launch(void* const* d_in, const int* in_sizes, int n_in, void* d_out, int out_size) {
    static Params P;
    static EncodeFn fn = nullptr;
    if (!fn) {
        cudaDriverEntryPointQueryResult q;
        cudaGetDriverEntryPoint("cuTensorMapEncodeTiled", (void**)&fn, cudaEnableDefault, &q);
        cudaFuncSetAttribute(fused_kernel, cudaFuncAttributeMaxDynamicSharedMemorySize, S_TOTAL);
    }
    const bf16* in[15];
    for (int i = 0; i < 15; i++) in[i] = (const bf16*)d_in[i];
    void *kvo, *ht;
    cudaGetSymbolAddress(&kvo, g_kvo);
    cudaGetSymbolAddress(&ht, g_ht);
    map_kmajor(fn, &P.tm[M_BX], in[9], 2048, 1024, 128);
    map_mnmajor(fn, &P.tm[M_WQ], in[11], 1024, 4096);
    map_mnmajor(fn, &P.tm[M_WK], in[12], 1024, 4096);
    map_mnmajor(fn, &P.tm[M_WV], in[13], 1024, 4096);
    map_mnmajor(fn, &P.tm[M_WO], in[14], 4096, 1024);
    map_kmajor(fn, &P.tm[M_OA], kvo, 3 * 2048, 4096, 128);
    P.swap_ri = in[4] < in[3];
    {
        const bf16* lo = P.swap_ri ? in[4] : in[3];
        const uint64_t diff = (uint64_t)((const char*)(P.swap_ri ? in[3] : in[4]) - (const char*)lo);
        const uint64_t d[4] = {1024, 8, 2, 128}, s[3] = {2048, diff, 16384}; const uint32_t b[4] = {64, 8, 2, 8}, bh[4] = {64, 8, 2, 4};
        encode(fn, &P.tm[M_AB], lo, 4, d, s, b);
        encode(fn, &P.tm[M_AB + M_HALF], lo, 4, d, s, bh);
    }
    {
        const uint64_t d[4] = {1024, 2, 4, 1024}, s[3] = {2048, 64 * 2048, 4096}; const uint32_t b[4] = {64, 2, 4, 16};
        encode(fn, &P.tm[M_AX], in[0], 4, d, s, b);
    }
    map_mnmajor(fn, &P.tm[M_HT], ht, 2048, 2048);
    map_kmajor(fn, &P.tm[M_CRE], in[5], 1024, 1024, 128);
    map_kmajor(fn, &P.tm[M_CIM], in[6], 1024, 1024, 128);
    map_store(fn, &P.tm[M_KVO], kvo, 3 * 2048, 4096);
    map_store(fn, &P.tm[M_HTS], ht, 2048, 2048);
    map_kmajor(fn, &P.tm[M_BX + M_HALF], in[9], 2048, 1024, 64);
    map_kmajor(fn, &P.tm[M_OA + M_HALF], kvo, 3 * 2048, 4096, 64);
    map_mnmajor(fn, &P.tm[M_HT + M_HALF], ht, 2048, 2048, 1);
    for (int i = 0; i < 3; i++) {
        const uint64_t d[3] = {64, 1024, 64}, s[2] = {8192, 128}; const uint32_t b[3] = {64, 16, 2};
        encode(fn, &P.tm[M_C1 + i], in[11 + i], 3, d, s, b);
    }
    {
        const uint64_t d[2] = {1024, 4096}, s[1] = {2048}; const uint32_t b[2] = {32, 32};
        encode(fn, &P.tm[M_CO], in[14], 2, d, s, b, CU_TENSOR_MAP_SWIZZLE_64B);
    }
    {
        const uint64_t d[3] = {64, 3 * 2048, 64}, s[2] = {8192, 128}; const uint32_t b[3] = {64, 32, 2};
        encode(fn, &P.tm[M_SEG], kvo, 3, d, s, b);
    }
    void* xs;
    cudaGetSymbolAddress(&xs, g_x);
    P.xb = (uint8_t*)(((uintptr_t)xs + (2u << 20) - 1) & ~(uintptr_t)((2u << 20) - 1));
    P.Wq = in[11]; P.Wk = in[12]; P.Wv = in[13]; P.Wo = in[14]; P.mem0 = in[10]; P.Bx = in[9];
    P.Ax = in[0]; P.Lre = in[1]; P.Lim = in[2]; P.logdt = in[7]; P.Dskip = in[8];
    P.out = (float*)d_out;
    int pv[10] = {1300, 0, 110, 0, 330, 0, 32, 32, 0, 0};
    int ef = 779;
    for (int i = 0; i < 12; i++) P.pol[i] = (ef >> i & 1) ? 0x12F0000000000000ull : 0x1000000000000000ull;
    P.dly = pv[0]; P.mrg = pv[2];
    P.rd = pv[4]; P.guard = pv[5]; P.clampv = pv[6]; P.clamp0 = pv[7]; P.kvd = pv[9]; P.xd = pv[8];
    cudaLaunchConfig_t cfg = {};
    cudaLaunchAttribute at[2];
    cfg.blockDim = dim3(384); cfg.dynamicSmemBytes = S_TOTAL; cfg.stream = cudaStreamPerThread; cfg.attrs = at;
    at[0].id = cudaLaunchAttributeClusterDimension;
    at[0].val.clusterDim.y = at[0].val.clusterDim.z = 1;
    at[1].id = cudaLaunchAttributeProgrammaticStreamSerialization;
    at[1].val.programmaticStreamSerializationAllowed = 1;
    for (int i = 0; i < 2; i++) {
        P.cta0 = i ? 2 * NCHAIN : 0;
        cfg.gridDim = dim3(i ? 2 * (NPAIR - NCHAIN) : 2 * NCHAIN);
        at[0].val.clusterDim.x = i ? 2 : 6;
        cfg.numAttrs = 1 + i;
        cudaLaunchKernelEx(&cfg, fused_kernel, P);
    }
}
```

```cpp
#include <cuda_runtime.h>
#include <cuda_bf16.h>
#include <cuda.h>
#include <stdint.h>
#include <string.h>

typedef __nv_bfloat16 bf16;

namespace {

constexpr int SPIN_LIMIT = 1 << 22;
#define POLLNS 100
constexpr int NPAIR = 66;
constexpr int NCHAIN = 48;
enum { T_KV = 0, T_QA = 1, T_OP = 2, T_A1 = 3, T_A2 = 4, T_CHAIN = 5 };
constexpr int URGENT = 2048;
constexpr int LAST = 16384;
constexpr int HALF = 4096;
enum { M_BX = 1, M_OA, M_AB, M_HT, M_HALF = 4, M_WK = 9, M_WV, M_WQ, M_WO, M_AX, M_CRE, M_CIM, M_KVO, M_HTS, M_C1, M_CO = M_C1 + 3, M_SEG, M_COUNT };
enum { C_KV = 0, C_O = 8, C_HT = 16, C_READ = 24, C_EPOCH = 25, C_COEF = 26, C_XMAX = 27, C_XCNT = 28, C_FLAG = 32 };

struct Params {
    CUtensorMap tm[M_COUNT];
    const bf16 *Wq, *Wk, *Wv, *Wo, *mem0, *Bx, *Ax, *Lre, *Lim, *logdt, *Dskip;
    float* out;
    uint8_t* xb;
    int swap_ri, zero;
    int dly, mrg, rd, guard, clampv, clamp0, kvd, xd;
    uint64_t pol[12];
    uint16_t cta0;
};

__constant__ uint16_t c_off[67] = {0, 4, 8, 12, 17, 21, 25, 29, 33, 38, 43, 48, 53, 58, 63, 68, 72, 76, 81, 86, 90, 94, 98, 102, 106, 110, 114, 118, 122, 127, 131, 135, 139, 144, 149, 153, 157, 162, 166, 170, 174, 179, 183, 188, 192, 196, 201, 206, 211, 231, 251, 270, 289, 308, 328, 347, 365, 385, 405, 425, 445, 465, 485, 505, 524, 543, 562};
__constant__ uint16_t c_items[700] = {
    0, 1280, 2473, 17026, 16, 1280, 2474, 16898, 32, 1280, 2476, 16995, 1, 1280, 486, 2823, 17473, 17, 1280, 495, 17059, 33, 1280, 417,
    16928, 2, 1280, 773, 16962, 18, 1280, 870, 17123, 34, 1280, 806, 807, 17571, 3, 1280, 2504, 2979, 29346, 19, 1280, 2503, 2945, 17505,
    35, 1280, 2529, 3043, 21154, 4, 1280, 2502, 770, 17440, 20, 1280, 2539, 932, 17537, 36, 1280, 2509, 2946, 17411, 5, 1280, 482, 16931,
    21, 1280, 2475, 16896, 37, 1280, 2471, 2919, 17472, 6, 1280, 2510, 834, 17507, 22, 1280, 489, 16993, 38, 1280, 2469, 17089, 7, 1280,
    2820, 16899, 23, 1280, 833, 17121, 39, 1280, 774, 17088, 8, 1280, 483, 16960, 24, 1280, 488, 17090, 40, 1280, 453, 17122, 9, 1280,
    449, 16992, 25, 1280, 2506, 963, 17409, 41, 1280, 492, 17025, 10, 1280, 451, 16897, 26, 1280, 416, 16929, 42, 1280, 2532, 866, 17568,
    11, 1280, 459, 802, 17634, 27, 1280, 2538, 16961, 43, 1280, 448, 17027, 12, 1280, 2508, 2948, 21216, 28, 1280, 2498, 17056, 44, 1280,
    431, 17091, 13, 1280, 2511, 17024, 29, 1280, 2466, 934, 17632, 45, 1280, 424, 16930, 14, 1280, 494, 868, 17538, 30, 1280, 430, 16994,
    46, 1280, 2528, 16963, 15, 1280, 838, 839, 17601, 31, 1280, 804, 2951, 17410, 47, 1280, 836, 2977, 17506, 48, 66, 84, 102, 256,
    124, 142, 160, 175, 191, 207, 224, 239, 230, 328, 386, 331, 928, 3010, 17504, 49, 67, 85, 103, 257, 125, 143, 161, 176,
    192, 208, 225, 240, 241, 399, 354, 335, 835, 998, 17474, 50, 68, 86, 104, 258, 126, 144, 162, 177, 193, 209, 226, 2350,
    388, 2412, 2819, 803, 2983, 17442, 51, 69, 87, 105, 259, 127, 145, 163, 178, 194, 210, 2438, 2446, 385, 355, 391, 899, 997,
    17600, 52, 70, 88, 106, 260, 128, 146, 164, 179, 195, 211, 329, 298, 2817, 395, 367, 2913, 3041, 17408, 53, 71, 89, 107,
    261, 129, 147, 165, 180, 196, 212, 229, 244, 245, 330, 297, 397, 837, 3008, 17569, 54, 72, 90, 108, 262, 130, 148, 166,
    181, 197, 213, 321, 394, 396, 326, 2370, 902, 2981, 17539, 55, 73, 91, 109, 263, 131, 149, 167, 182, 198, 214, 231, 327,
    362, 387, 299, 487, 17057, 56, 74, 92, 110, 264, 132, 150, 168, 183, 199, 215, 232, 247, 227, 323, 358, 366, 800, 3047,
    17635, 57, 75, 93, 111, 265, 133, 151, 169, 184, 200, 216, 233, 248, 254, 359, 334, 360, 896, 965, 17536, 58, 76, 94,
    112, 266, 134, 152, 170, 185, 201, 217, 234, 249, 243, 352, 332, 384, 901, 992, 17602, 59, 77, 95, 113, 267, 135, 153,
    171, 186, 202, 218, 235, 250, 255, 420, 356, 320, 832, 3009, 17475, 60, 78, 96, 114, 268, 136, 154, 172, 187, 203, 219,
    236, 251, 246, 419, 452, 361, 805, 3014, 17570, 61, 79, 97, 115, 269, 137, 155, 173, 188, 204, 220, 237, 252, 242, 392,
    457, 485, 864, 3015, 17441, 62, 80, 98, 116, 270, 138, 156, 174, 189, 205, 221, 238, 253, 228, 2349, 333, 295, 867, 3044,
    17443, 63, 81, 99, 117, 271, 139, 157, 288, 190, 292, 293, 296, 300, 429, 303, 493, 869, 3042, 17633, 64, 82, 100, 118,
    120, 122, 140, 158, 289, 206, 222, 294, 393, 422, 2413, 363, 801, 930, 17603, 65, 83, 101, 119, 121, 123, 141, 159, 290,
    291, 223, 389, 353, 2405, 324, 325, 768, 3012, 29408,
};
#define ITEM_OFF(p) c_off[p]
#define ITEM(i) c_items[i]

__device__ __align__(1024) bf16 g_kvo[3 * 2048 * 4096];
__device__ __align__(1024) bf16 g_ht[2048 * 2048];
__device__ __align__(1024) uint8_t g_x[4 << 20];
__device__ __align__(1024) uint32_t g_km[64 * 32 * 512];
__device__ __align__(1024) uint32_t g_vmt[64 * 32 * 512];
__device__ __align__(1024) float2 g_agg[8 * 1024];
__device__ __align__(1024) float4 g_coef[1024];
__device__ __align__(1024) uint32_t g_cntl[128 * 32];
#define g_cnt(i) g_cntl[(i) * 32]
__device__ __align__(1024) uint32_t g_hint[96 * 32];
#define PROF(i)
#define PROFDUMP()
#define PROFP(i)
constexpr int XG_SIDE = 65536, XG_T = 98304;
__device__ __forceinline__ uint32_t xg_buf(int b) { return (b & 1) * 128 + (b & 2) * 256 + (b & 4) * 32768; }
__device__ __forceinline__ uint32_t xg_lane(uint32_t lane) { return (lane >> 4) * 1024 + (lane & 8) * 32 + (lane & 7) * 16; }
__device__ __forceinline__ uint32_t xg_side(int b) { return XG_SIDE + (b >> 1) * 1024 + (b & 1) * 256; }

constexpr int STAGE = 49152, NSTAGE = 4;
constexpr int S_STG = NSTAGE * STAGE;
constexpr int S_BAR = S_STG + 32768;
constexpr int B_FULL = S_BAR, B_EMPTY = S_BAR + 32, B_RESUME = S_BAR + 64, B_KVFULL = S_BAR + 72, B_GO = S_BAR + 88, B_X = S_BAR + 96, B_PERS = S_BAR + 104,
              B_INIT = S_BAR + 112, B_RELM = S_BAR + 120, B_READY = S_BAR + 136, B_SFULL = S_BAR + 144, B_SFREE = S_BAR + 160, S_DESC = S_BAR + 176, B_RED = S_BAR + 216;
constexpr int S_EV = S_BAR + 80, S_EO = S_BAR + 84, B_INIT2 = S_BAR + 128, S_SC = S_BAR + 208, S_ISC = S_EV;
constexpr int S_XV = S_BAR + 256, S_LOG = S_XV + 2048;
constexpr int S_TOTAL = S_LOG + 768;
#define NRA 5
#define NRB 3
constexpr int S_W1 = 0;
constexpr int S_W2 = 4 * 4096 * (16 - NRA - NRB);
constexpr int S_KV = 188416;
constexpr int S_P1 = S_KV + 16384;
constexpr int S_X = S_P1 + 16384;
constexpr int S_SX = S_P1, S_OX = S_P1 + 2048;
constexpr int S_EM = S_X + 4096, S_TO = S_EM + 32, B_DONE = S_BAR + 224, B_P1 = S_BAR + 232, B_EPOCH = S_BAR + 240, S_EPOCH = S_BAR + 248;
static_assert(S_TO + 32 <= S_BAR && S_KV % 1024 == 0 && S_TOTAL <= 232448, "chain smem layout");

template <int V> struct IC { static constexpr int value = V; };
template <int B, int E, typename F> __device__ __forceinline__ void static_for(F&& f) { if constexpr (B < E) { f(IC<B>{}); static_for<B + 1, E>(f); } }
__device__ __forceinline__ uint32_t cluster_rank() { uint32_t r; asm volatile("mov.u32 %0, %%cluster_ctarank;" : "=r"(r)); return r; }
__device__ __forceinline__ void spin_fault() { asm volatile("st.global.u32 [%0], 0;" ::"l"(0ull) : "memory"); }
__device__ __forceinline__ uint32_t smem_u32(const void* p) { return (uint32_t)__cvta_generic_to_shared(p); }
__device__ __forceinline__ uint32_t opq(uint32_t x, int lane) { return __shfl_sync(0xffffffffu, x, lane); }
__device__ __forceinline__ uint32_t mapa(uint32_t a, uint32_t r) { uint32_t d; asm volatile("mapa.shared::cluster.u32 %0, %1, %2;" : "=r"(d) : "r"(a), "r"(r)); return d; }
__device__ __forceinline__ void mma16816(float* d, uint32_t a0, uint32_t a1, uint32_t a2, uint32_t a3, uint32_t b0, uint32_t b1) {
    asm("mma.sync.aligned.m16n8k16.row.col.f32.bf16.bf16.f32 {%0,%1,%2,%3}, {%4,%5,%6,%7}, {%8,%9}, {%0,%1,%2,%3};"
        : "+f"(d[0]), "+f"(d[1]), "+f"(d[2]), "+f"(d[3]) : "r"(a0), "r"(a1), "r"(a2), "r"(a3), "r"(b0), "r"(b1));
}
__device__ __forceinline__ void mma1688(float* d, uint32_t a0, uint32_t a1, uint32_t b0) {
    asm("mma.sync.aligned.m16n8k8.row.col.f32.bf16.bf16.f32 {%0,%1,%2,%3}, {%4,%5}, {%6}, {%0,%1,%2,%3};"
        : "+f"(d[0]), "+f"(d[1]), "+f"(d[2]), "+f"(d[3]) : "r"(a0), "r"(a1), "r"(b0));
}
__device__ __forceinline__ void ldsm4(uint32_t* r, uint32_t a) {
    asm volatile("ldmatrix.sync.aligned.m8n8.x4.shared.b16 {%0,%1,%2,%3}, [%4];" : "=r"(r[0]), "=r"(r[1]), "=r"(r[2]), "=r"(r[3]) : "r"(a));
}
__device__ __forceinline__ void ldsm4t(uint32_t* r, uint32_t a) {
    asm volatile("ldmatrix.sync.aligned.m8n8.x4.trans.shared.b16 {%0,%1,%2,%3}, [%4];" : "=r"(r[0]), "=r"(r[1]), "=r"(r[2]), "=r"(r[3]) : "r"(a));
}
__device__ __forceinline__ void stsm4(uint32_t a, uint32_t r0, uint32_t r1, uint32_t r2, uint32_t r3) {
    asm volatile("stmatrix.sync.aligned.m8n8.x4.shared.b16 [%0], {%1,%2,%3,%4};" ::"r"(a), "r"(r0), "r"(r1), "r"(r2), "r"(r3) : "memory");
}
__device__ __forceinline__ void stsm4t(uint32_t a, uint32_t r0, uint32_t r1, uint32_t r2, uint32_t r3) {
    asm volatile("stmatrix.sync.aligned.m8n8.x4.trans.shared.b16 [%0], {%1,%2,%3,%4};" ::"r"(a), "r"(r0), "r"(r1), "r"(r2), "r"(r3) : "memory");
}
__device__ __forceinline__ uint32_t movm(uint32_t a) { uint32_t d; asm volatile("movmatrix.sync.aligned.m8n8.trans.b16 %0, %1;" : "=r"(d) : "r"(a)); return d; }
__device__ __forceinline__ uint32_t pack2(float lo, float hi) { uint32_t d; asm("cvt.rn.bf16x2.f32 %0, %1, %2;" : "=r"(d) : "f"(hi), "f"(lo)); return d; }
__device__ __forceinline__ uint32_t prmt(uint32_t a, uint32_t b, uint32_t s) { uint32_t d; asm("prmt.b32 %0, %1, %2, %3;" : "=r"(d) : "r"(a), "r"(b), "r"(s)); return d; }
__device__ __forceinline__ uint32_t pack2h(float lo, float hi) { uint32_t d; asm("cvt.rn.f16x2.f32 %0, %1, %2;" : "=r"(d) : "f"(hi), "f"(lo)); return d; }
__device__ __forceinline__ uint32_t h2bf(uint32_t a, uint32_t b) {
    uint32_t d;
    asm("{\n.reg .b16 l, h, u;\n.reg .f32 x, y;\nmov.b32 {l, u}, %1;\ncvt.f32.f16 x, l;\nmov.b32 {u, h}, %2;\ncvt.f32.f16 y, h;\ncvt.rn.bf16x2.f32 %0, y, x;\n}" : "=r"(d) : "r"(a), "r"(b));
    return d;
}
__device__ __forceinline__ void cvt_block(uint32_t* u, uint32_t& x, uint32_t sel) {
    const uint32_t a = prmt(u[0], u[0], sel), b = prmt(u[1], u[1], sel), c = prmt(u[2], u[2], sel), d = prmt(u[3], x, sel);
    x ^= u[3] ^ d;
    u[0] = h2bf(a, a); u[1] = h2bf(b, b); u[2] = h2bf(c, c); u[3] = h2bf(d, d);
}
__device__ __forceinline__ uint32_t amax(uint32_t a, uint32_t b) { uint32_t d; asm("max.xorsign.abs.bf16x2 %0, %1, %2;" : "=r"(d) : "r"(a), "r"(b)); return d; }
__device__ __forceinline__ uint32_t amax4(uint32_t m, const uint32_t* v) { return amax(amax(m, amax(v[0], v[1])), amax(v[2], v[3])); }
__device__ __forceinline__ uint32_t warp_exp(uint32_t m) { return __reduce_max_sync(0xffffffffu, max(m & 0x7f80u, (m >> 16) & 0x7f80u)) >> 7; }
__device__ __forceinline__ void red_max_shared(uint32_t a, uint32_t x) { asm volatile("red.shared.max.u32 [%0], %1;" ::"r"(a), "r"(x) : "memory"); }
__device__ __forceinline__ uint32_t mul_bf2(uint32_t a, uint32_t b) { uint32_t d; asm("mul.rn.bf16x2 %0, %1, %2;" : "=r"(d) : "r"(a), "r"(b)); return d; }
__device__ __forceinline__ float bf_lo(uint32_t u) { return __uint_as_float(u << 16); }
__device__ __forceinline__ float bf_hi(uint32_t u) { return __uint_as_float(u & 0xffff0000u); }
__device__ __forceinline__ float ex2(float x) { float y; asm("ex2.approx.ftz.f32 %0, %1;" : "=f"(y) : "f"(x)); return y; }
__device__ __forceinline__ float rcp(float x) { float y; asm("rcp.approx.ftz.f32 %0, %1;" : "=f"(y) : "f"(x)); return y; }
__device__ __forceinline__ void st_relaxed4(const void* p, uint32_t a, uint32_t b, uint32_t c, uint32_t d) {
    asm volatile("{\n.reg .b128 t;\nmov.b128 t, {%1,%2,%3,%4};\nst.relaxed.gpu.global.b128 [%0], t;\n}" ::"l"(p), "r"(a), "r"(b), "r"(c), "r"(d) : "memory");
}
__device__ __forceinline__ void st_relaxed2(const void* p, uint32_t a, uint32_t b) {
    asm volatile("{\n.reg .b64 t;\nmov.b64 t, {%1,%2};\nst.relaxed.gpu.global.b64 [%0], t;\n}" ::"l"(p), "r"(a), "r"(b) : "memory");
}
__device__ __forceinline__ void ld_relaxed2_if(uint32_t& a, uint32_t& b, const void* p, bool on) {
    asm volatile("{\n.reg .pred P;\n.reg .b64 t;\nsetp.ne.u32 P, %3, 0;\nmov.b64 t, {%0,%1};\n@P ld.relaxed.gpu.global.b64 t, [%2];\nmov.b64 {%0,%1}, t;\n}" : "+r"(a), "+r"(b) : "l"(p), "r"((uint32_t)on) : "memory");
}
__device__ __forceinline__ void ld_relaxed4(uint32_t* v, const void* p) {
    asm volatile("ld.relaxed.gpu.global.L1::no_allocate.v4.b32 {%0,%1,%2,%3}, [%4];" : "=r"(v[0]), "=r"(v[1]), "=r"(v[2]), "=r"(v[3]) : "l"(p) : "memory");
}
__device__ __forceinline__ void ld_relaxed1n(uint32_t& v, const void* p) { asm volatile("ld.relaxed.gpu.global.L1::no_allocate.b32 %0, [%1];" : "=r"(v) : "l"(p) : "memory"); }
__device__ __forceinline__ void red_add4(const void* p, uint32_t a, uint32_t b, uint32_t c, uint32_t d) {
    asm volatile("red.relaxed.gpu.global.add.noftz.v4.f16x2 [%0], {%1,%2,%3,%4};" ::"l"(p), "r"(a), "r"(b), "r"(c), "r"(d) : "memory");
}
__device__ __forceinline__ void red_add1(const void* p, uint32_t a) { asm volatile("red.relaxed.gpu.global.add.noftz.f16x2 [%0], %1;" ::"l"(p), "r"(a) : "memory"); }
__device__ __forceinline__ void ld_relaxed2(uint32_t* v, const void* p) {
    asm volatile("{\n.reg .b64 t;\nld.relaxed.gpu.global.L1::no_allocate.b64 t, [%2];\nmov.b64 {%0,%1}, t;\n}" : "=r"(v[0]), "=r"(v[1]) : "l"(p) : "memory");
}
__device__ __forceinline__ uint32_t ld_relaxed1(const void* p) { uint32_t v; asm volatile("ld.relaxed.gpu.global.u32 %0, [%1];" : "=r"(v) : "l"(p) : "memory"); return v; }
__device__ __forceinline__ void st_relaxed1(const void* p, uint32_t v) { asm volatile("st.relaxed.gpu.global.u32 [%0], %1;" ::"l"(p), "r"(v) : "memory"); }
__device__ __forceinline__ uint32_t ld_acquire(const void* p) { uint32_t v; asm volatile("ld.acquire.gpu.global.u32 %0, [%1];" : "=r"(v) : "l"(p) : "memory"); return v; }
__device__ __forceinline__ void red_relaxed(void* p) { asm volatile("red.relaxed.gpu.global.add.u32 [%0], 1;" ::"l"(p) : "memory"); }
__device__ __forceinline__ void red_release(void* p) { asm volatile("red.release.gpu.global.add.u32 [%0], 1;" ::"l"(p) : "memory"); }
__device__ __forceinline__ void st_stream2(float* p, float a, float b) { asm volatile("st.global.cs.v2.f32 [%0], {%1, %2};" ::"l"(p), "f"(a), "f"(b) : "memory"); }
__device__ __forceinline__ void fence_async() { asm volatile("fence.proxy.async.global;" ::: "memory"); }
__device__ __forceinline__ void fence_async_smem() { asm volatile("fence.proxy.async.shared::cta;" ::: "memory"); }
__device__ __forceinline__ void wait_count(const uint32_t* p, uint32_t target) {
    while ((int32_t)(ld_acquire(p) - target) < 0) __nanosleep(POLLNS);
}
__device__ __forceinline__ void bar_sync(int id, int n) { asm volatile("bar.sync %0, %1;" ::"r"(id), "r"(n) : "memory"); }
__device__ __forceinline__ bool bar_and(int id, bool v) {
    uint32_t r;
    asm volatile("{\n.reg .pred P, Q;\nsetp.ne.u32 Q, %2, 0;\nbar.red.and.pred P, %1, 128, Q;\nselp.u32 %0, 1, 0, P;\n}" : "=r"(r) : "r"(id), "r"((uint32_t)v) : "memory");
    return r;
}
__device__ __forceinline__ void bar_arrive(int id, int n) { asm volatile("bar.arrive %0, %1;" ::"r"(id), "r"(n) : "memory"); }
__device__ __forceinline__ void lds128(uint32_t* v, uint32_t a) { asm volatile("ld.shared.v4.b32 {%0,%1,%2,%3}, [%4];" : "=r"(v[0]), "=r"(v[1]), "=r"(v[2]), "=r"(v[3]) : "r"(a) : "memory"); }
__device__ __forceinline__ uint32_t lds32(uint32_t a) { uint32_t v; asm volatile("ld.shared.b32 %0, [%1];" : "=r"(v) : "r"(a) : "memory"); return v; }
__device__ __forceinline__ void lds64(uint32_t* v, uint32_t a) { asm volatile("ld.shared.v2.b32 {%0,%1}, [%2];" : "=r"(v[0]), "=r"(v[1]) : "r"(a) : "memory"); }
__device__ __forceinline__ void lds64f(float* v, uint32_t a) { asm volatile("ld.shared.v2.f32 {%0,%1}, [%2];" : "=f"(v[0]), "=f"(v[1]) : "r"(a) : "memory"); }
__device__ __forceinline__ void sts128(uint32_t a, const uint32_t* v) { asm volatile("st.shared.v4.b32 [%0], {%1,%2,%3,%4};" ::"r"(a), "r"(v[0]), "r"(v[1]), "r"(v[2]), "r"(v[3]) : "memory"); }
__device__ __forceinline__ void sts64(uint32_t a, uint32_t x, uint32_t y) { asm volatile("st.shared.v2.b32 [%0], {%1,%2};" ::"r"(a), "r"(x), "r"(y) : "memory"); }
__device__ __forceinline__ void sts32(uint32_t a, uint32_t x) { asm volatile("st.shared.b32 [%0], %1;" ::"r"(a), "r"(x) : "memory"); }
__device__ __forceinline__ bool mbar_try(uint32_t b, uint32_t par) {
    uint32_t ok;
    asm volatile("{\n.reg .pred P;\nmbarrier.test_wait.parity.shared::cta.b64 P, [%1], %2;\nselp.u32 %0, 1, 0, P;\n}" : "=r"(ok) : "r"(b), "r"(par) : "memory");
    return ok;
}
__device__ __forceinline__ void mbar_wait(uint32_t b, uint32_t par) {
    asm volatile("{\n.reg .pred P;\nW: mbarrier.try_wait.parity.shared::cta.b64 P, [%0], %1;\n@!P bra W;\n}" ::"r"(b), "r"(par) : "memory");
}
__device__ __forceinline__ void mbar_wait_bounded(uint32_t b, uint32_t par) {
    asm volatile("{\n.reg .pred P, Q;\n.reg .u32 t, u;\nmov.u32 t, %%globaltimer_lo;\nW: mbarrier.try_wait.parity.shared::cta.b64 P, [%0], %1;\n"
                 "mov.u32 u, %%globaltimer_lo;\nsub.u32 u, u, t;\nsetp.gt.u32 Q, u, 2000000000;\n@Q st.global.u32 [%2], 0;\n@!P bra W;\n}" ::"r"(b), "r"(par), "l"(0ull) : "memory");
}
__device__ __forceinline__ void declare_fence(int zero) { asm volatile(".reg .pred PNEVER;\nsetp.ne.u32 PNEVER, %0, 0;" ::"r"(zero)); }
__device__ __forceinline__ void sched_fence() { asm volatile("{\n.reg .pred Q;\n.reg .u32 x;\n@!PNEVER bra D;\nF: ld.volatile.global.u32 x, [%0];\nsetp.ne.u32 Q, x, 0;\n@Q bra F;\nD:\n}" ::"l"(0ull) : "memory"); }
__device__ __forceinline__ void mbar_init(uint32_t b, uint32_t n) { asm volatile("mbarrier.init.shared::cta.b64 [%0], %1;" ::"r"(b), "r"(n) : "memory"); }
__device__ __forceinline__ void mbar_expect(uint32_t b, uint32_t bytes) { asm volatile("mbarrier.arrive.expect_tx.shared::cta.b64 _, [%0], %1;" ::"r"(b), "r"(bytes) : "memory"); }
__device__ __forceinline__ void mbar_arrive(uint32_t b) { asm volatile("mbarrier.arrive.shared::cta.b64 _, [%0];" ::"r"(b) : "memory"); }
__device__ __forceinline__ void mbar_arrive_cluster(uint32_t b) { asm volatile("mbarrier.arrive.shared::cluster.b64 _, [%0];" ::"r"(b) : "memory"); }
__device__ __forceinline__ void cluster_sync() { asm volatile("barrier.cluster.arrive.relaxed.aligned;\nbarrier.cluster.wait.aligned;" ::: "memory"); }
__device__ __forceinline__ uint32_t get_epoch(uint32_t sb) { mbar_wait(sb + B_EPOCH, 0); return __shfl_sync(0xffffffffu, lds32(sb + S_EPOCH), 0); }
__device__ __forceinline__ void tma2d(uint32_t dst, const CUtensorMap* m, int c0, int c1, uint32_t bar) {
    asm volatile("cp.async.bulk.tensor.2d.shared::cluster.global.mbarrier::complete_tx::bytes [%0], [%1, {%2, %3}], [%4];" ::"r"(dst), "l"(m), "r"(c0), "r"(c1), "r"(bar) : "memory");
}
__device__ __forceinline__ void tma3d(uint32_t dst, const CUtensorMap* m, int c0, int c1, int c2, uint32_t bar) {
    asm volatile("cp.async.bulk.tensor.3d.shared::cluster.global.mbarrier::complete_tx::bytes [%0], [%1, {%2, %3, %4}], [%5];" ::"r"(dst), "l"(m), "r"(c0), "r"(c1), "r"(c2), "r"(bar) : "memory");
}
__device__ __forceinline__ void l2_prefetch(const void* src, uint32_t bytes) { asm volatile("cp.async.bulk.prefetch.L2.global [%0], %1;" ::"l"(src), "r"(bytes) : "memory"); }
__device__ __forceinline__ void mbar_expect_e(uint32_t b, uint32_t bytes) {
    asm volatile("{\n.reg .pred E;\nelect.sync _|E, 0xffffffff;\n@E mbarrier.arrive.expect_tx.shared::cta.b64 _, [%0], %1;\n}" ::"r"(b), "r"(bytes) : "memory");
}
__device__ __forceinline__ void tma3d_mc_e(uint32_t dst, const CUtensorMap* m, int c0, int c1, int c2, uint32_t bar, uint16_t mask, uint64_t pol) {
    asm volatile("{\n.reg .pred E;\nelect.sync _|E, 0xffffffff;\n@E cp.async.bulk.tensor.3d.shared::cluster.global.mbarrier::complete_tx::bytes.multicast::cluster.L2::cache_hint [%0], [%1, {%2, %3, %4}], [%5], %6, %7;\n}" ::"r"(dst), "l"(m), "r"(c0), "r"(c1), "r"(c2), "r"(bar), "h"(mask), "l"(pol) : "memory");
}
__device__ __forceinline__ void tma4d_e(uint32_t dst, const CUtensorMap* m, int c0, int c1, int c3, uint32_t bar, uint64_t pol) {
    asm volatile("{\n.reg .pred E;\nelect.sync _|E, 0xffffffff;\n@E cp.async.bulk.tensor.4d.shared::cluster.global.mbarrier::complete_tx::bytes.L2::cache_hint [%0], [%1, {%2, %3, 0, %4}], [%5], %6;\n}" ::"r"(dst), "l"(m), "r"(c0), "r"(c1), "r"(c3), "r"(bar), "l"(pol) : "memory");
}
__device__ __forceinline__ void tma4d_mc_e(uint32_t dst, const CUtensorMap* m, int c0, int c1, int c3, uint32_t bar, uint16_t mask, uint64_t pol) {
    asm volatile("{\n.reg .pred E;\nelect.sync _|E, 0xffffffff;\n@E cp.async.bulk.tensor.4d.shared::cluster.global.mbarrier::complete_tx::bytes.multicast::cluster.L2::cache_hint [%0], [%1, {%2, %3, 0, %4}], [%5], %6, %7;\n}" ::"r"(dst), "l"(m), "r"(c0), "r"(c1), "r"(c3), "r"(bar), "h"(mask), "l"(pol) : "memory");
}
__device__ __forceinline__ void tma_prefetch4d_e(const CUtensorMap* m, int c0, int c3) {
    asm volatile("{\n.reg .pred E;\nelect.sync _|E, 0xffffffff;\n@E cp.async.bulk.prefetch.tensor.4d.L2.global [%0, {%1, 0, 0, %2}];\n}" ::"l"(m), "r"(c0), "r"(c3) : "memory");
}
__device__ __forceinline__ void tma_prefetch3d_e(const CUtensorMap* m, int c0, int c1, int c2) {
    asm volatile("{\n.reg .pred E;\nelect.sync _|E, 0xffffffff;\n@E cp.async.bulk.prefetch.tensor.3d.L2.global [%0, {%1, %2, %3}];\n}" ::"l"(m), "r"(c0), "r"(c1), "r"(c2) : "memory");
}
__device__ __forceinline__ void l2_prefetch_e(const void* src, uint32_t bytes) {
    asm volatile("{\n.reg .pred E;\nelect.sync _|E, 0xffffffff;\n@E cp.async.bulk.prefetch.L2.global [%0], %1;\n}" ::"l"(src), "r"(bytes) : "memory");
}
__device__ __forceinline__ void bulk_g2s_e(uint32_t dst, const void* src, uint32_t bytes, uint32_t bar) {
    asm volatile("{\n.reg .pred E;\nelect.sync _|E, 0xffffffff;\n@E cp.async.bulk.shared::cluster.global.mbarrier::complete_tx::bytes [%0], [%1], %2, [%3];\n}" ::"r"(dst), "l"(src), "r"(bytes), "r"(bar) : "memory");
}
__device__ __forceinline__ bool elect_one() {
    uint32_t r;
    asm volatile("{\n.reg .pred E;\nelect.sync _|E, 0xffffffff;\nselp.u32 %0, 1, 0, E;\n}" : "=r"(r));
    return r;
}
__device__ __forceinline__ void tma_store2d(const CUtensorMap* m, int c0, int c1, uint32_t src, uint64_t pol) {
    asm volatile("cp.async.bulk.tensor.2d.global.shared::cta.bulk_group.L2::cache_hint [%0, {%1, %2}], [%3], %4;" ::"l"(m), "r"(c0), "r"(c1), "r"(src), "l"(pol) : "memory");
}
__device__ __forceinline__ void bulk_commit() { asm volatile("cp.async.bulk.commit_group;" ::: "memory"); }
__device__ __forceinline__ void bulk_wait_read() { asm volatile("cp.async.bulk.wait_group.read 0;" ::: "memory"); }
__device__ __forceinline__ void bulk_wait_all() { asm volatile("cp.async.bulk.wait_group 0;" ::: "memory"); }
__device__ __forceinline__ uint64_t mkdesc(uint32_t addr, uint32_t lbo, uint32_t sbo, uint32_t swz) {
    return (uint64_t)((addr & 0x3FFFF) >> 4) | ((uint64_t)(lbo >> 4) << 16) | ((uint64_t)(sbo >> 4) << 32) | ((uint64_t)swz << 62);
}
__device__ __forceinline__ void wg_fence() { asm volatile("wgmma.fence.sync.aligned;" ::: "memory"); }
__device__ __forceinline__ void wg_commit() { asm volatile("wgmma.commit_group.sync.aligned;" ::: "memory"); }
template <int N> __device__ __forceinline__ void wg_wait() { asm volatile("wgmma.wait_group.sync.aligned %0;" ::"n"(N) : "memory"); }
template <typename T> __device__ __forceinline__ void pin_ptr(T*& p) { asm volatile("" : "+l"(p)); }
template <int N> __device__ __forceinline__ void pin(uint32_t* d) {
#pragma unroll
    for (int i = 0; i < N; i++) asm volatile("" : "+r"(d[i])::"memory");
}
template <int N> __device__ __forceinline__ void pin(float* d) {
#pragma unroll
    for (int i = 0; i < N; i++) asm volatile("" : "+f"(d[i])::"memory");
}

template <int TA, int TB>
__device__ __forceinline__ void wgmma_ss256(float* d, uint64_t da, uint64_t db) {
    asm volatile("wgmma.mma_async.sync.aligned.m64n256k16.f32.bf16.bf16 "
        "{%0, %1, %2, %3, %4, %5, %6, %7, %8, %9, %10, %11, %12, %13, %14, %15, %16, %17, %18, %19, %20, %21, %22, %23, %24, %25, %26, %27, %28, %29, %30, %31, %32, %33, %34, %35, %36, %37, %38, %39, %40, %41, %42, %43, %44, %45, %46, %47, %48, %49, %50, %51, %52, %53, %54, %55, %56, %57, %58, %59, %60, %61, %62, %63, %64, %65, %66, %67, %68, %69, %70, %71, %72, %73, %74, %75, %76, %77, %78, %79, %80, %81, %82, %83, %84, %85, %86, %87, %88, %89, %90, %91, %92, %93, %94, %95, %96, %97, %98, %99, %100, %101, %102, %103, %104, %105, %106, %107, %108, %109, %110, %111, %112, %113, %114, %115, %116, %117, %118, %119, %120, %121, %122, %123, %124, %125, %126, %127}, %128, %129, 1, 1, 1, %130, %131;"
        : "+f"(d[0]), "+f"(d[1]), "+f"(d[2]), "+f"(d[3]), "+f"(d[4]), "+f"(d[5]), "+f"(d[6]), "+f"(d[7]), "+f"(d[8]), "+f"(d[9]), "+f"(d[10]), "+f"(d[11]), "+f"(d[12]), "+f"(d[13]), "+f"(d[14]), "+f"(d[15]), "+f"(d[16]), "+f"(d[17]), "+f"(d[18]), "+f"(d[19]), "+f"(d[20]), "+f"(d[21]), "+f"(d[22]), "+f"(d[23]), "+f"(d[24]), "+f"(d[25]), "+f"(d[26]), "+f"(d[27]), "+f"(d[28]), "+f"(d[29]), "+f"(d[30]), "+f"(d[31]), "+f"(d[32]), "+f"(d[33]), "+f"(d[34]), "+f"(d[35]), "+f"(d[36]), "+f"(d[37]), "+f"(d[38]), "+f"(d[39]), "+f"(d[40]), "+f"(d[41]), "+f"(d[42]), "+f"(d[43]), "+f"(d[44]), "+f"(d[45]), "+f"(d[46]), "+f"(d[47]), "+f"(d[48]), "+f"(d[49]), "+f"(d[50]), "+f"(d[51]), "+f"(d[52]), "+f"(d[53]), "+f"(d[54]), "+f"(d[55]), "+f"(d[56]), "+f"(d[57]), "+f"(d[58]), "+f"(d[59]), "+f"(d[60]), "+f"(d[61]), "+f"(d[62]), "+f"(d[63]), "+f"(d[64]), "+f"(d[65]), "+f"(d[66]), "+f"(d[67]), "+f"(d[68]), "+f"(d[69]), "+f"(d[70]), "+f"(d[71]), "+f"(d[72]), "+f"(d[73]), "+f"(d[74]), "+f"(d[75]), "+f"(d[76]), "+f"(d[77]), "+f"(d[78]), "+f"(d[79]), "+f"(d[80]), "+f"(d[81]), "+f"(d[82]), "+f"(d[83]), "+f"(d[84]), "+f"(d[85]), "+f"(d[86]), "+f"(d[87]), "+f"(d[88]), "+f"(d[89]), "+f"(d[90]), "+f"(d[91]), "+f"(d[92]), "+f"(d[93]), "+f"(d[94]), "+f"(d[95]), "+f"(d[96]), "+f"(d[97]), "+f"(d[98]), "+f"(d[99]), "+f"(d[100]), "+f"(d[101]), "+f"(d[102]), "+f"(d[103]), "+f"(d[104]), "+f"(d[105]), "+f"(d[106]), "+f"(d[107]), "+f"(d[108]), "+f"(d[109]), "+f"(d[110]), "+f"(d[111]), "+f"(d[112]), "+f"(d[113]), "+f"(d[114]), "+f"(d[115]), "+f"(d[116]), "+f"(d[117]), "+f"(d[118]), "+f"(d[119]), "+f"(d[120]), "+f"(d[121]), "+f"(d[122]), "+f"(d[123]), "+f"(d[124]), "+f"(d[125]), "+f"(d[126]), "+f"(d[127])
        : "l"(da), "l"(db), "n"(TA), "n"(TB));
}
template <int TA, int TB>
__device__ __forceinline__ void wgmma_ss256_first(float* d, uint64_t da, uint64_t db) {
    asm volatile("wgmma.mma_async.sync.aligned.m64n256k16.f32.bf16.bf16 "
        "{%0, %1, %2, %3, %4, %5, %6, %7, %8, %9, %10, %11, %12, %13, %14, %15, %16, %17, %18, %19, %20, %21, %22, %23, %24, %25, %26, %27, %28, %29, %30, %31, %32, %33, %34, %35, %36, %37, %38, %39, %40, %41, %42, %43, %44, %45, %46, %47, %48, %49, %50, %51, %52, %53, %54, %55, %56, %57, %58, %59, %60, %61, %62, %63, %64, %65, %66, %67, %68, %69, %70, %71, %72, %73, %74, %75, %76, %77, %78, %79, %80, %81, %82, %83, %84, %85, %86, %87, %88, %89, %90, %91, %92, %93, %94, %95, %96, %97, %98, %99, %100, %101, %102, %103, %104, %105, %106, %107, %108, %109, %110, %111, %112, %113, %114, %115, %116, %117, %118, %119, %120, %121, %122, %123, %124, %125, %126, %127}, %128, %129, 0, 1, 1, %130, %131;"
        : "=f"(d[0]), "=f"(d[1]), "=f"(d[2]), "=f"(d[3]), "=f"(d[4]), "=f"(d[5]), "=f"(d[6]), "=f"(d[7]), "=f"(d[8]), "=f"(d[9]), "=f"(d[10]), "=f"(d[11]), "=f"(d[12]), "=f"(d[13]), "=f"(d[14]), "=f"(d[15]), "=f"(d[16]), "=f"(d[17]), "=f"(d[18]), "=f"(d[19]), "=f"(d[20]), "=f"(d[21]), "=f"(d[22]), "=f"(d[23]), "=f"(d[24]), "=f"(d[25]), "=f"(d[26]), "=f"(d[27]), "=f"(d[28]), "=f"(d[29]), "=f"(d[30]), "=f"(d[31]), "=f"(d[32]), "=f"(d[33]), "=f"(d[34]), "=f"(d[35]), "=f"(d[36]), "=f"(d[37]), "=f"(d[38]), "=f"(d[39]), "=f"(d[40]), "=f"(d[41]), "=f"(d[42]), "=f"(d[43]), "=f"(d[44]), "=f"(d[45]), "=f"(d[46]), "=f"(d[47]), "=f"(d[48]), "=f"(d[49]), "=f"(d[50]), "=f"(d[51]), "=f"(d[52]), "=f"(d[53]), "=f"(d[54]), "=f"(d[55]), "=f"(d[56]), "=f"(d[57]), "=f"(d[58]), "=f"(d[59]), "=f"(d[60]), "=f"(d[61]), "=f"(d[62]), "=f"(d[63]), "=f"(d[64]), "=f"(d[65]), "=f"(d[66]), "=f"(d[67]), "=f"(d[68]), "=f"(d[69]), "=f"(d[70]), "=f"(d[71]), "=f"(d[72]), "=f"(d[73]), "=f"(d[74]), "=f"(d[75]), "=f"(d[76]), "=f"(d[77]), "=f"(d[78]), "=f"(d[79]), "=f"(d[80]), "=f"(d[81]), "=f"(d[82]), "=f"(d[83]), "=f"(d[84]), "=f"(d[85]), "=f"(d[86]), "=f"(d[87]), "=f"(d[88]), "=f"(d[89]), "=f"(d[90]), "=f"(d[91]), "=f"(d[92]), "=f"(d[93]), "=f"(d[94]), "=f"(d[95]), "=f"(d[96]), "=f"(d[97]), "=f"(d[98]), "=f"(d[99]), "=f"(d[100]), "=f"(d[101]), "=f"(d[102]), "=f"(d[103]), "=f"(d[104]), "=f"(d[105]), "=f"(d[106]), "=f"(d[107]), "=f"(d[108]), "=f"(d[109]), "=f"(d[110]), "=f"(d[111]), "=f"(d[112]), "=f"(d[113]), "=f"(d[114]), "=f"(d[115]), "=f"(d[116]), "=f"(d[117]), "=f"(d[118]), "=f"(d[119]), "=f"(d[120]), "=f"(d[121]), "=f"(d[122]), "=f"(d[123]), "=f"(d[124]), "=f"(d[125]), "=f"(d[126]), "=f"(d[127])
        : "l"(da), "l"(db), "n"(TA), "n"(TB));
}
template <int TB>
__device__ __forceinline__ void wgmma_rs128(float* d, const uint32_t* a, uint64_t db, uint32_t acc) {
    asm volatile("{\n.reg .pred P;\nsetp.ne.u32 P, %69, 0;\nwgmma.mma_async.sync.aligned.m64n128k16.f32.bf16.bf16 "
        "{%0, %1, %2, %3, %4, %5, %6, %7, %8, %9, %10, %11, %12, %13, %14, %15, %16, %17, %18, %19, %20, %21, %22, %23, %24, %25, %26, %27, %28, %29, %30, %31, %32, %33, %34, %35, %36, %37, %38, %39, %40, %41, %42, %43, %44, %45, %46, %47, %48, %49, %50, %51, %52, %53, %54, %55, %56, %57, %58, %59, %60, %61, %62, %63}, {%64, %65, %66, %67}, %68, P, 1, 1, %70;\n}"
        : "+f"(d[0]), "+f"(d[1]), "+f"(d[2]), "+f"(d[3]), "+f"(d[4]), "+f"(d[5]), "+f"(d[6]), "+f"(d[7]), "+f"(d[8]), "+f"(d[9]), "+f"(d[10]), "+f"(d[11]), "+f"(d[12]), "+f"(d[13]), "+f"(d[14]), "+f"(d[15]), "+f"(d[16]), "+f"(d[17]), "+f"(d[18]), "+f"(d[19]), "+f"(d[20]), "+f"(d[21]), "+f"(d[22]), "+f"(d[23]), "+f"(d[24]), "+f"(d[25]), "+f"(d[26]), "+f"(d[27]), "+f"(d[28]), "+f"(d[29]), "+f"(d[30]), "+f"(d[31]), "+f"(d[32]), "+f"(d[33]), "+f"(d[34]), "+f"(d[35]), "+f"(d[36]), "+f"(d[37]), "+f"(d[38]), "+f"(d[39]), "+f"(d[40]), "+f"(d[41]), "+f"(d[42]), "+f"(d[43]), "+f"(d[44]), "+f"(d[45]), "+f"(d[46]), "+f"(d[47]), "+f"(d[48]), "+f"(d[49]), "+f"(d[50]), "+f"(d[51]), "+f"(d[52]), "+f"(d[53]), "+f"(d[54]), "+f"(d[55]), "+f"(d[56]), "+f"(d[57]), "+f"(d[58]), "+f"(d[59]), "+f"(d[60]), "+f"(d[61]), "+f"(d[62]), "+f"(d[63])
        : "r"(a[0]), "r"(a[1]), "r"(a[2]), "r"(a[3]), "l"(db), "r"(acc), "n"(TB));
}
template <int TB>
__device__ __forceinline__ void wgmma_rs64(float* d, const uint32_t* a, uint64_t db, uint32_t acc) {
    asm volatile("{\n.reg .pred P;\nsetp.ne.u32 P, %37, 0;\nwgmma.mma_async.sync.aligned.m64n64k16.f32.bf16.bf16 "
        "{%0, %1, %2, %3, %4, %5, %6, %7, %8, %9, %10, %11, %12, %13, %14, %15, %16, %17, %18, %19, %20, %21, %22, %23, %24, %25, %26, %27, %28, %29, %30, %31}, {%32, %33, %34, %35}, %36, P, 1, 1, %38;\n}"
        : "+f"(d[0]), "+f"(d[1]), "+f"(d[2]), "+f"(d[3]), "+f"(d[4]), "+f"(d[5]), "+f"(d[6]), "+f"(d[7]), "+f"(d[8]), "+f"(d[9]), "+f"(d[10]), "+f"(d[11]), "+f"(d[12]), "+f"(d[13]), "+f"(d[14]), "+f"(d[15]), "+f"(d[16]), "+f"(d[17]), "+f"(d[18]), "+f"(d[19]), "+f"(d[20]), "+f"(d[21]), "+f"(d[22]), "+f"(d[23]), "+f"(d[24]), "+f"(d[25]), "+f"(d[26]), "+f"(d[27]), "+f"(d[28]), "+f"(d[29]), "+f"(d[30]), "+f"(d[31])
        : "r"(a[0]), "r"(a[1]), "r"(a[2]), "r"(a[3]), "l"(db), "r"(acc), "n"(TB));
}
template <int TB>
__device__ __forceinline__ void wgmma_rs16(float* d, const uint32_t* a, uint64_t db, uint32_t acc) {
    asm volatile("{\n.reg .pred P;\nsetp.ne.u32 P, %13, 0;\nwgmma.mma_async.sync.aligned.m64n16k16.f32.bf16.bf16 "
        "{%0, %1, %2, %3, %4, %5, %6, %7}, {%8, %9, %10, %11}, %12, P, 1, 1, %14;\n}"
        : "+f"(d[0]), "+f"(d[1]), "+f"(d[2]), "+f"(d[3]), "+f"(d[4]), "+f"(d[5]), "+f"(d[6]), "+f"(d[7])
        : "r"(a[0]), "r"(a[1]), "r"(a[2]), "r"(a[3]), "l"(db), "r"(acc), "n"(TB));
}

__device__ __forceinline__ uint32_t delay_loop(int n, uint32_t x0) {
    uint32_t z;
    asm volatile("{\n.reg .pred P;\n.reg .u32 c, x;\nmov.u32 c, %1;\nmov.u32 x, %2;\nDL: mad.lo.u32 x, x, 1664525, 1013904223;\nadd.u32 c, c, -1;\nsetp.gt.s32 P, c, 0;\n@P bra DL;\n"
                 "setp.eq.u32 P, x, 0x7fffffff;\nselp.u32 %0, 16, 0, P;\n}" : "=r"(z) : "r"(n), "r"(x0) : "memory");
    return z;
}
__device__ __forceinline__ void wait_clocks(uint32_t n) {
    asm volatile("{\n.reg .pred P;\n.reg .u32 a, b;\nmov.u32 a, %%clock;\nW: mov.u32 b, %%clock;\nsub.u32 b, b, a;\nsetp.lt.u32 P, b, %0;\n@P bra W;\n}" ::"r"(n) : "memory");
}
__device__ __forceinline__ uint32_t gtime() { uint32_t t; asm volatile("mov.u32 %0, %%globaltimer_lo;" : "=r"(t)); return t; }
#define COUNT_RETRY(i)
__device__ __forceinline__ uint32_t stamp_word(uint32_t seq) { return (gtime() & ~31u) | (seq & 31u); }
__device__ __forceinline__ void wait_time(uint32_t t, uint32_t sb) { while ((int32_t)(gtime() - t) < 0) {} }
#define NAPMODE 1
__device__ __forceinline__ void nap(uint32_t ns) { if (NAPMODE) wait_clocks(ns * 7 / 4); else __nanosleep(ns); }
template <int STRIDE>
__device__ __forceinline__ uint32_t latest_stamp(const uint32_t* p, uint32_t seq, uint32_t ref, uint32_t sb) {
#pragma unroll 1
    for (int n = opq(0, 0);; n++) {
        uint32_t bad = 0; int32_t m = INT32_MIN;
#pragma unroll
        for (int i = 0; i < 3; i++) { const uint32_t v = ld_relaxed1(p + i * STRIDE); bad |= (v ^ seq) & 31u; m = max(m, (int32_t)((v & ~31u) - ref)); }
        if (__all_sync(0xffffffffu, bad == 0)) return ref + __reduce_max_sync(0xffffffffu, m);
        nap(100);
        if (n > SPIN_LIMIT) spin_fault();
    }
}
constexpr uint32_t ONES = 0x3C003C00u, FULL = 0x50005000u;
__device__ __forceinline__ void pacer(const Params& P, const uint32_t sb, const int cta, const int lane, const uint32_t epoch) {
    uint8_t* const zp = P.xb + cta * 2048 + xg_lane(lane);
    if (lane < 3) asm volatile("prefetch.tensormap [%0];" ::"l"(&P.tm[lane == 0 ? M_C1 + cta % 3 : lane == 1 ? M_CO : M_SEG]) : "memory");
    uint32_t e0 = 0;
#pragma unroll 2
    for (int i = 0; i < 32; i++) { const uint4 u = __ldg((const uint4*)P.mem0 + i * 32 + lane); e0 = amax(amax(e0, amax(u.x, u.y)), amax(u.z, u.w)); }
    e0 = min(max(warp_exp(e0), 31u), 253u) - 14;
    if (cta < 32) {
        const uint32_t* m = (const uint32_t*)(P.mem0 + (lane >> 2) * 1024 + cta * 32 + (lane & 3) * 2);
        const float sc = __uint_as_float((254 - e0) << 23);
        auto cv = [&](uint32_t u) { return pack2h(bf_lo(u) * sc, bf_hi(u) * sc); };
        const uint32_t y = cv(m[12]);
        st_relaxed4(zp, cv(m[0]), cv(m[4]), cv(m[8]), prmt(y, FULL, 0x7610));
        st_relaxed1(P.xb + xg_side(cta) + lane * 4, prmt(y, FULL, 0x3254));
    }
    if (cta < 40) {
#pragma unroll 1
        for (int b = 1; b < 8; b++) st_relaxed4(zp + xg_buf(b), 0, 0, 0, 0);
    }
    __threadfence();
    const uint32_t* ts = (const uint32_t*)(P.xb + XG_T) + lane;
    int32_t d0 = P.dly;
    const uint32_t go = mapa(sb + B_GO, (cta / 3 & 1) * 3 + 1 + (lane & 1));
    auto free_segment = [&]() { if (lane == 0) mbar_expect(sb + B_KVFULL, 16384); __syncwarp(); if (lane < 2) mbar_arrive_cluster(go); };
    for (int n = 0; (int32_t)(ld_acquire(&g_cnt(C_XCNT)) - (epoch + 1) * 256) < 0; n++) { __nanosleep(500); if (n > SPIN_LIMIT) spin_fault(); }
    const uint32_t ex = max(ld_relaxed1(&g_cnt(C_XMAX)) & 255, 67u);
    mbar_wait_bounded(sb + B_READY, 0);
    free_segment();
    if (lane == 0) st_relaxed2(g_hint + cta * 32, stamp_word(epoch + 1), lds32(sb + S_EV) | lds32(sb + S_EO) << 16);
    uint32_t a = gtime();
    for (int n = 0;; n++) {
        uint32_t bad = 0, e = 0; int32_t m = INT32_MIN;
#pragma unroll
        for (int i = 0; i < 3; i++) {
            uint32_t v[2];
            ld_relaxed2(v, g_hint + lane * 32 + i * 1024);
            bad |= (v[0] ^ (epoch + 1)) & 31u; m = max(m, (int32_t)((v[0] & ~31u) - a)); e = __vmaxu2(e, v[1]);
        }
        if (__all_sync(0xffffffffu, bad == 0)) {
            a += __reduce_max_sync(0xffffffffu, m);
            const uint32_t ev = __reduce_max_sync(0xffffffffu, e & 255), eo = __reduce_max_sync(0xffffffffu, e >> 16);
            if (lane == 0) { sts64(sb + S_SC, max(ev, 97u) + max(eo, 97u) - 244, ex); sts32(sb + S_ISC, e0 * 0x800080u); }
            break;
        }
        wait_clocks(100);
        if (n > SPIN_LIMIT) spin_fault();
    }
    wait_time(a, sb);
    if (lane == 0) mbar_arrive(sb + B_RELM);
#pragma unroll 1
    for (int s = 0; s < 63; s++) {
        const uint32_t seq = epoch * 63 + s + 1;
        mbar_wait_bounded(sb + B_P1, s & 1);
        const uint32_t tx = gtime();
        if (lane == 0) st_relaxed1(ts + (s & 1) * 256 + cta, (tx & ~31u) | (seq & 31u));
        { const uint32_t t = tx; PROFP(3) }
        if (s > 0) {
            const int32_t e0 = latest_stamp<32>(ts + (~s & 1) * 256 + 128, seq - 1, a, sb) + P.mrg - a;
            d0 += s < 3 ? e0 : min(max(e0, -P.clamp0), P.clampv) / 2;
        }
        while ((int32_t)(gtime() - tx) < P.rd) nap(20);
        a = latest_stamp<32>(ts + (s & 1) * 256, seq, tx, sb) + d0;
        { const uint32_t t = gtime(); PROFP(0) }
        while ((int32_t)(a - gtime()) > 250) nap(40);
        wait_time(a, sb);
        if (lane == 0) mbar_arrive(sb + B_RELM);
        { const uint32_t t = a; PROFP(2) }
        mbar_wait_bounded(sb + B_RED, s & 1);
        { const uint32_t t = gtime(); PROFP(1) }
        const uint32_t g = tx + __reduce_max_sync(0xffffffffu, lds32(sb + S_TO + (lane & 7) * 4) - tx);
        if (lane == 0) st_relaxed1(ts + (s & 1) * 256 + 128 + cta, (g & ~31u) | (seq & 31u));
        if (s < 62) { if (P.kvd) nap(P.kvd); free_segment(); }
    }
}
__device__ __forceinline__ void st_async2(uint32_t a, uint32_t x, uint32_t y, uint32_t bar) {
    asm volatile("st.async.weak.shared::cluster.mbarrier::complete_tx::bytes.v2.b32 [%0], {%1,%2}, [%3];" ::"r"(a), "r"(x), "r"(y), "r"(bar) : "memory");
}
__device__ __forceinline__ uint32_t xor_or(uint32_t a, uint32_t b, uint32_t t) { uint32_t d; asm("lop3.b32 %0, %1, %2, %3, 0x7E;" : "=r"(d) : "r"(a), "r"(b), "r"(t)); return d; }
__device__ __forceinline__ uint32_t or3(uint32_t a, uint32_t b, uint32_t c) { uint32_t d; asm("lop3.b32 %0, %1, %2, %3, 0xFE;" : "=r"(d) : "r"(a), "r"(b), "r"(c)); return d; }
__device__ __forceinline__ bool tags_ok(uint32_t bad, uint32_t mask = 1) {
    uint32_t r;
    asm volatile("{\n.reg .pred P;\n.reg .b32 x;\nand.b32 x, %1, %2;\nsetp.ne.b32 P, x, 0;\nvote.sync.any.pred P, P, 0xffffffff;\nselp.u32 %0, 0, 1, P;\n}" : "=r"(r) : "r"(bad), "r"(mask));
    return r;
}
constexpr int SROW = 56;
#define PREA 8
#define PREB 9
#define RING1 6
#define RING2 7
#define RING3 8
#define PRE2 10
#define PRE2A 0
#define PRE3 0
#define EFENCE 0
#define RFENCE 1
#define PROG 16
#define EARLY 0
#define PLATE 1
#define NDEP 0
#define EFENCE2 0
#define LAG2 8
#define LAG 4
#define PUT1 33
#define DEPS 3
#define ADELAY 120
#define BDELAY 0
#define HOLD 1
#define XDELAY 330
#define FENCEA 0x80
#define FENCEB 0x80
#define FENCE2 0x220
#define OFENCE 0
#define MASK3 0x57
#define MASK4 0x55
#define MASK5 0x25
#define OFF3 0x5320
#define OFF4 0x6420
#define OFF5 0x0520
#define RESA (NRA == 3 ? 15 : NRA == 4 ? 3 : 0)
#define RESB (NRB == 3 ? 0xcc : NRB == 4 ? 0x30 : 0)
#define RESB1 (NRB == 3 ? 0xcc : NRB == 4 ? 0xc : 0)
__host__ __device__ constexpr int smem_mask(int NR) { return NR == 3 ? MASK3 : NR == 4 ? MASK4 : MASK5; }
__host__ __device__ constexpr bool round_smem(int r, int NR) { return smem_mask(NR) >> r & 1; }
__host__ __device__ constexpr int kord(int r, int NR) { int c = 0; for (int i = 0; i < r; i++) c += round_smem(i, NR) == round_smem(r, NR); return round_smem(r, NR) ? NR + c : c; }
__host__ __device__ constexpr int slot_r(int n, int NR) { return n < 32 ? n >> 2 : (((n & 31) >> 2) + ((NR == 3 ? OFF3 : NR == 4 ? OFF4 : OFF5) >> (n & 3) * 4)) & 7; }
__host__ __device__ constexpr int slot_k(int n, int NR) { return kord(slot_r(n, NR), NR); }
__host__ __device__ constexpr int slot_sord(int n, int NR) { int c = 0; for (int i = 0; i < n; i++) c += slot_k(i, NR) >= NR; return c; }
__host__ __device__ constexpr int sfrag_slot(int q, int NR) { for (int n = 0; n < 64; n++) if (slot_k(n, NR) >= NR && slot_sord(n, NR) == q) return n; return -1; }
__host__ __device__ constexpr int w1_loaded(int n, int NR, int PRE) {
    int q = PRE;
    for (int i = 0; i <= n; i++) q += q < (8 - NR) * 8 && q - slot_sord(i + 1, NR) < (i < 32 ? RING1 : RING2);
    return q;
}
template <int Q, int NR>
__device__ __forceinline__ void load_w1(uint32_t* w, const uint32_t* a) {
    constexpr int n = sfrag_slot(Q, NR);
    ldsm4t(w, a[n & 3] + ((slot_k(n, NR) - NR) * 2 + (n >> 5)) * 2048);
}
constexpr int AB = NRA < 5, BB = 3 - AB;
__device__ __forceinline__ bool w2_full(int role, int warp) { return warp < (role == 2 ? 2 : 3); }
__device__ __forceinline__ int w2_nblk(int role, int warp) { return warp < 4 ? BB - !w2_full(role, warp) : AB; }
__host__ __device__ constexpr int w2_step(bool full, int i) { return AB ? (full ? 2 * i : 0) : full ? (i == 0 ? 0 : i == 1 ? 16 - 2 * EARLY : 18 - 2 * EARLY) : i; }
__device__ __forceinline__ int w2_block(int role, int warp) {
    const int f = role * 3 + warp, g = role == 2 ? warp : role;
    if (AB) return (warp >= 4 ? role * 4 + (warp - 4) : w2_full(role, warp) ? 16 + 4 * (f >> 1) + (f & 1) : 12 + g) ^ EARLY;
    return w2_full(role, warp) ? EARLY + 4 * (f >> 1) + (f & 1) : EARLY + 2 + 4 * g;
}
__device__ __forceinline__ int w2_res(int role, int warp) { return warp >= 4 ? RESA : w2_full(role, warp) ? RESB : RESB1; }
__device__ __forceinline__ int w2_units(int role, int warp) { return w2_nblk(role, warp) * 4 - (5 - (warp < 4 ? NRB : NRA)) * 2; }
constexpr int W2B = (BB * 4 - (5 - NRB) * 2) * 2048, W2A = (AB * 4 - (5 - NRA) * 2) * 2048;
static_assert(S_W2 + 4 * W2B - 8192 + 4 * W2A == S_KV, "weights");
__device__ __forceinline__ int w1_base(int warp) { return S_W1 + (warp < 4 ? warp * (8 - NRB) : 4 * (8 - NRB) + (warp - 4) * (8 - NRA)) * 4096; }
__device__ __forceinline__ int w2_base(int warp) { return S_W2 + (warp < 4 ? warp * W2B : 4 * W2B - 8192 + (warp - 4) * W2A); }
__device__ __forceinline__ void chain_load(const Params& P, uint32_t sb, int cta, int warp, int lane, int round) {
    const int role = cta % 3, h = cta / 3;
    mbar_expect_e(sb + B_INIT, round ? (8 - (warp < 4 ? NRB : NRA)) * 4096 : 20480);
    if (round) mbar_expect_e(sb + B_INIT2, w2_units(role, warp) * 2048);
    __syncwarp();
    const int m1 = (warp < 4 ? smem_mask(NRB) : smem_mask(NRA)) ^ (round ? 0 : 255), below = (1 << lane) - 1;
    const int m2 = (w2_res(role, warp) ^ (round ? 0xfff : 0)) & ((1 << w2_nblk(role, warp) * 4) - 1);
    const uint32_t d1 = sb + (round ? w1_base(warp) : warp * 20480), d2 = round ? sb + w2_base(warp) : d1 + __popc(m1) * 4096;
    if (m1 >> lane & 1) tma3d(d1 + __popc(m1 & below) * 4096, &P.tm[M_C1 + role], 0, warp * 128 + lane * 16, h * 2, sb + B_INIT);
    __syncwarp();
    if (m2 >> lane & 1)
        tma2d(d2 + __popc(m2 & below) * 2048, &P.tm[M_CO], (w2_block(role, warp) + w2_step(w2_full(role, warp), lane >> 2)) * 32, h * 128 + (lane & 3) * 32, sb + (round ? B_INIT2 : B_INIT));
    __syncwarp();
}

__device__ __forceinline__ void put_partials(bool TR, uint32_t a, const float* x, const float* y) {
    if (TR) stsm4t(a, pack2(x[0], x[1]), pack2(x[2], x[3]), pack2(y[0], y[1]), pack2(y[2], y[3]));
    else stsm4(a, pack2(x[0], x[1]), pack2(x[2], x[3]), pack2(y[0], y[1]), pack2(y[2], y[3]));
}
template <int NR, int PRE, int FM, int B, int E>
__device__ __forceinline__ void project(float (*acc)[4], bool TR, const uint32_t (*wr)[4], uint32_t (*as)[4], uint32_t (*v)[4], uint32_t* x, const uint32_t* w1a, uint32_t pp, uint32_t zero) {
    static_for<B, E>([&](auto I) {
        constexpr int n = I.value, kk = slot_k(n, NR), T = (n >> 5) * 4 + (n & 3), so = slot_sord(n, NR), q = w1_loaded(n - 1, NR, PRE);
        constexpr bool sm = kk >= NR;
        const uint32_t* w = sm ? as[so] : wr[sm ? 0 : (kk * 2 + (n >> 5)) * 4 + (n & 3)];
        if constexpr (n == 32 && PUT1 < 32) { put_partials(TR, pp, acc[0], acc[1]); put_partials(TR, pp + 4096, acc[2], acc[3]); }
        if constexpr (n == 0) {
            const uint32_t c = prmt(v[0][3], x[0], 0x3254);
            v[0][0] = h2bf(v[0][0], v[0][0]); v[0][1] = h2bf(v[0][1], v[0][1]); v[0][2] = h2bf(v[0][2], v[0][2]); v[0][3] = h2bf(v[0][3], x[0]);
            x[0] = c;
        }
        if constexpr ((n & 31) < 4) acc[T][0] = acc[T][1] = acc[T][2] = acc[T][3] = 0.f;
        mma16816(acc[T], w[0], w[1], w[2], w[3], v[slot_r(n, NR) >> 1][(slot_r(n, NR) & 1) * 2], v[slot_r(n, NR) >> 1][(slot_r(n, NR) & 1) * 2 + 1]);
        if constexpr (n == DEPS) {
            const uint32_t sel = __float_as_uint(acc[T][0]) * zero + 0x7610;
#pragma unroll
            for (int b = 1; b < 4; b++) {
                if (b <= NDEP) cvt_block(v[b], x[b], sel);
                else {
                    const uint32_t c = prmt(v[b][3], x[b], 0x3254);
                    v[b][0] = h2bf(v[b][0], v[b][0]); v[b][1] = h2bf(v[b][1], v[b][1]); v[b][2] = h2bf(v[b][2], v[b][2]); v[b][3] = h2bf(v[b][3], x[b]);
                    x[b] = c;
                }
            }
        }
        if constexpr (w1_loaded(n, NR, PRE) > q) load_w1<q, NR>(as[q], w1a);
        if constexpr (n == PUT1 && n >= 32) { put_partials(TR, pp, acc[0], acc[1]); put_partials(TR, pp + 4096, acc[2], acc[3]); }
        if constexpr (n % 4 == 3 && (FM >> (n / 4) & 1) && n != E - 1) sched_fence();
    });
    if constexpr (E == 64) { put_partials(TR, pp + 8192, acc[4], acc[5]); put_partials(TR, pp + 12288, acc[6], acc[7]); }
}
__device__ __forceinline__ void reduce8(const uint32_t (*x)[4], const uint32_t* sel, float sc, uint32_t& r0, uint32_t& r1) {
    float d[4][4];
#pragma unroll
    for (int i = 0; i < 4; i++) {
        d[i][0] = d[i][1] = d[i][2] = d[i][3] = 0.f;
        mma16816(d[i], x[i][0], x[i][1], x[i][2], x[i][3], sel[2 * i], sel[2 * i + 1]);
    }
    r0 = pack2(((d[0][0] + d[1][0]) + (d[2][0] + d[3][0])) * sc, ((d[0][1] + d[1][1]) + (d[2][1] + d[3][1])) * sc);
    r1 = pack2(((d[0][2] + d[1][2]) + (d[2][2] + d[3][2])) * sc, ((d[0][3] + d[1][3]) + (d[2][3] + d[3][3])) * sc);
}

#define ISTAMP(i)
__host__ __device__ constexpr int wo_count(int n, int RES, bool res) { int c = 0; for (int i = 0; i < n; i++) c += (RES >> (i >> 2) & 1) == res; return c; }
__host__ __device__ constexpr int wo_loaded(int n, int RES, int PRE, int end) { int q = PRE; for (int i = 0; i <= n; i++) q += q < end && q - wo_count(i + 1, RES, false) < RING3; return q; }
template <int Q>
__device__ __forceinline__ void load_w2(uint32_t* w, const uint32_t* a) { ldsm4t(w, a[Q & 1] + (Q >> 1) * 1024); }
template <int NB, int RES, int PRE, int FM>
__device__ __forceinline__ void wo_blocks(uint32_t (*w)[4], const uint32_t (*wp)[4], uint32_t oa, const uint32_t* wa, const uint8_t* dst, const uint8_t* dsd, bool odd) {
    float a[NB][4][4];
    uint32_t o[4][4], r[5];
    bar_sync(3, 256);
#pragma unroll
    for (int i = 0; i < 4; i++) ldsm4(o[i], oa + i * 512);
    if (FM & 1) sched_fence();
    static_for<0, NB * 16>([&](auto I) {
        constexpr int n = I.value, i = n & 15, end = wo_count(NB * 16, RES, false), q = wo_loaded(n - 1, RES, PRE, end);
        constexpr bool res = RES >> (n >> 2) & 1;
        const uint32_t* b = o[i >> 2] + (i & 2);
        const uint32_t* x = res ? wp[wo_count(n, RES, true)] : w[wo_count(n, RES, false)];
        float* d = a[n >> 4][i & 3];
        if constexpr (i < 4) d[0] = d[1] = d[2] = d[3] = 0.f;
        mma16816(d, x[0], x[1], x[2], x[3], b[0], b[1]);
        if constexpr (wo_loaded(n, RES, PRE, end) > q) load_w2<q>(w[q], wa);
        if constexpr (n == NB * 16 - 1 || (n >= 16 && i == LAG - 1)) {
            const float (*e)[4] = a[n == NB * 16 - 1 ? NB - 1 : (n >> 4) - 1];
            const uint32_t y = pack2h(e[1][2] + e[3][2], e[1][3] + e[3][3]);
            r[0] = movm(pack2h(e[0][0] + e[2][0], e[0][1] + e[2][1])); r[1] = movm(pack2h(e[0][2] + e[2][2], e[0][3] + e[2][3]));
            r[2] = movm(pack2h(e[1][0] + e[3][0], e[1][1] + e[3][1])); r[3] = movm(odd ? ONES : y); r[4] = movm(odd ? y : ONES);
        }
        if constexpr (n == NB * 16 - 1 || (n >= 16 && i == LAG2 - 1)) {
            constexpr int bs = w2_step(NB == BB, n == NB * 16 - 1 ? NB - 1 : (n >> 4) - 1);
            red_add4(dst + bs * 2048, r[0], r[1], r[2], r[3]);
            red_add1(dsd + (bs >> 1) * 1024 + (bs & 1) * 256, r[4]);
        }
        if constexpr (((FM >> (n / 4 + 1)) & 1) && (n & 3) == 3 && n != NB * 16 - 1) sched_fence();
    });
}
#define FRAG1(ln) ((((ln) & 7) + ((ln) >> 4) * 8) * 128 + ((((((ln) >> 3) & 1) << (ROLE == 1)) ^ ((ln) & 7)) << 4))
#define FRAG2(ln) ((((ln) & 7) + ((ln) >> 4) * 8) * 64 + (((((ln) >> 3) & 1) ^ (((ln) >> 1) & 3)) << 4))
#define TILE_X(i) (ROLE == 1 ? (((i) >> 1) << 6) | (((i) & 1) << 4) : (i) << 5)
__device__ __forceinline__ void chain_fetch(const Params& P, const uint32_t sb, const int cta, const int warp, const int lane, uint32_t (*wr)[4]) {
    const int ROLE = cta % 3, nr = warp < 4 ? NRB : NRA;
    mbar_wait(sb + B_INIT, 0);
    ISTAMP(0)
#pragma unroll
    for (int f = 0; f < 40; f++) {
        const bool w1 = f < (NRA < NRB ? NRA : NRB) * 8 || f < nr * 8;
        ldsm4t(wr[f], sb + warp * 20480 + (f >> 2) * 2048 + (w1 ? FRAG1(lane) ^ TILE_X(f & 3) : (f & 2) * 512 + (FRAG2(lane) ^ ((f & 1) << 5))));
    }
    fence_async_smem();
    mbar_wait(sb + B_SFREE + (warp >> 2) * 8, 0);
    bar_sync(1, 256);
    chain_load(P, sb, cta, warp, lane, 1);
    ISTAMP(1)
}
__device__ __forceinline__ void chain_bounds(const uint32_t sb, const int cta, const int warp, const int lane, const uint32_t (*wr)[4]) {
    const int ROLE = cta % 3, nr = warp < 4 ? NRB : NRA;
    uint32_t m[6] = {}, u[4];
#pragma unroll
    for (int f = 0; f < 40; f++) m[f < 24 ? 0 : f >> 3] = amax4(m[f < 24 ? 0 : f >> 3], wr[f]);
    uint32_t m1 = amax(m[0], amax(nr > 3 ? m[3] : 0, nr > 4 ? m[4] : 0)), m2 = amax(nr > 3 ? 0 : m[3], nr > 4 ? 0 : m[4]);
    ISTAMP(5)
    mbar_wait(sb + B_INIT, 1);
    ISTAMP(3)
    if (ROLE == 2) {
#pragma unroll 4
        for (int i = 0; i < S_W2 / 4096; i++) { lds128(u, sb + S_W1 + warp * (S_W2 / 8) + i * 512 + lane * 16); m1 = amax4(m1, u); }
    }
    mbar_wait(sb + B_INIT2, 0);
    ISTAMP(7)
    const int n = w2_units(ROLE, warp) * 4;
#pragma unroll 4
    for (int i = 0; i < n; i++) { lds128(u, sb + w2_base(warp) + i * 512 + lane * 16); m2 = amax4(m2, u); }
    m1 = warp_exp(m1); m2 = warp_exp(m2);
    if (lane == 0) { if (ROLE == 2) red_max_shared(sb + S_EV, m1); red_max_shared(sb + S_EO, m2); }
}
template <bool ATT>
__device__ __forceinline__ void chain_role(const Params& P, const uint32_t sb, const int cta, const int warp, const int lane, const uint32_t (*wr)[4]) {
    constexpr int NR = ATT ? NRA : NRB, PRE = ATT ? PREA : PREB;
    const int h = cta / 3, ROLE = cta - h * 3;
    ISTAMP(6)
    uint32_t l8 = opq(sb + lane * 8, lane);
    const uint8_t* persu = (const uint8_t*)((ROLE == 1 ? g_km : g_vmt) + h * 512) - (sb >> 1);
    auto persist = [&](int s, int tile, uint32_t r0, uint32_t r1) {
        uint32_t* pp = (uint32_t*)(persu + s * 65536 + (ROLE == 1 ? (tile >> 1) * 512 + (tile & 1) * 128 : tile * 256) + (l8 >> 1));
        pp[0] = r0; pp[ROLE == 1 ? 64 : 32] = r1;
    };
    const uint32_t rk0 = (h & 1) * 3, rd1 = __shfl_sync(0xffffffffu, mapa(sb, rk0 + (ROLE + 1) % 3) - sb, 0), rd2 = __shfl_sync(0xffffffffu, mapa(sb, rk0 + (ROLE + 2) % 3) - sb, 0);
    const uint32_t xo = (ROLE == 2 ? S_XV : S_X + ROLE * 2048) + warp * 256;
    const bool full = w2_full(ROLE, warp);
    const int blk = w2_block(ROLE, warp);
    const uint32_t om = blk * 2048, os = xg_side(blk);
    const uint32_t w1o = sb + w1_base(warp), w2o = sb + w2_base(warp);
    ISTAMP(2)
    if (lane == 0) mbar_arrive(sb + B_READY);
#pragma unroll 1
    for (int s = 0;; s++) {
        l8 += s & P.zero;
        uint32_t r0, r1;
        {
            uint32_t v[4][4], as[(8 - NR) * 8][4], w1a[4];
            float acc[8][4];
            const uint32_t pst = sb + S_P1 + (l8 - sb) * 16 + ((warp * 16) ^ ((l8 & 56) * 2));
#pragma unroll
            for (int i = 0; i < 4; i++) w1a[i] = w1o + (FRAG1((l8 - sb) >> 3) ^ TILE_X(i));
            auto preload = [&]() { static_for<0, PRE>([&](auto I) { load_w1<I.value, NR>(as[I.value], w1a); }); };
#pragma unroll 1
            while (true) {
                uint32_t x[4];
                if (!(PLATE >> ATT & 1)) preload();
                const uint32_t lm = opq(l8 - sb, (l8 - sb) >> 3);
                const uint8_t* pm = P.xb + xg_buf(s) + warp * 8192 + xg_lane(lm >> 3);
                const uint8_t* ps = P.xb + xg_buf(s) + XG_SIDE + warp * 2048 + (lm >> 1);
                pin_ptr(pm); pin_ptr(ps);
                mbar_wait(sb + B_RELM, s & 1);
                if (ATT ? ADELAY : BDELAY) wait_clocks(ATT ? ADELAY : BDELAY);
                PROF(10)
#pragma unroll
                for (int b = 0; b < 4; b++) { ld_relaxed4(v[b], pm + b * 2048); ld_relaxed1n(x[b], ps + (b >> 1) * 1024 + (b & 1) * 256); }
                if (PLATE >> ATT & 1) { preload(); if (PLATE >> (ATT + 2) & 1) sched_fence(); }
                project<NR, PRE, ATT ? FENCEA : FENCEB, 0, PROG>(acc, ROLE == 2, wr, as, v, x, w1a, pst, P.zero);
                const uint32_t bad = xor_or(x[0], x[1], FULL) | xor_or(x[2], x[3], FULL);
                if (tags_ok(bad, 0xffffffffu)) break;
                COUNT_RETRY(warp >> 1)
            }
            PROF(0)
            project<NR, PRE, ATT ? FENCEA : FENCEB, PROG, 64>(acc, ROLE == 2, wr, as, v, nullptr, w1a, pst, 0);
            PROF(1)
            const uint32_t isc = lds32(sb + S_ISC + (s & 1) * 4);
            const uint32_t lq = l8 + ((s >> 3) & P.zero), e1 = s == 63 ? 0 : rd1, e2 = s == 63 ? 0 : rd2;
            uint32_t x[4][4], sel[8], xd[6] = {l8 + xo, l8 + xo + e1, l8 + xo + e2, sb + B_X + e1, sb + B_X + e2, sb + S_P1 + warp * 2048 + (lq & 64) * 16 + (lq & 128) + (lq & 56) * 2};
#pragma unroll
            for (int i = 0; i < 8; i++) sel[i] = (lq & 224) == i * 32 ? 0x3F803F80u : 0u;
            pin<6>(xd); pin<8>(sel);
            if (RFENCE) sched_fence();
            bar_sync(1, 256);
#pragma unroll
            for (int i = 0; i < 4; i++) ldsm4t(x[i], xd[5] + i * 256);
            if (!ATT && l8 == sb + (warp - 3) * 1024) mbar_arrive(sb + B_P1);
            uint32_t em = warp_exp(amax(amax4(amax(amax(v[0][0], v[0][1]), amax(v[0][2], v[0][3])), v[1]), amax4(amax(amax(v[2][0], v[2][1]), amax(v[2][2], v[2][3])), v[3])));
            if (EFENCE2) sched_fence();
            reduce8(x, sel, bf_hi(isc), r0, r1);
            st_async2(xd[1], r0, r1, xd[3]);
            st_async2(xd[2], r0, r1, xd[4]);
            sts64(xd[0], r0, r1);
            if (s == 63) { persist(s, warp, r0, r1); break; }
            if (l8 == sb) sts32(sb + S_EM + warp * 4, em + (isc >> 23));
            __syncwarp();
            if (l8 == sb) mbar_arrive(sb + B_X);
            PROF(2)
        }
        uint32_t w[40][4], w2a[2], odd;
        const uint8_t *po, *pd;
        auto wo_addr = [&]() {
            const uint32_t lo = (l8 + ((s >> 2) & P.zero) - sb) >> 3;
            w2a[0] = w2o + FRAG2(lo); w2a[1] = w2o + (FRAG2(lo) ^ 32);
            po = P.xb + xg_buf(s + 1) + om + xg_lane(lo);
            pd = P.xb + xg_buf(s + 1) + os + lo * 4;
            odd = lo & 4;
            pin_ptr(po); pin_ptr(pd); pin<2>(w2a); pin<1>(&odd);
        };
        uint32_t oa = l8 * 2 + (S_OX - sb);
        if constexpr (ATT) {
            const uint32_t ln = (l8 + ((s >> 4) & P.zero) - sb) >> 3;
            const uint32_t va = sb + S_KV + 8192 + ((warp >> 1) & 1) * 4096 + ((ln & 7) + (ln >> 4) * 8) * 128 + ((((warp & 1) * 4 + ((ln >> 3) & 1)) ^ (ln & 7)) << 4);
            const uint32_t ka = sb + S_KV + (warp & 1) * 2048 + (ln & 15) * 128 + (((ln >> 4) ^ (ln & 7)) << 4);
            uint32_t ad[5] = {sb + S_SX + (ln & 3) * (8 * SROW) + (ln >> 2) * 4 + (warp < 6 ? (warp - 4) * 64 : 128 + (warp - 6) * 32), l8 + S_XV + (warp - 4) * 512,
                              l8 + S_SX + (ln >> 2) * (4 * SROW - 32), oa + (warp - 4) * 512, sb + S_ISC + (~s & 1) * 4};
            if constexpr (AB) { wo_addr(); pin<1>(&oa); }
            pin<5>(ad);
            const uint32_t sa = ad[0], sr = ad[2];
            uint32_t vf[4][4], vm[2][2], q[8][2];
            float S[4][4];
#pragma unroll
            for (int n = 0; n < 4; n++) { S[n][0] = S[n][1] = S[n][2] = S[n][3] = 0.f; }
            mbar_wait(sb + B_KVFULL, s & 1);
            if (warp < 6) {
                uint32_t kf[8][4];
#pragma unroll
                for (int k = 0; k < 8; k++) ldsm4(kf[k], (ka ^ ((k & 3) << 5)) + (k >> 2) * 4096);
#pragma unroll
                for (int i = 0; i < 4; i++) ldsm4t(vf[i], (va ^ ((i & 1) << 5)) + (i >> 1) * 2048);
                mbar_wait(sb + B_X, s & 1);
                PROF(11)
#pragma unroll
                for (int k = 0; k < 8; k++) lds64(q[k], l8 + S_X + k * 256);
#pragma unroll
                for (int k = 0; k < 8; k++) mma16816(S[k & 3], kf[k][0], kf[k][1], kf[k][2], kf[k][3], q[k][0], q[k][1]);
                sts32(sa, __float_as_uint((S[0][0] + S[1][0]) + (S[2][0] + S[3][0])));
                sts32(sa + 4 * SROW, __float_as_uint((S[0][1] + S[1][1]) + (S[2][1] + S[3][1])));
                sts32(sa + 32, __float_as_uint((S[0][2] + S[1][2]) + (S[2][2] + S[3][2])));
                sts32(sa + 4 * SROW + 32, __float_as_uint((S[0][3] + S[1][3]) + (S[2][3] + S[3][3])));
            } else {
#pragma unroll
                for (int i = 0; i < 4; i++) ldsm4t(vf[i], (va ^ ((i & 1) << 5)) + (i >> 1) * 2048);
                uint32_t xa = l8 + S_X + (warp - 6) * 1024;
                pin<1>(&xa);
                mbar_wait(sb + B_X, s & 1);
                PROF(11)
#pragma unroll
                for (int k = 0; k < 8; k++) lds64(q[k], xa + (k >> 2) * 2048 + (k & 3) * 256);
#pragma unroll
                for (int k = 0; k < 4; k++) mma16816(S[k], q[4 + (k & 2)][0], q[4 + (k & 2)][1], q[5 + (k & 2)][0], q[5 + (k & 2)][1], q[k][0], q[k][1]);
                sts32(sa, __float_as_uint((S[0][0] + S[2][0]) + (S[1][2] + S[3][2])));
                sts32(sa + 4 * SROW, __float_as_uint((S[0][1] + S[2][1]) + (S[1][3] + S[3][3])));
            }
            lds64(vm[0], ad[1]); lds64(vm[1], ad[1] + 256);
            PROF(7)
            bar_sync(2, 160);
            const float cs = 0.08838834764831845f * 1.4426950408889634f;
            float E[6][2];
#pragma unroll
            for (int i = 0; i < 6; i++) lds64f(E[(i + 4) % 6], sr + ((i + 4) % 6) * 32);
            const uint32_t isn = lds32(ad[4]);
            E[4][0] += E[5][0]; E[4][1] += E[5][1];
            float m = fmaxf(fmaxf(fmaxf(fmaxf(E[0][0], E[0][1]), fmaxf(E[1][0], E[1][1])), fmaxf(fmaxf(E[2][0], E[2][1]), fmaxf(E[3][0], E[3][1]))), fmaxf(E[4][0], E[4][1]));
            m = fmaxf(m, __shfl_xor_sync(0xffffffffu, m, 1));
            m = fmaxf(m, __shfl_xor_sync(0xffffffffu, m, 2));
            m *= cs;
            if constexpr (AB) static_for<0, PRE3>([&](auto I) { load_w2<I.value>(w[I.value], w2a); });
            uint32_t pa[5];
#pragma unroll
            for (int i = 0; i < 5; i++) { const int k = (i + 4) % 5; E[k][0] = ex2(fmaf(E[k][0], cs, -m)); E[k][1] = ex2(fmaf(E[k][1], cs, -m)); pa[k] = pack2(E[k][0], E[k][1]); }
            if (EFENCE) sched_fence();
            float O[2][4], Z[4];
#pragma unroll
            for (int i = 0; i < 4; i++) { O[0][i] = O[1][i] = Z[i] = 0.f; }
#pragma unroll
            for (int i = 0; i < 2; i++) {
                mma1688(O[i], vm[i][0], vm[i][1], pa[4]);
                mma16816(O[i], vf[i][0], vf[i][1], vf[i][2], vf[i][3], pa[0], pa[1]);
                mma16816(O[i], vf[2 + i][0], vf[2 + i][1], vf[2 + i][2], vf[2 + i][3], pa[2], pa[3]);
            }
            const float z = (((E[4][0] + E[4][1]) + (E[0][0] + E[0][1])) + ((E[1][0] + E[1][1]) + (E[2][0] + E[2][1]))) + (E[3][0] + E[3][1]);
            const float zh = __uint_as_float(__float_as_uint(z) & 0xffff0000u);
            mma1688(Z, isn, isn, pack2(zh, z - zh));
            const float i0 = rcp(Z[0]), i1 = rcp(Z[1]);
            stsm4t(ad[3], pack2(O[0][0] * i0, O[0][1] * i1), pack2(O[0][2] * i0, O[0][3] * i1), pack2(O[1][0] * i0, O[1][1] * i1), pack2(O[1][2] * i0, O[1][3] * i1));
            PROF(4)
            if constexpr (AB) wo_blocks<1, RESA, PRE3, OFENCE / 2>(w, wr + NR * 8, oa, w2a, po, pd, odd);
            else bar_arrive(3, 256);
            if (ROLE != 0) persist(s, warp, r0, r1);
            if (warp == 7 && l8 == sb) mbar_expect(sb + B_X, 4096);
        } else {
            if (ROLE != 0) persist(s, warp, r0, r1);
            wo_addr(); pin<1>(&oa);
            static_for<0, PRE2A>([&](auto I) { load_w2<I.value>(w[I.value], w2a); });
            mbar_wait(sb + B_X, s & 1);
            if (warp == 0) {
                uint32_t sc[2];
                lds64(sc, sb + S_SC);
                const int em = __reduce_max_sync(0xffffffffu, lds32(sb + S_EM + ((l8 >> 1) & 28)));
                if (l8 == sb) sts32(sb + S_ISC + (~s & 1) * 4, min(max(em - 127, (int)sc[1]) + (int)sc[0], 253) * 0x800080u);
                bar_arrive(2, 160);
            }
            wait_clocks(XDELAY - (warp == 0) * 100);
            constexpr int PRE1 = (BB - 1) * 16 - (5 - NRB) * 8 < PRE2 ? (BB - 1) * 16 - (5 - NRB) * 8 : PRE2;
            static_for<PRE2A, PRE1>([&](auto I) { load_w2<I.value>(w[I.value], w2a); });
            if (full) {
                static_for<PRE1, PRE2>([&](auto I) { load_w2<I.value>(w[I.value], w2a); });
                wo_blocks<BB, RESB, PRE2, FENCE2 * 2 + OFENCE % 2>(w, wr + NR * 8, oa, w2a, po, pd, odd);
            } else wo_blocks<BB - 1, RESB1, PRE1, FENCE2 * 2 + OFENCE % 2>(w, wr + NR * 8, oa, w2a, po, pd, odd);
        }
        PROF(5)
        if (l8 == sb) { sts32(sb + S_TO + warp * 4, gtime()); mbar_arrive(sb + B_RED); }
        if (HOLD && !(PLATE >> ATT & 1)) mbar_wait(sb + B_RED, s & 1);
        if (ROLE != 0 && (s & 3) == 3 && l8 == sb) mbar_arrive(sb + B_PERS);
        if (ROLE == 0 && s == 62) return;
    }
    __syncwarp();
    if (l8 == sb) mbar_arrive(sb + B_PERS);
}
#define IP(i)
struct Pipe { uint32_t stage, phase; };
struct Cons {
    uint32_t sb, rel;
    int wg, wq, lane, rank, pair;
    uint32_t nst;
    Pipe p;
};
__device__ __forceinline__ void pipe_next(Pipe& p) { p.stage = (p.stage + 1) & (NSTAGE - 1); p.phase ^= (p.stage == 0); }
__device__ __forceinline__ void release(const Cons& c, uint32_t stage) { if (c.lane < 2) mbar_arrive_cluster(c.rel + stage * 8); }
__device__ __forceinline__ void wait_full(const Cons& c) { mbar_wait(c.sb + B_FULL + c.p.stage * 8, c.p.phase); }

enum { PEND_NONE = 0, PEND_KVO = 1, PEND_HT = 2, PEND_OUT = 3 };
struct Pend { uint32_t pk[64]; int kind, row, col, cnt; };

__device__ __forceinline__ void staging_wait(const Cons& c) { if (c.nst) mbar_wait(c.sb + B_SFREE + c.wg * 8, (c.nst - 1) & 1); }
__device__ __forceinline__ void staging_post(Cons& c, int kind, int row, int col, int cnt) {
    __syncwarp();
    if (c.lane == 0) {
        if (c.wq == 0) { const uint32_t x[4] = {(uint32_t)kind, (uint32_t)row, (uint32_t)col, (uint32_t)cnt}; sts128(c.sb + S_DESC + c.wg * 16, x); }
        mbar_arrive(c.sb + B_SFULL + c.wg * 8);
    }
    c.nst++;
}
__device__ __forceinline__ void drain(const Params& P, Cons& c, Pend& d) {
    const uint32_t* pk = d.pk;
    if (d.kind == PEND_OUT) {
        float* o = P.out + (size_t)(d.row + c.wq * 16 + (c.lane >> 2)) * 2048 + d.col + (c.lane & 3) * 2;
#pragma unroll
        for (int j = 0; j < 16; j++) {
            st_stream2(o + j * 8, bf_lo(pk[j * 2]), bf_hi(pk[j * 2]));
            st_stream2(o + 8 * 2048 + j * 8, bf_lo(pk[j * 2 + 1]), bf_hi(pk[j * 2 + 1]));
        }
    } else {
        const bool ht = d.kind == PEND_HT;
        const int hi = (c.lane >> 3) & 1;
        const uint32_t base = c.sb + S_STG + c.wg * 16384 + ((ht ? hi * 32 + c.wq * 8 : c.wq * 16 + hi * 8) + (c.lane & 7)) * 128;
        staging_wait(c);
#pragma unroll
        for (int j = 0; j < 8; j++) {
            const int ch = (j & 3) * 2 + (c.lane >> 4);
            stsm4(base + (j >> 2) * 8192 + ((ch ^ (c.lane & 7)) << 4), pk[j * 4], pk[j * 4 + 1], pk[j * 4 + 2], pk[j * 4 + 3]);
        }
        fence_async_smem();
        staging_post(c, d.kind, d.row, d.col, (d.col & 128) ? d.cnt : -1);
    }
    if (d.col & 128) d.kind = PEND_NONE;
    d.col += 128;
#pragma unroll
    for (int i = 0; i < 32; i++) d.pk[i] = d.pk[32 + i];
}

constexpr int S_STG2 = 8 * 20480, PEND_BOTH = 8;
__device__ __forceinline__ void drain_both(Cons& c, const Pend& d) {
    const uint32_t base = c.sb + c.wg * 16384 + (c.wq * 16 + ((c.lane >> 3) & 1) * 8 + (c.lane & 7)) * 128;
#pragma unroll
    for (int j = 0; j < 16; j++)
        stsm4(base + (j < 8 ? S_STG : S_STG2) + (j >> 2 & 1) * 8192 + ((((j & 3) * 2 + (c.lane >> 4)) ^ (c.lane & 7)) << 4), d.pk[j * 4], d.pk[j * 4 + 1], d.pk[j * 4 + 2], d.pk[j * 4 + 3]);
    fence_async_smem();
    staging_post(c, PEND_KVO | PEND_BOTH, d.row, d.col, d.cnt);
}

__device__ __forceinline__ void store_warp(const Params& P, uint32_t sb, int wg, int cta) {
    if (cta < 128) {
        for (int i = 0; i < P.xd; i++) __nanosleep(1000);
        const uint32_t e1 = get_epoch(sb) + 1;
        const uint4* x = (const uint4*)P.Bx + (cta * 2 + wg) * 1024 + (threadIdx.x & 31);
        uint32_t m = 0;
#pragma unroll 4
        for (int i = 0; i < 32; i++) { const uint4 u = __ldg(x + i * 32); m = amax(amax(m, amax(u.x, u.y)), amax(u.z, u.w)); }
        m = warp_exp(m);
        if (elect_one()) { atomicMax(&g_cnt(C_XMAX), e1 << 8 | m); red_release(&g_cnt(C_XCNT)); }
        __syncwarp();
    }
    const uint32_t stg = sb + S_STG + wg * 16384;
#pragma unroll 1
    for (uint32_t n = 0;; n++) {
        mbar_wait(sb + B_SFULL + wg * 8, n & 1);
        uint32_t x[4];
        lds128(x, sb + S_DESC + wg * 16);
#pragma unroll
        for (int i = 0; i < 4; i++) x[i] = __shfl_sync(0xffffffffu, x[i], 0);
        if (x[0] == PEND_NONE) break;
        const bool ht = x[0] == PEND_HT;
        const CUtensorMap* m = &P.tm[ht ? M_HTS : M_KVO];
        const uint64_t pol = P.pol[ht ? 2 : x[1] >= 4096 ? 1 : (x[1] & 2047) < 1536 ? 0 : 10];
        if (elect_one()) {
#pragma unroll
            for (int i = 0; i < 4; i++) tma_store2d(m, x[2] + (i >> 1) * 64, x[1] + (i & 1) * (ht ? 1024 : 32), stg + i * 4096, pol);
            if (x[0] & PEND_BOTH) {
#pragma unroll 1
                for (int i = 0; i < 4; i++) tma_store2d(m, x[2] + 128 + (i >> 1) * 64, x[1] + (i & 1) * 32, stg + (S_STG2 - S_STG) + i * 4096, pol);
            }
            bulk_commit();
            bulk_wait_read();
            mbar_arrive(sb + B_SFREE + wg * 8);
            if ((int)x[3] >= 0) { bulk_wait_all(); fence_async(); red_relaxed(&g_cnt(x[3])); }
        }
        __syncwarp();
    }
}

template <int TA, int TB, bool FIRST>
__device__ __forceinline__ void issue_ktile(float* acc, const Cons& c) {
    const uint32_t a = c.sb + c.p.stage * STAGE + c.wg * 8192, b = c.sb + c.p.stage * STAGE + 16384;
    const uint64_t da = mkdesc(a, TA ? 8192 : 16, 1024, 1), db = mkdesc(b, TB ? 8192 : 16, 1024, 1);
    wg_fence();
#pragma unroll
    for (int k = 0; k < 4; k++) {
        if (FIRST && k == 0) wgmma_ss256_first<TA, TB>(acc, da, db);
        else wgmma_ss256<TA, TB>(acc, da + (TA ? 128 : 2) * k, db + (TB ? 128 : 2) * k);
    }
    wg_commit();
}
template <bool KVONLY, bool FIRST>
__device__ __forceinline__ void issue_any(float* acc, const Cons& c, int type) {
    wait_full(c);
    if (!KVONLY && type == T_A1) issue_ktile<0, 0, FIRST>(acc, c);
    else if (!KVONLY && type == T_A2) issue_ktile<1, 0, FIRST>(acc, c);
    else issue_ktile<0, 1, FIRST>(acc, c);
}
template <bool KVONLY = false>
__device__ __forceinline__ void mainloop(float* acc, const Params& P, Cons& c, Pend& d, int type, int nk) {
    issue_any<KVONLY, true>(acc, c, type);
    if (!KVONLY) { IP(0) }
    uint32_t prev = c.p.stage;
    pipe_next(c.p);
#pragma unroll 1
    for (int kt = 1; kt < nk; kt++) {
        if (!KVONLY && d.kind != PEND_NONE && kt != 2) drain(P, c, d);
        issue_any<KVONLY, false>(acc, c, type);
        wg_wait<1>();
        release(c, prev);
        prev = c.p.stage;
        pipe_next(c.p);
    }
    d.kind = PEND_NONE;
    wg_wait<0>();
    pin<128>(acc);
    release(c, prev);
    if (!KVONLY) { IP(1) }
}
__device__ __forceinline__ void pack_half(uint32_t* pk, const float* a) {
#pragma unroll
    for (int i = 0; i < 32; i++) pk[i] = pack2(a[2 * i], a[2 * i + 1]);
}

__device__ __forceinline__ void epi_kv(const float* acc, const Cons& c, Pend& d, int mb, int nb) {
    pack_half(d.pk, acc); pack_half(d.pk + 32, acc + 64);
    d.kind = PEND_KVO; d.row = (nb >> 4) * 2048 + mb * 256 + c.rank * 128 + c.wg * 64; d.col = (nb & 15) * 256; d.cnt = C_KV + mb;
}

__device__ __forceinline__ void qa_scores(float* S, float* Sm, const uint32_t* q, Cons& c) {
    wait_full(c);
    const uint32_t st = c.sb + c.p.stage * STAGE;
    const uint64_t dk = mkdesc(st + c.wg * 8192, 16, 1024, 1), dm = mkdesc(st + 32768 + c.wg * 4096, 128, 2048, 0);
    wg_fence();
#pragma unroll
    for (int i = 0; i < 8; i++) wgmma_rs64<0>(S, q + i * 4, dk + (i >> 2) * 1024 + (i & 3) * 2, i != 0);
#pragma unroll
    for (int i = 0; i < 8; i++) wgmma_rs16<0>(Sm, q + i * 4, dm + i * 16, i != 0);
    wg_commit();
    pipe_next(c.p);
}
__device__ __forceinline__ void qa_softmax(uint32_t (*pa)[4], const float* S, const float* Sm, const Cons& c) {
    const int t = c.lane & 3, i0 = (c.wq & 1) * 16 + (c.lane >> 2) - 2 * t;
    const bool sg = c.wq >= 2;
    const float cs = 0.08838834764831845f * 1.4426950408889634f;
    float x[2][10];
#pragma unroll
    for (int r = 0; r < 2; r++) {
#pragma unroll
        for (int j = 0; j < 4; j++)
#pragma unroll
            for (int e = 0; e < 2; e++) {
                const float v = sg ? S[16 + j * 4 + r * 2 + e] : S[j * 4 + r * 2 + e];
                x[r][j * 2 + e] = (j * 8 + e - r * 8 > i0) ? -1e9f / 0.08838834764831845f : v;
            }
        x[r][8] = sg ? Sm[4 + r * 2] : Sm[r * 2];
        x[r][9] = sg ? Sm[5 + r * 2] : Sm[1 + r * 2];
        float m = fmaxf(fmaxf(fmaxf(fmaxf(x[r][0], x[r][1]), fmaxf(x[r][2], x[r][3])), fmaxf(fmaxf(x[r][4], x[r][5]), fmaxf(x[r][6], x[r][7]))), fmaxf(x[r][8], x[r][9]));
        m = fmaxf(m, __shfl_xor_sync(0xffffffffu, m, 1));
        m = fmaxf(m, __shfl_xor_sync(0xffffffffu, m, 2));
        m *= -cs;
#pragma unroll
        for (int i = 0; i < 10; i++) x[r][i] = ex2(fmaf(x[r][i], cs, m));
        float sum = (((x[r][0] + x[r][1]) + (x[r][2] + x[r][3])) + ((x[r][4] + x[r][5]) + (x[r][6] + x[r][7]))) + (x[r][8] + x[r][9]);
        sum += __shfl_xor_sync(0xffffffffu, sum, 1);
        sum += __shfl_xor_sync(0xffffffffu, sum, 2);
        const float inv = rcp(sum);
#pragma unroll
        for (int i = 0; i < 10; i++) x[r][i] *= inv;
    }
#pragma unroll
    for (int ks = 0; ks < 2; ks++)
#pragma unroll
        for (int i = 0; i < 4; i++) {
            const uint32_t p = pack2(x[i & 1][ks * 4 + (i >> 1) * 2], x[i & 1][ks * 4 + (i >> 1) * 2 + 1]);
            pa[ks][i] = sg ? 0u : p;
            pa[2 + ks][i] = sg ? p : 0u;
        }
#pragma unroll
    for (int r = 0; r < 2; r++) {
        const uint32_t p = pack2(x[r][8], x[r][9]);
        pa[4][r] = sg ? 0u : p;
        pa[4][2 + r] = sg ? p : 0u;
    }
}
__device__ __forceinline__ void qa_values(float* O, uint32_t (*pa)[4], Cons& c) {
    wait_full(c);
    const uint32_t st = c.sb + c.p.stage * STAGE;
    const uint64_t dv = mkdesc(st + c.wg * 8192, 16384, 1024, 1), dm = mkdesc(st + 32768 + c.wg * 4096, 2048, 128, 0);
    pin<20>(&pa[0][0]);
    wg_fence();
#pragma unroll
    for (int ks = 0; ks < 4; ks++) wgmma_rs128<1>(O, pa[ks], dv + ks * 128, ks != 0);
    wgmma_rs128<0>(O, pa[4], dm, 1);
    wg_commit();
    pipe_next(c.p);
}
__device__ __forceinline__ void epi_qa(const float* acc, Cons& c, Pend& d, int mb, int nb) {
    uint32_t q[64], pa[2][5][4];
    float S0[32] = {}, M0[8] = {}, S1[32] = {}, M1[8] = {}, O0[64] = {}, O1[64] = {};
    const uint32_t k0 = c.p.stage;
    pack_half(q, acc);
    pin<32>(q); pin<32>(S0); pin<8>(M0);
    qa_scores(S0, M0, q, c);
    pack_half(q + 32, acc + 64);
    pin<32>(q + 32); pin<32>(S1); pin<8>(M1);
    qa_scores(S1, M1, q + 32, c);
    wg_wait<1>();
    pin<32>(S0); pin<8>(M0);
    release(c, k0);
    qa_softmax(pa[0], S0, M0, c);
    wg_wait<0>();
    pin<32>(S1); pin<8>(M1); pin<64>(q);
    release(c, (k0 + 1) & (NSTAGE - 1));
    pin<64>(O0);
    qa_values(O0, pa[0], c);
    qa_softmax(pa[1], S1, M1, c);
    pin<64>(O1);
    qa_values(O1, pa[1], c);
    wg_wait<1>();
    pin<64>(O0); pin<20>(&pa[0][0][0]);
    release(c, (k0 + 2) & (NSTAGE - 1));
    pack_half(d.pk, O0);
    wg_wait<0>();
    pin<64>(O1); pin<20>(&pa[1][0][0]);
    release(c, (k0 + 3) & (NSTAGE - 1));
    pack_half(d.pk + 32, O1);
    d.kind = PEND_KVO; d.row = 4096 + mb * 256 + c.rank * 128 + c.wg * 64; d.col = nb * 256; d.cnt = C_O + mb;
}

__device__ __forceinline__ void epi_op(const float* acc, const Cons& c, Pend& d, int mb, int nb) {
    pack_half(d.pk, acc); pack_half(d.pk + 32, acc + 64);
    d.kind = PEND_OUT; d.row = mb * 256 + c.rank * 128 + c.wg * 64; d.col = 1024 + nb * 256;
}

__device__ __forceinline__ void epi_a2(float* acc, const Params& P, Cons& c, int mb, int col0) {
    const int g = c.lane >> 2, t = c.lane & 3;
    const int row = mb * 256 + (g >> 1) * 64 + (c.rank * 16 + c.wg * 8 + c.wq * 2) * 2 + (g & 1);
    float* o = P.out + (size_t)row * 2048 + col0 + t * 2;
#pragma unroll 1
    for (int hf = P.zero; hf < 2; hf++) {
    wait_full(c);
    const uint32_t st = c.sb + c.p.stage * STAGE, xa = st + (c.wg * 64 + c.wq * 16 + g) * 128 + t * 4 + (g << 4), da = st + 32768 + t * 4;
#pragma unroll
    for (int j = 0; j < 16; j++) {
        const float* a = acc + j * 4;
        const uint32_t ad = (xa ^ ((j & 7) << 4)) + (j >> 3) * 16384;
        const uint32_t x0 = lds32(ad), x1 = lds32(ad + 1024), dv = lds32(da + j * 16);
        const uint32_t u0 = mul_bf2(x0, dv), u1 = mul_bf2(x1, dv);
        st_stream2(o + j * 8, a[0] + bf_lo(u0), a[1] + bf_hi(u0));
        st_stream2(o + 2 * 2048 + j * 8, a[2] + bf_lo(u1), a[3] + bf_hi(u1));
    }
    __syncwarp();
    release(c, c.p.stage);
    pipe_next(c.p);
    o += 128;
#pragma unroll
    for (int i = 0; i < 64; i++) acc[i] = acc[64 + i];
    }
}

#define TSTAMP(i)
__device__ __forceinline__ float2 cmul(float2 a, float2 b) { return make_float2(fmaf(a.x, b.x, -a.y * b.y), fmaf(a.x, b.y, a.y * b.x)); }
__device__ __forceinline__ float2 cfma(float2 a, float2 b, float2 u) { return make_float2(fmaf(a.x, b.x, fmaf(-a.y, b.y, u.x)), fmaf(a.x, b.y, fmaf(a.y, b.x, u.y))); }
__device__ __forceinline__ float4 ssm_coef(float lre, float lim, float logdt) {
    const float dt = __bfloat162float(__float2bfloat16(expf(logdt)));
    const float ea = expf(dt * lre);
    float sn, cn;
    sincosf(dt * lim, &sn, &cn);
    const float br = ea * cn, bi = ea * sn, nr = br - 1.f;
    const bool sw = fabsf(lre) < fabsf(lim);
    const float big = sw ? lim : lre, r = __fdividef(sw ? lre : lim, big), inv = __fdividef(1.f, fmaf(sw ? lre : lim, r, big));
    const float cr = (sw ? fmaf(nr, r, bi) : fmaf(bi, r, nr)) * inv, ci = (sw ? fmaf(bi, r, -nr) : fmaf(-nr, r, bi)) * inv;
    return make_float4(br, bi, cr, ci);
}
__device__ __forceinline__ void epi_a1(const float* acc, const Params& P, const Cons& c, Pend& d, int mb, int nb) {
    const uint32_t atag = (get_epoch(c.sb) + 1) & 1;
    const int t = c.lane & 3;
    const int p = nb * 128 + c.rank * 64 + c.wg * 32 + c.wq * 8 + (c.lane >> 2);
    const float4 cf = __ldcg(&g_coef[p]);
    const float2 lam = make_float2(cf.x, P.swap_ri ? -cf.y : cf.y);
    const float a0 = P.swap_ri ? -2.f * cf.w : 2.f * cf.z, a1 = P.swap_ri ? 2.f * cf.z : -2.f * cf.w;
    const float b0 = P.swap_ri ? -2.f * cf.z : -2.f * cf.w, b1 = P.swap_ri ? -2.f * cf.w : -2.f * cf.z;
    float2 h = make_float2(0.f, 0.f);
#pragma unroll
    for (int round = 0; round < 2; round++) {
#pragma unroll
        for (int j = 0; j < 32; j++) {
            h = cfma(lam, h, make_float2(acc[j * 4], acc[j * 4 + 2]));
            const float r0 = fmaf(a0, h.x, a1 * h.y), m0 = fmaf(b0, h.x, b1 * h.y);
            h = cfma(lam, h, make_float2(acc[j * 4 + 1], acc[j * 4 + 3]));
            d.pk[j * 2] = pack2(r0, fmaf(a0, h.x, a1 * h.y));
            d.pk[j * 2 + 1] = pack2(m0, fmaf(b0, h.x, b1 * h.y));
        }
        if (round) break;
        float2 l64 = lam;
#pragma unroll
        for (int i = 0; i < 6; i++) l64 = cmul(l64, l64);
        const float2 l128 = cmul(l64, l64), l256 = cmul(l128, l128);
        float2 o = make_float2(__shfl_up_sync(0xffffffffu, h.x, 1), __shfl_up_sync(0xffffffffu, h.y, 1));
        if (t >= 1) h = cfma(l64, o, h);
        o = make_float2(__shfl_up_sync(0xffffffffu, h.x, 2), __shfl_up_sync(0xffffffffu, h.y, 2));
        if (t >= 2) h = cfma(l128, o, h);
        IP(2)
        if (t == 3) st_relaxed2(&g_agg[mb * 1024 + p], (__float_as_uint(h.x) & ~1u) | atag, __float_as_uint(h.y));
        h = make_float2(__shfl_up_sync(0xffffffffu, h.x, 1), __shfl_up_sync(0xffffffffu, h.y, 1));
        if (t == 0) h = make_float2(0.f, 0.f);
        uint32_t ax[7], ay[7];
        while (true) {
            uint32_t bad = 0;
#pragma unroll
            for (int j = 0; j < 7; j++) { ax[j] = atag; ay[j] = 0; ld_relaxed2_if(ax[j], ay[j], &g_agg[j * 1024 + p], j < mb); }
#pragma unroll
            for (int j = 0; j < 7; j++) bad |= ax[j] ^ atag;
            if (tags_ok(bad)) break;
            __nanosleep(2 * POLLNS);
        }
        float2 carry = make_float2(0.f, 0.f);
#pragma unroll
        for (int j = 0; j < 7; j++) if (j < mb) carry = cfma(l256, carry, make_float2(__uint_as_float(ax[j]), __uint_as_float(ay[j])));
        float2 w = (t & 1) ? l64 : make_float2(1.f, 0.f);
        if (t & 2) w = cmul(w, l128);
        h = cfma(w, carry, h);
        IP(3)
    }
    IP(4)
    d.kind = PEND_HT; d.row = nb * 128 + c.rank * 64 + c.wg * 32; d.col = mb * 256; d.cnt = C_HT + mb;
}

__device__ __forceinline__ uint32_t fresh_tid() { uint32_t t; asm volatile("mov.u32 %0, %%tid.x;" : "=r"(t)); return t; }
__device__ __forceinline__ uint32_t acquire_stage(uint32_t sb, Pipe& p, uint32_t bytes) {
    mbar_wait(sb + B_EMPTY + p.stage * 8, p.phase ^ 1);
    mbar_expect_e(sb + B_FULL + p.stage * 8, bytes);
    return p.stage;
}
__device__ __forceinline__ void producer(const Params& P, const uint32_t sb, const int cta, const uint32_t epoch) {
    Pipe p = {0, 0};
    uint32_t resume = 1;
    const uint32_t e1 = epoch + 1;
    const int rank = cta & 1;
    const uint16_t both = 3 << (__shfl_sync(0xffffffffu, cluster_rank(), 0) & ~1u);
    for (int it = ITEM_OFF(cta >> 1), item = 0; !(item & LAST); it++) {
        item = ITEM(it);
        const int type = (item >> 8) & 7, mb = (item >> 5) & 7, nb = item & 31, half = item >> 12 & 1, hw = item >> 13 & 1;
        if (type == T_CHAIN) {
            const int h = cta / 3, role = cta - h * 3;
#pragma unroll 1
            for (int w = 0; w < 8; w++) {
                mbar_wait(sb + B_EMPTY + (w * 20480 + 20479) / STAGE * 8, 1);
                chain_load(P, sb, cta, w, threadIdx.x & 31, 0);
            }
            uint32_t* flag = &g_cnt(C_FLAG + (role == 2 ? 32 : 0) + h);
            if (role) { wait_count(&g_cnt(C_KV), e1 * 128); fence_async(); }
#pragma unroll 1
            for (int s = 0; s < 64 && role != 0; s++) {
                if (s < 63) {
                    mbar_wait(sb + B_GO, s & 1);
                    tma3d_mc_e(sb + S_KV + (role - 1) * 8192, &P.tm[M_SEG], 0, (role - 1) * 2048 + s * 32, h * 2, sb + B_KVFULL, 7 << ((h & 1) * 3), P.pol[s < 48 ? 8 : 11]);
                    if ((s & 7) == 7) { wait_count(&g_cnt(C_KV + 1 + (s >> 3)), e1 * 128); fence_async(); }
                    tma_prefetch3d_e(&P.tm[M_SEG], 0, (role - 1) * 2048 + s * 32 + 32, h * 2);
                }
                if (s > 0 && ((s & 3) == 0 || s == 63)) {
                    const int i = (s - 1) >> 2;
                    mbar_wait(sb + B_PERS, i & 1);
                    asm volatile("{\n.reg .pred E;\nelect.sync _|E, 0xffffffff;\n@E st.release.gpu.global.u32 [%0], %1;\n}" ::"l"(flag), "r"(epoch * 64 + i * 4 + 4) : "memory");
                }
            }
            if (role == 0) {
                const int lane = threadIdx.x & 31;
                if (lane == 0) mbar_arrive(sb + B_RELM);
#pragma unroll 1
                for (int s = 0; s < 63; s++) {
                    mbar_wait(sb + B_P1, s & 1);
                    if (s > 0) {
                        st_relaxed4(P.xb + xg_buf(s - 1) + h * 2048 + xg_lane(lane), 0, 0, 0, 0);
                        st_relaxed1(P.xb + xg_buf(s - 1) + xg_side(h) + lane * 4, 0);
                        __threadfence();
                    }
                    __syncwarp();
                    if (lane == 0) mbar_arrive(sb + B_RELM);
                }
            }
            if ((threadIdx.x & 31) < M_C1 - 1) asm volatile("prefetch.tensormap [%0];" ::"l"(&P.tm[1 + (threadIdx.x & 31)]) : "memory");
            resume = 0;
            continue;
        }
        const int m0 = mb * 256 + rank * 128, ssm = type >= T_A1;
        const CUtensorMap* ma = &P.tm[max(type, 1) + half * M_HALF];
        const CUtensorMap* mw = &P.tm[type ? M_WV + type : M_WK + (nb >> 4)];
        const int nk = type == T_OP ? 64 : type == T_A2 ? 32 : 16;
        const int a3 = type == T_A1 ? nb * 16 + rank * 8 + hw * 4 : type == T_A2 ? mb * 4 + rank * 2 + hw : (type == T_OP ? 4096 : 0) + m0 + hw * 64;
        const int b3 = type == T_A1 ? mb * 128 + rank * 16 : type == T_A2 ? (nb * 2 + rank) * 128 : (nb & 15) * 4 + rank * 2;
        if (type) {
            wait_count(&g_cnt(type == T_A1 ? C_COEF : (type >> 1) * 8 + mb), e1 * (type == T_A1 ? 4 : 128 >> (type >> 1)));
            fence_async();
        }
        if (type == T_A1) l2_prefetch_e(g_coef + nb * 128 + rank * 64, 1024);
        auto arrived = [&]() {
            const uint32_t t = fresh_tid();
            return __all_sync(0xffffffffu, (int32_t)(ld_acquire(&g_cnt(C_FLAG + (t & 2) * 16 + nb * 2 + (t & 1))) - (epoch * 64 + mb * 8 + rank * 4 + 4)) >= 0);
        };
        bool passed = false;
        mbar_wait(sb + B_RESUME, resume);
#pragma unroll 1
        for (int kt = 0; kt < nk; kt++) {
            if (type == T_QA && kt == 9) passed = arrived();
            const uint32_t st = acquire_stage(sb, p, STAGE - half * 8192), bar = sb + B_FULL + st * 8;
            const int a1 = type == T_A2 ? kt * 64 : 0, b0 = ssm ? (kt & 15) * 64 : 0;
            tma4d_e(sb + st * STAGE + hw * 8192, ma, kt * 64 - a1, a1, a3, bar, P.pol[11]);
            tma4d_mc_e(sb + st * STAGE + 16384 + rank * 16384, mw + (ssm & kt >> 4), b0, ssm ? 0 : kt * 64, b3, bar, both, P.pol[(item & 0x7e0) == 224 ? 9 : 11]);
            if (type == T_QA && kt < 8) tma_prefetch4d_e(&P.tm[M_OA], nb * 256 + (kt & 3) * 64, (kt >> 2) * 2048 + m0);
            pipe_next(p);
        }
        if (type == T_QA) {
            while (!passed) { passed = arrived(); if (!passed) __nanosleep(POLLNS); }
            fence_async();
        }
        const int q = type == T_QA;
#pragma unroll 1
        for (int e = 0; e < (q ? 4 : type == T_A2 ? 2 : 0); e++) {
            const uint32_t st = acquire_stage(sb, p, q ? 40960 : 32768 + 256), bar = sb + B_FULL + st * 8, dst = sb + st * STAGE;
#pragma unroll 1
            for (int i = 0; i < 2; i++) tma4d_e(dst + i * 16384, &P.tm[q ? M_OA : M_AX], nb * 256 + (e & 1) * 128 + i * 64, 0, q ? (e >> 1) * 2048 + m0 : mb * 128 + rank * 16, bar, P.pol[q ? 3 : 11]);
            const uint8_t* src = q ? (const uint8_t*)(((e >> 1) ? g_vmt : g_km) + ((mb * 8 + rank * 4) * 32 + nb * 2 + (e & 1)) * 512) : (const uint8_t*)(P.Dskip + nb * 256 + e * 128);
#pragma unroll 1
            for (int i = 0; i < (q ? 4 : 1); i++) bulk_g2s_e(dst + 32768 + i * 2048, src + i * 65536, q ? 2048 : 256, bar);
            pipe_next(p);
        }
    }
#pragma unroll 1
    for (int i = 0; i < NSTAGE; i++) { mbar_wait(sb + B_EMPTY + p.stage * 8, p.phase ^ 1); pipe_next(p); }
}

__device__ __forceinline__ uint32_t fresh_ctaid() { uint32_t t; asm volatile("mov.u32 %0, %%ctaid.x;" : "=r"(t)); return t; }
__device__ __forceinline__ void reset_state(const Params& P, Cons& c, Pend& d, uint32_t sb, bool resumed) {
    const uint32_t t = fresh_tid(), b = fresh_ctaid() + P.cta0;
    const int w = __shfl_sync(0xffffffffu, t >> 5, 0);
    c.sb = sb; c.wg = w >> 2; c.wq = w & 3; c.lane = t & 31;
    c.rank = __shfl_sync(0xffffffffu, b & 1, 0); c.pair = __shfl_sync(0xffffffffu, b >> 1, 0);
    c.rel = mapa(sb + B_EMPTY, cluster_rank() ^ (c.lane & 1));
    c.p.stage = 0; c.p.phase = 0;
    c.nst = resumed && c.pair < NCHAIN;
    d = Pend{};
}
#define PROF_ITEM(i, item)

__global__ void __launch_bounds__(384, 1) fused_kernel(const __grid_constant__ Params P) {
    extern __shared__ __align__(1024) uint8_t smem[];
    const uint32_t sb = smem_u32(smem);
    asm volatile("griddepcontrol.launch_dependents;");
    declare_fence(P.zero);
    const int tid = threadIdx.x, lane = tid & 31;
    const int warp = __shfl_sync(0xffffffffu, tid >> 5, 0);
    const int cta = __shfl_sync(0xffffffffu, blockIdx.x + P.cta0, 0), pair = cta >> 1, rank = cta & 1;
    if (tid == 0) {
        if (sb & 1023) spin_fault();
        for (int i = 0; i < NSTAGE; i++) { mbar_init(sb + B_FULL + i * 8, 1); mbar_init(sb + B_EMPTY + i * 8, 16); }
        mbar_init(sb + B_RESUME, 2);
        mbar_init(sb + B_KVFULL, 1);
        mbar_init(sb + B_GO, 3); mbar_init(sb + B_RED, 8); mbar_init(sb + B_P1, 1); mbar_init(sb + B_EPOCH, 1); mbar_init(sb + B_PERS, 8); mbar_init(sb + B_INIT, 8); mbar_init(sb + B_INIT2, 8);
        mbar_init(sb + B_READY, 8);
        for (int i = 0; i < 2; i++) { mbar_init(sb + B_SFULL + i * 8, 4); mbar_init(sb + B_SFREE + i * 8, 1); }
        mbar_init(sb + B_RELM, cta % 3 ? 1 : 2); mbar_init(sb + B_X, 9);
        mbar_init(sb + B_DONE, 2);
        mbar_expect(sb + B_X, 4096);
        sts64(sb + S_EV, 0, 0);
        asm volatile("fence.mbarrier_init.release.cluster;" ::: "memory");
    }
    __syncthreads();
    cluster_sync();
    if (warp >= 8) {
        asm volatile("setmaxnreg.dec.sync.aligned.u32 24;");
        if (warp == 8) {
            producer(P, sb, cta, get_epoch(sb));
        } else if (warp == 9) {
            const uint32_t epoch = __shfl_sync(0xffffffffu, ld_acquire(&g_cnt(C_EPOCH)), 0);
            if (lane == 0) { sts32(sb + S_EPOCH, epoch); mbar_arrive(sb + B_EPOCH); red_release(&g_cnt(C_READ)); }
            __syncwarp();
            if (pair < NCHAIN) pacer(P, sb, cta, lane, epoch);
            if (cta == 0 && lane == 0) {
                for (int n = 0; (int32_t)(ld_acquire(&g_cnt(C_READ)) - (epoch + 1) * (NPAIR * 2)) < 0; n++) if (n > SPIN_LIMIT) spin_fault();
                st_relaxed1(&g_cnt(C_EPOCH), epoch + 1);
            }
            __syncwarp();
            mbar_wait_bounded(sb + B_DONE, 0);
        } else {
            store_warp(P, sb, warp - 10, cta);
        }
    } else {
        asm volatile("setmaxnreg.inc.sync.aligned.u32 240;");
        Cons c;
        Pend d;
        if (pair < NCHAIN) {
            reset_state(P, c, d, sb, false);
            {
                const int item = ITEM(ITEM_OFF(pair));
                PROF_ITEM(0, item)
                float acc[128];
                mainloop<true>(acc, P, c, d, T_KV, 16);
                ISTAMP(4)
                epi_kv(acc, c, d, (item >> 5) & 7, item & 31);
            }
            ISTAMP(9)
            mbar_wait(sb + B_EMPTY + 3 * 8, 1);
            drain_both(c, d);
            ISTAMP(10)
            uint32_t wr[40][4];
            chain_fetch(P, sb, cta, warp, lane, wr);
            PROF_ITEM(1, T_CHAIN << 8)
            chain_bounds(sb, cta, warp, lane, wr);
            ISTAMP(11)
            if (warp < 4) chain_role<false>(P, sb, cta, warp, lane, wr);
            else chain_role<true>(P, sb, cta, warp, lane, wr);
            fence_async_smem();
            bar_sync(1, 256);
            const uint32_t t2 = fresh_tid();
            if (t2 < 2) mbar_arrive_cluster(mapa(sb + B_RESUME, cluster_rank() ^ t2));
        } else if (pair >= NPAIR - 2) {
            const int ch = (pair - (NPAIR - 2)) * 512 + rank * 256 + tid;
            g_coef[ch] = ssm_coef(__bfloat162float(P.Lre[ch]), __bfloat162float(P.Lim[ch]), __bfloat162float(P.logdt[ch]));
            bar_sync(1, 256);
            if (tid == 0) red_release(&g_cnt(C_COEF));
        }
        reset_state(P, c, d, sb, true);
        int it = ITEM_OFF(c.pair) + (c.pair < NCHAIN ? 2 : 0);
        for (int prev = c.pair < NCHAIN ? ITEM(it - 1) : 0;; prev = ITEM(it++)) {
            const bool last = prev & LAST;
            const int item = ITEM(it), type = (item >> 8) & 7, mb = (item >> 5) & 7, nb = item & 31;
            const bool idle = (item >> 12 & 3) == 3 - 2 * c.wg;
            if (d.kind != PEND_NONE && ((prev & (LAST | URGENT)) || idle || (type != T_KV && !bar_and(5 + c.wg, mbar_try(sb + B_FULL + c.p.stage * 8, c.p.phase))))) {
#pragma unroll 1
                while (d.kind != PEND_NONE) drain(P, c, d);
            }
            if (last) break;
            const int nk = type == T_OP ? 64 : type == T_A2 ? 32 : 16;
            PROF_ITEM(it - ITEM_OFF(c.pair), item)
            if (idle) {
#pragma unroll 1
                for (int kt = nk + (type == T_A2 ? 2 : type == T_QA ? 4 : 0); kt > 0; kt--) { wait_full(c); release(c, c.p.stage); pipe_next(c.p); }
                continue;
            }
            float acc[128];
            mainloop(acc, P, c, d, type, nk);
            if (type == T_KV) epi_kv(acc, c, d, mb, nb);
            else if (type == T_QA) epi_qa(acc, c, d, mb, nb);
            else if (type == T_OP) epi_op(acc, c, d, mb, nb);
            else if (type == T_A1) epi_a1(acc, P, c, d, mb, nb);
            else epi_a2(acc, P, c, mb, nb * 256);
        }
        staging_wait(c);
        staging_post(c, PEND_NONE, 0, 0, 0);
        if (c.wq == 0 && c.lane == 0) mbar_arrive(sb + B_DONE);
    }
}

typedef CUresult (*EncodeFn)(CUtensorMap*, CUtensorMapDataType, cuuint32_t, void*, const cuuint64_t*, const cuuint64_t*, const cuuint32_t*, const cuuint32_t*,
                             CUtensorMapInterleave, CUtensorMapSwizzle, CUtensorMapL2promotion, CUtensorMapFloatOOBfill);
void encode(EncodeFn fn, CUtensorMap* m, const void* base, int rank, const uint64_t* dims, const uint64_t* strides, const uint32_t* box, CUtensorMapSwizzle swz = CU_TENSOR_MAP_SWIZZLE_128B) {
    cuuint64_t d[5], s[5]; cuuint32_t b[5], e[5];
    for (int i = 0; i < rank; i++) { d[i] = dims[i]; b[i] = box[i]; e[i] = 1; if (i) s[i - 1] = strides[i - 1]; }
    fn(m, CU_TENSOR_MAP_DATA_TYPE_BFLOAT16, rank, (void*)base, d, s, b, e, CU_TENSOR_MAP_INTERLEAVE_NONE, swz,
       CU_TENSOR_MAP_L2_PROMOTION_L2_256B, CU_TENSOR_MAP_FLOAT_OOB_FILL_NONE);
}
void map_kmajor(EncodeFn fn, CUtensorMap* m, const void* base, uint64_t rows, uint64_t cols, uint32_t box_rows) {
    const uint64_t d[4] = {cols, 1, 1, rows}, s[3] = {cols * 2, cols * 2, cols * 2}; const uint32_t b[4] = {64, 1, 1, box_rows};
    encode(fn, m, base, 4, d, s, b);
}
void map_mnmajor(EncodeFn fn, CUtensorMap* m, const void* base, uint64_t krows, uint64_t cols, uint32_t groups = 2) {
    const uint64_t d[4] = {64, krows, 1, cols / 64}, s[3] = {cols * 2, 128, 128}; const uint32_t b[4] = {64, 64, 1, groups};
    encode(fn, m, base, 4, d, s, b);
}
void map_store(EncodeFn fn, CUtensorMap* m, const void* base, uint64_t rows, uint64_t cols) {
    const uint64_t d[2] = {cols, rows}, s[1] = {cols * 2}; const uint32_t b[2] = {64, 32};
    encode(fn, m, base, 2, d, s, b);
}

}

extern "C" void kernel_launch(void* const* d_in, const int* in_sizes, int n_in, void* d_out, int out_size) {
    static Params P;
    static EncodeFn fn = nullptr;
    if (!fn) {
        cudaDriverEntryPointQueryResult q;
        cudaGetDriverEntryPoint("cuTensorMapEncodeTiled", (void**)&fn, cudaEnableDefault, &q);
        cudaFuncSetAttribute(fused_kernel, cudaFuncAttributeMaxDynamicSharedMemorySize, S_TOTAL);
    }
    const bf16* in[15];
    for (int i = 0; i < 15; i++) in[i] = (const bf16*)d_in[i];
    void *kvo, *ht;
    cudaGetSymbolAddress(&kvo, g_kvo);
    cudaGetSymbolAddress(&ht, g_ht);
    map_kmajor(fn, &P.tm[M_BX], in[9], 2048, 1024, 128);
    map_mnmajor(fn, &P.tm[M_WQ], in[11], 1024, 4096);
    map_mnmajor(fn, &P.tm[M_WK], in[12], 1024, 4096);
    map_mnmajor(fn, &P.tm[M_WV], in[13], 1024, 4096);
    map_mnmajor(fn, &P.tm[M_WO], in[14], 4096, 1024);
    map_kmajor(fn, &P.tm[M_OA], kvo, 3 * 2048, 4096, 128);
    P.swap_ri = in[4] < in[3];
    {
        const bf16* lo = P.swap_ri ? in[4] : in[3];
        const uint64_t diff = (uint64_t)((const char*)(P.swap_ri ? in[3] : in[4]) - (const char*)lo);
        const uint64_t d[4] = {1024, 8, 2, 128}, s[3] = {2048, diff, 16384}; const uint32_t b[4] = {64, 8, 2, 8}, bh[4] = {64, 8, 2, 4};
        encode(fn, &P.tm[M_AB], lo, 4, d, s, b);
        encode(fn, &P.tm[M_AB + M_HALF], lo, 4, d, s, bh);
    }
    {
        const uint64_t d[4] = {1024, 2, 4, 1024}, s[3] = {2048, 64 * 2048, 4096}; const uint32_t b[4] = {64, 2, 4, 16};
        encode(fn, &P.tm[M_AX], in[0], 4, d, s, b);
    }
    map_mnmajor(fn, &P.tm[M_HT], ht, 2048, 2048);
    map_kmajor(fn, &P.tm[M_CRE], in[5], 1024, 1024, 128);
    map_kmajor(fn, &P.tm[M_CIM], in[6], 1024, 1024, 128);
    map_store(fn, &P.tm[M_KVO], kvo, 3 * 2048, 4096);
    map_store(fn, &P.tm[M_HTS], ht, 2048, 2048);
    map_kmajor(fn, &P.tm[M_BX + M_HALF], in[9], 2048, 1024, 64);
    map_kmajor(fn, &P.tm[M_OA + M_HALF], kvo, 3 * 2048, 4096, 64);
    map_mnmajor(fn, &P.tm[M_HT + M_HALF], ht, 2048, 2048, 1);
    for (int i = 0; i < 3; i++) {
        const uint64_t d[3] = {64, 1024, 64}, s[2] = {8192, 128}; const uint32_t b[3] = {64, 16, 2};
        encode(fn, &P.tm[M_C1 + i], in[11 + i], 3, d, s, b);
    }
    {
        const uint64_t d[2] = {1024, 4096}, s[1] = {2048}; const uint32_t b[2] = {32, 32};
        encode(fn, &P.tm[M_CO], in[14], 2, d, s, b, CU_TENSOR_MAP_SWIZZLE_64B);
    }
    {
        const uint64_t d[3] = {64, 3 * 2048, 64}, s[2] = {8192, 128}; const uint32_t b[3] = {64, 32, 2};
        encode(fn, &P.tm[M_SEG], kvo, 3, d, s, b);
    }
    void* xs;
    cudaGetSymbolAddress(&xs, g_x);
    P.xb = (uint8_t*)(((uintptr_t)xs + (2u << 20) - 1) & ~(uintptr_t)((2u << 20) - 1));
    P.Wq = in[11]; P.Wk = in[12]; P.Wv = in[13]; P.Wo = in[14]; P.mem0 = in[10]; P.Bx = in[9];
    P.Ax = in[0]; P.Lre = in[1]; P.Lim = in[2]; P.logdt = in[7]; P.Dskip = in[8];
    P.out = (float*)d_out;
    int pv[10] = {1300, 0, 110, 0, 330, 0, 32, 32, 0, 0};
    int ef = 779;
    for (int i = 0; i < 12; i++) P.pol[i] = (ef >> i & 1) ? 0x12F0000000000000ull : 0x1000000000000000ull;
    P.dly = pv[0]; P.mrg = pv[2];
    P.rd = pv[4]; P.guard = pv[5]; P.clampv = pv[6]; P.clamp0 = pv[7]; P.kvd = pv[9]; P.xd = pv[8];
    cudaLaunchConfig_t cfg = {};
    cudaLaunchAttribute at[2];
    cfg.blockDim = dim3(384); cfg.dynamicSmemBytes = S_TOTAL; cfg.stream = cudaStreamPerThread; cfg.attrs = at;
    at[0].id = cudaLaunchAttributeClusterDimension;
    at[0].val.clusterDim.y = at[0].val.clusterDim.z = 1;
    at[1].id = cudaLaunchAttributeProgrammaticStreamSerialization;
    at[1].val.programmaticStreamSerializationAllowed = 1;
    for (int i = 0; i < 2; i++) {
        P.cta0 = i ? 2 * NCHAIN : 0;
        cfg.gridDim = dim3(i ? 2 * (NPAIR - NCHAIN) : 2 * NCHAIN);
        at[0].val.clusterDim.x = i ? 2 : 6;
        cfg.numAttrs = 1 + i;
        cudaLaunchKernelEx(&cfg, fused_kernel, P);
    }
}
```

```cpp
#include <cuda_runtime.h>
#include <cuda_bf16.h>
#include <cuda.h>
#include <stdint.h>
#include <string.h>

typedef __nv_bfloat16 bf16;

namespace {

constexpr int SPIN_LIMIT = 1 << 22;
#define POLLNS 100
constexpr int NPAIR = 66;
constexpr int NCHAIN = 48;
enum { T_KV = 0, T_QA = 1, T_OP = 2, T_A1 = 3, T_A2 = 4, T_CHAIN = 5 };
constexpr int URGENT = 2048;
constexpr int LAST = 16384;
constexpr int HALF = 4096;
enum { M_BX = 1, M_OA, M_AB, M_HT, M_HALF = 4, M_WK = 9, M_WV, M_WQ, M_WO, M_AX, M_CRE, M_CIM, M_KVO, M_HTS, M_C1, M_CO = M_C1 + 3, M_SEG, M_COUNT };
enum { C_KV = 0, C_O = 128, C_HT = 256, C_READ = 24, C_EPOCH = 25, C_COEF = 26, C_XMAX = 27, C_XCNT = 28, C_FLAG = 32 };

struct Params {
    CUtensorMap tm[M_COUNT];
    const bf16 *Wq, *Wk, *Wv, *Wo, *mem0, *Bx, *Ax, *Lre, *Lim, *logdt, *Dskip;
    float* out;
    uint8_t* xb;
    int swap_ri, zero;
    int dly, mrg, rd, guard, clampv, clamp0, kvd, xd;
    uint64_t pol[12];
    uint16_t cta0;
};

__constant__ uint16_t c_off[67] = {0, 4, 8, 14, 20, 26, 32, 38, 43, 48, 53, 58, 63, 68, 73, 78, 83, 88, 93, 97, 101, 105, 109, 113, 117, 121, 125, 129, 133, 137, 141, 145, 149, 153, 157, 161, 165, 169, 173, 177, 181, 185, 189, 193, 197, 201, 205, 209, 213, 233, 253, 273, 293, 313, 333, 353, 373, 393, 412, 431, 450, 469, 488, 507, 526, 545, 564};
__constant__ uint16_t c_items[700] = {
    0, 1280, 512, 21728, 16, 1280, 513, 29920, 32, 1280, 800, 899, 3043, 21729, 1, 1280, 801, 900, 3044, 29921, 17, 1280, 802, 901,
    3045, 21730, 33, 1280, 803, 902, 3046, 29922, 2, 1280, 804, 903, 3047, 21731, 18, 1280, 805, 928, 29923, 34, 1280, 2496, 2913, 17408,
    3, 1280, 2528, 2914, 17409, 19, 1280, 768, 2915, 17410, 35, 1280, 769, 2916, 17411, 4, 1280, 770, 2917, 17440, 20, 1280, 771, 2918,
    17441, 36, 1280, 772, 2919, 17442, 5, 1280, 773, 2944, 17443, 21, 1280, 774, 2945, 17472, 37, 1280, 775, 2946, 17473, 6, 1280, 2497,
    16898, 22, 1280, 2529, 16899, 38, 1280, 2498, 16928, 7, 1280, 2530, 16929, 23, 1280, 2499, 16930, 39, 1280, 2531, 16931, 8, 1280, 2500,
    16960, 24, 1280, 2532, 16961, 40, 1280, 2501, 16962, 9, 1280, 2533, 16963, 25, 1280, 2502, 16992, 41, 1280, 2534, 16993, 10, 1280, 2503,
    16994, 26, 1280, 2535, 16995, 42, 1280, 2504, 17024, 11, 1280, 2536, 17025, 27, 1280, 2505, 17026, 43, 1280, 2537, 17027, 12, 1280, 2506,
    17056, 28, 1280, 2538, 17057, 44, 1280, 2507, 17058, 13, 1280, 2539, 17059, 29, 1280, 2508, 17088, 45, 1280, 2540, 17089, 14, 1280, 2509,
    17090, 30, 1280, 2541, 17091, 46, 1280, 2510, 17120, 15, 1280, 2542, 17121, 31, 1280, 2511, 17122, 47, 1280, 2543, 17123, 48, 66, 84,
    102, 111, 128, 144, 162, 178, 196, 212, 230, 246, 298, 332, 366, 416, 832, 3010, 17539, 49, 67, 85, 103, 112, 129, 145,
    163, 179, 197, 213, 231, 247, 299, 333, 367, 417, 833, 3011, 17568, 50, 68, 86, 104, 113, 130, 146, 164, 180, 198, 214,
    232, 248, 300, 334, 384, 418, 834, 3012, 17569, 51, 69, 87, 105, 114, 131, 147, 165, 181, 199, 215, 233, 249, 301, 335,
    385, 419, 835, 3013, 17570, 52, 70, 88, 106, 115, 132, 148, 166, 182, 200, 216, 234, 250, 302, 352, 386, 420, 836, 3014,
    17571, 53, 71, 89, 107, 116, 133, 149, 167, 183, 201, 217, 235, 251, 303, 353, 387, 421, 837, 3015, 17600, 54, 72, 90,
    108, 117, 134, 150, 168, 184, 202, 218, 236, 252, 320, 354, 388, 422, 838, 3040, 17601, 55, 73, 91, 109, 118, 135, 151,
    169, 185, 203, 219, 237, 253, 321, 355, 389, 423, 839, 3041, 17602, 56, 74, 92, 110, 119, 136, 152, 170, 186, 204, 220,
    238, 254, 322, 356, 390, 424, 864, 3042, 17603, 57, 75, 93, 256, 120, 137, 153, 171, 187, 205, 221, 288, 292, 324, 358,
    392, 426, 2978, 17475, 58, 76, 94, 257, 121, 138, 154, 172, 188, 206, 222, 289, 293, 325, 359, 393, 427, 2979, 17504, 59,
    77, 95, 258, 122, 139, 155, 173, 189, 270, 226, 242, 294, 326, 360, 394, 428, 2980, 17505, 60, 78, 96, 259, 123, 140,
    156, 174, 190, 271, 227, 243, 295, 327, 361, 395, 429, 2981, 17506, 61, 79, 97, 260, 124, 141, 157, 268, 194, 210, 228,
    244, 296, 328, 362, 396, 430, 2982, 17507, 62, 80, 98, 261, 125, 142, 158, 269, 195, 211, 229, 245, 297, 329, 363, 397,
    431, 2983, 17536, 63, 81, 99, 262, 126, 266, 159, 175, 191, 207, 223, 239, 255, 323, 357, 391, 425, 2977, 17474, 64, 82,
    100, 263, 127, 267, 160, 176, 192, 208, 224, 240, 290, 330, 364, 398, 806, 3008, 17537, 65, 83, 101, 264, 265, 143, 161,
    177, 193, 209, 225, 241, 291, 331, 365, 399, 807, 3009, 17538,
};
#define ITEM_OFF(p) c_off[p]
#define ITEM(i) c_items[i]

__device__ __align__(1024) bf16 g_kvo[3 * 2048 * 4096];
__device__ __align__(1024) bf16 g_ht[2048 * 2048];
__device__ __align__(1024) uint8_t g_x[4 << 20];
__device__ __align__(1024) uint32_t g_km[64 * 32 * 512];
__device__ __align__(1024) uint32_t g_vmt[64 * 32 * 512];
__device__ __align__(1024) float2 g_agg[8 * 1024];
__device__ __align__(1024) float4 g_coef[1024];
__device__ __align__(1024) uint32_t g_cntl[384 * 32];
#define g_cnt(i) g_cntl[(i) * 32]
__device__ __align__(1024) uint32_t g_hint[96 * 32];
#define PROF(i)
#define PROFDUMP()
#define PROFP(i)
constexpr int XG_SIDE = 65536, XG_T = 98304;
__device__ __forceinline__ uint32_t xg_buf(int b) { return (b & 1) * 128 + (b & 2) * 256 + (b & 4) * 32768; }
__device__ __forceinline__ uint32_t xg_lane(uint32_t lane) { return (lane >> 4) * 1024 + (lane & 8) * 32 + (lane & 7) * 16; }
__device__ __forceinline__ uint32_t xg_side(int b) { return XG_SIDE + (b >> 1) * 1024 + (b & 1) * 256; }

constexpr int STAGE = 49152, NSTAGE = 4;
constexpr int S_STG = NSTAGE * STAGE;
constexpr int S_BAR = S_STG + 32768;
constexpr int B_FULL = S_BAR, B_EMPTY = S_BAR + 32, B_RESUME = S_BAR + 64, B_KVFULL = S_BAR + 72, B_GO = S_BAR + 88, B_X = S_BAR + 96, B_PERS = S_BAR + 104,
              B_INIT = S_BAR + 112, B_RELM = S_BAR + 120, B_READY = S_BAR + 136, B_SFULL = S_BAR + 144, B_SFREE = S_BAR + 160, S_DESC = S_BAR + 176, B_RED = S_BAR + 216;
constexpr int S_EV = S_BAR + 80, S_EO = S_BAR + 84, B_INIT2 = S_BAR + 128, S_SC = S_BAR + 208, S_ISC = S_EV;
constexpr int S_XV = S_BAR + 256, S_LOG = S_XV + 2048;
constexpr int S_TOTAL = S_LOG + 768;
#define NRA 5
#define NRB 3
constexpr int S_W1 = 0;
constexpr int S_W2 = 4 * 4096 * (16 - NRA - NRB);
constexpr int S_KV = 188416;
constexpr int S_P1 = S_KV + 16384;
constexpr int S_X = S_P1 + 16384;
constexpr int S_SX = S_P1, S_OX = S_P1 + 2048;
constexpr int S_EM = S_X + 4096, S_TO = S_EM + 32, B_DONE = S_BAR + 224, B_P1 = S_BAR + 232, B_EPOCH = S_BAR + 240, S_EPOCH = S_BAR + 248;
static_assert(S_TO + 32 <= S_BAR && S_KV % 1024 == 0 && S_TOTAL <= 232448, "chain smem layout");

template <int V> struct IC { static constexpr int value = V; };
template <int B, int E, typename F> __device__ __forceinline__ void static_for(F&& f) { if constexpr (B < E) { f(IC<B>{}); static_for<B + 1, E>(f); } }
__device__ __forceinline__ uint32_t cluster_rank() { uint32_t r; asm volatile("mov.u32 %0, %%cluster_ctarank;" : "=r"(r)); return r; }
__device__ __forceinline__ void spin_fault() { asm volatile("st.global.u32 [%0], 0;" ::"l"(0ull) : "memory"); }
__device__ __forceinline__ uint32_t smem_u32(const void* p) { return (uint32_t)__cvta_generic_to_shared(p); }
__device__ __forceinline__ uint32_t opq(uint32_t x, int lane) { return __shfl_sync(0xffffffffu, x, lane); }
__device__ __forceinline__ uint32_t mapa(uint32_t a, uint32_t r) { uint32_t d; asm volatile("mapa.shared::cluster.u32 %0, %1, %2;" : "=r"(d) : "r"(a), "r"(r)); return d; }
__device__ __forceinline__ void mma16816(float* d, uint32_t a0, uint32_t a1, uint32_t a2, uint32_t a3, uint32_t b0, uint32_t b1) {
    asm("mma.sync.aligned.m16n8k16.row.col.f32.bf16.bf16.f32 {%0,%1,%2,%3}, {%4,%5,%6,%7}, {%8,%9}, {%0,%1,%2,%3};"
        : "+f"(d[0]), "+f"(d[1]), "+f"(d[2]), "+f"(d[3]) : "r"(a0), "r"(a1), "r"(a2), "r"(a3), "r"(b0), "r"(b1));
}
__device__ __forceinline__ void mma1688(float* d, uint32_t a0, uint32_t a1, uint32_t b0) {
    asm("mma.sync.aligned.m16n8k8.row.col.f32.bf16.bf16.f32 {%0,%1,%2,%3}, {%4,%5}, {%6}, {%0,%1,%2,%3};"
        : "+f"(d[0]), "+f"(d[1]), "+f"(d[2]), "+f"(d[3]) : "r"(a0), "r"(a1), "r"(b0));
}
__device__ __forceinline__ void ldsm4(uint32_t* r, uint32_t a) {
    asm volatile("ldmatrix.sync.aligned.m8n8.x4.shared.b16 {%0,%1,%2,%3}, [%4];" : "=r"(r[0]), "=r"(r[1]), "=r"(r[2]), "=r"(r[3]) : "r"(a));
}
__device__ __forceinline__ void ldsm4t(uint32_t* r, uint32_t a) {
    asm volatile("ldmatrix.sync.aligned.m8n8.x4.trans.shared.b16 {%0,%1,%2,%3}, [%4];" : "=r"(r[0]), "=r"(r[1]), "=r"(r[2]), "=r"(r[3]) : "r"(a));
}
__device__ __forceinline__ void stsm4(uint32_t a, uint32_t r0, uint32_t r1, uint32_t r2, uint32_t r3) {
    asm volatile("stmatrix.sync.aligned.m8n8.x4.shared.b16 [%0], {%1,%2,%3,%4};" ::"r"(a), "r"(r0), "r"(r1), "r"(r2), "r"(r3) : "memory");
}
__device__ __forceinline__ void stsm4t(uint32_t a, uint32_t r0, uint32_t r1, uint32_t r2, uint32_t r3) {
    asm volatile("stmatrix.sync.aligned.m8n8.x4.trans.shared.b16 [%0], {%1,%2,%3,%4};" ::"r"(a), "r"(r0), "r"(r1), "r"(r2), "r"(r3) : "memory");
}
__device__ __forceinline__ uint32_t movm(uint32_t a) { uint32_t d; asm volatile("movmatrix.sync.aligned.m8n8.trans.b16 %0, %1;" : "=r"(d) : "r"(a)); return d; }
__device__ __forceinline__ uint32_t pack2(float lo, float hi) { uint32_t d; asm("cvt.rn.bf16x2.f32 %0, %1, %2;" : "=r"(d) : "f"(hi), "f"(lo)); return d; }
__device__ __forceinline__ uint32_t prmt(uint32_t a, uint32_t b, uint32_t s) { uint32_t d; asm("prmt.b32 %0, %1, %2, %3;" : "=r"(d) : "r"(a), "r"(b), "r"(s)); return d; }
__device__ __forceinline__ uint32_t pack2h(float lo, float hi) { uint32_t d; asm("cvt.rn.f16x2.f32 %0, %1, %2;" : "=r"(d) : "f"(hi), "f"(lo)); return d; }
__device__ __forceinline__ uint32_t h2bf(uint32_t a, uint32_t b) {
    uint32_t d;
    asm("{\n.reg .b16 l, h, u;\n.reg .f32 x, y;\nmov.b32 {l, u}, %1;\ncvt.f32.f16 x, l;\nmov.b32 {u, h}, %2;\ncvt.f32.f16 y, h;\ncvt.rn.bf16x2.f32 %0, y, x;\n}" : "=r"(d) : "r"(a), "r"(b));
    return d;
}
__device__ __forceinline__ void cvt_block(uint32_t* u, uint32_t& x, uint32_t sel) {
    const uint32_t a = prmt(u[0], u[0], sel), b = prmt(u[1], u[1], sel), c = prmt(u[2], u[2], sel), d = prmt(u[3], x, sel);
    x ^= u[3] ^ d;
    u[0] = h2bf(a, a); u[1] = h2bf(b, b); u[2] = h2bf(c, c); u[3] = h2bf(d, d);
}
__device__ __forceinline__ uint32_t amax(uint32_t a, uint32_t b) { uint32_t d; asm("max.xorsign.abs.bf16x2 %0, %1, %2;" : "=r"(d) : "r"(a), "r"(b)); return d; }
__device__ __forceinline__ uint32_t amax4(uint32_t m, const uint32_t* v) { return amax(amax(m, amax(v[0], v[1])), amax(v[2], v[3])); }
__device__ __forceinline__ uint32_t warp_exp(uint32_t m) { return __reduce_max_sync(0xffffffffu, max(m & 0x7f80u, (m >> 16) & 0x7f80u)) >> 7; }
__device__ __forceinline__ void red_max_shared(uint32_t a, uint32_t x) { asm volatile("red.shared.max.u32 [%0], %1;" ::"r"(a), "r"(x) : "memory"); }
__device__ __forceinline__ uint32_t mul_bf2(uint32_t a, uint32_t b) { uint32_t d; asm("mul.rn.bf16x2 %0, %1, %2;" : "=r"(d) : "r"(a), "r"(b)); return d; }
__device__ __forceinline__ float bf_lo(uint32_t u) { return __uint_as_float(u << 16); }
__device__ __forceinline__ float bf_hi(uint32_t u) { return __uint_as_float(u & 0xffff0000u); }
__device__ __forceinline__ float ex2(float x) { float y; asm("ex2.approx.ftz.f32 %0, %1;" : "=f"(y) : "f"(x)); return y; }
__device__ __forceinline__ float rcp(float x) { float y; asm("rcp.approx.ftz.f32 %0, %1;" : "=f"(y) : "f"(x)); return y; }
__device__ __forceinline__ void st_relaxed4(const void* p, uint32_t a, uint32_t b, uint32_t c, uint32_t d) {
    asm volatile("{\n.reg .b128 t;\nmov.b128 t, {%1,%2,%3,%4};\nst.relaxed.gpu.global.b128 [%0], t;\n}" ::"l"(p), "r"(a), "r"(b), "r"(c), "r"(d) : "memory");
}
__device__ __forceinline__ void st_relaxed2(const void* p, uint32_t a, uint32_t b) {
    asm volatile("{\n.reg .b64 t;\nmov.b64 t, {%1,%2};\nst.relaxed.gpu.global.b64 [%0], t;\n}" ::"l"(p), "r"(a), "r"(b) : "memory");
}
__device__ __forceinline__ void ld_relaxed2_if(uint32_t& a, uint32_t& b, const void* p, bool on) {
    asm volatile("{\n.reg .pred P;\n.reg .b64 t;\nsetp.ne.u32 P, %3, 0;\nmov.b64 t, {%0,%1};\n@P ld.relaxed.gpu.global.b64 t, [%2];\nmov.b64 {%0,%1}, t;\n}" : "+r"(a), "+r"(b) : "l"(p), "r"((uint32_t)on) : "memory");
}
__device__ __forceinline__ void ld_relaxed4(uint32_t* v, const void* p) {
    asm volatile("ld.relaxed.gpu.global.L1::no_allocate.v4.b32 {%0,%1,%2,%3}, [%4];" : "=r"(v[0]), "=r"(v[1]), "=r"(v[2]), "=r"(v[3]) : "l"(p) : "memory");
}
__device__ __forceinline__ void ld_relaxed1n(uint32_t& v, const void* p) { asm volatile("ld.relaxed.gpu.global.L1::no_allocate.b32 %0, [%1];" : "=r"(v) : "l"(p) : "memory"); }
__device__ __forceinline__ void red_add4(const void* p, uint32_t a, uint32_t b, uint32_t c, uint32_t d) {
    asm volatile("red.relaxed.gpu.global.add.noftz.v4.f16x2 [%0], {%1,%2,%3,%4};" ::"l"(p), "r"(a), "r"(b), "r"(c), "r"(d) : "memory");
}
__device__ __forceinline__ void red_add1(const void* p, uint32_t a) { asm volatile("red.relaxed.gpu.global.add.noftz.f16x2 [%0], %1;" ::"l"(p), "r"(a) : "memory"); }
__device__ __forceinline__ void ld_relaxed2(uint32_t* v, const void* p) {
    asm volatile("{\n.reg .b64 t;\nld.relaxed.gpu.global.L1::no_allocate.b64 t, [%2];\nmov.b64 {%0,%1}, t;\n}" : "=r"(v[0]), "=r"(v[1]) : "l"(p) : "memory");
}
__device__ __forceinline__ uint32_t ld_relaxed1(const void* p) { uint32_t v; asm volatile("ld.relaxed.gpu.global.u32 %0, [%1];" : "=r"(v) : "l"(p) : "memory"); return v; }
__device__ __forceinline__ void st_relaxed1(const void* p, uint32_t v) { asm volatile("st.relaxed.gpu.global.u32 [%0], %1;" ::"l"(p), "r"(v) : "memory"); }
__device__ __forceinline__ uint32_t ld_acquire(const void* p) { uint32_t v; asm volatile("ld.acquire.gpu.global.u32 %0, [%1];" : "=r"(v) : "l"(p) : "memory"); return v; }
__device__ __forceinline__ void red_relaxed(void* p) { asm volatile("red.relaxed.gpu.global.add.u32 [%0], 1;" ::"l"(p) : "memory"); }
__device__ __forceinline__ void red_release(void* p) { asm volatile("red.release.gpu.global.add.u32 [%0], 1;" ::"l"(p) : "memory"); }
__device__ __forceinline__ void st_stream2(float* p, float a, float b) { asm volatile("st.global.cs.v2.f32 [%0], {%1, %2};" ::"l"(p), "f"(a), "f"(b) : "memory"); }
__device__ __forceinline__ void fence_async() { asm volatile("fence.proxy.async.global;" ::: "memory"); }
__device__ __forceinline__ void fence_async_smem() { asm volatile("fence.proxy.async.shared::cta;" ::: "memory"); }
__device__ __forceinline__ void wait_count(const uint32_t* p, uint32_t target) {
    while ((int32_t)(ld_acquire(p) - target) < 0) __nanosleep(POLLNS);
}
__device__ __forceinline__ void bar_sync(int id, int n) { asm volatile("bar.sync %0, %1;" ::"r"(id), "r"(n) : "memory"); }
__device__ __forceinline__ bool bar_and(int id, bool v) {
    uint32_t r;
    asm volatile("{\n.reg .pred P, Q;\nsetp.ne.u32 Q, %2, 0;\nbar.red.and.pred P, %1, 128, Q;\nselp.u32 %0, 1, 0, P;\n}" : "=r"(r) : "r"(id), "r"((uint32_t)v) : "memory");
    return r;
}
__device__ __forceinline__ void bar_arrive(int id, int n) { asm volatile("bar.arrive %0, %1;" ::"r"(id), "r"(n) : "memory"); }
__device__ __forceinline__ void lds128(uint32_t* v, uint32_t a) { asm volatile("ld.shared.v4.b32 {%0,%1,%2,%3}, [%4];" : "=r"(v[0]), "=r"(v[1]), "=r"(v[2]), "=r"(v[3]) : "r"(a) : "memory"); }
__device__ __forceinline__ uint32_t lds32(uint32_t a) { uint32_t v; asm volatile("ld.shared.b32 %0, [%1];" : "=r"(v) : "r"(a) : "memory"); return v; }
__device__ __forceinline__ void lds64(uint32_t* v, uint32_t a) { asm volatile("ld.shared.v2.b32 {%0,%1}, [%2];" : "=r"(v[0]), "=r"(v[1]) : "r"(a) : "memory"); }
__device__ __forceinline__ void lds64f(float* v, uint32_t a) { asm volatile("ld.shared.v2.f32 {%0,%1}, [%2];" : "=f"(v[0]), "=f"(v[1]) : "r"(a) : "memory"); }
__device__ __forceinline__ void sts128(uint32_t a, const uint32_t* v) { asm volatile("st.shared.v4.b32 [%0], {%1,%2,%3,%4};" ::"r"(a), "r"(v[0]), "r"(v[1]), "r"(v[2]), "r"(v[3]) : "memory"); }
__device__ __forceinline__ void sts64(uint32_t a, uint32_t x, uint32_t y) { asm volatile("st.shared.v2.b32 [%0], {%1,%2};" ::"r"(a), "r"(x), "r"(y) : "memory"); }
__device__ __forceinline__ void sts32(uint32_t a, uint32_t x) { asm volatile("st.shared.b32 [%0], %1;" ::"r"(a), "r"(x) : "memory"); }
__device__ __forceinline__ bool mbar_try(uint32_t b, uint32_t par) {
    uint32_t ok;
    asm volatile("{\n.reg .pred P;\nmbarrier.test_wait.parity.shared::cta.b64 P, [%1], %2;\nselp.u32 %0, 1, 0, P;\n}" : "=r"(ok) : "r"(b), "r"(par) : "memory");
    return ok;
}
__device__ __forceinline__ void mbar_wait(uint32_t b, uint32_t par) {
    asm volatile("{\n.reg .pred P;\nW: mbarrier.try_wait.parity.shared::cta.b64 P, [%0], %1;\n@!P bra W;\n}" ::"r"(b), "r"(par) : "memory");
}
__device__ __forceinline__ void mbar_wait_bounded(uint32_t b, uint32_t par) {
    asm volatile("{\n.reg .pred P, Q;\n.reg .u32 t, u;\nmov.u32 t, %%globaltimer_lo;\nW: mbarrier.try_wait.parity.shared::cta.b64 P, [%0], %1;\n"
                 "mov.u32 u, %%globaltimer_lo;\nsub.u32 u, u, t;\nsetp.gt.u32 Q, u, 2000000000;\n@Q st.global.u32 [%2], 0;\n@!P bra W;\n}" ::"r"(b), "r"(par), "l"(0ull) : "memory");
}
__device__ __forceinline__ void declare_fence(int zero) { asm volatile(".reg .pred PNEVER;\nsetp.ne.u32 PNEVER, %0, 0;" ::"r"(zero)); }
__device__ __forceinline__ void sched_fence() { asm volatile("{\n.reg .pred Q;\n.reg .u32 x;\n@!PNEVER bra D;\nF: ld.volatile.global.u32 x, [%0];\nsetp.ne.u32 Q, x, 0;\n@Q bra F;\nD:\n}" ::"l"(0ull) : "memory"); }
__device__ __forceinline__ void mbar_init(uint32_t b, uint32_t n) { asm volatile("mbarrier.init.shared::cta.b64 [%0], %1;" ::"r"(b), "r"(n) : "memory"); }
__device__ __forceinline__ void mbar_expect(uint32_t b, uint32_t bytes) { asm volatile("mbarrier.arrive.expect_tx.shared::cta.b64 _, [%0], %1;" ::"r"(b), "r"(bytes) : "memory"); }
__device__ __forceinline__ void mbar_arrive(uint32_t b) { asm volatile("mbarrier.arrive.shared::cta.b64 _, [%0];" ::"r"(b) : "memory"); }
__device__ __forceinline__ void mbar_arrive_cluster(uint32_t b) { asm volatile("mbarrier.arrive.shared::cluster.b64 _, [%0];" ::"r"(b) : "memory"); }
__device__ __forceinline__ void cluster_sync() { asm volatile("barrier.cluster.arrive.relaxed.aligned;\nbarrier.cluster.wait.aligned;" ::: "memory"); }
__device__ __forceinline__ uint32_t get_epoch(uint32_t sb) { mbar_wait(sb + B_EPOCH, 0); return __shfl_sync(0xffffffffu, lds32(sb + S_EPOCH), 0); }
__device__ __forceinline__ void tma2d(uint32_t dst, const CUtensorMap* m, int c0, int c1, uint32_t bar) {
    asm volatile("cp.async.bulk.tensor.2d.shared::cluster.global.mbarrier::complete_tx::bytes [%0], [%1, {%2, %3}], [%4];" ::"r"(dst), "l"(m), "r"(c0), "r"(c1), "r"(bar) : "memory");
}
__device__ __forceinline__ void tma3d(uint32_t dst, const CUtensorMap* m, int c0, int c1, int c2, uint32_t bar) {
    asm volatile("cp.async.bulk.tensor.3d.shared::cluster.global.mbarrier::complete_tx::bytes [%0], [%1, {%2, %3, %4}], [%5];" ::"r"(dst), "l"(m), "r"(c0), "r"(c1), "r"(c2), "r"(bar) : "memory");
}
__device__ __forceinline__ void l2_prefetch(const void* src, uint32_t bytes) { asm volatile("cp.async.bulk.prefetch.L2.global [%0], %1;" ::"l"(src), "r"(bytes) : "memory"); }
__device__ __forceinline__ void mbar_expect_e(uint32_t b, uint32_t bytes) {
    asm volatile("{\n.reg .pred E;\nelect.sync _|E, 0xffffffff;\n@E mbarrier.arrive.expect_tx.shared::cta.b64 _, [%0], %1;\n}" ::"r"(b), "r"(bytes) : "memory");
}
__device__ __forceinline__ void tma3d_mc_e(uint32_t dst, const CUtensorMap* m, int c0, int c1, int c2, uint32_t bar, uint16_t mask, uint64_t pol) {
    asm volatile("{\n.reg .pred E;\nelect.sync _|E, 0xffffffff;\n@E cp.async.bulk.tensor.3d.shared::cluster.global.mbarrier::complete_tx::bytes.multicast::cluster.L2::cache_hint [%0], [%1, {%2, %3, %4}], [%5], %6, %7;\n}" ::"r"(dst), "l"(m), "r"(c0), "r"(c1), "r"(c2), "r"(bar), "h"(mask), "l"(pol) : "memory");
}
__device__ __forceinline__ void tma4d_e(uint32_t dst, const CUtensorMap* m, int c0, int c1, int c3, uint32_t bar, uint64_t pol) {
    asm volatile("{\n.reg .pred E;\nelect.sync _|E, 0xffffffff;\n@E cp.async.bulk.tensor.4d.shared::cluster.global.mbarrier::complete_tx::bytes.L2::cache_hint [%0], [%1, {%2, %3, 0, %4}], [%5], %6;\n}" ::"r"(dst), "l"(m), "r"(c0), "r"(c1), "r"(c3), "r"(bar), "l"(pol) : "memory");
}
__device__ __forceinline__ void tma4d_mc_e(uint32_t dst, const CUtensorMap* m, int c0, int c1, int c3, uint32_t bar, uint16_t mask, uint64_t pol) {
    asm volatile("{\n.reg .pred E;\nelect.sync _|E, 0xffffffff;\n@E cp.async.bulk.tensor.4d.shared::cluster.global.mbarrier::complete_tx::bytes.multicast::cluster.L2::cache_hint [%0], [%1, {%2, %3, 0, %4}], [%5], %6, %7;\n}" ::"r"(dst), "l"(m), "r"(c0), "r"(c1), "r"(c3), "r"(bar), "h"(mask), "l"(pol) : "memory");
}
__device__ __forceinline__ void tma_prefetch4d_e(const CUtensorMap* m, int c0, int c3) {
    asm volatile("{\n.reg .pred E;\nelect.sync _|E, 0xffffffff;\n@E cp.async.bulk.prefetch.tensor.4d.L2.global [%0, {%1, 0, 0, %2}];\n}" ::"l"(m), "r"(c0), "r"(c3) : "memory");
}
__device__ __forceinline__ void tma_prefetch3d_e(const CUtensorMap* m, int c0, int c1, int c2) {
    asm volatile("{\n.reg .pred E;\nelect.sync _|E, 0xffffffff;\n@E cp.async.bulk.prefetch.tensor.3d.L2.global [%0, {%1, %2, %3}];\n}" ::"l"(m), "r"(c0), "r"(c1), "r"(c2) : "memory");
}
__device__ __forceinline__ void l2_prefetch_e(const void* src, uint32_t bytes) {
    asm volatile("{\n.reg .pred E;\nelect.sync _|E, 0xffffffff;\n@E cp.async.bulk.prefetch.L2.global [%0], %1;\n}" ::"l"(src), "r"(bytes) : "memory");
}
__device__ __forceinline__ void bulk_g2s_e(uint32_t dst, const void* src, uint32_t bytes, uint32_t bar) {
    asm volatile("{\n.reg .pred E;\nelect.sync _|E, 0xffffffff;\n@E cp.async.bulk.shared::cluster.global.mbarrier::complete_tx::bytes [%0], [%1], %2, [%3];\n}" ::"r"(dst), "l"(src), "r"(bytes), "r"(bar) : "memory");
}
__device__ __forceinline__ bool elect_one() {
    uint32_t r;
    asm volatile("{\n.reg .pred E;\nelect.sync _|E, 0xffffffff;\nselp.u32 %0, 1, 0, E;\n}" : "=r"(r));
    return r;
}
__device__ __forceinline__ void tma_store2d(const CUtensorMap* m, int c0, int c1, uint32_t src, uint64_t pol) {
    asm volatile("cp.async.bulk.tensor.2d.global.shared::cta.bulk_group.L2::cache_hint [%0, {%1, %2}], [%3], %4;" ::"l"(m), "r"(c0), "r"(c1), "r"(src), "l"(pol) : "memory");
}
__device__ __forceinline__ void bulk_commit() { asm volatile("cp.async.bulk.commit_group;" ::: "memory"); }
__device__ __forceinline__ void bulk_wait_read() { asm volatile("cp.async.bulk.wait_group.read 0;" ::: "memory"); }
__device__ __forceinline__ void bulk_wait_all() { asm volatile("cp.async.bulk.wait_group 0;" ::: "memory"); }
__device__ __forceinline__ uint64_t mkdesc(uint32_t addr, uint32_t lbo, uint32_t sbo, uint32_t swz) {
    return (uint64_t)((addr & 0x3FFFF) >> 4) | ((uint64_t)(lbo >> 4) << 16) | ((uint64_t)(sbo >> 4) << 32) | ((uint64_t)swz << 62);
}
__device__ __forceinline__ void wg_fence() { asm volatile("wgmma.fence.sync.aligned;" ::: "memory"); }
__device__ __forceinline__ void wg_commit() { asm volatile("wgmma.commit_group.sync.aligned;" ::: "memory"); }
template <int N> __device__ __forceinline__ void wg_wait() { asm volatile("wgmma.wait_group.sync.aligned %0;" ::"n"(N) : "memory"); }
template <typename T> __device__ __forceinline__ void pin_ptr(T*& p) { asm volatile("" : "+l"(p)); }
template <int N> __device__ __forceinline__ void pin(uint32_t* d) {
#pragma unroll
    for (int i = 0; i < N; i++) asm volatile("" : "+r"(d[i])::"memory");
}
template <int N> __device__ __forceinline__ void pin(float* d) {
#pragma unroll
    for (int i = 0; i < N; i++) asm volatile("" : "+f"(d[i])::"memory");
}

template <int TA, int TB>
__device__ __forceinline__ void wgmma_ss256(float* d, uint64_t da, uint64_t db) {
    asm volatile("wgmma.mma_async.sync.aligned.m64n256k16.f32.bf16.bf16 "
        "{%0, %1, %2, %3, %4, %5, %6, %7, %8, %9, %10, %11, %12, %13, %14, %15, %16, %17, %18, %19, %20, %21, %22, %23, %24, %25, %26, %27, %28, %29, %30, %31, %32, %33, %34, %35, %36, %37, %38, %39, %40, %41, %42, %43, %44, %45, %46, %47, %48, %49, %50, %51, %52, %53, %54, %55, %56, %57, %58, %59, %60, %61, %62, %63, %64, %65, %66, %67, %68, %69, %70, %71, %72, %73, %74, %75, %76, %77, %78, %79, %80, %81, %82, %83, %84, %85, %86, %87, %88, %89, %90, %91, %92, %93, %94, %95, %96, %97, %98, %99, %100, %101, %102, %103, %104, %105, %106, %107, %108, %109, %110, %111, %112, %113, %114, %115, %116, %117, %118, %119, %120, %121, %122, %123, %124, %125, %126, %127}, %128, %129, 1, 1, 1, %130, %131;"
        : "+f"(d[0]), "+f"(d[1]), "+f"(d[2]), "+f"(d[3]), "+f"(d[4]), "+f"(d[5]), "+f"(d[6]), "+f"(d[7]), "+f"(d[8]), "+f"(d[9]), "+f"(d[10]), "+f"(d[11]), "+f"(d[12]), "+f"(d[13]), "+f"(d[14]), "+f"(d[15]), "+f"(d[16]), "+f"(d[17]), "+f"(d[18]), "+f"(d[19]), "+f"(d[20]), "+f"(d[21]), "+f"(d[22]), "+f"(d[23]), "+f"(d[24]), "+f"(d[25]), "+f"(d[26]), "+f"(d[27]), "+f"(d[28]), "+f"(d[29]), "+f"(d[30]), "+f"(d[31]), "+f"(d[32]), "+f"(d[33]), "+f"(d[34]), "+f"(d[35]), "+f"(d[36]), "+f"(d[37]), "+f"(d[38]), "+f"(d[39]), "+f"(d[40]), "+f"(d[41]), "+f"(d[42]), "+f"(d[43]), "+f"(d[44]), "+f"(d[45]), "+f"(d[46]), "+f"(d[47]), "+f"(d[48]), "+f"(d[49]), "+f"(d[50]), "+f"(d[51]), "+f"(d[52]), "+f"(d[53]), "+f"(d[54]), "+f"(d[55]), "+f"(d[56]), "+f"(d[57]), "+f"(d[58]), "+f"(d[59]), "+f"(d[60]), "+f"(d[61]), "+f"(d[62]), "+f"(d[63]), "+f"(d[64]), "+f"(d[65]), "+f"(d[66]), "+f"(d[67]), "+f"(d[68]), "+f"(d[69]), "+f"(d[70]), "+f"(d[71]), "+f"(d[72]), "+f"(d[73]), "+f"(d[74]), "+f"(d[75]), "+f"(d[76]), "+f"(d[77]), "+f"(d[78]), "+f"(d[79]), "+f"(d[80]), "+f"(d[81]), "+f"(d[82]), "+f"(d[83]), "+f"(d[84]), "+f"(d[85]), "+f"(d[86]), "+f"(d[87]), "+f"(d[88]), "+f"(d[89]), "+f"(d[90]), "+f"(d[91]), "+f"(d[92]), "+f"(d[93]), "+f"(d[94]), "+f"(d[95]), "+f"(d[96]), "+f"(d[97]), "+f"(d[98]), "+f"(d[99]), "+f"(d[100]), "+f"(d[101]), "+f"(d[102]), "+f"(d[103]), "+f"(d[104]), "+f"(d[105]), "+f"(d[106]), "+f"(d[107]), "+f"(d[108]), "+f"(d[109]), "+f"(d[110]), "+f"(d[111]), "+f"(d[112]), "+f"(d[113]), "+f"(d[114]), "+f"(d[115]), "+f"(d[116]), "+f"(d[117]), "+f"(d[118]), "+f"(d[119]), "+f"(d[120]), "+f"(d[121]), "+f"(d[122]), "+f"(d[123]), "+f"(d[124]), "+f"(d[125]), "+f"(d[126]), "+f"(d[127])
        : "l"(da), "l"(db), "n"(TA), "n"(TB));
}
template <int TA, int TB>
__device__ __forceinline__ void wgmma_ss256_first(float* d, uint64_t da, uint64_t db) {
    asm volatile("wgmma.mma_async.sync.aligned.m64n256k16.f32.bf16.bf16 "
        "{%0, %1, %2, %3, %4, %5, %6, %7, %8, %9, %10, %11, %12, %13, %14, %15, %16, %17, %18, %19, %20, %21, %22, %23, %24, %25, %26, %27, %28, %29, %30, %31, %32, %33, %34, %35, %36, %37, %38, %39, %40, %41, %42, %43, %44, %45, %46, %47, %48, %49, %50, %51, %52, %53, %54, %55, %56, %57, %58, %59, %60, %61, %62, %63, %64, %65, %66, %67, %68, %69, %70, %71, %72, %73, %74, %75, %76, %77, %78, %79, %80, %81, %82, %83, %84, %85, %86, %87, %88, %89, %90, %91, %92, %93, %94, %95, %96, %97, %98, %99, %100, %101, %102, %103, %104, %105, %106, %107, %108, %109, %110, %111, %112, %113, %114, %115, %116, %117, %118, %119, %120, %121, %122, %123, %124, %125, %126, %127}, %128, %129, 0, 1, 1, %130, %131;"
        : "=f"(d[0]), "=f"(d[1]), "=f"(d[2]), "=f"(d[3]), "=f"(d[4]), "=f"(d[5]), "=f"(d[6]), "=f"(d[7]), "=f"(d[8]), "=f"(d[9]), "=f"(d[10]), "=f"(d[11]), "=f"(d[12]), "=f"(d[13]), "=f"(d[14]), "=f"(d[15]), "=f"(d[16]), "=f"(d[17]), "=f"(d[18]), "=f"(d[19]), "=f"(d[20]), "=f"(d[21]), "=f"(d[22]), "=f"(d[23]), "=f"(d[24]), "=f"(d[25]), "=f"(d[26]), "=f"(d[27]), "=f"(d[28]), "=f"(d[29]), "=f"(d[30]), "=f"(d[31]), "=f"(d[32]), "=f"(d[33]), "=f"(d[34]), "=f"(d[35]), "=f"(d[36]), "=f"(d[37]), "=f"(d[38]), "=f"(d[39]), "=f"(d[40]), "=f"(d[41]), "=f"(d[42]), "=f"(d[43]), "=f"(d[44]), "=f"(d[45]), "=f"(d[46]), "=f"(d[47]), "=f"(d[48]), "=f"(d[49]), "=f"(d[50]), "=f"(d[51]), "=f"(d[52]), "=f"(d[53]), "=f"(d[54]), "=f"(d[55]), "=f"(d[56]), "=f"(d[57]), "=f"(d[58]), "=f"(d[59]), "=f"(d[60]), "=f"(d[61]), "=f"(d[62]), "=f"(d[63]), "=f"(d[64]), "=f"(d[65]), "=f"(d[66]), "=f"(d[67]), "=f"(d[68]), "=f"(d[69]), "=f"(d[70]), "=f"(d[71]), "=f"(d[72]), "=f"(d[73]), "=f"(d[74]), "=f"(d[75]), "=f"(d[76]), "=f"(d[77]), "=f"(d[78]), "=f"(d[79]), "=f"(d[80]), "=f"(d[81]), "=f"(d[82]), "=f"(d[83]), "=f"(d[84]), "=f"(d[85]), "=f"(d[86]), "=f"(d[87]), "=f"(d[88]), "=f"(d[89]), "=f"(d[90]), "=f"(d[91]), "=f"(d[92]), "=f"(d[93]), "=f"(d[94]), "=f"(d[95]), "=f"(d[96]), "=f"(d[97]), "=f"(d[98]), "=f"(d[99]), "=f"(d[100]), "=f"(d[101]), "=f"(d[102]), "=f"(d[103]), "=f"(d[104]), "=f"(d[105]), "=f"(d[106]), "=f"(d[107]), "=f"(d[108]), "=f"(d[109]), "=f"(d[110]), "=f"(d[111]), "=f"(d[112]), "=f"(d[113]), "=f"(d[114]), "=f"(d[115]), "=f"(d[116]), "=f"(d[117]), "=f"(d[118]), "=f"(d[119]), "=f"(d[120]), "=f"(d[121]), "=f"(d[122]), "=f"(d[123]), "=f"(d[124]), "=f"(d[125]), "=f"(d[126]), "=f"(d[127])
        : "l"(da), "l"(db), "n"(TA), "n"(TB));
}
template <int TB>
__device__ __forceinline__ void wgmma_rs128(float* d, const uint32_t* a, uint64_t db, uint32_t acc) {
    asm volatile("{\n.reg .pred P;\nsetp.ne.u32 P, %69, 0;\nwgmma.mma_async.sync.aligned.m64n128k16.f32.bf16.bf16 "
        "{%0, %1, %2, %3, %4, %5, %6, %7, %8, %9, %10, %11, %12, %13, %14, %15, %16, %17, %18, %19, %20, %21, %22, %23, %24, %25, %26, %27, %28, %29, %30, %31, %32, %33, %34, %35, %36, %37, %38, %39, %40, %41, %42, %43, %44, %45, %46, %47, %48, %49, %50, %51, %52, %53, %54, %55, %56, %57, %58, %59, %60, %61, %62, %63}, {%64, %65, %66, %67}, %68, P, 1, 1, %70;\n}"
        : "+f"(d[0]), "+f"(d[1]), "+f"(d[2]), "+f"(d[3]), "+f"(d[4]), "+f"(d[5]), "+f"(d[6]), "+f"(d[7]), "+f"(d[8]), "+f"(d[9]), "+f"(d[10]), "+f"(d[11]), "+f"(d[12]), "+f"(d[13]), "+f"(d[14]), "+f"(d[15]), "+f"(d[16]), "+f"(d[17]), "+f"(d[18]), "+f"(d[19]), "+f"(d[20]), "+f"(d[21]), "+f"(d[22]), "+f"(d[23]), "+f"(d[24]), "+f"(d[25]), "+f"(d[26]), "+f"(d[27]), "+f"(d[28]), "+f"(d[29]), "+f"(d[30]), "+f"(d[31]), "+f"(d[32]), "+f"(d[33]), "+f"(d[34]), "+f"(d[35]), "+f"(d[36]), "+f"(d[37]), "+f"(d[38]), "+f"(d[39]), "+f"(d[40]), "+f"(d[41]), "+f"(d[42]), "+f"(d[43]), "+f"(d[44]), "+f"(d[45]), "+f"(d[46]), "+f"(d[47]), "+f"(d[48]), "+f"(d[49]), "+f"(d[50]), "+f"(d[51]), "+f"(d[52]), "+f"(d[53]), "+f"(d[54]), "+f"(d[55]), "+f"(d[56]), "+f"(d[57]), "+f"(d[58]), "+f"(d[59]), "+f"(d[60]), "+f"(d[61]), "+f"(d[62]), "+f"(d[63])
        : "r"(a[0]), "r"(a[1]), "r"(a[2]), "r"(a[3]), "l"(db), "r"(acc), "n"(TB));
}
template <int TB>
__device__ __forceinline__ void wgmma_rs64(float* d, const uint32_t* a, uint64_t db, uint32_t acc) {
    asm volatile("{\n.reg .pred P;\nsetp.ne.u32 P, %37, 0;\nwgmma.mma_async.sync.aligned.m64n64k16.f32.bf16.bf16 "
        "{%0, %1, %2, %3, %4, %5, %6, %7, %8, %9, %10, %11, %12, %13, %14, %15, %16, %17, %18, %19, %20, %21, %22, %23, %24, %25, %26, %27, %28, %29, %30, %31}, {%32, %33, %34, %35}, %36, P, 1, 1, %38;\n}"
        : "+f"(d[0]), "+f"(d[1]), "+f"(d[2]), "+f"(d[3]), "+f"(d[4]), "+f"(d[5]), "+f"(d[6]), "+f"(d[7]), "+f"(d[8]), "+f"(d[9]), "+f"(d[10]), "+f"(d[11]), "+f"(d[12]), "+f"(d[13]), "+f"(d[14]), "+f"(d[15]), "+f"(d[16]), "+f"(d[17]), "+f"(d[18]), "+f"(d[19]), "+f"(d[20]), "+f"(d[21]), "+f"(d[22]), "+f"(d[23]), "+f"(d[24]), "+f"(d[25]), "+f"(d[26]), "+f"(d[27]), "+f"(d[28]), "+f"(d[29]), "+f"(d[30]), "+f"(d[31])
        : "r"(a[0]), "r"(a[1]), "r"(a[2]), "r"(a[3]), "l"(db), "r"(acc), "n"(TB));
}
template <int TB>
__device__ __forceinline__ void wgmma_rs16(float* d, const uint32_t* a, uint64_t db, uint32_t acc) {
    asm volatile("{\n.reg .pred P;\nsetp.ne.u32 P, %13, 0;\nwgmma.mma_async.sync.aligned.m64n16k16.f32.bf16.bf16 "
        "{%0, %1, %2, %3, %4, %5, %6, %7}, {%8, %9, %10, %11}, %12, P, 1, 1, %14;\n}"
        : "+f"(d[0]), "+f"(d[1]), "+f"(d[2]), "+f"(d[3]), "+f"(d[4]), "+f"(d[5]), "+f"(d[6]), "+f"(d[7])
        : "r"(a[0]), "r"(a[1]), "r"(a[2]), "r"(a[3]), "l"(db), "r"(acc), "n"(TB));
}

__device__ __forceinline__ uint32_t delay_loop(int n, uint32_t x0) {
    uint32_t z;
    asm volatile("{\n.reg .pred P;\n.reg .u32 c, x;\nmov.u32 c, %1;\nmov.u32 x, %2;\nDL: mad.lo.u32 x, x, 1664525, 1013904223;\nadd.u32 c, c, -1;\nsetp.gt.s32 P, c, 0;\n@P bra DL;\n"
                 "setp.eq.u32 P, x, 0x7fffffff;\nselp.u32 %0, 16, 0, P;\n}" : "=r"(z) : "r"(n), "r"(x0) : "memory");
    return z;
}
__device__ __forceinline__ void wait_clocks(uint32_t n) {
    asm volatile("{\n.reg .pred P;\n.reg .u32 a, b;\nmov.u32 a, %%clock;\nW: mov.u32 b, %%clock;\nsub.u32 b, b, a;\nsetp.lt.u32 P, b, %0;\n@P bra W;\n}" ::"r"(n) : "memory");
}
__device__ __forceinline__ uint32_t gtime() { uint32_t t; asm volatile("mov.u32 %0, %%globaltimer_lo;" : "=r"(t)); return t; }
#define COUNT_RETRY(i)
__device__ __forceinline__ uint32_t stamp_word(uint32_t seq) { return (gtime() & ~31u) | (seq & 31u); }
__device__ __forceinline__ void wait_time(uint32_t t, uint32_t sb) { while ((int32_t)(gtime() - t) < 0) {} }
#define NAPMODE 1
__device__ __forceinline__ void nap(uint32_t ns) { if (NAPMODE) wait_clocks(ns * 7 / 4); else __nanosleep(ns); }
template <int STRIDE>
__device__ __forceinline__ uint32_t latest_stamp(const uint32_t* p, uint32_t seq, uint32_t ref, uint32_t sb) {
#pragma unroll 1
    for (int n = opq(0, 0);; n++) {
        uint32_t bad = 0; int32_t m = INT32_MIN;
#pragma unroll
        for (int i = 0; i < 3; i++) { const uint32_t v = ld_relaxed1(p + i * STRIDE); bad |= (v ^ seq) & 31u; m = max(m, (int32_t)((v & ~31u) - ref)); }
        if (__all_sync(0xffffffffu, bad == 0)) return ref + __reduce_max_sync(0xffffffffu, m);
        nap(100);
        if (n > SPIN_LIMIT) spin_fault();
    }
}
constexpr uint32_t ONES = 0x3C003C00u, FULL = 0x50005000u;
__device__ __forceinline__ void pacer(const Params& P, const uint32_t sb, const int cta, const int lane, const uint32_t epoch) {
    uint8_t* const zp = P.xb + cta * 2048 + xg_lane(lane);
    if (lane < 3) asm volatile("prefetch.tensormap [%0];" ::"l"(&P.tm[lane == 0 ? M_C1 + cta % 3 : lane == 1 ? M_CO : M_SEG]) : "memory");
    uint32_t e0 = 0;
#pragma unroll 2
    for (int i = 0; i < 32; i++) { const uint4 u = __ldg((const uint4*)P.mem0 + i * 32 + lane); e0 = amax(amax(e0, amax(u.x, u.y)), amax(u.z, u.w)); }
    e0 = min(max(warp_exp(e0), 31u), 253u) - 14;
    if (cta < 32) {
        const uint32_t* m = (const uint32_t*)(P.mem0 + (lane >> 2) * 1024 + cta * 32 + (lane & 3) * 2);
        const float sc = __uint_as_float((254 - e0) << 23);
        auto cv = [&](uint32_t u) { return pack2h(bf_lo(u) * sc, bf_hi(u) * sc); };
        const uint32_t y = cv(m[12]);
        st_relaxed4(zp, cv(m[0]), cv(m[4]), cv(m[8]), prmt(y, FULL, 0x7610));
        st_relaxed1(P.xb + xg_side(cta) + lane * 4, prmt(y, FULL, 0x3254));
    }
    if (cta < 40) {
#pragma unroll 1
        for (int b = 1; b < 8; b++) st_relaxed4(zp + xg_buf(b), 0, 0, 0, 0);
    }
    __threadfence();
    const uint32_t* ts = (const uint32_t*)(P.xb + XG_T) + lane;
    int32_t d0 = P.dly;
    const uint32_t go = mapa(sb + B_GO, (cta / 3 & 1) * 3 + 1 + (lane & 1));
    auto free_segment = [&]() { if (lane == 0) mbar_expect(sb + B_KVFULL, 16384); __syncwarp(); if (lane < 2) mbar_arrive_cluster(go); };
    for (int n = 0; (int32_t)(ld_acquire(&g_cnt(C_XCNT)) - (epoch + 1) * 256) < 0; n++) { __nanosleep(500); if (n > SPIN_LIMIT) spin_fault(); }
    const uint32_t ex = max(ld_relaxed1(&g_cnt(C_XMAX)) & 255, 67u);
    mbar_wait_bounded(sb + B_READY, 0);
    free_segment();
    if (lane == 0) st_relaxed2(g_hint + cta * 32, stamp_word(epoch + 1), lds32(sb + S_EV) | lds32(sb + S_EO) << 16);
    uint32_t a = gtime();
    for (int n = 0;; n++) {
        uint32_t bad = 0, e = 0; int32_t m = INT32_MIN;
#pragma unroll
        for (int i = 0; i < 3; i++) {
            uint32_t v[2];
            ld_relaxed2(v, g_hint + lane * 32 + i * 1024);
            bad |= (v[0] ^ (epoch + 1)) & 31u; m = max(m, (int32_t)((v[0] & ~31u) - a)); e = __vmaxu2(e, v[1]);
        }
        if (__all_sync(0xffffffffu, bad == 0)) {
            a += __reduce_max_sync(0xffffffffu, m);
            const uint32_t ev = __reduce_max_sync(0xffffffffu, e & 255), eo = __reduce_max_sync(0xffffffffu, e >> 16);
            if (lane == 0) { sts64(sb + S_SC, max(ev, 97u) + max(eo, 97u) - 244, ex); sts32(sb + S_ISC, e0 * 0x800080u); }
            break;
        }
        wait_clocks(100);
        if (n > SPIN_LIMIT) spin_fault();
    }
    wait_time(a, sb);
    if (lane == 0) mbar_arrive(sb + B_RELM);
#pragma unroll 1
    for (int s = 0; s < 63; s++) {
        const uint32_t seq = epoch * 63 + s + 1;
        mbar_wait_bounded(sb + B_P1, s & 1);
        const uint32_t tx = gtime();
        if (lane == 0) st_relaxed1(ts + (s & 1) * 256 + cta, (tx & ~31u) | (seq & 31u));
        { const uint32_t t = tx; PROFP(3) }
        if (s > 0) {
            const int32_t e0 = latest_stamp<32>(ts + (~s & 1) * 256 + 128, seq - 1, a, sb) + P.mrg - a;
            d0 += s < 3 ? e0 : min(max(e0, -P.clamp0), P.clampv) / 2;
        }
        while ((int32_t)(gtime() - tx) < P.rd) nap(20);
        a = latest_stamp<32>(ts + (s & 1) * 256, seq, tx, sb) + d0;
        { const uint32_t t = gtime(); PROFP(0) }
        while ((int32_t)(a - gtime()) > 250) nap(40);
        wait_time(a, sb);
        if (lane == 0) mbar_arrive(sb + B_RELM);
        { const uint32_t t = a; PROFP(2) }
        mbar_wait_bounded(sb + B_RED, s & 1);
        { const uint32_t t = gtime(); PROFP(1) }
        const uint32_t g = tx + __reduce_max_sync(0xffffffffu, lds32(sb + S_TO + (lane & 7) * 4) - tx);
        if (lane == 0) st_relaxed1(ts + (s & 1) * 256 + 128 + cta, (g & ~31u) | (seq & 31u));
        if (s < 62) { if (P.kvd) nap(P.kvd); free_segment(); }
    }
}
__device__ __forceinline__ void st_async2(uint32_t a, uint32_t x, uint32_t y, uint32_t bar) {
    asm volatile("st.async.weak.shared::cluster.mbarrier::complete_tx::bytes.v2.b32 [%0], {%1,%2}, [%3];" ::"r"(a), "r"(x), "r"(y), "r"(bar) : "memory");
}
__device__ __forceinline__ uint32_t xor_or(uint32_t a, uint32_t b, uint32_t t) { uint32_t d; asm("lop3.b32 %0, %1, %2, %3, 0x7E;" : "=r"(d) : "r"(a), "r"(b), "r"(t)); return d; }
__device__ __forceinline__ uint32_t or3(uint32_t a, uint32_t b, uint32_t c) { uint32_t d; asm("lop3.b32 %0, %1, %2, %3, 0xFE;" : "=r"(d) : "r"(a), "r"(b), "r"(c)); return d; }
__device__ __forceinline__ bool tags_ok(uint32_t bad, uint32_t mask = 1) {
    uint32_t r;
    asm volatile("{\n.reg .pred P;\n.reg .b32 x;\nand.b32 x, %1, %2;\nsetp.ne.b32 P, x, 0;\nvote.sync.any.pred P, P, 0xffffffff;\nselp.u32 %0, 0, 1, P;\n}" : "=r"(r) : "r"(bad), "r"(mask));
    return r;
}
constexpr int SROW = 56;
#define PREA 8
#define PREB 9
#define RING1 6
#define RING2 7
#define RING3 8
#define PRE2 10
#define PRE2A 0
#define PRE3 0
#define EFENCE 0
#define RFENCE 1
#define PROG 16
#define EARLY 0
#define PLATE 1
#define NDEP 0
#define EFENCE2 0
#define LAG2 8
#define LAG 4
#define PUT1 33
#define DEPS 3
#define ADELAY 120
#define BDELAY 0
#define HOLD 1
#define XDELAY 330
#define FENCEA 0x80
#define FENCEB 0x80
#define FENCE2 0x220
#define OFENCE 0
#define MASK3 0x57
#define MASK4 0x55
#define MASK5 0x25
#define OFF3 0x5320
#define OFF4 0x6420
#define OFF5 0x0520
#define RESA (NRA == 3 ? 15 : NRA == 4 ? 3 : 0)
#define RESB (NRB == 3 ? 0xcc : NRB == 4 ? 0x30 : 0)
#define RESB1 (NRB == 3 ? 0xcc : NRB == 4 ? 0xc : 0)
__host__ __device__ constexpr int smem_mask(int NR) { return NR == 3 ? MASK3 : NR == 4 ? MASK4 : MASK5; }
__host__ __device__ constexpr bool round_smem(int r, int NR) { return smem_mask(NR) >> r & 1; }
__host__ __device__ constexpr int kord(int r, int NR) { int c = 0; for (int i = 0; i < r; i++) c += round_smem(i, NR) == round_smem(r, NR); return round_smem(r, NR) ? NR + c : c; }
__host__ __device__ constexpr int slot_r(int n, int NR) { return n < 32 ? n >> 2 : (((n & 31) >> 2) + ((NR == 3 ? OFF3 : NR == 4 ? OFF4 : OFF5) >> (n & 3) * 4)) & 7; }
__host__ __device__ constexpr int slot_k(int n, int NR) { return kord(slot_r(n, NR), NR); }
__host__ __device__ constexpr int slot_sord(int n, int NR) { int c = 0; for (int i = 0; i < n; i++) c += slot_k(i, NR) >= NR; return c; }
__host__ __device__ constexpr int sfrag_slot(int q, int NR) { for (int n = 0; n < 64; n++) if (slot_k(n, NR) >= NR && slot_sord(n, NR) == q) return n; return -1; }
__host__ __device__ constexpr int w1_loaded(int n, int NR, int PRE) {
    int q = PRE;
    for (int i = 0; i <= n; i++) q += q < (8 - NR) * 8 && q - slot_sord(i + 1, NR) < (i < 32 ? RING1 : RING2);
    return q;
}
template <int Q, int NR>
__device__ __forceinline__ void load_w1(uint32_t* w, const uint32_t* a) {
    constexpr int n = sfrag_slot(Q, NR);
    ldsm4t(w, a[n & 3] + ((slot_k(n, NR) - NR) * 2 + (n >> 5)) * 2048);
}
constexpr int AB = NRA < 5, BB = 3 - AB;
__device__ __forceinline__ bool w2_full(int role, int warp) { return warp < (role == 2 ? 2 : 3); }
__device__ __forceinline__ int w2_nblk(int role, int warp) { return warp < 4 ? BB - !w2_full(role, warp) : AB; }
__host__ __device__ constexpr int w2_step(bool full, int i) { return AB ? (full ? 2 * i : 0) : full ? (i == 0 ? 0 : i == 1 ? 16 - 2 * EARLY : 18 - 2 * EARLY) : i; }
__device__ __forceinline__ int w2_block(int role, int warp) {
    const int f = role * 3 + warp, g = role == 2 ? warp : role;
    if (AB) return (warp >= 4 ? role * 4 + (warp - 4) : w2_full(role, warp) ? 16 + 4 * (f >> 1) + (f & 1) : 12 + g) ^ EARLY;
    return w2_full(role, warp) ? EARLY + 4 * (f >> 1) + (f & 1) : EARLY + 2 + 4 * g;
}
__device__ __forceinline__ int w2_res(int role, int warp) { return warp >= 4 ? RESA : w2_full(role, warp) ? RESB : RESB1; }
__device__ __forceinline__ int w2_units(int role, int warp) { return w2_nblk(role, warp) * 4 - (5 - (warp < 4 ? NRB : NRA)) * 2; }
constexpr int W2B = (BB * 4 - (5 - NRB) * 2) * 2048, W2A = (AB * 4 - (5 - NRA) * 2) * 2048;
static_assert(S_W2 + 4 * W2B - 8192 + 4 * W2A == S_KV, "weights");
__device__ __forceinline__ int w1_base(int warp) { return S_W1 + (warp < 4 ? warp * (8 - NRB) : 4 * (8 - NRB) + (warp - 4) * (8 - NRA)) * 4096; }
__device__ __forceinline__ int w2_base(int warp) { return S_W2 + (warp < 4 ? warp * W2B : 4 * W2B - 8192 + (warp - 4) * W2A); }
__device__ __forceinline__ void chain_load(const Params& P, uint32_t sb, int cta, int warp, int lane, int round) {
    const int role = cta % 3, h = cta / 3;
    mbar_expect_e(sb + B_INIT, round ? (8 - (warp < 4 ? NRB : NRA)) * 4096 : 20480);
    if (round) mbar_expect_e(sb + B_INIT2, w2_units(role, warp) * 2048);
    __syncwarp();
    const int m1 = (warp < 4 ? smem_mask(NRB) : smem_mask(NRA)) ^ (round ? 0 : 255), below = (1 << lane) - 1;
    const int m2 = (w2_res(role, warp) ^ (round ? 0xfff : 0)) & ((1 << w2_nblk(role, warp) * 4) - 1);
    const uint32_t d1 = sb + (round ? w1_base(warp) : warp * 20480), d2 = round ? sb + w2_base(warp) : d1 + __popc(m1) * 4096;
    if (m1 >> lane & 1) tma3d(d1 + __popc(m1 & below) * 4096, &P.tm[M_C1 + role], 0, warp * 128 + lane * 16, h * 2, sb + B_INIT);
    __syncwarp();
    if (m2 >> lane & 1)
        tma2d(d2 + __popc(m2 & below) * 2048, &P.tm[M_CO], (w2_block(role, warp) + w2_step(w2_full(role, warp), lane >> 2)) * 32, h * 128 + (lane & 3) * 32, sb + (round ? B_INIT2 : B_INIT));
    __syncwarp();
}

__device__ __forceinline__ void put_partials(bool TR, uint32_t a, const float* x, const float* y) {
    if (TR) stsm4t(a, pack2(x[0], x[1]), pack2(x[2], x[3]), pack2(y[0], y[1]), pack2(y[2], y[3]));
    else stsm4(a, pack2(x[0], x[1]), pack2(x[2], x[3]), pack2(y[0], y[1]), pack2(y[2], y[3]));
}
template <int NR, int PRE, int FM, int B, int E>
__device__ __forceinline__ void project(float (*acc)[4], bool TR, const uint32_t (*wr)[4], uint32_t (*as)[4], uint32_t (*v)[4], uint32_t* x, const uint32_t* w1a, uint32_t pp, uint32_t zero) {
    static_for<B, E>([&](auto I) {
        constexpr int n = I.value, kk = slot_k(n, NR), T = (n >> 5) * 4 + (n & 3), so = slot_sord(n, NR), q = w1_loaded(n - 1, NR, PRE);
        constexpr bool sm = kk >= NR;
        const uint32_t* w = sm ? as[so] : wr[sm ? 0 : (kk * 2 + (n >> 5)) * 4 + (n & 3)];
        if constexpr (n == 32 && PUT1 < 32) { put_partials(TR, pp, acc[0], acc[1]); put_partials(TR, pp + 4096, acc[2], acc[3]); }
        if constexpr (n == 0) {
            const uint32_t c = prmt(v[0][3], x[0], 0x3254);
            v[0][0] = h2bf(v[0][0], v[0][0]); v[0][1] = h2bf(v[0][1], v[0][1]); v[0][2] = h2bf(v[0][2], v[0][2]); v[0][3] = h2bf(v[0][3], x[0]);
            x[0] = c;
        }
        if constexpr ((n & 31) < 4) acc[T][0] = acc[T][1] = acc[T][2] = acc[T][3] = 0.f;
        mma16816(acc[T], w[0], w[1], w[2], w[3], v[slot_r(n, NR) >> 1][(slot_r(n, NR) & 1) * 2], v[slot_r(n, NR) >> 1][(slot_r(n, NR) & 1) * 2 + 1]);
        if constexpr (n == DEPS) {
            const uint32_t sel = __float_as_uint(acc[T][0]) * zero + 0x7610;
#pragma unroll
            for (int b = 1; b < 4; b++) {
                if (b <= NDEP) cvt_block(v[b], x[b], sel);
                else {
                    const uint32_t c = prmt(v[b][3], x[b], 0x3254);
                    v[b][0] = h2bf(v[b][0], v[b][0]); v[b][1] = h2bf(v[b][1], v[b][1]); v[b][2] = h2bf(v[b][2], v[b][2]); v[b][3] = h2bf(v[b][3], x[b]);
                    x[b] = c;
                }
            }
        }
        if constexpr (w1_loaded(n, NR, PRE) > q) load_w1<q, NR>(as[q], w1a);
        if constexpr (n == PUT1 && n >= 32) { put_partials(TR, pp, acc[0], acc[1]); put_partials(TR, pp + 4096, acc[2], acc[3]); }
        if constexpr (n % 4 == 3 && (FM >> (n / 4) & 1) && n != E - 1) sched_fence();
    });
    if constexpr (E == 64) { put_partials(TR, pp + 8192, acc[4], acc[5]); put_partials(TR, pp + 12288, acc[6], acc[7]); }
}
__device__ __forceinline__ void reduce8(const uint32_t (*x)[4], const uint32_t* sel, float sc, uint32_t& r0, uint32_t& r1) {
    float d[4][4];
#pragma unroll
    for (int i = 0; i < 4; i++) {
        d[i][0] = d[i][1] = d[i][2] = d[i][3] = 0.f;
        mma16816(d[i], x[i][0], x[i][1], x[i][2], x[i][3], sel[2 * i], sel[2 * i + 1]);
    }
    r0 = pack2(((d[0][0] + d[1][0]) + (d[2][0] + d[3][0])) * sc, ((d[0][1] + d[1][1]) + (d[2][1] + d[3][1])) * sc);
    r1 = pack2(((d[0][2] + d[1][2]) + (d[2][2] + d[3][2])) * sc, ((d[0][3] + d[1][3]) + (d[2][3] + d[3][3])) * sc);
}

#define ISTAMP(i)
__host__ __device__ constexpr int wo_count(int n, int RES, bool res) { int c = 0; for (int i = 0; i < n; i++) c += (RES >> (i >> 2) & 1) == res; return c; }
__host__ __device__ constexpr int wo_loaded(int n, int RES, int PRE, int end) { int q = PRE; for (int i = 0; i <= n; i++) q += q < end && q - wo_count(i + 1, RES, false) < RING3; return q; }
template <int Q>
__device__ __forceinline__ void load_w2(uint32_t* w, const uint32_t* a) { ldsm4t(w, a[Q & 1] + (Q >> 1) * 1024); }
template <int NB, int RES, int PRE, int FM>
__device__ __forceinline__ void wo_blocks(uint32_t (*w)[4], const uint32_t (*wp)[4], uint32_t oa, const uint32_t* wa, const uint8_t* dst, const uint8_t* dsd, bool odd) {
    float a[NB][4][4];
    uint32_t o[4][4], r[5];
    bar_sync(3, 256);
#pragma unroll
    for (int i = 0; i < 4; i++) ldsm4(o[i], oa + i * 512);
    if (FM & 1) sched_fence();
    static_for<0, NB * 16>([&](auto I) {
        constexpr int n = I.value, i = n & 15, end = wo_count(NB * 16, RES, false), q = wo_loaded(n - 1, RES, PRE, end);
        constexpr bool res = RES >> (n >> 2) & 1;
        const uint32_t* b = o[i >> 2] + (i & 2);
        const uint32_t* x = res ? wp[wo_count(n, RES, true)] : w[wo_count(n, RES, false)];
        float* d = a[n >> 4][i & 3];
        if constexpr (i < 4) d[0] = d[1] = d[2] = d[3] = 0.f;
        mma16816(d, x[0], x[1], x[2], x[3], b[0], b[1]);
        if constexpr (wo_loaded(n, RES, PRE, end) > q) load_w2<q>(w[q], wa);
        if constexpr (n == NB * 16 - 1 || (n >= 16 && i == LAG - 1)) {
            const float (*e)[4] = a[n == NB * 16 - 1 ? NB - 1 : (n >> 4) - 1];
            const uint32_t y = pack2h(e[1][2] + e[3][2], e[1][3] + e[3][3]);
            r[0] = movm(pack2h(e[0][0] + e[2][0], e[0][1] + e[2][1])); r[1] = movm(pack2h(e[0][2] + e[2][2], e[0][3] + e[2][3]));
            r[2] = movm(pack2h(e[1][0] + e[3][0], e[1][1] + e[3][1])); r[3] = movm(odd ? ONES : y); r[4] = movm(odd ? y : ONES);
        }
        if constexpr (n == NB * 16 - 1 || (n >= 16 && i == LAG2 - 1)) {
            constexpr int bs = w2_step(NB == BB, n == NB * 16 - 1 ? NB - 1 : (n >> 4) - 1);
            red_add4(dst + bs * 2048, r[0], r[1], r[2], r[3]);
            red_add1(dsd + (bs >> 1) * 1024 + (bs & 1) * 256, r[4]);
        }
        if constexpr (((FM >> (n / 4 + 1)) & 1) && (n & 3) == 3 && n != NB * 16 - 1) sched_fence();
    });
}
#define FRAG1(ln) ((((ln) & 7) + ((ln) >> 4) * 8) * 128 + ((((((ln) >> 3) & 1) << (ROLE == 1)) ^ ((ln) & 7)) << 4))
#define FRAG2(ln) ((((ln) & 7) + ((ln) >> 4) * 8) * 64 + (((((ln) >> 3) & 1) ^ (((ln) >> 1) & 3)) << 4))
#define TILE_X(i) (ROLE == 1 ? (((i) >> 1) << 6) | (((i) & 1) << 4) : (i) << 5)
__device__ __forceinline__ void chain_fetch(const Params& P, const uint32_t sb, const int cta, const int warp, const int lane, uint32_t (*wr)[4]) {
    const int ROLE = cta % 3, nr = warp < 4 ? NRB : NRA;
    mbar_wait(sb + B_INIT, 0);
    ISTAMP(0)
#pragma unroll
    for (int f = 0; f < 40; f++) {
        const bool w1 = f < (NRA < NRB ? NRA : NRB) * 8 || f < nr * 8;
        ldsm4t(wr[f], sb + warp * 20480 + (f >> 2) * 2048 + (w1 ? FRAG1(lane) ^ TILE_X(f & 3) : (f & 2) * 512 + (FRAG2(lane) ^ ((f & 1) << 5))));
    }
    fence_async_smem();
    mbar_wait(sb + B_SFREE + (warp >> 2) * 8, 0);
    bar_sync(1, 256);
    chain_load(P, sb, cta, warp, lane, 1);
    ISTAMP(1)
}
__device__ __forceinline__ void chain_bounds(const uint32_t sb, const int cta, const int warp, const int lane, const uint32_t (*wr)[4]) {
    const int ROLE = cta % 3, nr = warp < 4 ? NRB : NRA;
    uint32_t m[6] = {}, u[4];
#pragma unroll
    for (int f = 0; f < 40; f++) m[f < 24 ? 0 : f >> 3] = amax4(m[f < 24 ? 0 : f >> 3], wr[f]);
    uint32_t m1 = amax(m[0], amax(nr > 3 ? m[3] : 0, nr > 4 ? m[4] : 0)), m2 = amax(nr > 3 ? 0 : m[3], nr > 4 ? 0 : m[4]);
    ISTAMP(5)
    mbar_wait(sb + B_INIT, 1);
    ISTAMP(3)
    if (ROLE == 2) {
#pragma unroll 4
        for (int i = 0; i < S_W2 / 4096; i++) { lds128(u, sb + S_W1 + warp * (S_W2 / 8) + i * 512 + lane * 16); m1 = amax4(m1, u); }
    }
    mbar_wait(sb + B_INIT2, 0);
    ISTAMP(7)
    const int n = w2_units(ROLE, warp) * 4;
#pragma unroll 4
    for (int i = 0; i < n; i++) { lds128(u, sb + w2_base(warp) + i * 512 + lane * 16); m2 = amax4(m2, u); }
    m1 = warp_exp(m1); m2 = warp_exp(m2);
    if (lane == 0) { if (ROLE == 2) red_max_shared(sb + S_EV, m1); red_max_shared(sb + S_EO, m2); }
}
template <bool ATT>
__device__ __forceinline__ void chain_role(const Params& P, const uint32_t sb, const int cta, const int warp, const int lane, const uint32_t (*wr)[4]) {
    constexpr int NR = ATT ? NRA : NRB, PRE = ATT ? PREA : PREB;
    const int h = cta / 3, ROLE = cta - h * 3;
    ISTAMP(6)
    uint32_t l8 = opq(sb + lane * 8, lane);
    const uint8_t* persu = (const uint8_t*)((ROLE == 1 ? g_km : g_vmt) + h * 512) - (sb >> 1);
    auto persist = [&](int s, int tile, uint32_t r0, uint32_t r1) {
        uint32_t* pp = (uint32_t*)(persu + s * 65536 + (ROLE == 1 ? (tile >> 1) * 512 + (tile & 1) * 128 : tile * 256) + (l8 >> 1));
        pp[0] = r0; pp[ROLE == 1 ? 64 : 32] = r1;
    };
    const uint32_t rk0 = (h & 1) * 3, rd1 = __shfl_sync(0xffffffffu, mapa(sb, rk0 + (ROLE + 1) % 3) - sb, 0), rd2 = __shfl_sync(0xffffffffu, mapa(sb, rk0 + (ROLE + 2) % 3) - sb, 0);
    const uint32_t xo = (ROLE == 2 ? S_XV : S_X + ROLE * 2048) + warp * 256;
    const bool full = w2_full(ROLE, warp);
    const int blk = w2_block(ROLE, warp);
    const uint32_t om = blk * 2048, os = xg_side(blk);
    const uint32_t w1o = sb + w1_base(warp), w2o = sb + w2_base(warp);
    ISTAMP(2)
    if (lane == 0) mbar_arrive(sb + B_READY);
#pragma unroll 1
    for (int s = 0;; s++) {
        l8 += s & P.zero;
        uint32_t r0, r1;
        {
            uint32_t v[4][4], as[(8 - NR) * 8][4], w1a[4];
            float acc[8][4];
            const uint32_t pst = sb + S_P1 + (l8 - sb) * 16 + ((warp * 16) ^ ((l8 & 56) * 2));
#pragma unroll
            for (int i = 0; i < 4; i++) w1a[i] = w1o + (FRAG1((l8 - sb) >> 3) ^ TILE_X(i));
            auto preload = [&]() { static_for<0, PRE>([&](auto I) { load_w1<I.value, NR>(as[I.value], w1a); }); };
#pragma unroll 1
            while (true) {
                uint32_t x[4];
                if (!(PLATE >> ATT & 1)) preload();
                const uint32_t lm = opq(l8 - sb, (l8 - sb) >> 3);
                const uint8_t* pm = P.xb + xg_buf(s) + warp * 8192 + xg_lane(lm >> 3);
                const uint8_t* ps = P.xb + xg_buf(s) + XG_SIDE + warp * 2048 + (lm >> 1);
                pin_ptr(pm); pin_ptr(ps);
                mbar_wait(sb + B_RELM, s & 1);
                if (ATT ? ADELAY : BDELAY) wait_clocks(ATT ? ADELAY : BDELAY);
                PROF(10)
#pragma unroll
                for (int b = 0; b < 4; b++) { ld_relaxed4(v[b], pm + b * 2048); ld_relaxed1n(x[b], ps + (b >> 1) * 1024 + (b & 1) * 256); }
                if (PLATE >> ATT & 1) { preload(); if (PLATE >> (ATT + 2) & 1) sched_fence(); }
                project<NR, PRE, ATT ? FENCEA : FENCEB, 0, PROG>(acc, ROLE == 2, wr, as, v, x, w1a, pst, P.zero);
                const uint32_t bad = xor_or(x[0], x[1], FULL) | xor_or(x[2], x[3], FULL);
                if (tags_ok(bad, 0xffffffffu)) break;
                COUNT_RETRY(warp >> 1)
            }
            PROF(0)
            project<NR, PRE, ATT ? FENCEA : FENCEB, PROG, 64>(acc, ROLE == 2, wr, as, v, nullptr, w1a, pst, 0);
            PROF(1)
            const uint32_t isc = lds32(sb + S_ISC + (s & 1) * 4);
            const uint32_t lq = l8 + ((s >> 3) & P.zero), e1 = s == 63 ? 0 : rd1, e2 = s == 63 ? 0 : rd2;
            uint32_t x[4][4], sel[8], xd[6] = {l8 + xo, l8 + xo + e1, l8 + xo + e2, sb + B_X + e1, sb + B_X + e2, sb + S_P1 + warp * 2048 + (lq & 64) * 16 + (lq & 128) + (lq & 56) * 2};
#pragma unroll
            for (int i = 0; i < 8; i++) sel[i] = (lq & 224) == i * 32 ? 0x3F803F80u : 0u;
            pin<6>(xd); pin<8>(sel);
            if (RFENCE) sched_fence();
            bar_sync(1, 256);
#pragma unroll
            for (int i = 0; i < 4; i++) ldsm4t(x[i], xd[5] + i * 256);
            if (!ATT && l8 == sb + (warp - 3) * 1024) mbar_arrive(sb + B_P1);
            uint32_t em = warp_exp(amax(amax4(amax(amax(v[0][0], v[0][1]), amax(v[0][2], v[0][3])), v[1]), amax4(amax(amax(v[2][0], v[2][1]), amax(v[2][2], v[2][3])), v[3])));
            if (EFENCE2) sched_fence();
            reduce8(x, sel, bf_hi(isc), r0, r1);
            st_async2(xd[1], r0, r1, xd[3]);
            st_async2(xd[2], r0, r1, xd[4]);
            sts64(xd[0], r0, r1);
            if (s == 63) { persist(s, warp, r0, r1); break; }
            if (l8 == sb) sts32(sb + S_EM + warp * 4, em + (isc >> 23));
            __syncwarp();
            if (l8 == sb) mbar_arrive(sb + B_X);
            PROF(2)
        }
        uint32_t w[40][4], w2a[2], odd;
        const uint8_t *po, *pd;
        auto wo_addr = [&]() {
            const uint32_t lo = (l8 + ((s >> 2) & P.zero) - sb) >> 3;
            w2a[0] = w2o + FRAG2(lo); w2a[1] = w2o + (FRAG2(lo) ^ 32);
            po = P.xb + xg_buf(s + 1) + om + xg_lane(lo);
            pd = P.xb + xg_buf(s + 1) + os + lo * 4;
            odd = lo & 4;
            pin_ptr(po); pin_ptr(pd); pin<2>(w2a); pin<1>(&odd);
        };
        uint32_t oa = l8 * 2 + (S_OX - sb);
        if constexpr (ATT) {
            const uint32_t ln = (l8 + ((s >> 4) & P.zero) - sb) >> 3;
            const uint32_t va = sb + S_KV + 8192 + ((warp >> 1) & 1) * 4096 + ((ln & 7) + (ln >> 4) * 8) * 128 + ((((warp & 1) * 4 + ((ln >> 3) & 1)) ^ (ln & 7)) << 4);
            const uint32_t ka = sb + S_KV + (warp & 1) * 2048 + (ln & 15) * 128 + (((ln >> 4) ^ (ln & 7)) << 4);
            uint32_t ad[5] = {sb + S_SX + (ln & 3) * (8 * SROW) + (ln >> 2) * 4 + (warp < 6 ? (warp - 4) * 64 : 128 + (warp - 6) * 32), l8 + S_XV + (warp - 4) * 512,
                              l8 + S_SX + (ln >> 2) * (4 * SROW - 32), oa + (warp - 4) * 512, sb + S_ISC + (~s & 1) * 4};
            if constexpr (AB) { wo_addr(); pin<1>(&oa); }
            pin<5>(ad);
            const uint32_t sa = ad[0], sr = ad[2];
            uint32_t vf[4][4], vm[2][2], q[8][2];
            float S[8][4];
#pragma unroll
            for (int n = 0; n < 8; n++) { S[n][0] = S[n][1] = S[n][2] = S[n][3] = 0.f; }
            mbar_wait(sb + B_KVFULL, s & 1);
            if (warp < 6) {
                uint32_t kf[8][4];
#pragma unroll
                for (int k = 0; k < 8; k++) ldsm4(kf[k], (ka ^ ((k & 3) << 5)) + (k >> 2) * 4096);
#pragma unroll
                for (int i = 0; i < 4; i++) ldsm4t(vf[i], (va ^ ((i & 1) << 5)) + (i >> 1) * 2048);
                mbar_wait(sb + B_X, s & 1);
                PROF(11)
#pragma unroll
                for (int k = 0; k < 8; k++) lds64(q[k], l8 + S_X + k * 256);
#pragma unroll
                for (int k = 0; k < 8; k++) mma16816(S[k], kf[k][0], kf[k][1], kf[k][2], kf[k][3], q[k][0], q[k][1]);
#pragma unroll
                for (int k = 0; k < 4; k++) { S[k][0] = S[2 * k][0] + S[2 * k + 1][0]; S[k][1] = S[2 * k][1] + S[2 * k + 1][1]; S[k][2] = S[2 * k][2] + S[2 * k + 1][2]; S[k][3] = S[2 * k][3] + S[2 * k + 1][3]; }
                sts32(sa, __float_as_uint((S[0][0] + S[1][0]) + (S[2][0] + S[3][0])));
                sts32(sa + 4 * SROW, __float_as_uint((S[0][1] + S[1][1]) + (S[2][1] + S[3][1])));
                sts32(sa + 32, __float_as_uint((S[0][2] + S[1][2]) + (S[2][2] + S[3][2])));
                sts32(sa + 4 * SROW + 32, __float_as_uint((S[0][3] + S[1][3]) + (S[2][3] + S[3][3])));
            } else {
#pragma unroll
                for (int i = 0; i < 4; i++) ldsm4t(vf[i], (va ^ ((i & 1) << 5)) + (i >> 1) * 2048);
                uint32_t xa = l8 + S_X + (warp - 6) * 1024;
                pin<1>(&xa);
                mbar_wait(sb + B_X, s & 1);
                PROF(11)
#pragma unroll
                for (int k = 0; k < 8; k++) lds64(q[k], xa + (k >> 2) * 2048 + (k & 3) * 256);
#pragma unroll
                for (int k = 0; k < 4; k++) mma16816(S[k], q[4 + (k & 2)][0], q[4 + (k & 2)][1], q[5 + (k & 2)][0], q[5 + (k & 2)][1], q[k][0], q[k][1]);
                sts32(sa, __float_as_uint((S[0][0] + S[2][0]) + (S[1][2] + S[3][2])));
                sts32(sa + 4 * SROW, __float_as_uint((S[0][1] + S[2][1]) + (S[1][3] + S[3][3])));
            }
            lds64(vm[0], ad[1]); lds64(vm[1], ad[1] + 256);
            PROF(7)
            bar_sync(2, 160);
            const float cs = 0.08838834764831845f * 1.4426950408889634f;
            float E[6][2];
#pragma unroll
            for (int i = 0; i < 6; i++) lds64f(E[(i + 4) % 6], sr + ((i + 4) % 6) * 32);
            const uint32_t isn = lds32(ad[4]);
            E[4][0] += E[5][0]; E[4][1] += E[5][1];
            float m = fmaxf(fmaxf(fmaxf(fmaxf(E[0][0], E[0][1]), fmaxf(E[1][0], E[1][1])), fmaxf(fmaxf(E[2][0], E[2][1]), fmaxf(E[3][0], E[3][1]))), fmaxf(E[4][0], E[4][1]));
            m = fmaxf(m, __shfl_xor_sync(0xffffffffu, m, 1));
            m = fmaxf(m, __shfl_xor_sync(0xffffffffu, m, 2));
            m *= cs;
            if constexpr (AB) static_for<0, PRE3>([&](auto I) { load_w2<I.value>(w[I.value], w2a); });
            uint32_t pa[5];
#pragma unroll
            for (int i = 0; i < 5; i++) { const int k = (i + 4) % 5; E[k][0] = ex2(fmaf(E[k][0], cs, -m)); E[k][1] = ex2(fmaf(E[k][1], cs, -m)); pa[k] = pack2(E[k][0], E[k][1]); }
            if (EFENCE) sched_fence();
            float O[2][4], Z[4];
#pragma unroll
            for (int i = 0; i < 4; i++) { O[0][i] = O[1][i] = Z[i] = 0.f; }
            mma1688(Z, isn, isn, pa[4]);
            mma1688(O[0], vm[0][0], vm[0][1], pa[4]);
            mma1688(O[1], vm[1][0], vm[1][1], pa[4]);
#pragma unroll
            for (int k = 0; k < 2; k++) {
                mma16816(Z, isn, isn, isn, isn, pa[2 * k], pa[2 * k + 1]);
#pragma unroll
                for (int i = 0; i < 2; i++) mma16816(O[i], vf[2 * k + i][0], vf[2 * k + i][1], vf[2 * k + i][2], vf[2 * k + i][3], pa[2 * k], pa[2 * k + 1]);
            }
            const float i0 = rcp(Z[0]), i1 = rcp(Z[1]);
            stsm4t(ad[3], pack2(O[0][0] * i0, O[0][1] * i1), pack2(O[0][2] * i0, O[0][3] * i1), pack2(O[1][0] * i0, O[1][1] * i1), pack2(O[1][2] * i0, O[1][3] * i1));
            PROF(4)
            if constexpr (AB) wo_blocks<1, RESA, PRE3, OFENCE / 2>(w, wr + NR * 8, oa, w2a, po, pd, odd);
            else bar_arrive(3, 256);
            if (ROLE != 0) persist(s, warp, r0, r1);
            if (warp == 7 && l8 == sb) mbar_expect(sb + B_X, 4096);
        } else {
            if (ROLE != 0) persist(s, warp, r0, r1);
            wo_addr(); pin<1>(&oa);
            static_for<0, PRE2A>([&](auto I) { load_w2<I.value>(w[I.value], w2a); });
            mbar_wait(sb + B_X, s & 1);
            if (warp == 0) {
                uint32_t sc[2];
                lds64(sc, sb + S_SC);
                const int em = __reduce_max_sync(0xffffffffu, lds32(sb + S_EM + ((l8 >> 1) & 28)));
                if (l8 == sb) sts32(sb + S_ISC + (~s & 1) * 4, min(max(em - 127, (int)sc[1]) + (int)sc[0], 253) * 0x800080u);
                bar_arrive(2, 160);
            }
            wait_clocks(XDELAY - (warp == 0) * 100);
            constexpr int PRE1 = (BB - 1) * 16 - (5 - NRB) * 8 < PRE2 ? (BB - 1) * 16 - (5 - NRB) * 8 : PRE2;
            static_for<PRE2A, PRE1>([&](auto I) { load_w2<I.value>(w[I.value], w2a); });
            if (full) {
                static_for<PRE1, PRE2>([&](auto I) { load_w2<I.value>(w[I.value], w2a); });
                wo_blocks<BB, RESB, PRE2, FENCE2 * 2 + OFENCE % 2>(w, wr + NR * 8, oa, w2a, po, pd, odd);
            } else wo_blocks<BB - 1, RESB1, PRE1, FENCE2 * 2 + OFENCE % 2>(w, wr + NR * 8, oa, w2a, po, pd, odd);
        }
        PROF(5)
        if (l8 == sb) { sts32(sb + S_TO + warp * 4, gtime()); mbar_arrive(sb + B_RED); }
        if (HOLD && !(PLATE >> ATT & 1)) mbar_wait(sb + B_RED, s & 1);
        if (ROLE != 0 && (s & 3) == 3 && l8 == sb) mbar_arrive(sb + B_PERS);
        if (ROLE == 0 && s == 62) return;
    }
    __syncwarp();
    if (l8 == sb) mbar_arrive(sb + B_PERS);
}
#define IP(i)
struct Pipe { uint32_t stage, phase; };
struct Cons {
    uint32_t sb, rel;
    int wg, wq, lane, rank, pair;
    uint32_t nst;
    Pipe p;
};
__device__ __forceinline__ void pipe_next(Pipe& p) { p.stage = (p.stage + 1) & (NSTAGE - 1); p.phase ^= (p.stage == 0); }
__device__ __forceinline__ void release(const Cons& c, uint32_t stage) { if (c.lane < 2) mbar_arrive_cluster(c.rel + stage * 8); }
__device__ __forceinline__ void wait_full(const Cons& c) { mbar_wait(c.sb + B_FULL + c.p.stage * 8, c.p.phase); }

enum { PEND_NONE = 0, PEND_KVO = 1, PEND_HT = 2, PEND_OUT = 3 };
struct Pend { uint32_t pk[64]; int kind, row, col, cnt; };

__device__ __forceinline__ void staging_wait(const Cons& c) { if (c.nst) mbar_wait(c.sb + B_SFREE + c.wg * 8, (c.nst - 1) & 1); }
__device__ __forceinline__ void staging_post(Cons& c, int kind, int row, int col, int cnt) {
    __syncwarp();
    if (c.lane == 0) {
        if (c.wq == 0) { const uint32_t x[4] = {(uint32_t)kind, (uint32_t)row, (uint32_t)col, (uint32_t)cnt}; sts128(c.sb + S_DESC + c.wg * 16, x); }
        mbar_arrive(c.sb + B_SFULL + c.wg * 8);
    }
    c.nst++;
}
__device__ __forceinline__ void drain(const Params& P, Cons& c, Pend& d) {
    const uint32_t* pk = d.pk;
    if (d.kind == PEND_OUT) {
        float* o = P.out + (size_t)(d.row + c.wq * 16 + (c.lane >> 2)) * 2048 + d.col + (c.lane & 3) * 2;
#pragma unroll
        for (int j = 0; j < 16; j++) {
            st_stream2(o + j * 8, bf_lo(pk[j * 2]), bf_hi(pk[j * 2]));
            st_stream2(o + 8 * 2048 + j * 8, bf_lo(pk[j * 2 + 1]), bf_hi(pk[j * 2 + 1]));
        }
    } else {
        const bool ht = d.kind == PEND_HT;
        const int hi = (c.lane >> 3) & 1;
        const uint32_t base = c.sb + S_STG + c.wg * 16384 + ((ht ? hi * 32 + c.wq * 8 : c.wq * 16 + hi * 8) + (c.lane & 7)) * 128;
        staging_wait(c);
#pragma unroll
        for (int j = 0; j < 8; j++) {
            const int ch = (j & 3) * 2 + (c.lane >> 4);
            stsm4(base + (j >> 2) * 8192 + ((ch ^ (c.lane & 7)) << 4), pk[j * 4], pk[j * 4 + 1], pk[j * 4 + 2], pk[j * 4 + 3]);
        }
        fence_async_smem();
        staging_post(c, d.kind, d.row, d.col, (d.col & 128) ? d.cnt : -1);
    }
    if (d.col & 128) d.kind = PEND_NONE;
    d.col += 128;
#pragma unroll
    for (int i = 0; i < 32; i++) d.pk[i] = d.pk[32 + i];
}

constexpr int S_STG2 = 8 * 20480, PEND_BOTH = 8;
__device__ __forceinline__ void drain_both(Cons& c, const Pend& d) {
    const uint32_t base = c.sb + c.wg * 16384 + (c.wq * 16 + ((c.lane >> 3) & 1) * 8 + (c.lane & 7)) * 128;
#pragma unroll
    for (int j = 0; j < 16; j++)
        stsm4(base + (j < 8 ? S_STG : S_STG2) + (j >> 2 & 1) * 8192 + ((((j & 3) * 2 + (c.lane >> 4)) ^ (c.lane & 7)) << 4), d.pk[j * 4], d.pk[j * 4 + 1], d.pk[j * 4 + 2], d.pk[j * 4 + 3]);
    fence_async_smem();
    staging_post(c, PEND_KVO | PEND_BOTH, d.row, d.col, d.cnt);
}

__device__ __forceinline__ void store_warp(const Params& P, uint32_t sb, int wg, int cta) {
    if (cta < 128) {
        for (int i = 0; i < P.xd; i++) __nanosleep(1000);
        const uint32_t e1 = get_epoch(sb) + 1;
        const uint4* x = (const uint4*)P.Bx + (cta * 2 + wg) * 1024 + (threadIdx.x & 31);
        uint32_t m = 0;
#pragma unroll 4
        for (int i = 0; i < 32; i++) { const uint4 u = __ldg(x + i * 32); m = amax(amax(m, amax(u.x, u.y)), amax(u.z, u.w)); }
        m = warp_exp(m);
        if (elect_one()) { atomicMax(&g_cnt(C_XMAX), e1 << 8 | m); red_release(&g_cnt(C_XCNT)); }
        __syncwarp();
    }
    const uint32_t stg = sb + S_STG + wg * 16384;
#pragma unroll 1
    for (uint32_t n = 0;; n++) {
        mbar_wait(sb + B_SFULL + wg * 8, n & 1);
        uint32_t x[4];
        lds128(x, sb + S_DESC + wg * 16);
#pragma unroll
        for (int i = 0; i < 4; i++) x[i] = __shfl_sync(0xffffffffu, x[i], 0);
        if (x[0] == PEND_NONE) break;
        const bool ht = x[0] == PEND_HT;
        const CUtensorMap* m = &P.tm[ht ? M_HTS : M_KVO];
        const uint64_t pol = P.pol[ht ? 2 : x[1] >= 4096 ? 1 : (x[1] & 2047) < 1536 ? 0 : 10];
        if (elect_one()) {
#pragma unroll
            for (int i = 0; i < 4; i++) tma_store2d(m, x[2] + (i >> 1) * 64, x[1] + (i & 1) * (ht ? 1024 : 32), stg + i * 4096, pol);
            if (x[0] & PEND_BOTH) {
#pragma unroll 1
                for (int i = 0; i < 4; i++) tma_store2d(m, x[2] + 128 + (i >> 1) * 64, x[1] + (i & 1) * 32, stg + (S_STG2 - S_STG) + i * 4096, pol);
            }
            bulk_commit();
            bulk_wait_read();
            mbar_arrive(sb + B_SFREE + wg * 8);
            if ((int)x[3] >= 0) { bulk_wait_all(); fence_async(); red_relaxed(&g_cnt(x[3])); }
        }
        __syncwarp();
    }
}

template <int TA, int TB, bool FIRST>
__device__ __forceinline__ void issue_ktile(float* acc, const Cons& c) {
    const uint32_t a = c.sb + c.p.stage * STAGE + c.wg * 8192, b = c.sb + c.p.stage * STAGE + 16384;
    const uint64_t da = mkdesc(a, TA ? 8192 : 16, 1024, 1), db = mkdesc(b, TB ? 8192 : 16, 1024, 1);
    wg_fence();
#pragma unroll
    for (int k = 0; k < 4; k++) {
        if (FIRST && k == 0) wgmma_ss256_first<TA, TB>(acc, da, db);
        else wgmma_ss256<TA, TB>(acc, da + (TA ? 128 : 2) * k, db + (TB ? 128 : 2) * k);
    }
    wg_commit();
}
template <bool KVONLY, bool FIRST>
__device__ __forceinline__ void issue_any(float* acc, const Cons& c, int type) {
    wait_full(c);
    if (!KVONLY && type == T_A1) issue_ktile<0, 0, FIRST>(acc, c);
    else if (!KVONLY && type == T_A2) issue_ktile<1, 0, FIRST>(acc, c);
    else issue_ktile<0, 1, FIRST>(acc, c);
}
template <bool KVONLY = false>
__device__ __forceinline__ void mainloop(float* acc, const Params& P, Cons& c, Pend& d, int type, int nk) {
    issue_any<KVONLY, true>(acc, c, type);
    if (!KVONLY) { IP(0) }
    uint32_t prev = c.p.stage;
    pipe_next(c.p);
#pragma unroll 1
    for (int kt = 1; kt < nk; kt++) {
        if (!KVONLY && d.kind != PEND_NONE && kt != 2) drain(P, c, d);
        issue_any<KVONLY, false>(acc, c, type);
        wg_wait<1>();
        release(c, prev);
        prev = c.p.stage;
        pipe_next(c.p);
    }
    d.kind = PEND_NONE;
    wg_wait<0>();
    pin<128>(acc);
    release(c, prev);
    if (!KVONLY) { IP(1) }
}
__device__ __forceinline__ void pack_half(uint32_t* pk, const float* a) {
#pragma unroll
    for (int i = 0; i < 32; i++) pk[i] = pack2(a[2 * i], a[2 * i + 1]);
}

__device__ __forceinline__ void epi_kv(const float* acc, const Cons& c, Pend& d, int mb, int nb) {
    pack_half(d.pk, acc); pack_half(d.pk + 32, acc + 64);
    d.kind = PEND_KVO; d.row = (nb >> 4) * 2048 + mb * 256 + c.rank * 128 + c.wg * 64; d.col = (nb & 15) * 256; d.cnt = C_KV + mb;
}

__device__ __forceinline__ void qa_scores(float* S, float* Sm, const uint32_t* q, Cons& c) {
    wait_full(c);
    const uint32_t st = c.sb + c.p.stage * STAGE;
    const uint64_t dk = mkdesc(st + c.wg * 8192, 16, 1024, 1), dm = mkdesc(st + 32768 + c.wg * 4096, 128, 2048, 0);
    wg_fence();
#pragma unroll
    for (int i = 0; i < 8; i++) wgmma_rs64<0>(S, q + i * 4, dk + (i >> 2) * 1024 + (i & 3) * 2, i != 0);
#pragma unroll
    for (int i = 0; i < 8; i++) wgmma_rs16<0>(Sm, q + i * 4, dm + i * 16, i != 0);
    wg_commit();
    pipe_next(c.p);
}
__device__ __forceinline__ void qa_softmax(uint32_t (*pa)[4], const float* S, const float* Sm, const Cons& c) {
    const int t = c.lane & 3, i0 = (c.wq & 1) * 16 + (c.lane >> 2) - 2 * t;
    const bool sg = c.wq >= 2;
    const float cs = 0.08838834764831845f * 1.4426950408889634f;
    float x[2][10];
#pragma unroll
    for (int r = 0; r < 2; r++) {
#pragma unroll
        for (int j = 0; j < 4; j++)
#pragma unroll
            for (int e = 0; e < 2; e++) {
                const float v = sg ? S[16 + j * 4 + r * 2 + e] : S[j * 4 + r * 2 + e];
                x[r][j * 2 + e] = (j * 8 + e - r * 8 > i0) ? -1e9f / 0.08838834764831845f : v;
            }
        x[r][8] = sg ? Sm[4 + r * 2] : Sm[r * 2];
        x[r][9] = sg ? Sm[5 + r * 2] : Sm[1 + r * 2];
        float m = fmaxf(fmaxf(fmaxf(fmaxf(x[r][0], x[r][1]), fmaxf(x[r][2], x[r][3])), fmaxf(fmaxf(x[r][4], x[r][5]), fmaxf(x[r][6], x[r][7]))), fmaxf(x[r][8], x[r][9]));
        m = fmaxf(m, __shfl_xor_sync(0xffffffffu, m, 1));
        m = fmaxf(m, __shfl_xor_sync(0xffffffffu, m, 2));
        m *= -cs;
#pragma unroll
        for (int i = 0; i < 10; i++) x[r][i] = ex2(fmaf(x[r][i], cs, m));
        float sum = (((x[r][0] + x[r][1]) + (x[r][2] + x[r][3])) + ((x[r][4] + x[r][5]) + (x[r][6] + x[r][7]))) + (x[r][8] + x[r][9]);
        sum += __shfl_xor_sync(0xffffffffu, sum, 1);
        sum += __shfl_xor_sync(0xffffffffu, sum, 2);
        const float inv = rcp(sum);
#pragma unroll
        for (int i = 0; i < 10; i++) x[r][i] *= inv;
    }
#pragma unroll
    for (int ks = 0; ks < 2; ks++)
#pragma unroll
        for (int i = 0; i < 4; i++) {
            const uint32_t p = pack2(x[i & 1][ks * 4 + (i >> 1) * 2], x[i & 1][ks * 4 + (i >> 1) * 2 + 1]);
            pa[ks][i] = sg ? 0u : p;
            pa[2 + ks][i] = sg ? p : 0u;
        }
#pragma unroll
    for (int r = 0; r < 2; r++) {
        const uint32_t p = pack2(x[r][8], x[r][9]);
        pa[4][r] = sg ? 0u : p;
        pa[4][2 + r] = sg ? p : 0u;
    }
}
__device__ __forceinline__ void qa_values(float* O, uint32_t (*pa)[4], Cons& c) {
    wait_full(c);
    const uint32_t st = c.sb + c.p.stage * STAGE;
    const uint64_t dv = mkdesc(st + c.wg * 8192, 16384, 1024, 1), dm = mkdesc(st + 32768 + c.wg * 4096, 2048, 128, 0);
    pin<20>(&pa[0][0]);
    wg_fence();
#pragma unroll
    for (int ks = 0; ks < 4; ks++) wgmma_rs128<1>(O, pa[ks], dv + ks * 128, ks != 0);
    wgmma_rs128<0>(O, pa[4], dm, 1);
    wg_commit();
    pipe_next(c.p);
}
__device__ __forceinline__ void epi_qa(const float* acc, Cons& c, Pend& d, int mb, int nb) {
    uint32_t q[64], pa[2][5][4];
    float S0[32] = {}, M0[8] = {}, S1[32] = {}, M1[8] = {}, O0[64] = {}, O1[64] = {};
    const uint32_t k0 = c.p.stage;
    pack_half(q, acc);
    pin<32>(q); pin<32>(S0); pin<8>(M0);
    qa_scores(S0, M0, q, c);
    pack_half(q + 32, acc + 64);
    pin<32>(q + 32); pin<32>(S1); pin<8>(M1);
    qa_scores(S1, M1, q + 32, c);
    wg_wait<1>();
    pin<32>(S0); pin<8>(M0);
    release(c, k0);
    qa_softmax(pa[0], S0, M0, c);
    wg_wait<0>();
    pin<32>(S1); pin<8>(M1); pin<64>(q);
    release(c, (k0 + 1) & (NSTAGE - 1));
    pin<64>(O0);
    qa_values(O0, pa[0], c);
    qa_softmax(pa[1], S1, M1, c);
    pin<64>(O1);
    qa_values(O1, pa[1], c);
    wg_wait<1>();
    pin<64>(O0); pin<20>(&pa[0][0][0]);
    release(c, (k0 + 2) & (NSTAGE - 1));
    pack_half(d.pk, O0);
    wg_wait<0>();
    pin<64>(O1); pin<20>(&pa[1][0][0]);
    release(c, (k0 + 3) & (NSTAGE - 1));
    pack_half(d.pk + 32, O1);
    d.kind = PEND_KVO; d.row = 4096 + mb * 256 + c.rank * 128 + c.wg * 64; d.col = nb * 256; d.cnt = C_O + mb * 16 + nb;
}

__device__ __forceinline__ void epi_op(const float* acc, const Cons& c, Pend& d, int mb, int nb) {
    pack_half(d.pk, acc); pack_half(d.pk + 32, acc + 64);
    d.kind = PEND_OUT; d.row = mb * 256 + c.rank * 128 + c.wg * 64; d.col = 1024 + nb * 256;
}

__device__ __forceinline__ void epi_a2(float* acc, const Params& P, Cons& c, int mb, int col0) {
    const int g = c.lane >> 2, t = c.lane & 3;
    const int row = mb * 256 + (g >> 1) * 64 + (c.rank * 16 + c.wg * 8 + c.wq * 2) * 2 + (g & 1);
    float* o = P.out + (size_t)row * 2048 + col0 + t * 2;
#pragma unroll 1
    for (int hf = P.zero; hf < 2; hf++) {
    wait_full(c);
    const uint32_t st = c.sb + c.p.stage * STAGE, xa = st + (c.wg * 64 + c.wq * 16 + g) * 128 + t * 4 + (g << 4), da = st + 32768 + t * 4;
#pragma unroll
    for (int j = 0; j < 16; j++) {
        const float* a = acc + j * 4;
        const uint32_t ad = (xa ^ ((j & 7) << 4)) + (j >> 3) * 16384;
        const uint32_t x0 = lds32(ad), x1 = lds32(ad + 1024), dv = lds32(da + j * 16);
        const uint32_t u0 = mul_bf2(x0, dv), u1 = mul_bf2(x1, dv);
        st_stream2(o + j * 8, a[0] + bf_lo(u0), a[1] + bf_hi(u0));
        st_stream2(o + 2 * 2048 + j * 8, a[2] + bf_lo(u1), a[3] + bf_hi(u1));
    }
    __syncwarp();
    release(c, c.p.stage);
    pipe_next(c.p);
    o += 128;
#pragma unroll
    for (int i = 0; i < 64; i++) acc[i] = acc[64 + i];
    }
}

#define TSTAMP(i)
__device__ __forceinline__ float2 cmul(float2 a, float2 b) { return make_float2(fmaf(a.x, b.x, -a.y * b.y), fmaf(a.x, b.y, a.y * b.x)); }
__device__ __forceinline__ float2 cfma(float2 a, float2 b, float2 u) { return make_float2(fmaf(a.x, b.x, fmaf(-a.y, b.y, u.x)), fmaf(a.x, b.y, fmaf(a.y, b.x, u.y))); }
__device__ __forceinline__ float4 ssm_coef(float lre, float lim, float logdt) {
    const float dt = __bfloat162float(__float2bfloat16(expf(logdt)));
    const float ea = expf(dt * lre);
    float sn, cn;
    sincosf(dt * lim, &sn, &cn);
    const float br = ea * cn, bi = ea * sn, nr = br - 1.f;
    const bool sw = fabsf(lre) < fabsf(lim);
    const float big = sw ? lim : lre, r = __fdividef(sw ? lre : lim, big), inv = __fdividef(1.f, fmaf(sw ? lre : lim, r, big));
    const float cr = (sw ? fmaf(nr, r, bi) : fmaf(bi, r, nr)) * inv, ci = (sw ? fmaf(bi, r, -nr) : fmaf(-nr, r, bi)) * inv;
    return make_float4(br, bi, cr, ci);
}
__device__ __forceinline__ void epi_a1(const float* acc, const Params& P, const Cons& c, Pend& d, int mb, int nb) {
    const uint32_t atag = (get_epoch(c.sb) + 1) & 1;
    const int t = c.lane & 3;
    const int p = nb * 128 + c.rank * 64 + c.wg * 32 + c.wq * 8 + (c.lane >> 2);
    const float4 cf = __ldcg(&g_coef[p]);
    const float2 lam = make_float2(cf.x, P.swap_ri ? -cf.y : cf.y);
    const float a0 = P.swap_ri ? -2.f * cf.w : 2.f * cf.z, a1 = P.swap_ri ? 2.f * cf.z : -2.f * cf.w;
    const float b0 = P.swap_ri ? -2.f * cf.z : -2.f * cf.w, b1 = P.swap_ri ? -2.f * cf.w : -2.f * cf.z;
    float2 h = make_float2(0.f, 0.f);
#pragma unroll
    for (int round = 0; round < 2; round++) {
#pragma unroll
        for (int j = 0; j < 32; j++) {
            h = cfma(lam, h, make_float2(acc[j * 4], acc[j * 4 + 2]));
            const float r0 = fmaf(a0, h.x, a1 * h.y), m0 = fmaf(b0, h.x, b1 * h.y);
            h = cfma(lam, h, make_float2(acc[j * 4 + 1], acc[j * 4 + 3]));
            d.pk[j * 2] = pack2(r0, fmaf(a0, h.x, a1 * h.y));
            d.pk[j * 2 + 1] = pack2(m0, fmaf(b0, h.x, b1 * h.y));
        }
        if (round) break;
        float2 l64 = lam;
#pragma unroll
        for (int i = 0; i < 6; i++) l64 = cmul(l64, l64);
        const float2 l128 = cmul(l64, l64), l256 = cmul(l128, l128);
        float2 o = make_float2(__shfl_up_sync(0xffffffffu, h.x, 1), __shfl_up_sync(0xffffffffu, h.y, 1));
        if (t >= 1) h = cfma(l64, o, h);
        o = make_float2(__shfl_up_sync(0xffffffffu, h.x, 2), __shfl_up_sync(0xffffffffu, h.y, 2));
        if (t >= 2) h = cfma(l128, o, h);
        IP(2)
        if (t == 3) st_relaxed2(&g_agg[mb * 1024 + p], (__float_as_uint(h.x) & ~1u) | atag, __float_as_uint(h.y));
        h = make_float2(__shfl_up_sync(0xffffffffu, h.x, 1), __shfl_up_sync(0xffffffffu, h.y, 1));
        if (t == 0) h = make_float2(0.f, 0.f);
        uint32_t ax[7], ay[7];
        while (true) {
            uint32_t bad = 0;
#pragma unroll
            for (int j = 0; j < 7; j++) { ax[j] = atag; ay[j] = 0; ld_relaxed2_if(ax[j], ay[j], &g_agg[j * 1024 + p], j < mb); }
#pragma unroll
            for (int j = 0; j < 7; j++) bad |= ax[j] ^ atag;
            if (tags_ok(bad)) break;
            __nanosleep(2 * POLLNS);
        }
        float2 carry = make_float2(0.f, 0.f);
#pragma unroll
        for (int j = 0; j < 7; j++) if (j < mb) carry = cfma(l256, carry, make_float2(__uint_as_float(ax[j]), __uint_as_float(ay[j])));
        float2 w = (t & 1) ? l64 : make_float2(1.f, 0.f);
        if (t & 2) w = cmul(w, l128);
        h = cfma(w, carry, h);
        IP(3)
    }
    IP(4)
    d.kind = PEND_HT; d.row = nb * 128 + c.rank * 64 + c.wg * 32; d.col = mb * 256; d.cnt = C_HT + mb * 16 + nb;
}

__device__ __forceinline__ uint32_t fresh_tid() { uint32_t t; asm volatile("mov.u32 %0, %%tid.x;" : "=r"(t)); return t; }
__device__ __forceinline__ uint32_t acquire_stage(uint32_t sb, Pipe& p, uint32_t bytes) {
    mbar_wait(sb + B_EMPTY + p.stage * 8, p.phase ^ 1);
    mbar_expect_e(sb + B_FULL + p.stage * 8, bytes);
    return p.stage;
}
__device__ __forceinline__ void producer(const Params& P, const uint32_t sb, const int cta) {
    Pipe p = {0, 0};
    uint32_t resume = 1;
    const int rank = cta & 1;
    const uint16_t both = 3 << (__shfl_sync(0xffffffffu, cluster_rank(), 0) & ~1u);
    for (int it = ITEM_OFF(cta >> 1), item = 0; !(item & LAST); it++) {
        item = ITEM(it);
        const int type = (item >> 8) & 7, mb = (item >> 5) & 7, nb = item & 31, half = item >> 12 & 1, hw = item >> 13 & 1;
        const uint32_t epoch = type ? get_epoch(sb) : 0, e1 = epoch + 1;
        if (type == T_CHAIN) {
            const int h = cta / 3, role = cta - h * 3;
#pragma unroll 1
            for (int w = 0; w < 8; w++) {
                mbar_wait(sb + B_EMPTY + (w * 20480 + 20479) / STAGE * 8, 1);
                chain_load(P, sb, cta, w, threadIdx.x & 31, 0);
            }
            uint32_t* flag = &g_cnt(C_FLAG + (role == 2 ? 32 : 0) + h);
            if (role) { wait_count(&g_cnt(C_KV), e1 * 128); fence_async(); }
#pragma unroll 1
            for (int s = 0; s < 64 && role != 0; s++) {
                if (s < 63) {
                    mbar_wait(sb + B_GO, s & 1);
                    tma3d_mc_e(sb + S_KV + (role - 1) * 8192, &P.tm[M_SEG], 0, (role - 1) * 2048 + s * 32, h * 2, sb + B_KVFULL, 7 << ((h & 1) * 3), P.pol[s < 48 ? 8 : 11]);
                    if ((s & 7) == 7) { wait_count(&g_cnt(C_KV + 1 + (s >> 3)), e1 * 128); fence_async(); }
                    tma_prefetch3d_e(&P.tm[M_SEG], 0, (role - 1) * 2048 + s * 32 + 32, h * 2);
                }
                if (s > 0 && ((s & 3) == 0 || s == 63)) {
                    const int i = (s - 1) >> 2;
                    mbar_wait(sb + B_PERS, i & 1);
                    asm volatile("{\n.reg .pred E;\nelect.sync _|E, 0xffffffff;\n@E st.release.gpu.global.u32 [%0], %1;\n}" ::"l"(flag), "r"(epoch * 64 + i * 4 + 4) : "memory");
                }
            }
            if (role == 0) {
                const int lane = threadIdx.x & 31;
                if (lane == 0) mbar_arrive(sb + B_RELM);
#pragma unroll 1
                for (int s = 0; s < 63; s++) {
                    mbar_wait(sb + B_P1, s & 1);
                    if (s > 0) {
                        st_relaxed4(P.xb + xg_buf(s - 1) + h * 2048 + xg_lane(lane), 0, 0, 0, 0);
                        st_relaxed1(P.xb + xg_buf(s - 1) + xg_side(h) + lane * 4, 0);
                        __threadfence();
                    }
                    __syncwarp();
                    if (lane == 0) mbar_arrive(sb + B_RELM);
                }
            }
            if ((threadIdx.x & 31) < M_C1 - 1) asm volatile("prefetch.tensormap [%0];" ::"l"(&P.tm[1 + (threadIdx.x & 31)]) : "memory");
            resume = 0;
            continue;
        }
        const int m0 = mb * 256 + rank * 128, ssm = type >= T_A1;
        const CUtensorMap* ma = &P.tm[max(type, 1) + half * M_HALF];
        const CUtensorMap* mw = &P.tm[type ? M_WV + type : M_WK + (nb >> 4)];
        const int nk = type == T_OP ? 64 : type == T_A2 ? 32 : 16;
        const int a3 = type == T_A1 ? nb * 16 + rank * 8 + hw * 4 : type == T_A2 ? mb * 4 + rank * 2 + hw : (type == T_OP ? 4096 : 0) + m0 + hw * 64;
        const int b3 = type == T_A1 ? mb * 128 + rank * 16 : type == T_A2 ? (nb * 2 + rank) * 128 : (nb & 15) * 4 + rank * 2;
        if (type & 1) {
            wait_count(&g_cnt(type == T_A1 ? C_COEF : C_KV + mb), e1 * (type == T_A1 ? 4 : 128));
            fence_async();
        }
        uint32_t ready = type == T_OP || type == T_A2 ? 0 : ~0u;
        if (type == T_A1) l2_prefetch_e(g_coef + nb * 128 + rank * 64, 1024);
        auto arrived = [&]() {
            const uint32_t t = fresh_tid();
            return __all_sync(0xffffffffu, (int32_t)(ld_acquire(&g_cnt(C_FLAG + (t & 2) * 16 + nb * 2 + (t & 1))) - (epoch * 64 + mb * 8 + rank * 4 + 4)) >= 0);
        };
        bool passed = false;
        mbar_wait(sb + B_RESUME, resume);
#pragma unroll 1
        for (int kt = 0; kt < nk; kt++) {
            if (type == T_QA && kt == 9) passed = arrived();
            while (~ready & (ssm ? 2 | 1 << ((kt & 15) >> 1) : 1 << (kt >> 2))) {
                if (ready) __nanosleep(POLLNS);
                ready = __ballot_sync(0xffffffffu, (int32_t)(ld_acquire(&g_cnt(type * 64 + mb * 16 + (fresh_tid() & 15))) - e1 * 4) >= 0) | 1u << 31;
                fence_async();
            }
            const uint32_t st = acquire_stage(sb, p, STAGE - half * 8192), bar = sb + B_FULL + st * 8;
            const int a1 = type == T_A2 ? kt * 64 : 0, b0 = ssm ? (kt & 15) * 64 : 0;
            tma4d_e(sb + st * STAGE + hw * 8192, ma, kt * 64 - a1, a1, a3, bar, P.pol[11]);
            tma4d_mc_e(sb + st * STAGE + 16384 + rank * 16384, mw + (ssm & kt >> 4), b0, ssm ? 0 : kt * 64, b3, bar, both, P.pol[(item & 0x7e0) == 224 ? 9 : 11]);
            if (type == T_QA && kt < 8) tma_prefetch4d_e(&P.tm[M_OA], nb * 256 + (kt & 3) * 64, (kt >> 2) * 2048 + m0);
            pipe_next(p);
        }
        if (type == T_QA) {
            while (!passed) { passed = arrived(); if (!passed) __nanosleep(POLLNS); }
            fence_async();
        }
        const int q = type == T_QA;
#pragma unroll 1
        for (int e = 0; e < (q ? 4 : type == T_A2 ? 2 : 0); e++) {
            const uint32_t st = acquire_stage(sb, p, q ? 40960 : 32768 + 256), bar = sb + B_FULL + st * 8, dst = sb + st * STAGE;
#pragma unroll 1
            for (int i = 0; i < 2; i++) tma4d_e(dst + i * 16384, &P.tm[q ? M_OA : M_AX], nb * 256 + (e & 1) * 128 + i * 64, 0, q ? (e >> 1) * 2048 + m0 : mb * 128 + rank * 16, bar, P.pol[q ? 3 : 11]);
            const uint8_t* src = q ? (const uint8_t*)(((e >> 1) ? g_vmt : g_km) + ((mb * 8 + rank * 4) * 32 + nb * 2 + (e & 1)) * 512) : (const uint8_t*)(P.Dskip + nb * 256 + e * 128);
#pragma unroll 1
            for (int i = 0; i < (q ? 4 : 1); i++) bulk_g2s_e(dst + 32768 + i * 2048, src + i * 65536, q ? 2048 : 256, bar);
            pipe_next(p);
        }
    }
#pragma unroll 1
    for (int i = 0; i < NSTAGE; i++) { mbar_wait(sb + B_EMPTY + p.stage * 8, p.phase ^ 1); pipe_next(p); }
}

__device__ __forceinline__ uint32_t fresh_ctaid() { uint32_t t; asm volatile("mov.u32 %0, %%ctaid.x;" : "=r"(t)); return t; }
__device__ __forceinline__ void reset_state(const Params& P, Cons& c, Pend& d, uint32_t sb, bool resumed) {
    const uint32_t t = fresh_tid(), b = fresh_ctaid() + P.cta0;
    const int w = __shfl_sync(0xffffffffu, t >> 5, 0);
    c.sb = sb; c.wg = w >> 2; c.wq = w & 3; c.lane = t & 31;
    c.rank = __shfl_sync(0xffffffffu, b & 1, 0); c.pair = __shfl_sync(0xffffffffu, b >> 1, 0);
    c.rel = mapa(sb + B_EMPTY, cluster_rank() ^ (c.lane & 1));
    c.p.stage = 0; c.p.phase = 0;
    c.nst = resumed && c.pair < NCHAIN;
    d = Pend{};
}
#define PROF_ITEM(i, item)

__global__ void __launch_bounds__(384, 1) fused_kernel(const __grid_constant__ Params P) {
    extern __shared__ __align__(1024) uint8_t smem[];
    const uint32_t sb = smem_u32(smem);
    asm volatile("griddepcontrol.launch_dependents;");
    declare_fence(P.zero);
    const int tid = threadIdx.x, lane = tid & 31;
    const int warp = __shfl_sync(0xffffffffu, tid >> 5, 0);
    const int cta = __shfl_sync(0xffffffffu, blockIdx.x + P.cta0, 0), pair = cta >> 1, rank = cta & 1;
    if (tid == 0) {
        if (sb & 1023) spin_fault();
        for (int i = 0; i < NSTAGE; i++) { mbar_init(sb + B_FULL + i * 8, 1); mbar_init(sb + B_EMPTY + i * 8, 16); }
        mbar_init(sb + B_RESUME, 2);
        mbar_init(sb + B_KVFULL, 1);
        mbar_init(sb + B_GO, 3); mbar_init(sb + B_RED, 8); mbar_init(sb + B_P1, 1); mbar_init(sb + B_EPOCH, 1); mbar_init(sb + B_PERS, 8); mbar_init(sb + B_INIT, 8); mbar_init(sb + B_INIT2, 8);
        mbar_init(sb + B_READY, 8);
        for (int i = 0; i < 2; i++) { mbar_init(sb + B_SFULL + i * 8, 4); mbar_init(sb + B_SFREE + i * 8, 1); }
        mbar_init(sb + B_RELM, cta % 3 ? 1 : 2); mbar_init(sb + B_X, 9);
        mbar_init(sb + B_DONE, 2);
        mbar_expect(sb + B_X, 4096);
        sts64(sb + S_EV, 0, 0);
        asm volatile("fence.mbarrier_init.release.cluster;" ::: "memory");
    }
    __syncthreads();
    cluster_sync();
    if (warp >= 8) {
        asm volatile("setmaxnreg.dec.sync.aligned.u32 24;");
        if (warp == 8) {
            producer(P, sb, cta);
        } else if (warp == 9) {
            const uint32_t epoch = __shfl_sync(0xffffffffu, ld_acquire(&g_cnt(C_EPOCH)), 0);
            if (lane == 0) { sts32(sb + S_EPOCH, epoch); mbar_arrive(sb + B_EPOCH); red_release(&g_cnt(C_READ)); }
            __syncwarp();
            if (pair < NCHAIN) pacer(P, sb, cta, lane, epoch);
            if (cta == 0 && lane == 0) {
                for (int n = 0; (int32_t)(ld_acquire(&g_cnt(C_READ)) - (epoch + 1) * (NPAIR * 2)) < 0; n++) if (n > SPIN_LIMIT) spin_fault();
                st_relaxed1(&g_cnt(C_EPOCH), epoch + 1);
            }
            __syncwarp();
            mbar_wait_bounded(sb + B_DONE, 0);
        } else {
            store_warp(P, sb, warp - 10, cta);
        }
    } else {
        asm volatile("setmaxnreg.inc.sync.aligned.u32 240;");
        Cons c;
        Pend d;
        if (pair < NCHAIN) {
            reset_state(P, c, d, sb, false);
            {
                const int item = ITEM(ITEM_OFF(pair));
                PROF_ITEM(0, item)
                float acc[128];
                mainloop<true>(acc, P, c, d, T_KV, 16);
                ISTAMP(4)
                epi_kv(acc, c, d, (item >> 5) & 7, item & 31);
            }
            ISTAMP(9)
            mbar_wait(sb + B_EMPTY + 3 * 8, 1);
            drain_both(c, d);
            ISTAMP(10)
            uint32_t wr[40][4];
            chain_fetch(P, sb, cta, warp, lane, wr);
            PROF_ITEM(1, T_CHAIN << 8)
            chain_bounds(sb, cta, warp, lane, wr);
            ISTAMP(11)
            if (warp < 4) chain_role<false>(P, sb, cta, warp, lane, wr);
            else chain_role<true>(P, sb, cta, warp, lane, wr);
            fence_async_smem();
            bar_sync(1, 256);
            const uint32_t t2 = fresh_tid();
            if (t2 < 2) mbar_arrive_cluster(mapa(sb + B_RESUME, cluster_rank() ^ t2));
        } else if (pair >= NPAIR - 2) {
            const int ch = (pair - (NPAIR - 2)) * 512 + rank * 256 + tid;
            g_coef[ch] = ssm_coef(__bfloat162float(P.Lre[ch]), __bfloat162float(P.Lim[ch]), __bfloat162float(P.logdt[ch]));
            bar_sync(1, 256);
            if (tid == 0) red_release(&g_cnt(C_COEF));
        }
        reset_state(P, c, d, sb, true);
        int it = ITEM_OFF(c.pair) + (c.pair < NCHAIN ? 2 : 0);
        for (int prev = c.pair < NCHAIN ? ITEM(it - 1) : 0;; prev = ITEM(it++)) {
            const bool last = prev & LAST;
            const int item = ITEM(it), type = (item >> 8) & 7, mb = (item >> 5) & 7, nb = item & 31;
            const bool idle = (item >> 12 & 3) == 3 - 2 * c.wg;
            if (d.kind != PEND_NONE && ((prev & (LAST | URGENT)) || idle || (type != T_KV && !bar_and(5 + c.wg, mbar_try(sb + B_FULL + c.p.stage * 8, c.p.phase))))) {
#pragma unroll 1
                while (d.kind != PEND_NONE) drain(P, c, d);
            }
            if (last) break;
            const int nk = type == T_OP ? 64 : type == T_A2 ? 32 : 16;
            PROF_ITEM(it - ITEM_OFF(c.pair), item)
            if (idle) {
#pragma unroll 1
                for (int kt = nk + (type == T_A2 ? 2 : type == T_QA ? 4 : 0); kt > 0; kt--) { wait_full(c); release(c, c.p.stage); pipe_next(c.p); }
                continue;
            }
            float acc[128];
            mainloop(acc, P, c, d, type, nk);
            if (type == T_KV) epi_kv(acc, c, d, mb, nb);
            else if (type == T_QA) epi_qa(acc, c, d, mb, nb);
            else if (type == T_OP) epi_op(acc, c, d, mb, nb);
            else if (type == T_A1) epi_a1(acc, P, c, d, mb, nb);
            else epi_a2(acc, P, c, mb, nb * 256);
        }
        staging_wait(c);
        staging_post(c, PEND_NONE, 0, 0, 0);
        if (c.wq == 0 && c.lane == 0) mbar_arrive(sb + B_DONE);
    }
}

typedef CUresult (*EncodeFn)(CUtensorMap*, CUtensorMapDataType, cuuint32_t, void*, const cuuint64_t*, const cuuint64_t*, const cuuint32_t*, const cuuint32_t*,
                             CUtensorMapInterleave, CUtensorMapSwizzle, CUtensorMapL2promotion, CUtensorMapFloatOOBfill);
void encode(EncodeFn fn, CUtensorMap* m, const void* base, int rank, const uint64_t* dims, const uint64_t* strides, const uint32_t* box, CUtensorMapSwizzle swz = CU_TENSOR_MAP_SWIZZLE_128B) {
    cuuint64_t d[5], s[5]; cuuint32_t b[5], e[5];
    for (int i = 0; i < rank; i++) { d[i] = dims[i]; b[i] = box[i]; e[i] = 1; if (i) s[i - 1] = strides[i - 1]; }
    fn(m, CU_TENSOR_MAP_DATA_TYPE_BFLOAT16, rank, (void*)base, d, s, b, e, CU_TENSOR_MAP_INTERLEAVE_NONE, swz,
       CU_TENSOR_MAP_L2_PROMOTION_L2_256B, CU_TENSOR_MAP_FLOAT_OOB_FILL_NONE);
}
void map_kmajor(EncodeFn fn, CUtensorMap* m, const void* base, uint64_t rows, uint64_t cols, uint32_t box_rows) {
    const uint64_t d[4] = {cols, 1, 1, rows}, s[3] = {cols * 2, cols * 2, cols * 2}; const uint32_t b[4] = {64, 1, 1, box_rows};
    encode(fn, m, base, 4, d, s, b);
}
void map_mnmajor(EncodeFn fn, CUtensorMap* m, const void* base, uint64_t krows, uint64_t cols, uint32_t groups = 2) {
    const uint64_t d[4] = {64, krows, 1, cols / 64}, s[3] = {cols * 2, 128, 128}; const uint32_t b[4] = {64, 64, 1, groups};
    encode(fn, m, base, 4, d, s, b);
}
void map_store(EncodeFn fn, CUtensorMap* m, const void* base, uint64_t rows, uint64_t cols) {
    const uint64_t d[2] = {cols, rows}, s[1] = {cols * 2}; const uint32_t b[2] = {64, 32};
    encode(fn, m, base, 2, d, s, b);
}

}

extern "C" void kernel_launch(void* const* d_in, const int* in_sizes, int n_in, void* d_out, int out_size) {
    static Params P;
    static EncodeFn fn = nullptr;
    if (!fn) {
        cudaDriverEntryPointQueryResult q;
        cudaGetDriverEntryPoint("cuTensorMapEncodeTiled", (void**)&fn, cudaEnableDefault, &q);
        cudaFuncSetAttribute(fused_kernel, cudaFuncAttributeMaxDynamicSharedMemorySize, S_TOTAL);
    }
    const bf16* in[15];
    for (int i = 0; i < 15; i++) in[i] = (const bf16*)d_in[i];
    void *kvo, *ht;
    cudaGetSymbolAddress(&kvo, g_kvo);
    cudaGetSymbolAddress(&ht, g_ht);
    map_kmajor(fn, &P.tm[M_BX], in[9], 2048, 1024, 128);
    map_mnmajor(fn, &P.tm[M_WQ], in[11], 1024, 4096);
    map_mnmajor(fn, &P.tm[M_WK], in[12], 1024, 4096);
    map_mnmajor(fn, &P.tm[M_WV], in[13], 1024, 4096);
    map_mnmajor(fn, &P.tm[M_WO], in[14], 4096, 1024);
    map_kmajor(fn, &P.tm[M_OA], kvo, 3 * 2048, 4096, 128);
    P.swap_ri = in[4] < in[3];
    {
        const bf16* lo = P.swap_ri ? in[4] : in[3];
        const uint64_t diff = (uint64_t)((const char*)(P.swap_ri ? in[3] : in[4]) - (const char*)lo);
        const uint64_t d[4] = {1024, 8, 2, 128}, s[3] = {2048, diff, 16384}; const uint32_t b[4] = {64, 8, 2, 8}, bh[4] = {64, 8, 2, 4};
        encode(fn, &P.tm[M_AB], lo, 4, d, s, b);
        encode(fn, &P.tm[M_AB + M_HALF], lo, 4, d, s, bh);
    }
    {
        const uint64_t d[4] = {1024, 2, 4, 1024}, s[3] = {2048, 64 * 2048, 4096}; const uint32_t b[4] = {64, 2, 4, 16};
        encode(fn, &P.tm[M_AX], in[0], 4, d, s, b);
    }
    map_mnmajor(fn, &P.tm[M_HT], ht, 2048, 2048);
    map_kmajor(fn, &P.tm[M_CRE], in[5], 1024, 1024, 128);
    map_kmajor(fn, &P.tm[M_CIM], in[6], 1024, 1024, 128);
    map_store(fn, &P.tm[M_KVO], kvo, 3 * 2048, 4096);
    map_store(fn, &P.tm[M_HTS], ht, 2048, 2048);
    map_kmajor(fn, &P.tm[M_BX + M_HALF], in[9], 2048, 1024, 64);
    map_kmajor(fn, &P.tm[M_OA + M_HALF], kvo, 3 * 2048, 4096, 64);
    map_mnmajor(fn, &P.tm[M_HT + M_HALF], ht, 2048, 2048, 1);
    for (int i = 0; i < 3; i++) {
        const uint64_t d[3] = {64, 1024, 64}, s[2] = {8192, 128}; const uint32_t b[3] = {64, 16, 2};
        encode(fn, &P.tm[M_C1 + i], in[11 + i], 3, d, s, b);
    }
    {
        const uint64_t d[2] = {1024, 4096}, s[1] = {2048}; const uint32_t b[2] = {32, 32};
        encode(fn, &P.tm[M_CO], in[14], 2, d, s, b, CU_TENSOR_MAP_SWIZZLE_64B);
    }
    {
        const uint64_t d[3] = {64, 3 * 2048, 64}, s[2] = {8192, 128}; const uint32_t b[3] = {64, 32, 2};
        encode(fn, &P.tm[M_SEG], kvo, 3, d, s, b);
    }
    void* xs;
    cudaGetSymbolAddress(&xs, g_x);
    P.xb = (uint8_t*)(((uintptr_t)xs + (2u << 20) - 1) & ~(uintptr_t)((2u << 20) - 1));
    P.Wq = in[11]; P.Wk = in[12]; P.Wv = in[13]; P.Wo = in[14]; P.mem0 = in[10]; P.Bx = in[9];
    P.Ax = in[0]; P.Lre = in[1]; P.Lim = in[2]; P.logdt = in[7]; P.Dskip = in[8];
    P.out = (float*)d_out;
    int pv[10] = {1180, 0, 110, 0, 330, 0, 32, 32, 0, 0};
    int ef = 779;
    for (int i = 0; i < 12; i++) P.pol[i] = (ef >> i & 1) ? 0x12F0000000000000ull : 0x1000000000000000ull;
    P.dly = pv[0]; P.mrg = pv[2];
    P.rd = pv[4]; P.guard = pv[5]; P.clampv = pv[6]; P.clamp0 = pv[7]; P.kvd = pv[9]; P.xd = pv[8];
    cudaLaunchConfig_t cfg = {};
    cudaLaunchAttribute at[2];
    cfg.blockDim = dim3(384); cfg.dynamicSmemBytes = S_TOTAL; cfg.stream = cudaStreamPerThread; cfg.attrs = at;
    at[0].id = cudaLaunchAttributeClusterDimension;
    at[0].val.clusterDim.y = at[0].val.clusterDim.z = 1;
    at[1].id = cudaLaunchAttributeProgrammaticStreamSerialization;
    at[1].val.programmaticStreamSerializationAllowed = 1;
    for (int i = 0; i < 2; i++) {
        P.cta0 = i ? 2 * NCHAIN : 0;
        cfg.gridDim = dim3(i ? 2 * (NPAIR - NCHAIN) : 2 * NCHAIN);
        at[0].val.clusterDim.x = i ? 2 : 6;
        cfg.numAttrs = 1 + i;
        cudaLaunchKernelEx(&cfg, fused_kernel, P);
    }
}
```

```cpp
#include <cuda_runtime.h>
#include <cuda_bf16.h>
#include <cuda.h>
#include <stdint.h>
#include <string.h>

typedef __nv_bfloat16 bf16;

namespace {

constexpr int SPIN_LIMIT = 1 << 22;
#define POLLNS 100
constexpr int NPAIR = 66;
constexpr int NCHAIN = 48;
enum { T_KV = 0, T_QA = 1, T_OP = 2, T_A1 = 3, T_A2 = 4, T_CHAIN = 5 };
constexpr int URGENT = 2048;
constexpr int LAST = 16384;
constexpr int HALF = 4096;
enum { M_BX = 1, M_OA, M_AB, M_HT, M_HALF = 4, M_WK = 9, M_WV, M_WQ, M_WO, M_AX, M_CRE, M_CIM, M_KVO, M_HTS, M_C1, M_CO = M_C1 + 3, M_SEG, M_COUNT };
enum { C_KV = 0, C_O = 128, C_HT = 256, C_READ = 24, C_EPOCH = 25, C_COEF = 26, C_XMAX = 27, C_XCNT = 28, C_FLAG = 32 };

struct Params {
    CUtensorMap tm[M_COUNT];
    const bf16 *Wq, *Wk, *Wv, *Wo, *mem0, *Bx, *Ax, *Lre, *Lim, *logdt, *Dskip;
    float* out;
    uint8_t* xb;
    int swap_ri, zero;
    int dly, mrg, rd, guard, clampv, clamp0, kvd, xd;
    uint64_t pol[12];
    uint16_t cta0;
};

__constant__ uint16_t c_off[67] = {0, 4, 8, 14, 20, 26, 32, 38, 43, 48, 53, 58, 63, 68, 73, 78, 83, 88, 93, 97, 101, 105, 109, 113, 117, 121, 125, 129, 133, 137, 141, 145, 149, 153, 157, 161, 165, 169, 173, 177, 181, 185, 189, 193, 197, 201, 205, 209, 213, 233, 253, 273, 293, 313, 333, 353, 373, 393, 412, 431, 450, 469, 488, 507, 526, 545, 564};
__constant__ uint16_t c_items[700] = {
    0, 1280, 512, 21728, 16, 1280, 513, 29920, 32, 1280, 800, 899, 3043, 21729, 1, 1280, 801, 900, 3044, 29921, 17, 1280, 802, 901,
    3045, 21730, 33, 1280, 803, 902, 3046, 29922, 2, 1280, 804, 903, 3047, 21731, 18, 1280, 805, 928, 29923, 34, 1280, 2496, 2913, 17408,
    3, 1280, 2528, 2914, 17409, 19, 1280, 768, 2915, 17410, 35, 1280, 769, 2916, 17411, 4, 1280, 770, 2917, 17440, 20, 1280, 771, 2918,
    17441, 36, 1280, 772, 2919, 17442, 5, 1280, 773, 2944, 17443, 21, 1280, 774, 2945, 17472, 37, 1280, 775, 2946, 17473, 6, 1280, 2497,
    16898, 22, 1280, 2529, 16899, 38, 1280, 2498, 16928, 7, 1280, 2530, 16929, 23, 1280, 2499, 16930, 39, 1280, 2531, 16931, 8, 1280, 2500,
    16960, 24, 1280, 2532, 16961, 40, 1280, 2501, 16962, 9, 1280, 2533, 16963, 25, 1280, 2502, 16992, 41, 1280, 2534, 16993, 10, 1280, 2503,
    16994, 26, 1280, 2535, 16995, 42, 1280, 2504, 17024, 11, 1280, 2536, 17025, 27, 1280, 2505, 17026, 43, 1280, 2537, 17027, 12, 1280, 2506,
    17056, 28, 1280, 2538, 17057, 44, 1280, 2507, 17058, 13, 1280, 2539, 17059, 29, 1280, 2508, 17088, 45, 1280, 2540, 17089, 14, 1280, 2509,
    17090, 30, 1280, 2541, 17091, 46, 1280, 2510, 17120, 15, 1280, 2542, 17121, 31, 1280, 2511, 17122, 47, 1280, 2543, 17123, 48, 66, 84,
    102, 111, 128, 144, 162, 178, 196, 212, 230, 246, 298, 332, 366, 416, 832, 3010, 17539, 49, 67, 85, 103, 112, 129, 145,
    163, 179, 197, 213, 231, 247, 299, 333, 367, 417, 833, 3011, 17568, 50, 68, 86, 104, 113, 130, 146, 164, 180, 198, 214,
    232, 248, 300, 334, 384, 418, 834, 3012, 17569, 51, 69, 87, 105, 114, 131, 147, 165, 181, 199, 215, 233, 249, 301, 335,
    385, 419, 835, 3013, 17570, 52, 70, 88, 106, 115, 132, 148, 166, 182, 200, 216, 234, 250, 302, 352, 386, 420, 836, 3014,
    17571, 53, 71, 89, 107, 116, 133, 149, 167, 183, 201, 217, 235, 251, 303, 353, 387, 421, 837, 3015, 17600, 54, 72, 90,
    108, 117, 134, 150, 168, 184, 202, 218, 236, 252, 320, 354, 388, 422, 838, 3040, 17601, 55, 73, 91, 109, 118, 135, 151,
    169, 185, 203, 219, 237, 253, 321, 355, 389, 423, 839, 3041, 17602, 56, 74, 92, 110, 119, 136, 152, 170, 186, 204, 220,
    238, 254, 322, 356, 390, 424, 864, 3042, 17603, 57, 75, 93, 256, 120, 137, 153, 171, 187, 205, 221, 288, 292, 324, 358,
    392, 426, 2978, 17475, 58, 76, 94, 257, 121, 138, 154, 172, 188, 206, 222, 289, 293, 325, 359, 393, 427, 2979, 17504, 59,
    77, 95, 258, 122, 139, 155, 173, 189, 270, 226, 242, 294, 326, 360, 394, 428, 2980, 17505, 60, 78, 96, 259, 123, 140,
    156, 174, 190, 271, 227, 243, 295, 327, 361, 395, 429, 2981, 17506, 61, 79, 97, 260, 124, 141, 157, 268, 194, 210, 228,
    244, 296, 328, 362, 396, 430, 2982, 17507, 62, 80, 98, 261, 125, 142, 158, 269, 195, 211, 229, 245, 297, 329, 363, 397,
    431, 2983, 17536, 63, 81, 99, 262, 126, 266, 159, 175, 191, 207, 223, 239, 255, 323, 357, 391, 425, 2977, 17474, 64, 82,
    100, 263, 127, 267, 160, 176, 192, 208, 224, 240, 290, 330, 364, 398, 806, 3008, 17537, 65, 83, 101, 264, 265, 143, 161,
    177, 193, 209, 225, 241, 291, 331, 365, 399, 807, 3009, 17538,
};
#define ITEM_OFF(p) c_off[p]
#define ITEM(i) c_items[i]

__device__ __align__(1024) bf16 g_kvo[3 * 2048 * 4096];
__device__ __align__(1024) bf16 g_ht[2048 * 2048];
__device__ __align__(1024) uint8_t g_x[4 << 20];
__device__ __align__(1024) uint32_t g_km[64 * 32 * 512];
__device__ __align__(1024) uint32_t g_vmt[64 * 32 * 512];
__device__ __align__(1024) float2 g_agg[8 * 1024];
__device__ __align__(1024) float4 g_coef[1024];
__device__ __align__(1024) uint32_t g_cntl[384 * 32];
#define g_cnt(i) g_cntl[(i) * 32]
__device__ __align__(1024) uint32_t g_hint[96 * 32];
#define PROF(i)
#define PROFDUMP()
#define PROFP(i)
constexpr int XG_SIDE = 65536, XG_T = 98304;
__device__ __forceinline__ uint32_t xg_buf(int b) { return (b & 1) * 128 + (b & 2) * 256 + (b & 4) * 32768; }
__device__ __forceinline__ uint32_t xg_lane(uint32_t lane) { return (lane >> 4) * 1024 + (lane & 8) * 32 + (lane & 7) * 16; }
__device__ __forceinline__ uint32_t xg_side(int b) { return XG_SIDE + (b >> 1) * 1024 + (b & 1) * 256; }

constexpr int STAGE = 49152, NSTAGE = 4;
constexpr int S_STG = NSTAGE * STAGE;
constexpr int S_BAR = S_STG + 32768;
constexpr int B_FULL = S_BAR, B_EMPTY = S_BAR + 32, B_RESUME = S_BAR + 64, B_KVFULL = S_BAR + 72, B_GO = S_BAR + 88, B_X = S_BAR + 96, B_PERS = S_BAR + 104,
              B_INIT = S_BAR + 112, B_RELM = S_BAR + 120, B_READY = S_BAR + 136, B_SFULL = S_BAR + 144, B_SFREE = S_BAR + 160, S_DESC = S_BAR + 176, B_RED = S_BAR + 216;
constexpr int S_EV = S_BAR + 80, S_EO = S_BAR + 84, B_INIT2 = S_BAR + 128, S_SC = S_BAR + 208, S_ISC = S_EV;
constexpr int S_XV = S_BAR + 256, S_LOG = S_XV + 2048;
constexpr int S_TOTAL = S_LOG + 768;
#define NRA 5
#define NRB 3
constexpr int S_W1 = 0;
constexpr int S_W2 = 4 * 4096 * (16 - NRA - NRB);
constexpr int S_KV = 188416;
constexpr int S_P1 = S_KV + 16384;
constexpr int S_X = S_P1 + 16384;
constexpr int S_SX = S_P1, S_OX = S_P1 + 2048;
constexpr int S_EM = S_X + 4096, S_TO = S_EM + 32, B_DONE = S_BAR + 224, B_P1 = S_BAR + 232, B_EPOCH = S_BAR + 240, S_EPOCH = S_BAR + 248;
static_assert(S_TO + 32 <= S_BAR && S_KV % 1024 == 0 && S_TOTAL <= 232448, "chain smem layout");

template <int V> struct IC { static constexpr int value = V; };
template <int B, int E, typename F> __device__ __forceinline__ void static_for(F&& f) { if constexpr (B < E) { f(IC<B>{}); static_for<B + 1, E>(f); } }
__device__ __forceinline__ uint32_t cluster_rank() { uint32_t r; asm volatile("mov.u32 %0, %%cluster_ctarank;" : "=r"(r)); return r; }
__device__ __forceinline__ void spin_fault() { asm volatile("st.global.u32 [%0], 0;" ::"l"(0ull) : "memory"); }
__device__ __forceinline__ uint32_t smem_u32(const void* p) { return (uint32_t)__cvta_generic_to_shared(p); }
__device__ __forceinline__ uint32_t opq(uint32_t x, int lane) { return __shfl_sync(0xffffffffu, x, lane); }
__device__ __forceinline__ uint32_t mapa(uint32_t a, uint32_t r) { uint32_t d; asm volatile("mapa.shared::cluster.u32 %0, %1, %2;" : "=r"(d) : "r"(a), "r"(r)); return d; }
__device__ __forceinline__ void mma16816(float* d, uint32_t a0, uint32_t a1, uint32_t a2, uint32_t a3, uint32_t b0, uint32_t b1) {
    asm("mma.sync.aligned.m16n8k16.row.col.f32.bf16.bf16.f32 {%0,%1,%2,%3}, {%4,%5,%6,%7}, {%8,%9}, {%0,%1,%2,%3};"
        : "+f"(d[0]), "+f"(d[1]), "+f"(d[2]), "+f"(d[3]) : "r"(a0), "r"(a1), "r"(a2), "r"(a3), "r"(b0), "r"(b1));
}
__device__ __forceinline__ void mma1688(float* d, uint32_t a0, uint32_t a1, uint32_t b0) {
    asm("mma.sync.aligned.m16n8k8.row.col.f32.bf16.bf16.f32 {%0,%1,%2,%3}, {%4,%5}, {%6}, {%0,%1,%2,%3};"
        : "+f"(d[0]), "+f"(d[1]), "+f"(d[2]), "+f"(d[3]) : "r"(a0), "r"(a1), "r"(b0));
}
__device__ __forceinline__ void ldsm4(uint32_t* r, uint32_t a) {
    asm volatile("ldmatrix.sync.aligned.m8n8.x4.shared.b16 {%0,%1,%2,%3}, [%4];" : "=r"(r[0]), "=r"(r[1]), "=r"(r[2]), "=r"(r[3]) : "r"(a));
}
__device__ __forceinline__ void ldsm4t(uint32_t* r, uint32_t a) {
    asm volatile("ldmatrix.sync.aligned.m8n8.x4.trans.shared.b16 {%0,%1,%2,%3}, [%4];" : "=r"(r[0]), "=r"(r[1]), "=r"(r[2]), "=r"(r[3]) : "r"(a));
}
__device__ __forceinline__ void stsm4(uint32_t a, uint32_t r0, uint32_t r1, uint32_t r2, uint32_t r3) {
    asm volatile("stmatrix.sync.aligned.m8n8.x4.shared.b16 [%0], {%1,%2,%3,%4};" ::"r"(a), "r"(r0), "r"(r1), "r"(r2), "r"(r3) : "memory");
}
__device__ __forceinline__ void stsm4t(uint32_t a, uint32_t r0, uint32_t r1, uint32_t r2, uint32_t r3) {
    asm volatile("stmatrix.sync.aligned.m8n8.x4.trans.shared.b16 [%0], {%1,%2,%3,%4};" ::"r"(a), "r"(r0), "r"(r1), "r"(r2), "r"(r3) : "memory");
}
__device__ __forceinline__ uint32_t movm(uint32_t a) { uint32_t d; asm volatile("movmatrix.sync.aligned.m8n8.trans.b16 %0, %1;" : "=r"(d) : "r"(a)); return d; }
__device__ __forceinline__ uint32_t pack2(float lo, float hi) { uint32_t d; asm("cvt.rn.bf16x2.f32 %0, %1, %2;" : "=r"(d) : "f"(hi), "f"(lo)); return d; }
__device__ __forceinline__ uint32_t prmt(uint32_t a, uint32_t b, uint32_t s) { uint32_t d; asm("prmt.b32 %0, %1, %2, %3;" : "=r"(d) : "r"(a), "r"(b), "r"(s)); return d; }
__device__ __forceinline__ uint32_t pack2h(float lo, float hi) { uint32_t d; asm("cvt.rn.f16x2.f32 %0, %1, %2;" : "=r"(d) : "f"(hi), "f"(lo)); return d; }
__device__ __forceinline__ uint32_t h2bf(uint32_t a, uint32_t b) {
    uint32_t d;
    asm("{\n.reg .b16 l, h, u;\n.reg .f32 x, y;\nmov.b32 {l, u}, %1;\ncvt.f32.f16 x, l;\nmov.b32 {u, h}, %2;\ncvt.f32.f16 y, h;\ncvt.rn.bf16x2.f32 %0, y, x;\n}" : "=r"(d) : "r"(a), "r"(b));
    return d;
}
__device__ __forceinline__ void cvt_block(uint32_t* u, uint32_t& x, uint32_t sel) {
    const uint32_t a = prmt(u[0], u[0], sel), b = prmt(u[1], u[1], sel), c = prmt(u[2], u[2], sel), d = prmt(u[3], x, sel);
    x ^= u[3] ^ d;
    u[0] = h2bf(a, a); u[1] = h2bf(b, b); u[2] = h2bf(c, c); u[3] = h2bf(d, d);
}
__device__ __forceinline__ uint32_t amax(uint32_t a, uint32_t b) { uint32_t d; asm("max.xorsign.abs.bf16x2 %0, %1, %2;" : "=r"(d) : "r"(a), "r"(b)); return d; }
__device__ __forceinline__ uint32_t amax4(uint32_t m, const uint32_t* v) { return amax(amax(m, amax(v[0], v[1])), amax(v[2], v[3])); }
__device__ __forceinline__ uint32_t warp_exp(uint32_t m) { return __reduce_max_sync(0xffffffffu, max(m & 0x7f80u, (m >> 16) & 0x7f80u)) >> 7; }
__device__ __forceinline__ void red_max_shared(uint32_t a, uint32_t x) { asm volatile("red.shared.max.u32 [%0], %1;" ::"r"(a), "r"(x) : "memory"); }
__device__ __forceinline__ uint32_t mul_bf2(uint32_t a, uint32_t b) { uint32_t d; asm("mul.rn.bf16x2 %0, %1, %2;" : "=r"(d) : "r"(a), "r"(b)); return d; }
__device__ __forceinline__ float bf_lo(uint32_t u) { return __uint_as_float(u << 16); }
__device__ __forceinline__ float bf_hi(uint32_t u) { return __uint_as_float(u & 0xffff0000u); }
__device__ __forceinline__ float ex2(float x) { float y; asm("ex2.approx.ftz.f32 %0, %1;" : "=f"(y) : "f"(x)); return y; }
__device__ __forceinline__ float rcp(float x) { float y; asm("rcp.approx.ftz.f32 %0, %1;" : "=f"(y) : "f"(x)); return y; }
__device__ __forceinline__ void st_relaxed4(const void* p, uint32_t a, uint32_t b, uint32_t c, uint32_t d) {
    asm volatile("{\n.reg .b128 t;\nmov.b128 t, {%1,%2,%3,%4};\nst.relaxed.gpu.global.b128 [%0], t;\n}" ::"l"(p), "r"(a), "r"(b), "r"(c), "r"(d) : "memory");
}
__device__ __forceinline__ void st_relaxed2(const void* p, uint32_t a, uint32_t b) {
    asm volatile("{\n.reg .b64 t;\nmov.b64 t, {%1,%2};\nst.relaxed.gpu.global.b64 [%0], t;\n}" ::"l"(p), "r"(a), "r"(b) : "memory");
}
__device__ __forceinline__ void ld_relaxed2_if(uint32_t& a, uint32_t& b, const void* p, bool on) {
    asm volatile("{\n.reg .pred P;\n.reg .b64 t;\nsetp.ne.u32 P, %3, 0;\nmov.b64 t, {%0,%1};\n@P ld.relaxed.gpu.global.b64 t, [%2];\nmov.b64 {%0,%1}, t;\n}" : "+r"(a), "+r"(b) : "l"(p), "r"((uint32_t)on) : "memory");
}
__device__ __forceinline__ void ld_relaxed4(uint32_t* v, const void* p) {
    asm volatile("ld.relaxed.gpu.global.L1::no_allocate.v4.b32 {%0,%1,%2,%3}, [%4];" : "=r"(v[0]), "=r"(v[1]), "=r"(v[2]), "=r"(v[3]) : "l"(p) : "memory");
}
__device__ __forceinline__ void ld_relaxed1n(uint32_t& v, const void* p) { asm volatile("ld.relaxed.gpu.global.L1::no_allocate.b32 %0, [%1];" : "=r"(v) : "l"(p) : "memory"); }
__device__ __forceinline__ void red_add4(const void* p, uint32_t a, uint32_t b, uint32_t c, uint32_t d) {
    asm volatile("red.relaxed.gpu.global.add.noftz.v4.f16x2 [%0], {%1,%2,%3,%4};" ::"l"(p), "r"(a), "r"(b), "r"(c), "r"(d) : "memory");
}
__device__ __forceinline__ void red_add1(const void* p, uint32_t a) { asm volatile("red.relaxed.gpu.global.add.noftz.f16x2 [%0], %1;" ::"l"(p), "r"(a) : "memory"); }
__device__ __forceinline__ void ld_relaxed2(uint32_t* v, const void* p) {
    asm volatile("{\n.reg .b64 t;\nld.relaxed.gpu.global.L1::no_allocate.b64 t, [%2];\nmov.b64 {%0,%1}, t;\n}" : "=r"(v[0]), "=r"(v[1]) : "l"(p) : "memory");
}
__device__ __forceinline__ uint32_t ld_relaxed1(const void* p) { uint32_t v; asm volatile("ld.relaxed.gpu.global.u32 %0, [%1];" : "=r"(v) : "l"(p) : "memory"); return v; }
__device__ __forceinline__ void st_relaxed1(const void* p, uint32_t v) { asm volatile("st.relaxed.gpu.global.u32 [%0], %1;" ::"l"(p), "r"(v) : "memory"); }
__device__ __forceinline__ uint32_t ld_acquire(const void* p) { uint32_t v; asm volatile("ld.acquire.gpu.global.u32 %0, [%1];" : "=r"(v) : "l"(p) : "memory"); return v; }
__device__ __forceinline__ void red_relaxed(void* p) { asm volatile("red.relaxed.gpu.global.add.u32 [%0], 1;" ::"l"(p) : "memory"); }
__device__ __forceinline__ void red_release(void* p) { asm volatile("red.release.gpu.global.add.u32 [%0], 1;" ::"l"(p) : "memory"); }
__device__ __forceinline__ void st_stream2(float* p, float a, float b) { asm volatile("st.global.cs.v2.f32 [%0], {%1, %2};" ::"l"(p), "f"(a), "f"(b) : "memory"); }
__device__ __forceinline__ void fence_async() { asm volatile("fence.proxy.async.global;" ::: "memory"); }
__device__ __forceinline__ void fence_async_smem() { asm volatile("fence.proxy.async.shared::cta;" ::: "memory"); }
__device__ __forceinline__ void wait_count(const uint32_t* p, uint32_t target) {
    while ((int32_t)(ld_acquire(p) - target) < 0) __nanosleep(POLLNS);
}
__device__ __forceinline__ void bar_sync(int id, int n) { asm volatile("bar.sync %0, %1;" ::"r"(id), "r"(n) : "memory"); }
__device__ __forceinline__ bool bar_and(int id, bool v) {
    uint32_t r;
    asm volatile("{\n.reg .pred P, Q;\nsetp.ne.u32 Q, %2, 0;\nbar.red.and.pred P, %1, 128, Q;\nselp.u32 %0, 1, 0, P;\n}" : "=r"(r) : "r"(id), "r"((uint32_t)v) : "memory");
    return r;
}
__device__ __forceinline__ void bar_arrive(int id, int n) { asm volatile("bar.arrive %0, %1;" ::"r"(id), "r"(n) : "memory"); }
__device__ __forceinline__ void lds128(uint32_t* v, uint32_t a) { asm volatile("ld.shared.v4.b32 {%0,%1,%2,%3}, [%4];" : "=r"(v[0]), "=r"(v[1]), "=r"(v[2]), "=r"(v[3]) : "r"(a) : "memory"); }
__device__ __forceinline__ uint32_t lds32(uint32_t a) { uint32_t v; asm volatile("ld.shared.b32 %0, [%1];" : "=r"(v) : "r"(a) : "memory"); return v; }
__device__ __forceinline__ void lds64(uint32_t* v, uint32_t a) { asm volatile("ld.shared.v2.b32 {%0,%1}, [%2];" : "=r"(v[0]), "=r"(v[1]) : "r"(a) : "memory"); }
__device__ __forceinline__ void lds64f(float* v, uint32_t a) { asm volatile("ld.shared.v2.f32 {%0,%1}, [%2];" : "=f"(v[0]), "=f"(v[1]) : "r"(a) : "memory"); }
__device__ __forceinline__ void sts128(uint32_t a, const uint32_t* v) { asm volatile("st.shared.v4.b32 [%0], {%1,%2,%3,%4};" ::"r"(a), "r"(v[0]), "r"(v[1]), "r"(v[2]), "r"(v[3]) : "memory"); }
__device__ __forceinline__ void sts64(uint32_t a, uint32_t x, uint32_t y) { asm volatile("st.shared.v2.b32 [%0], {%1,%2};" ::"r"(a), "r"(x), "r"(y) : "memory"); }
__device__ __forceinline__ void sts32(uint32_t a, uint32_t x) { asm volatile("st.shared.b32 [%0], %1;" ::"r"(a), "r"(x) : "memory"); }
__device__ __forceinline__ bool mbar_try(uint32_t b, uint32_t par) {
    uint32_t ok;
    asm volatile("{\n.reg .pred P;\nmbarrier.test_wait.parity.shared::cta.b64 P, [%1], %2;\nselp.u32 %0, 1, 0, P;\n}" : "=r"(ok) : "r"(b), "r"(par) : "memory");
    return ok;
}
__device__ __forceinline__ void mbar_wait(uint32_t b, uint32_t par) {
    asm volatile("{\n.reg .pred P;\nW: mbarrier.try_wait.parity.shared::cta.b64 P, [%0], %1;\n@!P bra W;\n}" ::"r"(b), "r"(par) : "memory");
}
__device__ __forceinline__ void mbar_wait_bounded(uint32_t b, uint32_t par) {
    asm volatile("{\n.reg .pred P, Q;\n.reg .u32 t, u;\nmov.u32 t, %%globaltimer_lo;\nW: mbarrier.try_wait.parity.shared::cta.b64 P, [%0], %1;\n"
                 "mov.u32 u, %%globaltimer_lo;\nsub.u32 u, u, t;\nsetp.gt.u32 Q, u, 2000000000;\n@Q st.global.u32 [%2], 0;\n@!P bra W;\n}" ::"r"(b), "r"(par), "l"(0ull) : "memory");
}
__device__ __forceinline__ void declare_fence(int zero) { asm volatile(".reg .pred PNEVER;\nsetp.ne.u32 PNEVER, %0, 0;" ::"r"(zero)); }
__device__ __forceinline__ void sched_fence() { asm volatile("{\n.reg .pred Q;\n.reg .u32 x;\n@!PNEVER bra D;\nF: ld.volatile.global.u32 x, [%0];\nsetp.ne.u32 Q, x, 0;\n@Q bra F;\nD:\n}" ::"l"(0ull) : "memory"); }
__device__ __forceinline__ void mbar_init(uint32_t b, uint32_t n) { asm volatile("mbarrier.init.shared::cta.b64 [%0], %1;" ::"r"(b), "r"(n) : "memory"); }
__device__ __forceinline__ void mbar_expect(uint32_t b, uint32_t bytes) { asm volatile("mbarrier.arrive.expect_tx.shared::cta.b64 _, [%0], %1;" ::"r"(b), "r"(bytes) : "memory"); }
__device__ __forceinline__ void mbar_arrive(uint32_t b) { asm volatile("mbarrier.arrive.shared::cta.b64 _, [%0];" ::"r"(b) : "memory"); }
__device__ __forceinline__ void mbar_arrive_cluster(uint32_t b) { asm volatile("mbarrier.arrive.shared::cluster.b64 _, [%0];" ::"r"(b) : "memory"); }
__device__ __forceinline__ void cluster_sync() { asm volatile("barrier.cluster.arrive.relaxed.aligned;\nbarrier.cluster.wait.aligned;" ::: "memory"); }
__device__ __forceinline__ uint32_t get_epoch(uint32_t sb) { mbar_wait(sb + B_EPOCH, 0); return __shfl_sync(0xffffffffu, lds32(sb + S_EPOCH), 0); }
__device__ __forceinline__ void tma2d(uint32_t dst, const CUtensorMap* m, int c0, int c1, uint32_t bar) {
    asm volatile("cp.async.bulk.tensor.2d.shared::cluster.global.mbarrier::complete_tx::bytes [%0], [%1, {%2, %3}], [%4];" ::"r"(dst), "l"(m), "r"(c0), "r"(c1), "r"(bar) : "memory");
}
__device__ __forceinline__ void tma3d(uint32_t dst, const CUtensorMap* m, int c0, int c1, int c2, uint32_t bar) {
    asm volatile("cp.async.bulk.tensor.3d.shared::cluster.global.mbarrier::complete_tx::bytes [%0], [%1, {%2, %3, %4}], [%5];" ::"r"(dst), "l"(m), "r"(c0), "r"(c1), "r"(c2), "r"(bar) : "memory");
}
__device__ __forceinline__ void l2_prefetch(const void* src, uint32_t bytes) { asm volatile("cp.async.bulk.prefetch.L2.global [%0], %1;" ::"l"(src), "r"(bytes) : "memory"); }
__device__ __forceinline__ void mbar_expect_e(uint32_t b, uint32_t bytes) {
    asm volatile("{\n.reg .pred E;\nelect.sync _|E, 0xffffffff;\n@E mbarrier.arrive.expect_tx.shared::cta.b64 _, [%0], %1;\n}" ::"r"(b), "r"(bytes) : "memory");
}
__device__ __forceinline__ void tma3d_mc_e(uint32_t dst, const CUtensorMap* m, int c0, int c1, int c2, uint32_t bar, uint16_t mask, uint64_t pol) {
    asm volatile("{\n.reg .pred E;\nelect.sync _|E, 0xffffffff;\n@E cp.async.bulk.tensor.3d.shared::cluster.global.mbarrier::complete_tx::bytes.multicast::cluster.L2::cache_hint [%0], [%1, {%2, %3, %4}], [%5], %6, %7;\n}" ::"r"(dst), "l"(m), "r"(c0), "r"(c1), "r"(c2), "r"(bar), "h"(mask), "l"(pol) : "memory");
}
__device__ __forceinline__ void tma4d_e(uint32_t dst, const CUtensorMap* m, int c0, int c1, int c3, uint32_t bar, uint64_t pol) {
    asm volatile("{\n.reg .pred E;\nelect.sync _|E, 0xffffffff;\n@E cp.async.bulk.tensor.4d.shared::cluster.global.mbarrier::complete_tx::bytes.L2::cache_hint [%0], [%1, {%2, %3, 0, %4}], [%5], %6;\n}" ::"r"(dst), "l"(m), "r"(c0), "r"(c1), "r"(c3), "r"(bar), "l"(pol) : "memory");
}
__device__ __forceinline__ void tma4d_mc_e(uint32_t dst, const CUtensorMap* m, int c0, int c1, int c3, uint32_t bar, uint16_t mask, uint64_t pol) {
    asm volatile("{\n.reg .pred E;\nelect.sync _|E, 0xffffffff;\n@E cp.async.bulk.tensor.4d.shared::cluster.global.mbarrier::complete_tx::bytes.multicast::cluster.L2::cache_hint [%0], [%1, {%2, %3, 0, %4}], [%5], %6, %7;\n}" ::"r"(dst), "l"(m), "r"(c0), "r"(c1), "r"(c3), "r"(bar), "h"(mask), "l"(pol) : "memory");
}
__device__ __forceinline__ void tma_prefetch4d_e(const CUtensorMap* m, int c0, int c3) {
    asm volatile("{\n.reg .pred E;\nelect.sync _|E, 0xffffffff;\n@E cp.async.bulk.prefetch.tensor.4d.L2.global [%0, {%1, 0, 0, %2}];\n}" ::"l"(m), "r"(c0), "r"(c3) : "memory");
}
__device__ __forceinline__ void tma_prefetch3d_e(const CUtensorMap* m, int c0, int c1, int c2) {
    asm volatile("{\n.reg .pred E;\nelect.sync _|E, 0xffffffff;\n@E cp.async.bulk.prefetch.tensor.3d.L2.global [%0, {%1, %2, %3}];\n}" ::"l"(m), "r"(c0), "r"(c1), "r"(c2) : "memory");
}
__device__ __forceinline__ void l2_prefetch_e(const void* src, uint32_t bytes) {
    asm volatile("{\n.reg .pred E;\nelect.sync _|E, 0xffffffff;\n@E cp.async.bulk.prefetch.L2.global [%0], %1;\n}" ::"l"(src), "r"(bytes) : "memory");
}
__device__ __forceinline__ void bulk_g2s_e(uint32_t dst, const void* src, uint32_t bytes, uint32_t bar) {
    asm volatile("{\n.reg .pred E;\nelect.sync _|E, 0xffffffff;\n@E cp.async.bulk.shared::cluster.global.mbarrier::complete_tx::bytes [%0], [%1], %2, [%3];\n}" ::"r"(dst), "l"(src), "r"(bytes), "r"(bar) : "memory");
}
__device__ __forceinline__ bool elect_one() {
    uint32_t r;
    asm volatile("{\n.reg .pred E;\nelect.sync _|E, 0xffffffff;\nselp.u32 %0, 1, 0, E;\n}" : "=r"(r));
    return r;
}
__device__ __forceinline__ void tma_store2d(const CUtensorMap* m, int c0, int c1, uint32_t src, uint64_t pol) {
    asm volatile("cp.async.bulk.tensor.2d.global.shared::cta.bulk_group.L2::cache_hint [%0, {%1, %2}], [%3], %4;" ::"l"(m), "r"(c0), "r"(c1), "r"(src), "l"(pol) : "memory");
}
__device__ __forceinline__ void bulk_commit() { asm volatile("cp.async.bulk.commit_group;" ::: "memory"); }
__device__ __forceinline__ void bulk_wait_read() { asm volatile("cp.async.bulk.wait_group.read 0;" ::: "memory"); }
__device__ __forceinline__ void bulk_wait_all() { asm volatile("cp.async.bulk.wait_group 0;" ::: "memory"); }
__device__ __forceinline__ uint64_t mkdesc(uint32_t addr, uint32_t lbo, uint32_t sbo, uint32_t swz) {
    return (uint64_t)((addr & 0x3FFFF) >> 4) | ((uint64_t)(lbo >> 4) << 16) | ((uint64_t)(sbo >> 4) << 32) | ((uint64_t)swz << 62);
}
__device__ __forceinline__ void wg_fence() { asm volatile("wgmma.fence.sync.aligned;" ::: "memory"); }
__device__ __forceinline__ void wg_commit() { asm volatile("wgmma.commit_group.sync.aligned;" ::: "memory"); }
template <int N> __device__ __forceinline__ void wg_wait() { asm volatile("wgmma.wait_group.sync.aligned %0;" ::"n"(N) : "memory"); }
template <typename T> __device__ __forceinline__ void pin_ptr(T*& p) { asm volatile("" : "+l"(p)); }
template <int N> __device__ __forceinline__ void pin(uint32_t* d) {
#pragma unroll
    for (int i = 0; i < N; i++) asm volatile("" : "+r"(d[i])::"memory");
}
template <int N> __device__ __forceinline__ void pin(float* d) {
#pragma unroll
    for (int i = 0; i < N; i++) asm volatile("" : "+f"(d[i])::"memory");
}

template <int TA, int TB>
__device__ __forceinline__ void wgmma_ss256(float* d, uint64_t da, uint64_t db) {
    asm volatile("wgmma.mma_async.sync.aligned.m64n256k16.f32.bf16.bf16 "
        "{%0, %1, %2, %3, %4, %5, %6, %7, %8, %9, %10, %11, %12, %13, %14, %15, %16, %17, %18, %19, %20, %21, %22, %23, %24, %25, %26, %27, %28, %29, %30, %31, %32, %33, %34, %35, %36, %37, %38, %39, %40, %41, %42, %43, %44, %45, %46, %47, %48, %49, %50, %51, %52, %53, %54, %55, %56, %57, %58, %59, %60, %61, %62, %63, %64, %65, %66, %67, %68, %69, %70, %71, %72, %73, %74, %75, %76, %77, %78, %79, %80, %81, %82, %83, %84, %85, %86, %87, %88, %89, %90, %91, %92, %93, %94, %95, %96, %97, %98, %99, %100, %101, %102, %103, %104, %105, %106, %107, %108, %109, %110, %111, %112, %113, %114, %115, %116, %117, %118, %119, %120, %121, %122, %123, %124, %125, %126, %127}, %128, %129, 1, 1, 1, %130, %131;"
        : "+f"(d[0]), "+f"(d[1]), "+f"(d[2]), "+f"(d[3]), "+f"(d[4]), "+f"(d[5]), "+f"(d[6]), "+f"(d[7]), "+f"(d[8]), "+f"(d[9]), "+f"(d[10]), "+f"(d[11]), "+f"(d[12]), "+f"(d[13]), "+f"(d[14]), "+f"(d[15]), "+f"(d[16]), "+f"(d[17]), "+f"(d[18]), "+f"(d[19]), "+f"(d[20]), "+f"(d[21]), "+f"(d[22]), "+f"(d[23]), "+f"(d[24]), "+f"(d[25]), "+f"(d[26]), "+f"(d[27]), "+f"(d[28]), "+f"(d[29]), "+f"(d[30]), "+f"(d[31]), "+f"(d[32]), "+f"(d[33]), "+f"(d[34]), "+f"(d[35]), "+f"(d[36]), "+f"(d[37]), "+f"(d[38]), "+f"(d[39]), "+f"(d[40]), "+f"(d[41]), "+f"(d[42]), "+f"(d[43]), "+f"(d[44]), "+f"(d[45]), "+f"(d[46]), "+f"(d[47]), "+f"(d[48]), "+f"(d[49]), "+f"(d[50]), "+f"(d[51]), "+f"(d[52]), "+f"(d[53]), "+f"(d[54]), "+f"(d[55]), "+f"(d[56]), "+f"(d[57]), "+f"(d[58]), "+f"(d[59]), "+f"(d[60]), "+f"(d[61]), "+f"(d[62]), "+f"(d[63]), "+f"(d[64]), "+f"(d[65]), "+f"(d[66]), "+f"(d[67]), "+f"(d[68]), "+f"(d[69]), "+f"(d[70]), "+f"(d[71]), "+f"(d[72]), "+f"(d[73]), "+f"(d[74]), "+f"(d[75]), "+f"(d[76]), "+f"(d[77]), "+f"(d[78]), "+f"(d[79]), "+f"(d[80]), "+f"(d[81]), "+f"(d[82]), "+f"(d[83]), "+f"(d[84]), "+f"(d[85]), "+f"(d[86]), "+f"(d[87]), "+f"(d[88]), "+f"(d[89]), "+f"(d[90]), "+f"(d[91]), "+f"(d[92]), "+f"(d[93]), "+f"(d[94]), "+f"(d[95]), "+f"(d[96]), "+f"(d[97]), "+f"(d[98]), "+f"(d[99]), "+f"(d[100]), "+f"(d[101]), "+f"(d[102]), "+f"(d[103]), "+f"(d[104]), "+f"(d[105]), "+f"(d[106]), "+f"(d[107]), "+f"(d[108]), "+f"(d[109]), "+f"(d[110]), "+f"(d[111]), "+f"(d[112]), "+f"(d[113]), "+f"(d[114]), "+f"(d[115]), "+f"(d[116]), "+f"(d[117]), "+f"(d[118]), "+f"(d[119]), "+f"(d[120]), "+f"(d[121]), "+f"(d[122]), "+f"(d[123]), "+f"(d[124]), "+f"(d[125]), "+f"(d[126]), "+f"(d[127])
        : "l"(da), "l"(db), "n"(TA), "n"(TB));
}
template <int TA, int TB>
__device__ __forceinline__ void wgmma_ss256_first(float* d, uint64_t da, uint64_t db) {
    asm volatile("wgmma.mma_async.sync.aligned.m64n256k16.f32.bf16.bf16 "
        "{%0, %1, %2, %3, %4, %5, %6, %7, %8, %9, %10, %11, %12, %13, %14, %15, %16, %17, %18, %19, %20, %21, %22, %23, %24, %25, %26, %27, %28, %29, %30, %31, %32, %33, %34, %35, %36, %37, %38, %39, %40, %41, %42, %43, %44, %45, %46, %47, %48, %49, %50, %51, %52, %53, %54, %55, %56, %57, %58, %59, %60, %61, %62, %63, %64, %65, %66, %67, %68, %69, %70, %71, %72, %73, %74, %75, %76, %77, %78, %79, %80, %81, %82, %83, %84, %85, %86, %87, %88, %89, %90, %91, %92, %93, %94, %95, %96, %97, %98, %99, %100, %101, %102, %103, %104, %105, %106, %107, %108, %109, %110, %111, %112, %113, %114, %115, %116, %117, %118, %119, %120, %121, %122, %123, %124, %125, %126, %127}, %128, %129, 0, 1, 1, %130, %131;"
        : "=f"(d[0]), "=f"(d[1]), "=f"(d[2]), "=f"(d[3]), "=f"(d[4]), "=f"(d[5]), "=f"(d[6]), "=f"(d[7]), "=f"(d[8]), "=f"(d[9]), "=f"(d[10]), "=f"(d[11]), "=f"(d[12]), "=f"(d[13]), "=f"(d[14]), "=f"(d[15]), "=f"(d[16]), "=f"(d[17]), "=f"(d[18]), "=f"(d[19]), "=f"(d[20]), "=f"(d[21]), "=f"(d[22]), "=f"(d[23]), "=f"(d[24]), "=f"(d[25]), "=f"(d[26]), "=f"(d[27]), "=f"(d[28]), "=f"(d[29]), "=f"(d[30]), "=f"(d[31]), "=f"(d[32]), "=f"(d[33]), "=f"(d[34]), "=f"(d[35]), "=f"(d[36]), "=f"(d[37]), "=f"(d[38]), "=f"(d[39]), "=f"(d[40]), "=f"(d[41]), "=f"(d[42]), "=f"(d[43]), "=f"(d[44]), "=f"(d[45]), "=f"(d[46]), "=f"(d[47]), "=f"(d[48]), "=f"(d[49]), "=f"(d[50]), "=f"(d[51]), "=f"(d[52]), "=f"(d[53]), "=f"(d[54]), "=f"(d[55]), "=f"(d[56]), "=f"(d[57]), "=f"(d[58]), "=f"(d[59]), "=f"(d[60]), "=f"(d[61]), "=f"(d[62]), "=f"(d[63]), "=f"(d[64]), "=f"(d[65]), "=f"(d[66]), "=f"(d[67]), "=f"(d[68]), "=f"(d[69]), "=f"(d[70]), "=f"(d[71]), "=f"(d[72]), "=f"(d[73]), "=f"(d[74]), "=f"(d[75]), "=f"(d[76]), "=f"(d[77]), "=f"(d[78]), "=f"(d[79]), "=f"(d[80]), "=f"(d[81]), "=f"(d[82]), "=f"(d[83]), "=f"(d[84]), "=f"(d[85]), "=f"(d[86]), "=f"(d[87]), "=f"(d[88]), "=f"(d[89]), "=f"(d[90]), "=f"(d[91]), "=f"(d[92]), "=f"(d[93]), "=f"(d[94]), "=f"(d[95]), "=f"(d[96]), "=f"(d[97]), "=f"(d[98]), "=f"(d[99]), "=f"(d[100]), "=f"(d[101]), "=f"(d[102]), "=f"(d[103]), "=f"(d[104]), "=f"(d[105]), "=f"(d[106]), "=f"(d[107]), "=f"(d[108]), "=f"(d[109]), "=f"(d[110]), "=f"(d[111]), "=f"(d[112]), "=f"(d[113]), "=f"(d[114]), "=f"(d[115]), "=f"(d[116]), "=f"(d[117]), "=f"(d[118]), "=f"(d[119]), "=f"(d[120]), "=f"(d[121]), "=f"(d[122]), "=f"(d[123]), "=f"(d[124]), "=f"(d[125]), "=f"(d[126]), "=f"(d[127])
        : "l"(da), "l"(db), "n"(TA), "n"(TB));
}
template <int TB>
__device__ __forceinline__ void wgmma_rs128(float* d, const uint32_t* a, uint64_t db, uint32_t acc) {
    asm volatile("{\n.reg .pred P;\nsetp.ne.u32 P, %69, 0;\nwgmma.mma_async.sync.aligned.m64n128k16.f32.bf16.bf16 "
        "{%0, %1, %2, %3, %4, %5, %6, %7, %8, %9, %10, %11, %12, %13, %14, %15, %16, %17, %18, %19, %20, %21, %22, %23, %24, %25, %26, %27, %28, %29, %30, %31, %32, %33, %34, %35, %36, %37, %38, %39, %40, %41, %42, %43, %44, %45, %46, %47, %48, %49, %50, %51, %52, %53, %54, %55, %56, %57, %58, %59, %60, %61, %62, %63}, {%64, %65, %66, %67}, %68, P, 1, 1, %70;\n}"
        : "+f"(d[0]), "+f"(d[1]), "+f"(d[2]), "+f"(d[3]), "+f"(d[4]), "+f"(d[5]), "+f"(d[6]), "+f"(d[7]), "+f"(d[8]), "+f"(d[9]), "+f"(d[10]), "+f"(d[11]), "+f"(d[12]), "+f"(d[13]), "+f"(d[14]), "+f"(d[15]), "+f"(d[16]), "+f"(d[17]), "+f"(d[18]), "+f"(d[19]), "+f"(d[20]), "+f"(d[21]), "+f"(d[22]), "+f"(d[23]), "+f"(d[24]), "+f"(d[25]), "+f"(d[26]), "+f"(d[27]), "+f"(d[28]), "+f"(d[29]), "+f"(d[30]), "+f"(d[31]), "+f"(d[32]), "+f"(d[33]), "+f"(d[34]), "+f"(d[35]), "+f"(d[36]), "+f"(d[37]), "+f"(d[38]), "+f"(d[39]), "+f"(d[40]), "+f"(d[41]), "+f"(d[42]), "+f"(d[43]), "+f"(d[44]), "+f"(d[45]), "+f"(d[46]), "+f"(d[47]), "+f"(d[48]), "+f"(d[49]), "+f"(d[50]), "+f"(d[51]), "+f"(d[52]), "+f"(d[53]), "+f"(d[54]), "+f"(d[55]), "+f"(d[56]), "+f"(d[57]), "+f"(d[58]), "+f"(d[59]), "+f"(d[60]), "+f"(d[61]), "+f"(d[62]), "+f"(d[63])
        : "r"(a[0]), "r"(a[1]), "r"(a[2]), "r"(a[3]), "l"(db), "r"(acc), "n"(TB));
}
template <int TB>
__device__ __forceinline__ void wgmma_rs64(float* d, const uint32_t* a, uint64_t db, uint32_t acc) {
    asm volatile("{\n.reg .pred P;\nsetp.ne.u32 P, %37, 0;\nwgmma.mma_async.sync.aligned.m64n64k16.f32.bf16.bf16 "
        "{%0, %1, %2, %3, %4, %5, %6, %7, %8, %9, %10, %11, %12, %13, %14, %15, %16, %17, %18, %19, %20, %21, %22, %23, %24, %25, %26, %27, %28, %29, %30, %31}, {%32, %33, %34, %35}, %36, P, 1, 1, %38;\n}"
        : "+f"(d[0]), "+f"(d[1]), "+f"(d[2]), "+f"(d[3]), "+f"(d[4]), "+f"(d[5]), "+f"(d[6]), "+f"(d[7]), "+f"(d[8]), "+f"(d[9]), "+f"(d[10]), "+f"(d[11]), "+f"(d[12]), "+f"(d[13]), "+f"(d[14]), "+f"(d[15]), "+f"(d[16]), "+f"(d[17]), "+f"(d[18]), "+f"(d[19]), "+f"(d[20]), "+f"(d[21]), "+f"(d[22]), "+f"(d[23]), "+f"(d[24]), "+f"(d[25]), "+f"(d[26]), "+f"(d[27]), "+f"(d[28]), "+f"(d[29]), "+f"(d[30]), "+f"(d[31])
        : "r"(a[0]), "r"(a[1]), "r"(a[2]), "r"(a[3]), "l"(db), "r"(acc), "n"(TB));
}
template <int TB>
__device__ __forceinline__ void wgmma_rs16(float* d, const uint32_t* a, uint64_t db, uint32_t acc) {
    asm volatile("{\n.reg .pred P;\nsetp.ne.u32 P, %13, 0;\nwgmma.mma_async.sync.aligned.m64n16k16.f32.bf16.bf16 "
        "{%0, %1, %2, %3, %4, %5, %6, %7}, {%8, %9, %10, %11}, %12, P, 1, 1, %14;\n}"
        : "+f"(d[0]), "+f"(d[1]), "+f"(d[2]), "+f"(d[3]), "+f"(d[4]), "+f"(d[5]), "+f"(d[6]), "+f"(d[7])
        : "r"(a[0]), "r"(a[1]), "r"(a[2]), "r"(a[3]), "l"(db), "r"(acc), "n"(TB));
}

__device__ __forceinline__ uint32_t delay_loop(int n, uint32_t x0) {
    uint32_t z;
    asm volatile("{\n.reg .pred P;\n.reg .u32 c, x;\nmov.u32 c, %1;\nmov.u32 x, %2;\nDL: mad.lo.u32 x, x, 1664525, 1013904223;\nadd.u32 c, c, -1;\nsetp.gt.s32 P, c, 0;\n@P bra DL;\n"
                 "setp.eq.u32 P, x, 0x7fffffff;\nselp.u32 %0, 16, 0, P;\n}" : "=r"(z) : "r"(n), "r"(x0) : "memory");
    return z;
}
__device__ __forceinline__ void wait_clocks(uint32_t n) {
    asm volatile("{\n.reg .pred P;\n.reg .u32 a, b;\nmov.u32 a, %%clock;\nW: mov.u32 b, %%clock;\nsub.u32 b, b, a;\nsetp.lt.u32 P, b, %0;\n@P bra W;\n}" ::"r"(n) : "memory");
}
__device__ __forceinline__ uint32_t gtime() { uint32_t t; asm volatile("mov.u32 %0, %%globaltimer_lo;" : "=r"(t)); return t; }
#define COUNT_RETRY(i)
__device__ __forceinline__ uint32_t stamp_word(uint32_t seq) { return (gtime() & ~31u) | (seq & 31u); }
__device__ __forceinline__ void wait_time(uint32_t t, uint32_t sb) { while ((int32_t)(gtime() - t) < 0) {} }
#define NAPMODE 1
__device__ __forceinline__ void nap(uint32_t ns) { if (NAPMODE) wait_clocks(ns * 7 / 4); else __nanosleep(ns); }
template <int STRIDE>
__device__ __forceinline__ uint32_t latest_stamp(const uint32_t* p, uint32_t seq, uint32_t ref, uint32_t sb) {
#pragma unroll 1
    for (int n = opq(0, 0);; n++) {
        uint32_t bad = 0; int32_t m = INT32_MIN;
#pragma unroll
        for (int i = 0; i < 3; i++) { const uint32_t v = ld_relaxed1(p + i * STRIDE); bad |= (v ^ seq) & 31u; m = max(m, (int32_t)((v & ~31u) - ref)); }
        if (__all_sync(0xffffffffu, bad == 0)) return ref + __reduce_max_sync(0xffffffffu, m);
        nap(100);
        if (n > SPIN_LIMIT) spin_fault();
    }
}
constexpr uint32_t ONES = 0x3C003C00u, FULL = 0x50005000u;
__device__ __forceinline__ void pacer(const Params& P, const uint32_t sb, const int cta, const int lane, const uint32_t epoch) {
    uint8_t* const zp = P.xb + cta * 2048 + xg_lane(lane);
    if (lane < 3) asm volatile("prefetch.tensormap [%0];" ::"l"(&P.tm[lane == 0 ? M_C1 + cta % 3 : lane == 1 ? M_CO : M_SEG]) : "memory");
    uint32_t e0 = 0;
#pragma unroll 2
    for (int i = 0; i < 32; i++) { const uint4 u = __ldg((const uint4*)P.mem0 + i * 32 + lane); e0 = amax(amax(e0, amax(u.x, u.y)), amax(u.z, u.w)); }
    e0 = min(max(warp_exp(e0), 31u), 253u) - 14;
    if (cta < 32) {
        const uint32_t* m = (const uint32_t*)(P.mem0 + (lane >> 2) * 1024 + cta * 32 + (lane & 3) * 2);
        const float sc = __uint_as_float((254 - e0) << 23);
        auto cv = [&](uint32_t u) { return pack2h(bf_lo(u) * sc, bf_hi(u) * sc); };
        const uint32_t y = cv(m[12]);
        st_relaxed4(zp, cv(m[0]), cv(m[4]), cv(m[8]), prmt(y, FULL, 0x7610));
        st_relaxed1(P.xb + xg_side(cta) + lane * 4, prmt(y, FULL, 0x3254));
    }
    if (cta < 40) {
#pragma unroll 1
        for (int b = 1; b < 8; b++) st_relaxed4(zp + xg_buf(b), 0, 0, 0, 0);
    }
    __threadfence();
    const uint32_t* ts = (const uint32_t*)(P.xb + XG_T) + lane;
    int32_t d0 = P.dly;
    const uint32_t go = mapa(sb + B_GO, (cta / 3 & 1) * 3 + 1 + (lane & 1));
    auto free_segment = [&]() { if (lane == 0) mbar_expect(sb + B_KVFULL, 16384); __syncwarp(); if (lane < 2) mbar_arrive_cluster(go); };
    for (int n = 0; (int32_t)(ld_acquire(&g_cnt(C_XCNT)) - (epoch + 1) * 256) < 0; n++) { __nanosleep(500); if (n > SPIN_LIMIT) spin_fault(); }
    const uint32_t ex = max(ld_relaxed1(&g_cnt(C_XMAX)) & 255, 67u);
    mbar_wait_bounded(sb + B_READY, 0);
    free_segment();
    if (lane == 0) st_relaxed2(g_hint + cta * 32, stamp_word(epoch + 1), lds32(sb + S_EV) | lds32(sb + S_EO) << 16);
    uint32_t a = gtime();
    for (int n = 0;; n++) {
        uint32_t bad = 0, e = 0; int32_t m = INT32_MIN;
#pragma unroll
        for (int i = 0; i < 3; i++) {
            uint32_t v[2];
            ld_relaxed2(v, g_hint + lane * 32 + i * 1024);
            bad |= (v[0] ^ (epoch + 1)) & 31u; m = max(m, (int32_t)((v[0] & ~31u) - a)); e = __vmaxu2(e, v[1]);
        }
        if (__all_sync(0xffffffffu, bad == 0)) {
            a += __reduce_max_sync(0xffffffffu, m);
            const uint32_t ev = __reduce_max_sync(0xffffffffu, e & 255), eo = __reduce_max_sync(0xffffffffu, e >> 16);
            if (lane == 0) { sts64(sb + S_SC, max(ev, 97u) + max(eo, 97u) - 244, ex); sts32(sb + S_ISC, e0 * 0x800080u); }
            break;
        }
        wait_clocks(100);
        if (n > SPIN_LIMIT) spin_fault();
    }
    wait_time(a, sb);
    if (lane == 0) mbar_arrive(sb + B_RELM);
#pragma unroll 1
    for (int s = 0; s < 63; s++) {
        const uint32_t seq = epoch * 63 + s + 1;
        mbar_wait_bounded(sb + B_P1, s & 1);
        const uint32_t tx = gtime();
        if (lane == 0) st_relaxed1(ts + (s & 1) * 256 + cta, (tx & ~31u) | (seq & 31u));
        { const uint32_t t = tx; PROFP(3) }
        if (s > 0) {
            const int32_t e0 = latest_stamp<32>(ts + (~s & 1) * 256 + 128, seq - 1, a, sb) + P.mrg - a;
            d0 += s < 3 ? e0 : min(max(e0, -P.clamp0), P.clampv) / 2;
        }
        while ((int32_t)(gtime() - tx) < P.rd) nap(20);
        a = latest_stamp<32>(ts + (s & 1) * 256, seq, tx, sb) + d0;
        { const uint32_t t = gtime(); PROFP(0) }
        while ((int32_t)(a - gtime()) > 250) nap(40);
        wait_time(a, sb);
        if (lane == 0) mbar_arrive(sb + B_RELM);
        { const uint32_t t = a; PROFP(2) }
        mbar_wait_bounded(sb + B_RED, s & 1);
        { const uint32_t t = gtime(); PROFP(1) }
        const uint32_t g = tx + __reduce_max_sync(0xffffffffu, lds32(sb + S_TO + (lane & 7) * 4) - tx);
        if (lane == 0) st_relaxed1(ts + (s & 1) * 256 + 128 + cta, (g & ~31u) | (seq & 31u));
        if (s < 62) { if (P.kvd) nap(P.kvd); free_segment(); }
    }
}
__device__ __forceinline__ void st_async2(uint32_t a, uint32_t x, uint32_t y, uint32_t bar) {
    asm volatile("st.async.weak.shared::cluster.mbarrier::complete_tx::bytes.v2.b32 [%0], {%1,%2}, [%3];" ::"r"(a), "r"(x), "r"(y), "r"(bar) : "memory");
}
__device__ __forceinline__ uint32_t xor_or(uint32_t a, uint32_t b, uint32_t t) { uint32_t d; asm("lop3.b32 %0, %1, %2, %3, 0x7E;" : "=r"(d) : "r"(a), "r"(b), "r"(t)); return d; }
__device__ __forceinline__ uint32_t or3(uint32_t a, uint32_t b, uint32_t c) { uint32_t d; asm("lop3.b32 %0, %1, %2, %3, 0xFE;" : "=r"(d) : "r"(a), "r"(b), "r"(c)); return d; }
__device__ __forceinline__ bool tags_ok(uint32_t bad, uint32_t mask = 1) {
    uint32_t r;
    asm volatile("{\n.reg .pred P;\n.reg .b32 x;\nand.b32 x, %1, %2;\nsetp.ne.b32 P, x, 0;\nvote.sync.any.pred P, P, 0xffffffff;\nselp.u32 %0, 0, 1, P;\n}" : "=r"(r) : "r"(bad), "r"(mask));
    return r;
}
constexpr int SROW = 56;
#define PREA 8
#define PREB 9
#define RING1 6
#define RING2 7
#define RING3 8
#define PRE2 10
#define PRE2A 0
#define PRE3 0
#define EFENCE 0
#define RFENCE 1
#define PROG 16
#define EARLY 0
#define PLATE 1
#define NDEP 0
#define EFENCE2 0
#define LAG2 8
#define LAG 4
#define PUT1 33
#define DEPS 3
#define ADELAY 120
#define BDELAY 0
#define HOLD 1
#define XDELAY 330
#define FENCEA 0x80
#define FENCEB 0x80
#define FENCE2 0x220
#define OFENCE 0
#define MASK3 0x57
#define MASK4 0x55
#define MASK5 0x25
#define OFF3 0x5320
#define OFF4 0x6420
#define OFF5 0x0520
#define RESA (NRA == 3 ? 15 : NRA == 4 ? 3 : 0)
#define RESB (NRB == 3 ? 0xcc : NRB == 4 ? 0x30 : 0)
#define RESB1 (NRB == 3 ? 0xcc : NRB == 4 ? 0xc : 0)
__host__ __device__ constexpr int smem_mask(int NR) { return NR == 3 ? MASK3 : NR == 4 ? MASK4 : MASK5; }
__host__ __device__ constexpr bool round_smem(int r, int NR) { return smem_mask(NR) >> r & 1; }
__host__ __device__ constexpr int kord(int r, int NR) { int c = 0; for (int i = 0; i < r; i++) c += round_smem(i, NR) == round_smem(r, NR); return round_smem(r, NR) ? NR + c : c; }
__host__ __device__ constexpr int slot_r(int n, int NR) { return n < 32 ? n >> 2 : (((n & 31) >> 2) + ((NR == 3 ? OFF3 : NR == 4 ? OFF4 : OFF5) >> (n & 3) * 4)) & 7; }
__host__ __device__ constexpr int slot_k(int n, int NR) { return kord(slot_r(n, NR), NR); }
__host__ __device__ constexpr int slot_sord(int n, int NR) { int c = 0; for (int i = 0; i < n; i++) c += slot_k(i, NR) >= NR; return c; }
__host__ __device__ constexpr int sfrag_slot(int q, int NR) { for (int n = 0; n < 64; n++) if (slot_k(n, NR) >= NR && slot_sord(n, NR) == q) return n; return -1; }
__host__ __device__ constexpr int w1_loaded(int n, int NR, int PRE) {
    int q = PRE;
    for (int i = 0; i <= n; i++) q += q < (8 - NR) * 8 && q - slot_sord(i + 1, NR) < (i < 32 ? RING1 : RING2);
    return q;
}
template <int Q, int NR>
__device__ __forceinline__ void load_w1(uint32_t* w, const uint32_t* a) {
    constexpr int n = sfrag_slot(Q, NR);
    ldsm4t(w, a[n & 3] + ((slot_k(n, NR) - NR) * 2 + (n >> 5)) * 2048);
}
constexpr int AB = NRA < 5, BB = 3 - AB;
__device__ __forceinline__ bool w2_full(int role, int warp) { return warp < (role == 2 ? 2 : 3); }
__device__ __forceinline__ int w2_nblk(int role, int warp) { return warp < 4 ? BB - !w2_full(role, warp) : AB; }
__host__ __device__ constexpr int w2_step(bool full, int i) { return AB ? (full ? 2 * i : 0) : full ? (i == 0 ? 0 : i == 1 ? 16 - 2 * EARLY : 18 - 2 * EARLY) : i; }
__device__ __forceinline__ int w2_block(int role, int warp) {
    const int f = role * 3 + warp, g = role == 2 ? warp : role;
    if (AB) return (warp >= 4 ? role * 4 + (warp - 4) : w2_full(role, warp) ? 16 + 4 * (f >> 1) + (f & 1) : 12 + g) ^ EARLY;
    return w2_full(role, warp) ? EARLY + 4 * (f >> 1) + (f & 1) : EARLY + 2 + 4 * g;
}
__device__ __forceinline__ int w2_res(int role, int warp) { return warp >= 4 ? RESA : w2_full(role, warp) ? RESB : RESB1; }
__device__ __forceinline__ int w2_units(int role, int warp) { return w2_nblk(role, warp) * 4 - (5 - (warp < 4 ? NRB : NRA)) * 2; }
constexpr int W2B = (BB * 4 - (5 - NRB) * 2) * 2048, W2A = (AB * 4 - (5 - NRA) * 2) * 2048;
static_assert(S_W2 + 4 * W2B - 8192 + 4 * W2A == S_KV, "weights");
__device__ __forceinline__ int w1_base(int warp) { return S_W1 + (warp < 4 ? warp * (8 - NRB) : 4 * (8 - NRB) + (warp - 4) * (8 - NRA)) * 4096; }
__device__ __forceinline__ int w2_base(int warp) { return S_W2 + (warp < 4 ? warp * W2B : 4 * W2B - 8192 + (warp - 4) * W2A); }
__device__ __forceinline__ void chain_load(const Params& P, uint32_t sb, int cta, int warp, int lane, int round) {
    const int role = cta % 3, h = cta / 3;
    mbar_expect_e(sb + B_INIT, round ? (8 - (warp < 4 ? NRB : NRA)) * 4096 : 20480);
    if (round) mbar_expect_e(sb + B_INIT2, w2_units(role, warp) * 2048);
    __syncwarp();
    const int m1 = (warp < 4 ? smem_mask(NRB) : smem_mask(NRA)) ^ (round ? 0 : 255), below = (1 << lane) - 1;
    const int m2 = (w2_res(role, warp) ^ (round ? 0xfff : 0)) & ((1 << w2_nblk(role, warp) * 4) - 1);
    const uint32_t d1 = sb + (round ? w1_base(warp) : warp * 20480), d2 = round ? sb + w2_base(warp) : d1 + __popc(m1) * 4096;
    if (m1 >> lane & 1) tma3d(d1 + __popc(m1 & below) * 4096, &P.tm[M_C1 + role], 0, warp * 128 + lane * 16, h * 2, sb + B_INIT);
    __syncwarp();
    if (m2 >> lane & 1)
        tma2d(d2 + __popc(m2 & below) * 2048, &P.tm[M_CO], (w2_block(role, warp) + w2_step(w2_full(role, warp), lane >> 2)) * 32, h * 128 + (lane & 3) * 32, sb + (round ? B_INIT2 : B_INIT));
    __syncwarp();
}

__device__ __forceinline__ void put_partials(bool TR, uint32_t a, const float* x, const float* y) {
    if (TR) stsm4t(a, pack2(x[0], x[1]), pack2(x[2], x[3]), pack2(y[0], y[1]), pack2(y[2], y[3]));
    else stsm4(a, pack2(x[0], x[1]), pack2(x[2], x[3]), pack2(y[0], y[1]), pack2(y[2], y[3]));
}
template <int NR, int PRE, int FM, int B, int E>
__device__ __forceinline__ void project(float (*acc)[4], bool TR, const uint32_t (*wr)[4], uint32_t (*as)[4], uint32_t (*v)[4], uint32_t* x, const uint32_t* w1a, uint32_t pp, uint32_t zero) {
    static_for<B, E>([&](auto I) {
        constexpr int n = I.value, kk = slot_k(n, NR), T = (n >> 5) * 4 + (n & 3), so = slot_sord(n, NR), q = w1_loaded(n - 1, NR, PRE);
        constexpr bool sm = kk >= NR;
        const uint32_t* w = sm ? as[so] : wr[sm ? 0 : (kk * 2 + (n >> 5)) * 4 + (n & 3)];
        if constexpr (n == 32 && PUT1 < 32) { put_partials(TR, pp, acc[0], acc[1]); put_partials(TR, pp + 4096, acc[2], acc[3]); }
        if constexpr (n == 0) {
            const uint32_t c = prmt(v[0][3], x[0], 0x3254);
            v[0][0] = h2bf(v[0][0], v[0][0]); v[0][1] = h2bf(v[0][1], v[0][1]); v[0][2] = h2bf(v[0][2], v[0][2]); v[0][3] = h2bf(v[0][3], x[0]);
            x[0] = c;
        }
        if constexpr ((n & 31) < 4) acc[T][0] = acc[T][1] = acc[T][2] = acc[T][3] = 0.f;
        mma16816(acc[T], w[0], w[1], w[2], w[3], v[slot_r(n, NR) >> 1][(slot_r(n, NR) & 1) * 2], v[slot_r(n, NR) >> 1][(slot_r(n, NR) & 1) * 2 + 1]);
        if constexpr (n == DEPS) {
            const uint32_t sel = __float_as_uint(acc[T][0]) * zero + 0x7610;
#pragma unroll
            for (int b = 1; b < 4; b++) {
                if (b <= NDEP) cvt_block(v[b], x[b], sel);
                else {
                    const uint32_t c = prmt(v[b][3], x[b], 0x3254);
                    v[b][0] = h2bf(v[b][0], v[b][0]); v[b][1] = h2bf(v[b][1], v[b][1]); v[b][2] = h2bf(v[b][2], v[b][2]); v[b][3] = h2bf(v[b][3], x[b]);
                    x[b] = c;
                }
            }
        }
        if constexpr (w1_loaded(n, NR, PRE) > q) load_w1<q, NR>(as[q], w1a);
        if constexpr (n == PUT1 && n >= 32) { put_partials(TR, pp, acc[0], acc[1]); put_partials(TR, pp + 4096, acc[2], acc[3]); }
        if constexpr (n % 4 == 3 && (FM >> (n / 4) & 1) && n != E - 1) sched_fence();
    });
    if constexpr (E == 64) { put_partials(TR, pp + 8192, acc[4], acc[5]); put_partials(TR, pp + 12288, acc[6], acc[7]); }
}
__device__ __forceinline__ void reduce8(const uint32_t (*x)[4], const uint32_t* sel, float sc, uint32_t& r0, uint32_t& r1) {
    float d[4][4];
#pragma unroll
    for (int i = 0; i < 4; i++) {
        d[i][0] = d[i][1] = d[i][2] = d[i][3] = 0.f;
        mma16816(d[i], x[i][0], x[i][1], x[i][2], x[i][3], sel[2 * i], sel[2 * i + 1]);
    }
    r0 = pack2(((d[0][0] + d[1][0]) + (d[2][0] + d[3][0])) * sc, ((d[0][1] + d[1][1]) + (d[2][1] + d[3][1])) * sc);
    r1 = pack2(((d[0][2] + d[1][2]) + (d[2][2] + d[3][2])) * sc, ((d[0][3] + d[1][3]) + (d[2][3] + d[3][3])) * sc);
}

#define ISTAMP(i)
__host__ __device__ constexpr int wo_count(int n, int RES, bool res) { int c = 0; for (int i = 0; i < n; i++) c += (RES >> (i >> 2) & 1) == res; return c; }
__host__ __device__ constexpr int wo_loaded(int n, int RES, int PRE, int end) { int q = PRE; for (int i = 0; i <= n; i++) q += q < end && q - wo_count(i + 1, RES, false) < RING3; return q; }
template <int Q>
__device__ __forceinline__ void load_w2(uint32_t* w, const uint32_t* a) { ldsm4t(w, a[Q & 1] + (Q >> 1) * 1024); }
template <int NB, int RES, int PRE, int FM>
__device__ __forceinline__ void wo_blocks(uint32_t (*w)[4], const uint32_t (*wp)[4], uint32_t oa, const uint32_t* wa, const uint8_t* dst, const uint8_t* dsd, bool odd) {
    float a[NB][4][4];
    uint32_t o[4][4], r[5];
    bar_sync(3, 256);
#pragma unroll
    for (int i = 0; i < 4; i++) ldsm4(o[i], oa + i * 512);
    if (FM & 1) sched_fence();
    static_for<0, NB * 16>([&](auto I) {
        constexpr int n = I.value, i = n & 15, end = wo_count(NB * 16, RES, false), q = wo_loaded(n - 1, RES, PRE, end);
        constexpr bool res = RES >> (n >> 2) & 1;
        const uint32_t* b = o[i >> 2] + (i & 2);
        const uint32_t* x = res ? wp[wo_count(n, RES, true)] : w[wo_count(n, RES, false)];
        float* d = a[n >> 4][i & 3];
        if constexpr (i < 4) d[0] = d[1] = d[2] = d[3] = 0.f;
        mma16816(d, x[0], x[1], x[2], x[3], b[0], b[1]);
        if constexpr (wo_loaded(n, RES, PRE, end) > q) load_w2<q>(w[q], wa);
        if constexpr (n == NB * 16 - 1 || (n >= 16 && i == LAG - 1)) {
            const float (*e)[4] = a[n == NB * 16 - 1 ? NB - 1 : (n >> 4) - 1];
            const uint32_t y = pack2h(e[1][2] + e[3][2], e[1][3] + e[3][3]);
            r[0] = movm(pack2h(e[0][0] + e[2][0], e[0][1] + e[2][1])); r[1] = movm(pack2h(e[0][2] + e[2][2], e[0][3] + e[2][3]));
            r[2] = movm(pack2h(e[1][0] + e[3][0], e[1][1] + e[3][1])); r[3] = movm(odd ? ONES : y); r[4] = movm(odd ? y : ONES);
        }
        if constexpr (n == NB * 16 - 1 || (n >= 16 && i == LAG2 - 1)) {
            constexpr int bs = w2_step(NB == BB, n == NB * 16 - 1 ? NB - 1 : (n >> 4) - 1);
            red_add4(dst + bs * 2048, r[0], r[1], r[2], r[3]);
            red_add1(dsd + (bs >> 1) * 1024 + (bs & 1) * 256, r[4]);
        }
        if constexpr (((FM >> (n / 4 + 1)) & 1) && (n & 3) == 3 && n != NB * 16 - 1) sched_fence();
    });
}
#define FRAG1(ln) ((((ln) & 7) + ((ln) >> 4) * 8) * 128 + ((((((ln) >> 3) & 1) << (ROLE == 1)) ^ ((ln) & 7)) << 4))
#define FRAG2(ln) ((((ln) & 7) + ((ln) >> 4) * 8) * 64 + (((((ln) >> 3) & 1) ^ (((ln) >> 1) & 3)) << 4))
#define TILE_X(i) (ROLE == 1 ? (((i) >> 1) << 6) | (((i) & 1) << 4) : (i) << 5)
__device__ __forceinline__ void chain_fetch(const Params& P, const uint32_t sb, const int cta, const int warp, const int lane, uint32_t (*wr)[4]) {
    const int ROLE = cta % 3, nr = warp < 4 ? NRB : NRA;
    mbar_wait(sb + B_INIT, 0);
    ISTAMP(0)
#pragma unroll
    for (int f = 0; f < 40; f++) {
        const bool w1 = f < (NRA < NRB ? NRA : NRB) * 8 || f < nr * 8;
        ldsm4t(wr[f], sb + warp * 20480 + (f >> 2) * 2048 + (w1 ? FRAG1(lane) ^ TILE_X(f & 3) : (f & 2) * 512 + (FRAG2(lane) ^ ((f & 1) << 5))));
    }
    fence_async_smem();
    mbar_wait(sb + B_SFREE + (warp >> 2) * 8, 0);
    bar_sync(1, 256);
    chain_load(P, sb, cta, warp, lane, 1);
    ISTAMP(1)
}
__device__ __forceinline__ void chain_bounds(const uint32_t sb, const int cta, const int warp, const int lane, const uint32_t (*wr)[4]) {
    const int ROLE = cta % 3, nr = warp < 4 ? NRB : NRA;
    uint32_t m[6] = {}, u[4];
#pragma unroll
    for (int f = 0; f < 40; f++) m[f < 24 ? 0 : f >> 3] = amax4(m[f < 24 ? 0 : f >> 3], wr[f]);
    uint32_t m1 = amax(m[0], amax(nr > 3 ? m[3] : 0, nr > 4 ? m[4] : 0)), m2 = amax(nr > 3 ? 0 : m[3], nr > 4 ? 0 : m[4]);
    ISTAMP(5)
    mbar_wait(sb + B_INIT, 1);
    ISTAMP(3)
    if (ROLE == 2) {
#pragma unroll 4
        for (int i = 0; i < S_W2 / 4096; i++) { lds128(u, sb + S_W1 + warp * (S_W2 / 8) + i * 512 + lane * 16); m1 = amax4(m1, u); }
    }
    mbar_wait(sb + B_INIT2, 0);
    ISTAMP(7)
    const int n = w2_units(ROLE, warp) * 4;
#pragma unroll 4
    for (int i = 0; i < n; i++) { lds128(u, sb + w2_base(warp) + i * 512 + lane * 16); m2 = amax4(m2, u); }
    m1 = warp_exp(m1); m2 = warp_exp(m2);
    if (lane == 0) { if (ROLE == 2) red_max_shared(sb + S_EV, m1); red_max_shared(sb + S_EO, m2); }
}
template <bool ATT>
__device__ __forceinline__ void chain_role(const Params& P, const uint32_t sb, const int cta, const int warp, const int lane, const uint32_t (*wr)[4]) {
    constexpr int NR = ATT ? NRA : NRB, PRE = ATT ? PREA : PREB;
    const int h = cta / 3, ROLE = cta - h * 3;
    ISTAMP(6)
    uint32_t l8 = opq(sb + lane * 8, lane);
    const uint8_t* persu = (const uint8_t*)((ROLE == 1 ? g_km : g_vmt) + h * 512) - (sb >> 1);
    auto persist = [&](int s, int tile, uint32_t r0, uint32_t r1) {
        uint32_t* pp = (uint32_t*)(persu + s * 65536 + (ROLE == 1 ? (tile >> 1) * 512 + (tile & 1) * 128 : tile * 256) + (l8 >> 1));
        pp[0] = r0; pp[ROLE == 1 ? 64 : 32] = r1;
    };
    const uint32_t rk0 = (h & 1) * 3, rd1 = __shfl_sync(0xffffffffu, mapa(sb, rk0 + (ROLE + 1) % 3) - sb, 0), rd2 = __shfl_sync(0xffffffffu, mapa(sb, rk0 + (ROLE + 2) % 3) - sb, 0);
    const uint32_t xo = (ROLE == 2 ? S_XV : S_X + ROLE * 2048) + warp * 256;
    const bool full = w2_full(ROLE, warp);
    const int blk = w2_block(ROLE, warp);
    const uint32_t om = blk * 2048, os = xg_side(blk);
    const uint32_t w1o = sb + w1_base(warp), w2o = sb + w2_base(warp);
    ISTAMP(2)
    if (lane == 0) mbar_arrive(sb + B_READY);
#pragma unroll 1
    for (int s = 0;; s++) {
        l8 += s & P.zero;
        uint32_t r0, r1;
        {
            uint32_t v[4][4], as[(8 - NR) * 8][4], w1a[4];
            float acc[8][4];
            const uint32_t pst = sb + S_P1 + (l8 - sb) * 16 + ((warp * 16) ^ ((l8 & 56) * 2));
#pragma unroll
            for (int i = 0; i < 4; i++) w1a[i] = w1o + (FRAG1((l8 - sb) >> 3) ^ TILE_X(i));
            auto preload = [&]() { static_for<0, PRE>([&](auto I) { load_w1<I.value, NR>(as[I.value], w1a); }); };
#pragma unroll 1
            while (true) {
                uint32_t x[4];
                if (!(PLATE >> ATT & 1)) preload();
                const uint32_t lm = opq(l8 - sb, (l8 - sb) >> 3);
                const uint8_t* pm = P.xb + xg_buf(s) + warp * 8192 + xg_lane(lm >> 3);
                const uint8_t* ps = P.xb + xg_buf(s) + XG_SIDE + warp * 2048 + (lm >> 1);
                pin_ptr(pm); pin_ptr(ps);
                mbar_wait(sb + B_RELM, s & 1);
                if (ATT ? ADELAY : BDELAY) wait_clocks(ATT ? ADELAY : BDELAY);
                PROF(10)
#pragma unroll
                for (int b = 0; b < 4; b++) { ld_relaxed4(v[b], pm + b * 2048); ld_relaxed1n(x[b], ps + (b >> 1) * 1024 + (b & 1) * 256); }
                if (PLATE >> ATT & 1) { preload(); if (PLATE >> (ATT + 2) & 1) sched_fence(); }
                project<NR, PRE, ATT ? FENCEA : FENCEB, 0, PROG>(acc, ROLE == 2, wr, as, v, x, w1a, pst, P.zero);
                const uint32_t bad = xor_or(x[0], x[1], FULL) | xor_or(x[2], x[3], FULL);
                if (tags_ok(bad, 0xffffffffu)) break;
                COUNT_RETRY(warp >> 1)
            }
            PROF(0)
            project<NR, PRE, ATT ? FENCEA : FENCEB, PROG, 64>(acc, ROLE == 2, wr, as, v, nullptr, w1a, pst, 0);
            PROF(1)
            const uint32_t isc = lds32(sb + S_ISC + (s & 1) * 4);
            const uint32_t lq = l8 + ((s >> 3) & P.zero), e1 = s == 63 ? 0 : rd1, e2 = s == 63 ? 0 : rd2;
            uint32_t x[4][4], sel[8], xd[6] = {l8 + xo, l8 + xo + e1, l8 + xo + e2, sb + B_X + e1, sb + B_X + e2, sb + S_P1 + warp * 2048 + (lq & 64) * 16 + (lq & 128) + (lq & 56) * 2};
#pragma unroll
            for (int i = 0; i < 8; i++) sel[i] = (lq & 224) == i * 32 ? 0x3F803F80u : 0u;
            pin<6>(xd); pin<8>(sel);
            if (RFENCE) sched_fence();
            bar_sync(1, 256);
#pragma unroll
            for (int i = 0; i < 4; i++) ldsm4t(x[i], xd[5] + i * 256);
            if (!ATT && l8 == sb + (warp - 3) * 1024) mbar_arrive(sb + B_P1);
            uint32_t em = warp_exp(amax(amax4(amax(amax(v[0][0], v[0][1]), amax(v[0][2], v[0][3])), v[1]), amax4(amax(amax(v[2][0], v[2][1]), amax(v[2][2], v[2][3])), v[3])));
            if (EFENCE2) sched_fence();
            reduce8(x, sel, bf_hi(isc), r0, r1);
            st_async2(xd[1], r0, r1, xd[3]);
            st_async2(xd[2], r0, r1, xd[4]);
            sts64(xd[0], r0, r1);
            if (s == 63) { persist(s, warp, r0, r1); break; }
            if (l8 == sb) sts32(sb + S_EM + warp * 4, em + (isc >> 23));
            __syncwarp();
            if (l8 == sb) mbar_arrive(sb + B_X);
            PROF(2)
        }
        uint32_t w[40][4], w2a[2], odd;
        const uint8_t *po, *pd;
        auto wo_addr = [&]() {
            const uint32_t lo = (l8 + ((s >> 2) & P.zero) - sb) >> 3;
            w2a[0] = w2o + FRAG2(lo); w2a[1] = w2o + (FRAG2(lo) ^ 32);
            po = P.xb + xg_buf(s + 1) + om + xg_lane(lo);
            pd = P.xb + xg_buf(s + 1) + os + lo * 4;
            odd = lo & 4;
            pin_ptr(po); pin_ptr(pd); pin<2>(w2a); pin<1>(&odd);
        };
        uint32_t oa = l8 * 2 + (S_OX - sb);
        if constexpr (ATT) {
            const uint32_t ln = (l8 + ((s >> 4) & P.zero) - sb) >> 3;
            const uint32_t va = sb + S_KV + 8192 + ((warp >> 1) & 1) * 4096 + ((ln & 7) + (ln >> 4) * 8) * 128 + ((((warp & 1) * 4 + ((ln >> 3) & 1)) ^ (ln & 7)) << 4);
            const uint32_t ka = sb + S_KV + (warp & 1) * 2048 + (ln & 15) * 128 + (((ln >> 4) ^ (ln & 7)) << 4);
            uint32_t ad[5] = {sb + S_SX + (ln & 3) * (8 * SROW) + (ln >> 2) * 4 + (warp < 6 ? (warp - 4) * 64 : 128 + (warp - 6) * 32), l8 + S_XV + (warp - 4) * 512,
                              l8 + S_SX + (ln >> 2) * (4 * SROW - 32), oa + (warp - 4) * 512, sb + S_ISC + (~s & 1) * 4};
            if constexpr (AB) { wo_addr(); pin<1>(&oa); }
            pin<5>(ad);
            const uint32_t sa = ad[0], sr = ad[2];
            uint32_t vf[4][4], vm[2][2], q[8][2];
            float S[8][4];
#pragma unroll
            for (int n = 0; n < 8; n++) { S[n][0] = S[n][1] = S[n][2] = S[n][3] = 0.f; }
            mbar_wait(sb + B_KVFULL, s & 1);
            if (warp < 6) {
                uint32_t kf[8][4];
#pragma unroll
                for (int k = 0; k < 8; k++) ldsm4(kf[k], (ka ^ ((k & 3) << 5)) + (k >> 2) * 4096);
#pragma unroll
                for (int i = 0; i < 4; i++) ldsm4t(vf[i], (va ^ ((i & 1) << 5)) + (i >> 1) * 2048);
                mbar_wait(sb + B_X, s & 1);
                PROF(11)
#pragma unroll
                for (int k = 0; k < 8; k++) lds64(q[k], l8 + S_X + k * 256);
#pragma unroll
                for (int k = 0; k < 8; k++) mma16816(S[k], kf[k][0], kf[k][1], kf[k][2], kf[k][3], q[k][0], q[k][1]);
#pragma unroll
                for (int k = 0; k < 4; k++) { S[k][0] = S[2 * k][0] + S[2 * k + 1][0]; S[k][1] = S[2 * k][1] + S[2 * k + 1][1]; S[k][2] = S[2 * k][2] + S[2 * k + 1][2]; S[k][3] = S[2 * k][3] + S[2 * k + 1][3]; }
                sts32(sa, __float_as_uint((S[0][0] + S[1][0]) + (S[2][0] + S[3][0])));
                sts32(sa + 4 * SROW, __float_as_uint((S[0][1] + S[1][1]) + (S[2][1] + S[3][1])));
                sts32(sa + 32, __float_as_uint((S[0][2] + S[1][2]) + (S[2][2] + S[3][2])));
                sts32(sa + 4 * SROW + 32, __float_as_uint((S[0][3] + S[1][3]) + (S[2][3] + S[3][3])));
            } else {
#pragma unroll
                for (int i = 0; i < 4; i++) ldsm4t(vf[i], (va ^ ((i & 1) << 5)) + (i >> 1) * 2048);
                uint32_t xa = l8 + S_X + (warp - 6) * 1024;
                pin<1>(&xa);
                mbar_wait(sb + B_X, s & 1);
                PROF(11)
#pragma unroll
                for (int k = 0; k < 8; k++) lds64(q[k], xa + (k >> 2) * 2048 + (k & 3) * 256);
#pragma unroll
                for (int k = 0; k < 4; k++) mma16816(S[k], q[4 + (k & 2)][0], q[4 + (k & 2)][1], q[5 + (k & 2)][0], q[5 + (k & 2)][1], q[k][0], q[k][1]);
                sts32(sa, __float_as_uint((S[0][0] + S[2][0]) + (S[1][2] + S[3][2])));
                sts32(sa + 4 * SROW, __float_as_uint((S[0][1] + S[2][1]) + (S[1][3] + S[3][3])));
            }
            lds64(vm[0], ad[1]); lds64(vm[1], ad[1] + 256);
            PROF(7)
            bar_sync(2, 160);
            const float cs = 0.08838834764831845f * 1.4426950408889634f;
            float E[6][2];
#pragma unroll
            for (int i = 0; i < 6; i++) lds64f(E[(i + 4) % 6], sr + ((i + 4) % 6) * 32);
            const uint32_t isn = lds32(ad[4]);
            E[4][0] += E[5][0]; E[4][1] += E[5][1];
            float m = fmaxf(fmaxf(fmaxf(fmaxf(E[0][0], E[0][1]), fmaxf(E[1][0], E[1][1])), fmaxf(fmaxf(E[2][0], E[2][1]), fmaxf(E[3][0], E[3][1]))), fmaxf(E[4][0], E[4][1]));
            m = fmaxf(m, __shfl_xor_sync(0xffffffffu, m, 1));
            m = fmaxf(m, __shfl_xor_sync(0xffffffffu, m, 2));
            m *= cs;
            if constexpr (AB) static_for<0, PRE3>([&](auto I) { load_w2<I.value>(w[I.value], w2a); });
            uint32_t pa[5];
#pragma unroll
            for (int i = 0; i < 5; i++) { const int k = (i + 4) % 5; E[k][0] = ex2(fmaf(E[k][0], cs, -m)); E[k][1] = ex2(fmaf(E[k][1], cs, -m)); pa[k] = pack2(E[k][0], E[k][1]); }
            if (EFENCE) sched_fence();
            float O[2][4], Z[4];
#pragma unroll
            for (int i = 0; i < 4; i++) { O[0][i] = O[1][i] = Z[i] = 0.f; }
            mma1688(Z, isn, isn, pa[4]);
            mma1688(O[0], vm[0][0], vm[0][1], pa[4]);
            mma1688(O[1], vm[1][0], vm[1][1], pa[4]);
#pragma unroll
            for (int k = 0; k < 2; k++) {
                mma16816(Z, isn, isn, isn, isn, pa[2 * k], pa[2 * k + 1]);
#pragma unroll
                for (int i = 0; i < 2; i++) mma16816(O[i], vf[2 * k + i][0], vf[2 * k + i][1], vf[2 * k + i][2], vf[2 * k + i][3], pa[2 * k], pa[2 * k + 1]);
            }
            const float i0 = rcp(Z[0]), i1 = rcp(Z[1]);
            stsm4t(ad[3], pack2(O[0][0] * i0, O[0][1] * i1), pack2(O[0][2] * i0, O[0][3] * i1), pack2(O[1][0] * i0, O[1][1] * i1), pack2(O[1][2] * i0, O[1][3] * i1));
            PROF(4)
            if constexpr (AB) wo_blocks<1, RESA, PRE3, OFENCE / 2>(w, wr + NR * 8, oa, w2a, po, pd, odd);
            else bar_arrive(3, 256);
            if (ROLE != 0) persist(s, warp, r0, r1);
            if (warp == 7 && l8 == sb) mbar_expect(sb + B_X, 4096);
        } else {
            if (ROLE != 0) persist(s, warp, r0, r1);
            wo_addr(); pin<1>(&oa);
            static_for<0, PRE2A>([&](auto I) { load_w2<I.value>(w[I.value], w2a); });
            mbar_wait(sb + B_X, s & 1);
            if (warp == 0) {
                uint32_t sc[2];
                lds64(sc, sb + S_SC);
                const int em = __reduce_max_sync(0xffffffffu, lds32(sb + S_EM + ((l8 >> 1) & 28)));
                if (l8 == sb) sts32(sb + S_ISC + (~s & 1) * 4, min(max(em - 127, (int)sc[1]) + (int)sc[0], 253) * 0x800080u);
                bar_arrive(2, 160);
            }
            wait_clocks(XDELAY - (warp == 0) * 100);
            constexpr int PRE1 = (BB - 1) * 16 - (5 - NRB) * 8 < PRE2 ? (BB - 1) * 16 - (5 - NRB) * 8 : PRE2;
            static_for<PRE2A, PRE1>([&](auto I) { load_w2<I.value>(w[I.value], w2a); });
            if (full) {
                static_for<PRE1, PRE2>([&](auto I) { load_w2<I.value>(w[I.value], w2a); });
                wo_blocks<BB, RESB, PRE2, FENCE2 * 2 + OFENCE % 2>(w, wr + NR * 8, oa, w2a, po, pd, odd);
            } else wo_blocks<BB - 1, RESB1, PRE1, FENCE2 * 2 + OFENCE % 2>(w, wr + NR * 8, oa, w2a, po, pd, odd);
        }
        PROF(5)
        if (l8 == sb) { sts32(sb + S_TO + warp * 4, gtime()); mbar_arrive(sb + B_RED); }
        if (HOLD && !(PLATE >> ATT & 1)) mbar_wait(sb + B_RED, s & 1);
        if (ROLE != 0 && (s & 3) == 3 && l8 == sb) mbar_arrive(sb + B_PERS);
        if (ROLE == 0 && s == 62) return;
    }
    __syncwarp();
    if (l8 == sb) mbar_arrive(sb + B_PERS);
}
#define IP(i)
struct Pipe { uint32_t stage, phase; };
struct Cons {
    uint32_t sb, rel;
    int wg, wq, lane, rank, pair;
    uint32_t nst;
    Pipe p;
};
__device__ __forceinline__ void pipe_next(Pipe& p) { p.stage = (p.stage + 1) & (NSTAGE - 1); p.phase ^= (p.stage == 0); }
__device__ __forceinline__ void release(const Cons& c, uint32_t stage) { if (c.lane < 2) mbar_arrive_cluster(c.rel + stage * 8); }
__device__ __forceinline__ void wait_full(const Cons& c) { mbar_wait(c.sb + B_FULL + c.p.stage * 8, c.p.phase); }

enum { PEND_NONE = 0, PEND_KVO = 1, PEND_HT = 2, PEND_OUT = 3 };
struct Pend { uint32_t pk[64]; int kind, row, col, cnt; };

__device__ __forceinline__ void staging_wait(const Cons& c) { if (c.nst) mbar_wait(c.sb + B_SFREE + c.wg * 8, (c.nst - 1) & 1); }
__device__ __forceinline__ void staging_post(Cons& c, int kind, int row, int col, int cnt) {
    __syncwarp();
    if (c.lane == 0) {
        if (c.wq == 0) { const uint32_t x[4] = {(uint32_t)kind, (uint32_t)row, (uint32_t)col, (uint32_t)cnt}; sts128(c.sb + S_DESC + c.wg * 16, x); }
        mbar_arrive(c.sb + B_SFULL + c.wg * 8);
    }
    c.nst++;
}
__device__ __forceinline__ void drain(const Params& P, Cons& c, Pend& d) {
    const uint32_t* pk = d.pk;
    if (d.kind == PEND_OUT) {
        float* o = P.out + (size_t)(d.row + c.wq * 16 + (c.lane >> 2)) * 2048 + d.col + (c.lane & 3) * 2;
#pragma unroll
        for (int j = 0; j < 16; j++) {
            st_stream2(o + j * 8, bf_lo(pk[j * 2]), bf_hi(pk[j * 2]));
            st_stream2(o + 8 * 2048 + j * 8, bf_lo(pk[j * 2 + 1]), bf_hi(pk[j * 2 + 1]));
        }
    } else {
        const bool ht = d.kind == PEND_HT;
        const int hi = (c.lane >> 3) & 1;
        const uint32_t base = c.sb + S_STG + c.wg * 16384 + ((ht ? hi * 32 + c.wq * 8 : c.wq * 16 + hi * 8) + (c.lane & 7)) * 128;
        staging_wait(c);
#pragma unroll
        for (int j = 0; j < 8; j++) {
            const int ch = (j & 3) * 2 + (c.lane >> 4);
            stsm4(base + (j >> 2) * 8192 + ((ch ^ (c.lane & 7)) << 4), pk[j * 4], pk[j * 4 + 1], pk[j * 4 + 2], pk[j * 4 + 3]);
        }
        fence_async_smem();
        staging_post(c, d.kind, d.row, d.col, (d.col & 128) ? d.cnt : -1);
    }
    if (d.col & 128) d.kind = PEND_NONE;
    d.col += 128;
#pragma unroll
    for (int i = 0; i < 32; i++) d.pk[i] = d.pk[32 + i];
}

constexpr int S_STG2 = 8 * 20480, PEND_BOTH = 8;
__device__ __forceinline__ void drain_both(Cons& c, const Pend& d) {
    const uint32_t base = c.sb + c.wg * 16384 + (c.wq * 16 + ((c.lane >> 3) & 1) * 8 + (c.lane & 7)) * 128;
#pragma unroll
    for (int j = 0; j < 16; j++)
        stsm4(base + (j < 8 ? S_STG : S_STG2) + (j >> 2 & 1) * 8192 + ((((j & 3) * 2 + (c.lane >> 4)) ^ (c.lane & 7)) << 4), d.pk[j * 4], d.pk[j * 4 + 1], d.pk[j * 4 + 2], d.pk[j * 4 + 3]);
    fence_async_smem();
    staging_post(c, PEND_KVO | PEND_BOTH, d.row, d.col, d.cnt);
}

__device__ __forceinline__ void store_warp(const Params& P, uint32_t sb, int wg, int cta) {
    if (cta < 128) {
        for (int i = 0; i < P.xd; i++) __nanosleep(1000);
        const uint32_t e1 = get_epoch(sb) + 1;
        const uint4* x = (const uint4*)P.Bx + (cta * 2 + wg) * 1024 + (threadIdx.x & 31);
        uint32_t m = 0;
#pragma unroll 4
        for (int i = 0; i < 32; i++) { const uint4 u = __ldg(x + i * 32); m = amax(amax(m, amax(u.x, u.y)), amax(u.z, u.w)); }
        m = warp_exp(m);
        if (elect_one()) { atomicMax(&g_cnt(C_XMAX), e1 << 8 | m); red_release(&g_cnt(C_XCNT)); }
        __syncwarp();
    }
    const uint32_t stg = sb + S_STG + wg * 16384;
#pragma unroll 1
    for (uint32_t n = 0;; n++) {
        mbar_wait(sb + B_SFULL + wg * 8, n & 1);
        uint32_t x[4];
        lds128(x, sb + S_DESC + wg * 16);
#pragma unroll
        for (int i = 0; i < 4; i++) x[i] = __shfl_sync(0xffffffffu, x[i], 0);
        if (x[0] == PEND_NONE) break;
        const bool ht = x[0] == PEND_HT;
        const CUtensorMap* m = &P.tm[ht ? M_HTS : M_KVO];
        const uint64_t pol = P.pol[ht ? 2 : x[1] >= 4096 ? 1 : (x[1] & 2047) < 1536 ? 0 : 10];
        if (elect_one()) {
#pragma unroll
            for (int i = 0; i < 4; i++) tma_store2d(m, x[2] + (i >> 1) * 64, x[1] + (i & 1) * (ht ? 1024 : 32), stg + i * 4096, pol);
            if (x[0] & PEND_BOTH) {
#pragma unroll 1
                for (int i = 0; i < 4; i++) tma_store2d(m, x[2] + 128 + (i >> 1) * 64, x[1] + (i & 1) * 32, stg + (S_STG2 - S_STG) + i * 4096, pol);
            }
            bulk_commit();
            bulk_wait_read();
            mbar_arrive(sb + B_SFREE + wg * 8);
            if ((int)x[3] >= 0) { bulk_wait_all(); fence_async(); red_relaxed(&g_cnt(x[3])); }
        }
        __syncwarp();
    }
}

template <int TA, int TB, bool FIRST>
__device__ __forceinline__ void issue_ktile(float* acc, const Cons& c) {
    const uint32_t a = c.sb + c.p.stage * STAGE + c.wg * 8192, b = c.sb + c.p.stage * STAGE + 16384;
    const uint64_t da = mkdesc(a, TA ? 8192 : 16, 1024, 1), db = mkdesc(b, TB ? 8192 : 16, 1024, 1);
    wg_fence();
#pragma unroll
    for (int k = 0; k < 4; k++) {
        if (FIRST && k == 0) wgmma_ss256_first<TA, TB>(acc, da, db);
        else wgmma_ss256<TA, TB>(acc, da + (TA ? 128 : 2) * k, db + (TB ? 128 : 2) * k);
    }
    wg_commit();
}
template <bool KVONLY, bool FIRST>
__device__ __forceinline__ void issue_any(float* acc, const Cons& c, int type) {
    wait_full(c);
    if (!KVONLY && type == T_A1) issue_ktile<0, 0, FIRST>(acc, c);
    else if (!KVONLY && type == T_A2) issue_ktile<1, 0, FIRST>(acc, c);
    else issue_ktile<0, 1, FIRST>(acc, c);
}
template <bool KVONLY = false>
__device__ __forceinline__ void mainloop(float* acc, const Params& P, Cons& c, Pend& d, int type, int nk) {
    issue_any<KVONLY, true>(acc, c, type);
    if (!KVONLY) { IP(0) }
    uint32_t prev = c.p.stage;
    pipe_next(c.p);
#pragma unroll 1
    for (int kt = 1; kt < nk; kt++) {
        if (!KVONLY && d.kind != PEND_NONE && kt != 2) drain(P, c, d);
        issue_any<KVONLY, false>(acc, c, type);
        wg_wait<1>();
        release(c, prev);
        prev = c.p.stage;
        pipe_next(c.p);
    }
    d.kind = PEND_NONE;
    wg_wait<0>();
    pin<128>(acc);
    release(c, prev);
    if (!KVONLY) { IP(1) }
}
__device__ __forceinline__ void pack_half(uint32_t* pk, const float* a) {
#pragma unroll
    for (int i = 0; i < 32; i++) pk[i] = pack2(a[2 * i], a[2 * i + 1]);
}

__device__ __forceinline__ void epi_kv(const float* acc, const Cons& c, Pend& d, int mb, int nb) {
    pack_half(d.pk, acc); pack_half(d.pk + 32, acc + 64);
    d.kind = PEND_KVO; d.row = (nb >> 4) * 2048 + mb * 256 + c.rank * 128 + c.wg * 64; d.col = (nb & 15) * 256; d.cnt = C_KV + mb;
}

__device__ __forceinline__ void qa_scores(float* S, float* Sm, const uint32_t* q, Cons& c) {
    wait_full(c);
    const uint32_t st = c.sb + c.p.stage * STAGE;
    const uint64_t dk = mkdesc(st + c.wg * 8192, 16, 1024, 1), dm = mkdesc(st + 32768 + c.wg * 4096, 128, 2048, 0);
    wg_fence();
#pragma unroll
    for (int i = 0; i < 8; i++) wgmma_rs64<0>(S, q + i * 4, dk + (i >> 2) * 1024 + (i & 3) * 2, i != 0);
#pragma unroll
    for (int i = 0; i < 8; i++) wgmma_rs16<0>(Sm, q + i * 4, dm + i * 16, i != 0);
    wg_commit();
    pipe_next(c.p);
}
__device__ __forceinline__ void qa_softmax(uint32_t (*pa)[4], const float* S, const float* Sm, const Cons& c) {
    const int t = c.lane & 3, i0 = (c.wq & 1) * 16 + (c.lane >> 2) - 2 * t;
    const bool sg = c.wq >= 2;
    const float cs = 0.08838834764831845f * 1.4426950408889634f;
    float x[2][10];
#pragma unroll
    for (int r = 0; r < 2; r++) {
#pragma unroll
        for (int j = 0; j < 4; j++)
#pragma unroll
            for (int e = 0; e < 2; e++) {
                const float v = sg ? S[16 + j * 4 + r * 2 + e] : S[j * 4 + r * 2 + e];
                x[r][j * 2 + e] = (j * 8 + e - r * 8 > i0) ? -1e9f / 0.08838834764831845f : v;
            }
        x[r][8] = sg ? Sm[4 + r * 2] : Sm[r * 2];
        x[r][9] = sg ? Sm[5 + r * 2] : Sm[1 + r * 2];
        float m = fmaxf(fmaxf(fmaxf(fmaxf(x[r][0], x[r][1]), fmaxf(x[r][2], x[r][3])), fmaxf(fmaxf(x[r][4], x[r][5]), fmaxf(x[r][6], x[r][7]))), fmaxf(x[r][8], x[r][9]));
        m = fmaxf(m, __shfl_xor_sync(0xffffffffu, m, 1));
        m = fmaxf(m, __shfl_xor_sync(0xffffffffu, m, 2));
        m *= -cs;
#pragma unroll
        for (int i = 0; i < 10; i++) x[r][i] = ex2(fmaf(x[r][i], cs, m));
        float sum = (((x[r][0] + x[r][1]) + (x[r][2] + x[r][3])) + ((x[r][4] + x[r][5]) + (x[r][6] + x[r][7]))) + (x[r][8] + x[r][9]);
        sum += __shfl_xor_sync(0xffffffffu, sum, 1);
        sum += __shfl_xor_sync(0xffffffffu, sum, 2);
        const float inv = rcp(sum);
#pragma unroll
        for (int i = 0; i < 10; i++) x[r][i] *= inv;
    }
#pragma unroll
    for (int ks = 0; ks < 2; ks++)
#pragma unroll
        for (int i = 0; i < 4; i++) {
            const uint32_t p = pack2(x[i & 1][ks * 4 + (i >> 1) * 2], x[i & 1][ks * 4 + (i >> 1) * 2 + 1]);
            pa[ks][i] = sg ? 0u : p;
            pa[2 + ks][i] = sg ? p : 0u;
        }
#pragma unroll
    for (int r = 0; r < 2; r++) {
        const uint32_t p = pack2(x[r][8], x[r][9]);
        pa[4][r] = sg ? 0u : p;
        pa[4][2 + r] = sg ? p : 0u;
    }
}
__device__ __forceinline__ void qa_values(float* O, uint32_t (*pa)[4], Cons& c) {
    wait_full(c);
    const uint32_t st = c.sb + c.p.stage * STAGE;
    const uint64_t dv = mkdesc(st + c.wg * 8192, 16384, 1024, 1), dm = mkdesc(st + 32768 + c.wg * 4096, 2048, 128, 0);
    pin<20>(&pa[0][0]);
    wg_fence();
#pragma unroll
    for (int ks = 0; ks < 4; ks++) wgmma_rs128<1>(O, pa[ks], dv + ks * 128, ks != 0);
    wgmma_rs128<0>(O, pa[4], dm, 1);
    wg_commit();
    pipe_next(c.p);
}
__device__ __forceinline__ void epi_qa(const float* acc, Cons& c, Pend& d, int mb, int nb) {
    uint32_t q[64], pa[2][5][4];
    float S0[32] = {}, M0[8] = {}, S1[32] = {}, M1[8] = {}, O0[64] = {}, O1[64] = {};
    const uint32_t k0 = c.p.stage;
    pack_half(q, acc);
    pin<32>(q); pin<32>(S0); pin<8>(M0);
    qa_scores(S0, M0, q, c);
    pack_half(q + 32, acc + 64);
    pin<32>(q + 32); pin<32>(S1); pin<8>(M1);
    qa_scores(S1, M1, q + 32, c);
    wg_wait<1>();
    pin<32>(S0); pin<8>(M0);
    release(c, k0);
    qa_softmax(pa[0], S0, M0, c);
    wg_wait<0>();
    pin<32>(S1); pin<8>(M1); pin<64>(q);
    release(c, (k0 + 1) & (NSTAGE - 1));
    pin<64>(O0);
    qa_values(O0, pa[0], c);
    qa_softmax(pa[1], S1, M1, c);
    pin<64>(O1);
    qa_values(O1, pa[1], c);
    wg_wait<1>();
    pin<64>(O0); pin<20>(&pa[0][0][0]);
    release(c, (k0 + 2) & (NSTAGE - 1));
    pack_half(d.pk, O0);
    wg_wait<0>();
    pin<64>(O1); pin<20>(&pa[1][0][0]);
    release(c, (k0 + 3) & (NSTAGE - 1));
    pack_half(d.pk + 32, O1);
    d.kind = PEND_KVO; d.row = 4096 + mb * 256 + c.rank * 128 + c.wg * 64; d.col = nb * 256; d.cnt = C_O + mb * 16 + nb;
}

__device__ __forceinline__ void epi_op(const float* acc, const Cons& c, Pend& d, int mb, int nb) {
    pack_half(d.pk, acc); pack_half(d.pk + 32, acc + 64);
    d.kind = PEND_OUT; d.row = mb * 256 + c.rank * 128 + c.wg * 64; d.col = 1024 + nb * 256;
}

__device__ __forceinline__ void epi_a2(float* acc, const Params& P, Cons& c, int mb, int col0) {
    const int g = c.lane >> 2, t = c.lane & 3;
    const int row = mb * 256 + (g >> 1) * 64 + (c.rank * 16 + c.wg * 8 + c.wq * 2) * 2 + (g & 1);
    float* o = P.out + (size_t)row * 2048 + col0 + t * 2;
#pragma unroll 1
    for (int hf = P.zero; hf < 2; hf++) {
    wait_full(c);
    const uint32_t st = c.sb + c.p.stage * STAGE, xa = st + (c.wg * 64 + c.wq * 16 + g) * 128 + t * 4 + (g << 4), da = st + 32768 + t * 4;
#pragma unroll
    for (int j = 0; j < 16; j++) {
        const float* a = acc + j * 4;
        const uint32_t ad = (xa ^ ((j & 7) << 4)) + (j >> 3) * 16384;
        const uint32_t x0 = lds32(ad), x1 = lds32(ad + 1024), dv = lds32(da + j * 16);
        const uint32_t u0 = mul_bf2(x0, dv), u1 = mul_bf2(x1, dv);
        st_stream2(o + j * 8, a[0] + bf_lo(u0), a[1] + bf_hi(u0));
        st_stream2(o + 2 * 2048 + j * 8, a[2] + bf_lo(u1), a[3] + bf_hi(u1));
    }
    __syncwarp();
    release(c, c.p.stage);
    pipe_next(c.p);
    o += 128;
#pragma unroll
    for (int i = 0; i < 64; i++) acc[i] = acc[64 + i];
    }
}

#define TSTAMP(i)
__device__ __forceinline__ float2 cmul(float2 a, float2 b) { return make_float2(fmaf(a.x, b.x, -a.y * b.y), fmaf(a.x, b.y, a.y * b.x)); }
__device__ __forceinline__ float2 cfma(float2 a, float2 b, float2 u) { return make_float2(fmaf(a.x, b.x, fmaf(-a.y, b.y, u.x)), fmaf(a.x, b.y, fmaf(a.y, b.x, u.y))); }
__device__ __forceinline__ float4 ssm_coef(float lre, float lim, float logdt) {
    const float dt = __bfloat162float(__float2bfloat16(expf(logdt)));
    const float ea = expf(dt * lre);
    float sn, cn;
    sincosf(dt * lim, &sn, &cn);
    const float br = ea * cn, bi = ea * sn, nr = br - 1.f;
    const bool sw = fabsf(lre) < fabsf(lim);
    const float big = sw ? lim : lre, r = __fdividef(sw ? lre : lim, big), inv = __fdividef(1.f, fmaf(sw ? lre : lim, r, big));
    const float cr = (sw ? fmaf(nr, r, bi) : fmaf(bi, r, nr)) * inv, ci = (sw ? fmaf(bi, r, -nr) : fmaf(-nr, r, bi)) * inv;
    return make_float4(br, bi, cr, ci);
}
__device__ __forceinline__ void epi_a1(const float* acc, const Params& P, const Cons& c, Pend& d, int mb, int nb) {
    const uint32_t atag = (get_epoch(c.sb) + 1) & 1;
    const int t = c.lane & 3;
    const int p = nb * 128 + c.rank * 64 + c.wg * 32 + c.wq * 8 + (c.lane >> 2);
    const float4 cf = __ldcg(&g_coef[p]);
    const float2 lam = make_float2(cf.x, P.swap_ri ? -cf.y : cf.y);
    const float a0 = P.swap_ri ? -2.f * cf.w : 2.f * cf.z, a1 = P.swap_ri ? 2.f * cf.z : -2.f * cf.w;
    const float b0 = P.swap_ri ? -2.f * cf.z : -2.f * cf.w, b1 = P.swap_ri ? -2.f * cf.w : -2.f * cf.z;
    float2 h = make_float2(0.f, 0.f);
#pragma unroll
    for (int round = 0; round < 2; round++) {
#pragma unroll
        for (int j = 0; j < 32; j++) {
            h = cfma(lam, h, make_float2(acc[j * 4], acc[j * 4 + 2]));
            const float r0 = fmaf(a0, h.x, a1 * h.y), m0 = fmaf(b0, h.x, b1 * h.y);
            h = cfma(lam, h, make_float2(acc[j * 4 + 1], acc[j * 4 + 3]));
            d.pk[j * 2] = pack2(r0, fmaf(a0, h.x, a1 * h.y));
            d.pk[j * 2 + 1] = pack2(m0, fmaf(b0, h.x, b1 * h.y));
        }
        if (round) break;
        float2 l64 = lam;
#pragma unroll
        for (int i = 0; i < 6; i++) l64 = cmul(l64, l64);
        const float2 l128 = cmul(l64, l64), l256 = cmul(l128, l128);
        float2 o = make_float2(__shfl_up_sync(0xffffffffu, h.x, 1), __shfl_up_sync(0xffffffffu, h.y, 1));
        if (t >= 1) h = cfma(l64, o, h);
        o = make_float2(__shfl_up_sync(0xffffffffu, h.x, 2), __shfl_up_sync(0xffffffffu, h.y, 2));
        if (t >= 2) h = cfma(l128, o, h);
        IP(2)
        if (t == 3) st_relaxed2(&g_agg[mb * 1024 + p], (__float_as_uint(h.x) & ~1u) | atag, __float_as_uint(h.y));
        h = make_float2(__shfl_up_sync(0xffffffffu, h.x, 1), __shfl_up_sync(0xffffffffu, h.y, 1));
        if (t == 0) h = make_float2(0.f, 0.f);
        uint32_t ax[7], ay[7];
        while (true) {
            uint32_t bad = 0;
#pragma unroll
            for (int j = 0; j < 7; j++) { ax[j] = atag; ay[j] = 0; ld_relaxed2_if(ax[j], ay[j], &g_agg[j * 1024 + p], j < mb); }
#pragma unroll
            for (int j = 0; j < 7; j++) bad |= ax[j] ^ atag;
            if (tags_ok(bad)) break;
            __nanosleep(2 * POLLNS);
        }
        float2 carry = make_float2(0.f, 0.f);
#pragma unroll
        for (int j = 0; j < 7; j++) if (j < mb) carry = cfma(l256, carry, make_float2(__uint_as_float(ax[j]), __uint_as_float(ay[j])));
        float2 w = (t & 1) ? l64 : make_float2(1.f, 0.f);
        if (t & 2) w = cmul(w, l128);
        h = cfma(w, carry, h);
        IP(3)
    }
    IP(4)
    d.kind = PEND_HT; d.row = nb * 128 + c.rank * 64 + c.wg * 32; d.col = mb * 256; d.cnt = C_HT + mb * 16 + nb;
}

__device__ __forceinline__ uint32_t fresh_tid() { uint32_t t; asm volatile("mov.u32 %0, %%tid.x;" : "=r"(t)); return t; }
__device__ __forceinline__ uint32_t acquire_stage(uint32_t sb, Pipe& p, uint32_t bytes) {
    mbar_wait(sb + B_EMPTY + p.stage * 8, p.phase ^ 1);
    mbar_expect_e(sb + B_FULL + p.stage * 8, bytes);
    return p.stage;
}
__device__ __forceinline__ void producer(const Params& P, const uint32_t sb, const int cta) {
    Pipe p = {0, 0};
    uint32_t resume = 1;
    const int rank = cta & 1;
    const uint16_t both = 3 << (__shfl_sync(0xffffffffu, cluster_rank(), 0) & ~1u);
    for (int it = ITEM_OFF(cta >> 1), item = 0; !(item & LAST); it++) {
        item = ITEM(it);
        const int type = (item >> 8) & 7, mb = (item >> 5) & 7, nb = item & 31, half = item >> 12 & 1, hw = item >> 13 & 1;
        const uint32_t epoch = type ? get_epoch(sb) : 0, e1 = epoch + 1;
        if (type == T_CHAIN) {
            const int h = cta / 3, role = cta - h * 3;
#pragma unroll 1
            for (int w = 0; w < 8; w++) {
                mbar_wait(sb + B_EMPTY + (w * 20480 + 20479) / STAGE * 8, 1);
                chain_load(P, sb, cta, w, threadIdx.x & 31, 0);
            }
            uint32_t* flag = &g_cnt(C_FLAG + (role == 2 ? 32 : 0) + h);
            if (role) { wait_count(&g_cnt(C_KV), e1 * 128); fence_async(); }
#pragma unroll 1
            for (int s = 0; s < 63 && role != 0; s++) {
                {
                    mbar_wait(sb + B_GO, s & 1);
                    tma3d_mc_e(sb + S_KV + (role - 1) * 8192, &P.tm[M_SEG], 0, (role - 1) * 2048 + s * 32, h * 2, sb + B_KVFULL, 7 << ((h & 1) * 3), P.pol[s < 48 ? 8 : 11]);
                    if ((s & 7) == 7) { wait_count(&g_cnt(C_KV + 1 + (s >> 3)), e1 * 128); fence_async(); }
                    tma_prefetch3d_e(&P.tm[M_SEG], 0, (role - 1) * 2048 + s * 32 + 32, h * 2);
                }
                if (s > 0 && (s & 3) == 0) {
                    const int i = (s - 1) >> 2;
                    mbar_wait(sb + B_PERS, i & 1);
                    asm volatile("{\n.reg .pred E;\nelect.sync _|E, 0xffffffff;\n@E st.release.gpu.global.u32 [%0], %1;\n}" ::"l"(flag), "r"(epoch * 64 + i * 4 + 4) : "memory");
                }
            }
            if (role == 0) {
                const int lane = threadIdx.x & 31;
                if (lane == 0) mbar_arrive(sb + B_RELM);
#pragma unroll 1
                for (int s = 0; s < 63; s++) {
                    mbar_wait(sb + B_P1, s & 1);
                    if (s > 0) {
                        st_relaxed4(P.xb + xg_buf(s - 1) + h * 2048 + xg_lane(lane), 0, 0, 0, 0);
                        st_relaxed1(P.xb + xg_buf(s - 1) + xg_side(h) + lane * 4, 0);
                        __threadfence();
                    }
                    __syncwarp();
                    if (lane == 0) mbar_arrive(sb + B_RELM);
                }
            }
            if ((threadIdx.x & 31) < M_C1 - 1) asm volatile("prefetch.tensormap [%0];" ::"l"(&P.tm[1 + (threadIdx.x & 31)]) : "memory");
            resume = 0;
            continue;
        }
        const int m0 = mb * 256 + rank * 128, ssm = type >= T_A1;
        const CUtensorMap* ma = &P.tm[max(type, 1) + half * M_HALF];
        const CUtensorMap* mw = &P.tm[type ? M_WV + type : M_WK + (nb >> 4)];
        const int nk = type == T_OP ? 64 : type == T_A2 ? 32 : 16;
        const int a3 = type == T_A1 ? nb * 16 + rank * 8 + hw * 4 : type == T_A2 ? mb * 4 + rank * 2 + hw : (type == T_OP ? 4096 : 0) + m0 + hw * 64;
        const int b3 = type == T_A1 ? mb * 128 + rank * 16 : type == T_A2 ? (nb * 2 + rank) * 128 : (nb & 15) * 4 + rank * 2;
        if (type & 1) {
            wait_count(&g_cnt(type == T_A1 ? C_COEF : C_KV + mb), e1 * (type == T_A1 ? 4 : 128));
            fence_async();
        }
        uint32_t ready = type == T_OP || type == T_A2 ? 0 : ~0u;
        if (type == T_A1) l2_prefetch_e(g_coef + nb * 128 + rank * 64, 1024);
        auto arrived = [&]() {
            const uint32_t t = fresh_tid();
            return __all_sync(0xffffffffu, (int32_t)(ld_acquire(&g_cnt(C_FLAG + (t & 2) * 16 + nb * 2 + (t & 1))) - (epoch * 64 + mb * 8 + rank * 4 + 4)) >= 0);
        };
        bool passed = false;
        mbar_wait(sb + B_RESUME, resume);
#pragma unroll 1
        for (int kt = 0; kt < nk; kt++) {
            if (type == T_QA && kt == 9) passed = arrived();
            while (~ready & (ssm ? 2 | 1 << ((kt & 15) >> 1) : 1 << (kt >> 2))) {
                if (ready) __nanosleep(POLLNS);
                ready = __ballot_sync(0xffffffffu, (int32_t)(ld_acquire(&g_cnt(type * 64 + mb * 16 + (fresh_tid() & 15))) - e1 * 4) >= 0) | 1u << 31;
                fence_async();
            }
            const uint32_t st = acquire_stage(sb, p, STAGE - half * 8192), bar = sb + B_FULL + st * 8;
            const int a1 = type == T_A2 ? kt * 64 : 0, b0 = ssm ? (kt & 15) * 64 : 0;
            tma4d_e(sb + st * STAGE + hw * 8192, ma, kt * 64 - a1, a1, a3, bar, P.pol[11]);
            tma4d_mc_e(sb + st * STAGE + 16384 + rank * 16384, mw + (ssm & kt >> 4), b0, ssm ? 0 : kt * 64, b3, bar, both, P.pol[(item & 0x7e0) == 224 ? 9 : 11]);
            if (type == T_QA && kt < 8) tma_prefetch4d_e(&P.tm[M_OA], nb * 256 + (kt & 3) * 64, (kt >> 2) * 2048 + m0);
            pipe_next(p);
        }
        if (type == T_QA) {
            while (!passed) { passed = arrived(); if (!passed) __nanosleep(POLLNS); }
            fence_async();
        }
        const int q = type == T_QA;
#pragma unroll 1
        for (int e = 0; e < (q ? 4 : type == T_A2 ? 2 : 0); e++) {
            const uint32_t st = acquire_stage(sb, p, q ? 40960 : 32768 + 256), bar = sb + B_FULL + st * 8, dst = sb + st * STAGE;
#pragma unroll 1
            for (int i = 0; i < 2; i++) tma4d_e(dst + i * 16384, &P.tm[q ? M_OA : M_AX], nb * 256 + (e & 1) * 128 + i * 64, 0, q ? (e >> 1) * 2048 + m0 : mb * 128 + rank * 16, bar, P.pol[q ? 3 : 11]);
            const uint8_t* src = q ? (const uint8_t*)(((e >> 1) ? g_vmt : g_km) + ((mb * 8 + rank * 4) * 32 + nb * 2 + (e & 1)) * 512) : (const uint8_t*)(P.Dskip + nb * 256 + e * 128);
#pragma unroll 1
            for (int i = 0; i < (q ? 4 : 1); i++) bulk_g2s_e(dst + 32768 + i * 2048, src + i * 65536, q ? 2048 : 256, bar);
            pipe_next(p);
        }
    }
#pragma unroll 1
    for (int i = 0; i < NSTAGE; i++) { mbar_wait(sb + B_EMPTY + p.stage * 8, p.phase ^ 1); pipe_next(p); }
}

__device__ __forceinline__ uint32_t fresh_ctaid() { uint32_t t; asm volatile("mov.u32 %0, %%ctaid.x;" : "=r"(t)); return t; }
__device__ __forceinline__ void reset_state(const Params& P, Cons& c, Pend& d, uint32_t sb, bool resumed) {
    const uint32_t t = fresh_tid(), b = fresh_ctaid() + P.cta0;
    const int w = __shfl_sync(0xffffffffu, t >> 5, 0);
    c.sb = sb; c.wg = w >> 2; c.wq = w & 3; c.lane = t & 31;
    c.rank = __shfl_sync(0xffffffffu, b & 1, 0); c.pair = __shfl_sync(0xffffffffu, b >> 1, 0);
    c.rel = mapa(sb + B_EMPTY, cluster_rank() ^ (c.lane & 1));
    c.p.stage = 0; c.p.phase = 0;
    c.nst = resumed && c.pair < NCHAIN;
    d = Pend{};
}
#define PROF_ITEM(i, item)

__global__ void __launch_bounds__(384, 1) fused_kernel(const __grid_constant__ Params P) {
    extern __shared__ __align__(1024) uint8_t smem[];
    const uint32_t sb = smem_u32(smem);
    asm volatile("griddepcontrol.launch_dependents;");
    declare_fence(P.zero);
    const int tid = threadIdx.x, lane = tid & 31;
    const int warp = __shfl_sync(0xffffffffu, tid >> 5, 0);
    const int cta = __shfl_sync(0xffffffffu, blockIdx.x + P.cta0, 0), pair = cta >> 1, rank = cta & 1;
    if (tid == 0) {
        if (sb & 1023) spin_fault();
        for (int i = 0; i < NSTAGE; i++) { mbar_init(sb + B_FULL + i * 8, 1); mbar_init(sb + B_EMPTY + i * 8, 16); }
        mbar_init(sb + B_RESUME, 2);
        mbar_init(sb + B_KVFULL, 1);
        mbar_init(sb + B_GO, 3); mbar_init(sb + B_RED, 8); mbar_init(sb + B_P1, 1); mbar_init(sb + B_EPOCH, 1); mbar_init(sb + B_PERS, 8); mbar_init(sb + B_INIT, 8); mbar_init(sb + B_INIT2, 8);
        mbar_init(sb + B_READY, 8);
        for (int i = 0; i < 2; i++) { mbar_init(sb + B_SFULL + i * 8, 4); mbar_init(sb + B_SFREE + i * 8, 1); }
        mbar_init(sb + B_RELM, cta % 3 ? 1 : 2); mbar_init(sb + B_X, 9);
        mbar_init(sb + B_DONE, 2);
        mbar_expect(sb + B_X, 4096);
        sts64(sb + S_EV, 0, 0);
        asm volatile("fence.mbarrier_init.release.cluster;" ::: "memory");
    }
    __syncthreads();
    cluster_sync();
    if (warp >= 8) {
        asm volatile("setmaxnreg.dec.sync.aligned.u32 24;");
        if (warp == 8) {
            producer(P, sb, cta);
        } else if (warp == 9) {
            const uint32_t epoch = __shfl_sync(0xffffffffu, ld_acquire(&g_cnt(C_EPOCH)), 0);
            if (lane == 0) { sts32(sb + S_EPOCH, epoch); mbar_arrive(sb + B_EPOCH); red_release(&g_cnt(C_READ)); }
            __syncwarp();
            if (pair < NCHAIN) pacer(P, sb, cta, lane, epoch);
            if (pair < NCHAIN && cta % 3) {
                mbar_wait_bounded(sb + B_PERS, 1);
                if (lane == 0) asm volatile("st.release.gpu.global.u32 [%0], %1;" ::"l"(&g_cnt(C_FLAG + (cta % 3 == 2 ? 32 : 0) + cta / 3)), "r"(epoch * 64 + 64) : "memory");
            }
            if (cta == 0 && lane == 0) {
                for (int n = 0; (int32_t)(ld_acquire(&g_cnt(C_READ)) - (epoch + 1) * (NPAIR * 2)) < 0; n++) if (n > SPIN_LIMIT) spin_fault();
                st_relaxed1(&g_cnt(C_EPOCH), epoch + 1);
            }
            __syncwarp();
            mbar_wait_bounded(sb + B_DONE, 0);
        } else {
            store_warp(P, sb, warp - 10, cta);
        }
    } else {
        asm volatile("setmaxnreg.inc.sync.aligned.u32 240;");
        Cons c;
        Pend d;
        if (pair < NCHAIN) {
            reset_state(P, c, d, sb, false);
            {
                const int item = ITEM(ITEM_OFF(pair));
                PROF_ITEM(0, item)
                float acc[128];
                mainloop<true>(acc, P, c, d, T_KV, 16);
                ISTAMP(4)
                epi_kv(acc, c, d, (item >> 5) & 7, item & 31);
            }
            ISTAMP(9)
            mbar_wait(sb + B_EMPTY + 3 * 8, 1);
            drain_both(c, d);
            ISTAMP(10)
            uint32_t wr[40][4];
            chain_fetch(P, sb, cta, warp, lane, wr);
            PROF_ITEM(1, T_CHAIN << 8)
            chain_bounds(sb, cta, warp, lane, wr);
            ISTAMP(11)
            if (warp < 4) chain_role<false>(P, sb, cta, warp, lane, wr);
            else chain_role<true>(P, sb, cta, warp, lane, wr);
            ISTAMP(14)
            bar_sync(1, 256);
            ISTAMP(15)
            const uint32_t t2 = fresh_tid();
            if (t2 < 2) mbar_arrive_cluster(mapa(sb + B_RESUME, cluster_rank() ^ t2));
        } else if (pair >= NPAIR - 2) {
            const int ch = (pair - (NPAIR - 2)) * 512 + rank * 256 + tid;
            g_coef[ch] = ssm_coef(__bfloat162float(P.Lre[ch]), __bfloat162float(P.Lim[ch]), __bfloat162float(P.logdt[ch]));
            bar_sync(1, 256);
            if (tid == 0) red_release(&g_cnt(C_COEF));
        }
        reset_state(P, c, d, sb, true);
        int it = ITEM_OFF(c.pair) + (c.pair < NCHAIN ? 2 : 0);
        for (int prev = c.pair < NCHAIN ? ITEM(it - 1) : 0;; prev = ITEM(it++)) {
            const bool last = prev & LAST;
            const int item = ITEM(it), type = (item >> 8) & 7, mb = (item >> 5) & 7, nb = item & 31;
            const bool idle = (item >> 12 & 3) == 3 - 2 * c.wg;
            if (d.kind != PEND_NONE && ((prev & (LAST | URGENT)) || idle || (type != T_KV && !bar_and(5 + c.wg, mbar_try(sb + B_FULL + c.p.stage * 8, c.p.phase))))) {
#pragma unroll 1
                while (d.kind != PEND_NONE) drain(P, c, d);
            }
            if (last) break;
            const int nk = type == T_OP ? 64 : type == T_A2 ? 32 : 16;
            PROF_ITEM(it - ITEM_OFF(c.pair), item)
            if (idle) {
#pragma unroll 1
                for (int kt = nk + (type == T_A2 ? 2 : type == T_QA ? 4 : 0); kt > 0; kt--) { wait_full(c); release(c, c.p.stage); pipe_next(c.p); }
                continue;
            }
            float acc[128];
            mainloop(acc, P, c, d, type, nk);
            if (type == T_KV) epi_kv(acc, c, d, mb, nb);
            else if (type == T_QA) epi_qa(acc, c, d, mb, nb);
            else if (type == T_OP) epi_op(acc, c, d, mb, nb);
            else if (type == T_A1) epi_a1(acc, P, c, d, mb, nb);
            else epi_a2(acc, P, c, mb, nb * 256);
        }
        staging_wait(c);
        staging_post(c, PEND_NONE, 0, 0, 0);
        if (c.wq == 0 && c.lane == 0) mbar_arrive(sb + B_DONE);
    }
}

typedef CUresult (*EncodeFn)(CUtensorMap*, CUtensorMapDataType, cuuint32_t, void*, const cuuint64_t*, const cuuint64_t*, const cuuint32_t*, const cuuint32_t*,
                             CUtensorMapInterleave, CUtensorMapSwizzle, CUtensorMapL2promotion, CUtensorMapFloatOOBfill);
void encode(EncodeFn fn, CUtensorMap* m, const void* base, int rank, const uint64_t* dims, const uint64_t* strides, const uint32_t* box, CUtensorMapSwizzle swz = CU_TENSOR_MAP_SWIZZLE_128B) {
    cuuint64_t d[5], s[5]; cuuint32_t b[5], e[5];
    for (int i = 0; i < rank; i++) { d[i] = dims[i]; b[i] = box[i]; e[i] = 1; if (i) s[i - 1] = strides[i - 1]; }
    fn(m, CU_TENSOR_MAP_DATA_TYPE_BFLOAT16, rank, (void*)base, d, s, b, e, CU_TENSOR_MAP_INTERLEAVE_NONE, swz,
       CU_TENSOR_MAP_L2_PROMOTION_L2_256B, CU_TENSOR_MAP_FLOAT_OOB_FILL_NONE);
}
void map_kmajor(EncodeFn fn, CUtensorMap* m, const void* base, uint64_t rows, uint64_t cols, uint32_t box_rows) {
    const uint64_t d[4] = {cols, 1, 1, rows}, s[3] = {cols * 2, cols * 2, cols * 2}; const uint32_t b[4] = {64, 1, 1, box_rows};
    encode(fn, m, base, 4, d, s, b);
}
void map_mnmajor(EncodeFn fn, CUtensorMap* m, const void* base, uint64_t krows, uint64_t cols, uint32_t groups = 2) {
    const uint64_t d[4] = {64, krows, 1, cols / 64}, s[3] = {cols * 2, 128, 128}; const uint32_t b[4] = {64, 64, 1, groups};
    encode(fn, m, base, 4, d, s, b);
}
void map_store(EncodeFn fn, CUtensorMap* m, const void* base, uint64_t rows, uint64_t cols) {
    const uint64_t d[2] = {cols, rows}, s[1] = {cols * 2}; const uint32_t b[2] = {64, 32};
    encode(fn, m, base, 2, d, s, b);
}

}

extern "C" void kernel_launch(void* const* d_in, const int* in_sizes, int n_in, void* d_out, int out_size) {
    static Params P;
    static EncodeFn fn = nullptr;
    if (!fn) {
        cudaDriverEntryPointQueryResult q;
        cudaGetDriverEntryPoint("cuTensorMapEncodeTiled", (void**)&fn, cudaEnableDefault, &q);
        cudaFuncSetAttribute(fused_kernel, cudaFuncAttributeMaxDynamicSharedMemorySize, S_TOTAL);
    }
    const bf16* in[15];
    for (int i = 0; i < 15; i++) in[i] = (const bf16*)d_in[i];
    void *kvo, *ht;
    cudaGetSymbolAddress(&kvo, g_kvo);
    cudaGetSymbolAddress(&ht, g_ht);
    map_kmajor(fn, &P.tm[M_BX], in[9], 2048, 1024, 128);
    map_mnmajor(fn, &P.tm[M_WQ], in[11], 1024, 4096);
    map_mnmajor(fn, &P.tm[M_WK], in[12], 1024, 4096);
    map_mnmajor(fn, &P.tm[M_WV], in[13], 1024, 4096);
    map_mnmajor(fn, &P.tm[M_WO], in[14], 4096, 1024);
    map_kmajor(fn, &P.tm[M_OA], kvo, 3 * 2048, 4096, 128);
    P.swap_ri = in[4] < in[3];
    {
        const bf16* lo = P.swap_ri ? in[4] : in[3];
        const uint64_t diff = (uint64_t)((const char*)(P.swap_ri ? in[3] : in[4]) - (const char*)lo);
        const uint64_t d[4] = {1024, 8, 2, 128}, s[3] = {2048, diff, 16384}; const uint32_t b[4] = {64, 8, 2, 8}, bh[4] = {64, 8, 2, 4};
        encode(fn, &P.tm[M_AB], lo, 4, d, s, b);
        encode(fn, &P.tm[M_AB + M_HALF], lo, 4, d, s, bh);
    }
    {
        const uint64_t d[4] = {1024, 2, 4, 1024}, s[3] = {2048, 64 * 2048, 4096}; const uint32_t b[4] = {64, 2, 4, 16};
        encode(fn, &P.tm[M_AX], in[0], 4, d, s, b);
    }
    map_mnmajor(fn, &P.tm[M_HT], ht, 2048, 2048);
    map_kmajor(fn, &P.tm[M_CRE], in[5], 1024, 1024, 128);
    map_kmajor(fn, &P.tm[M_CIM], in[6], 1024, 1024, 128);
    map_store(fn, &P.tm[M_KVO], kvo, 3 * 2048, 4096);
    map_store(fn, &P.tm[M_HTS], ht, 2048, 2048);
    map_kmajor(fn, &P.tm[M_BX + M_HALF], in[9], 2048, 1024, 64);
    map_kmajor(fn, &P.tm[M_OA + M_HALF], kvo, 3 * 2048, 4096, 64);
    map_mnmajor(fn, &P.tm[M_HT + M_HALF], ht, 2048, 2048, 1);
    for (int i = 0; i < 3; i++) {
        const uint64_t d[3] = {64, 1024, 64}, s[2] = {8192, 128}; const uint32_t b[3] = {64, 16, 2};
        encode(fn, &P.tm[M_C1 + i], in[11 + i], 3, d, s, b);
    }
    {
        const uint64_t d[2] = {1024, 4096}, s[1] = {2048}; const uint32_t b[2] = {32, 32};
        encode(fn, &P.tm[M_CO], in[14], 2, d, s, b, CU_TENSOR_MAP_SWIZZLE_64B);
    }
    {
        const uint64_t d[3] = {64, 3 * 2048, 64}, s[2] = {8192, 128}; const uint32_t b[3] = {64, 32, 2};
        encode(fn, &P.tm[M_SEG], kvo, 3, d, s, b);
    }
    void* xs;
    cudaGetSymbolAddress(&xs, g_x);
    P.xb = (uint8_t*)(((uintptr_t)xs + (2u << 20) - 1) & ~(uintptr_t)((2u << 20) - 1));
    P.Wq = in[11]; P.Wk = in[12]; P.Wv = in[13]; P.Wo = in[14]; P.mem0 = in[10]; P.Bx = in[9];
    P.Ax = in[0]; P.Lre = in[1]; P.Lim = in[2]; P.logdt = in[7]; P.Dskip = in[8];
    P.out = (float*)d_out;
    int pv[10] = {1180, 0, 110, 0, 330, 0, 32, 32, 0, 0};
    int ef = 779;
    for (int i = 0; i < 12; i++) P.pol[i] = (ef >> i & 1) ? 0x12F0000000000000ull : 0x1000000000000000ull;
    P.dly = pv[0]; P.mrg = pv[2];
    P.rd = pv[4]; P.guard = pv[5]; P.clampv = pv[6]; P.clamp0 = pv[7]; P.kvd = pv[9]; P.xd = pv[8];
    cudaLaunchConfig_t cfg = {};
    cudaLaunchAttribute at[2];
    cfg.blockDim = dim3(384); cfg.dynamicSmemBytes = S_TOTAL; cfg.stream = cudaStreamPerThread; cfg.attrs = at;
    at[0].id = cudaLaunchAttributeClusterDimension;
    at[0].val.clusterDim.y = at[0].val.clusterDim.z = 1;
    at[1].id = cudaLaunchAttributeProgrammaticStreamSerialization;
    at[1].val.programmaticStreamSerializationAllowed = 1;
    for (int i = 0; i < 2; i++) {
        P.cta0 = i ? 2 * NCHAIN : 0;
        cfg.gridDim = dim3(i ? 2 * (NPAIR - NCHAIN) : 2 * NCHAIN);
        at[0].val.clusterDim.x = i ? 2 : 6;
        cfg.numAttrs = 1 + i;
        cudaLaunchKernelEx(&cfg, fused_kernel, P);
    }
}
```

```cpp
#include <cuda_runtime.h>
#include <cuda_bf16.h>
#include <cuda.h>
#include <stdint.h>
#include <string.h>

typedef __nv_bfloat16 bf16;

namespace {

constexpr int SPIN_LIMIT = 1 << 22;
#define POLLNS 100
constexpr int NPAIR = 66;
constexpr int NCHAIN = 48;
enum { T_KV = 0, T_QA = 1, T_OP = 2, T_A1 = 3, T_A2 = 4, T_CHAIN = 5 };
constexpr int URGENT = 2048;
constexpr int LAST = 16384;
constexpr int HALF = 4096;
enum { M_BX = 1, M_OA, M_AB, M_HT, M_HALF = 4, M_WK = 9, M_WV, M_WQ, M_WO, M_AX, M_CRE, M_CIM, M_KVO, M_HTS, M_C1, M_CO = M_C1 + 3, M_SEG, M_COUNT };
enum { C_KV = 0, C_O = 128, C_HT = 256, C_READ = 24, C_EPOCH = 25, C_COEF = 26, C_XMAX = 27, C_XCNT = 28, C_FLAG = 32 };

struct Params {
    CUtensorMap tm[M_COUNT];
    const bf16 *Wq, *Wk, *Wv, *Wo, *mem0, *Bx, *Ax, *Lre, *Lim, *logdt, *Dskip;
    float* out;
    uint8_t* xb;
    int swap_ri, zero;
    int dly, mrg, rd, guard, clampv, clamp0, kvd, xd;
    uint64_t pol[12];
    uint16_t cta0;
};

__constant__ uint16_t c_off[67] = {0, 4, 8, 14, 20, 26, 32, 38, 44, 49, 54, 59, 64, 69, 74, 79, 84, 89, 94, 98, 102, 106, 110, 114, 118, 122, 126, 130, 134, 138, 142, 146, 150, 154, 158, 162, 166, 170, 174, 178, 182, 186, 190, 194, 198, 202, 206, 210, 214, 234, 253, 272, 292, 312, 332, 352, 371, 391, 410, 430, 449, 468, 487, 506, 525, 545, 564};
__constant__ uint16_t c_items[700] = {
    0, 1280, 512, 21728, 16, 1280, 513, 29920, 32, 1280, 800, 898, 3042, 21729, 1, 1280, 801, 899, 3043, 29921, 17, 1280, 802, 900,
    3044, 21730, 33, 1280, 803, 901, 3045, 29922, 2, 1280, 804, 902, 3046, 21731, 18, 1280, 805, 903, 3047, 29923, 34, 1280, 2496, 2912,
    17408, 3, 1280, 2528, 2913, 17409, 19, 1280, 768, 2914, 17410, 35, 1280, 769, 2915, 17411, 4, 1280, 770, 2916, 17440, 20, 1280, 771,
    2917, 17441, 36, 1280, 772, 2918, 17442, 5, 1280, 773, 2919, 17443, 21, 1280, 774, 2944, 17472, 37, 1280, 775, 2945, 17473, 6, 1280,
    2497, 16898, 22, 1280, 2529, 16899, 38, 1280, 2498, 16928, 7, 1280, 2530, 16929, 23, 1280, 2499, 16930, 39, 1280, 2531, 16931, 8, 1280,
    2500, 16960, 24, 1280, 2532, 16961, 40, 1280, 2501, 16962, 9, 1280, 2533, 16963, 25, 1280, 2502, 16992, 41, 1280, 2534, 16993, 10, 1280,
    2503, 16994, 26, 1280, 2535, 16995, 42, 1280, 2504, 17024, 11, 1280, 2536, 17025, 27, 1280, 2505, 17026, 43, 1280, 2537, 17027, 12, 1280,
    2506, 17056, 28, 1280, 2538, 17057, 44, 1280, 2507, 17058, 13, 1280, 2539, 17059, 29, 1280, 2508, 17088, 45, 1280, 2540, 17089, 14, 1280,
    2509, 17090, 30, 1280, 2541, 17091, 46, 1280, 2510, 17120, 15, 1280, 2542, 17121, 31, 1280, 2511, 17122, 47, 1280, 2543, 17123, 48, 66,
    84, 102, 117, 131, 147, 161, 178, 194, 207, 222, 235, 248, 332, 366, 416, 835, 3010, 17568, 49, 67, 85, 256, 128, 141,
    155, 170, 187, 203, 215, 296, 301, 323, 357, 391, 425, 2979, 17505, 50, 68, 86, 103, 259, 142, 156, 171, 188, 288, 216,
    231, 302, 324, 358, 392, 806, 2976, 17474, 51, 69, 87, 104, 118, 132, 148, 162, 179, 195, 208, 223, 236, 249, 333, 367,
    417, 836, 3011, 17569, 52, 70, 88, 105, 119, 133, 149, 163, 180, 196, 209, 224, 237, 250, 334, 384, 418, 837, 3012, 17570,
    53, 71, 89, 106, 120, 134, 150, 164, 181, 197, 210, 225, 238, 251, 335, 385, 419, 838, 3013, 17571, 54, 72, 90, 107,
    121, 135, 151, 165, 182, 198, 211, 226, 239, 252, 352, 386, 420, 839, 3014, 17600, 55, 73, 91, 108, 260, 264, 160, 176,
    192, 291, 220, 299, 245, 328, 362, 396, 428, 3009, 17539, 56, 74, 92, 109, 122, 136, 152, 166, 183, 199, 212, 227, 240,
    253, 353, 387, 421, 429, 3015, 17601, 57, 75, 93, 110, 123, 263, 267, 175, 271, 206, 218, 233, 243, 322, 356, 390, 424,
    2978, 17504, 58, 76, 94, 111, 124, 137, 153, 167, 184, 200, 213, 228, 241, 254, 354, 388, 422, 430, 3040, 17602, 59, 77,
    95, 112, 125, 138, 265, 269, 191, 290, 219, 298, 246, 329, 363, 397, 832, 2982, 17536, 60, 78, 96, 113, 261, 143, 157,
    172, 270, 292, 221, 300, 247, 330, 364, 398, 833, 2983, 17537, 61, 79, 97, 257, 129, 144, 158, 173, 189, 204, 294, 297,
    244, 325, 359, 393, 426, 2980, 17506, 62, 80, 98, 258, 130, 145, 268, 177, 193, 205, 217, 232, 303, 326, 360, 394, 807,
    2977, 17475, 63, 81, 99, 114, 262, 146, 159, 174, 190, 289, 295, 234, 321, 331, 365, 399, 834, 3008, 17538, 64, 82, 100,
    115, 126, 139, 154, 168, 185, 201, 214, 229, 242, 255, 355, 389, 423, 431, 3041, 17603, 65, 83, 101, 116, 127, 140, 266,
    169, 186, 202, 293, 230, 320, 327, 361, 395, 427, 2981, 17507,
};
#define ITEM_OFF(p) c_off[p]
#define ITEM(i) c_items[i]

__device__ __align__(1024) bf16 g_kvo[3 * 2048 * 4096];
__device__ __align__(1024) bf16 g_ht[2048 * 2048];
__device__ __align__(1024) uint8_t g_x[4 << 20];
__device__ __align__(1024) uint32_t g_km[64 * 32 * 512];
__device__ __align__(1024) uint32_t g_vmt[64 * 32 * 512];
__device__ __align__(1024) float2 g_agg[8 * 1024];
__device__ __align__(1024) float4 g_coef[1024];
__device__ __align__(1024) uint32_t g_cntl[384 * 32];
#define g_cnt(i) g_cntl[(i) * 32]
__device__ __align__(1024) uint32_t g_hint[96 * 32];
#define PROF(i)
#define PROFDUMP()
#define PROFP(i)
constexpr int XG_SIDE = 65536, XG_T = 98304;
__device__ __forceinline__ uint32_t xg_buf(int b) { return (b & 1) * 128 + (b & 2) * 256 + (b & 4) * 32768; }
__device__ __forceinline__ uint32_t xg_lane(uint32_t lane) { return (lane >> 4) * 1024 + (lane & 8) * 32 + (lane & 7) * 16; }
__device__ __forceinline__ uint32_t xg_side(int b) { return XG_SIDE + (b >> 1) * 1024 + (b & 1) * 256; }

constexpr int STAGE = 49152, NSTAGE = 4;
constexpr int S_STG = NSTAGE * STAGE;
constexpr int S_BAR = S_STG + 32768;
constexpr int B_FULL = S_BAR, B_EMPTY = S_BAR + 32, B_RESUME = S_BAR + 64, B_KVFULL = S_BAR + 72, B_GO = S_BAR + 88, B_X = S_BAR + 96, B_PERS = S_BAR + 104,
              B_INIT = S_BAR + 112, B_RELM = S_BAR + 120, B_READY = S_BAR + 136, B_SFULL = S_BAR + 144, B_SFREE = S_BAR + 160, S_DESC = S_BAR + 176, B_RED = S_BAR + 216;
constexpr int S_EV = S_BAR + 80, S_EO = S_BAR + 84, B_INIT2 = S_BAR + 128, S_SC = S_BAR + 208, S_ISC = S_EV;
constexpr int S_XV = S_BAR + 256, S_LOG = S_XV + 2048;
constexpr int S_TOTAL = S_LOG + 768;
#define NRA 5
#define NRB 3
constexpr int S_W1 = 0;
constexpr int S_W2 = 4 * 4096 * (16 - NRA - NRB);
constexpr int S_KV = 188416;
constexpr int S_P1 = S_KV + 16384;
constexpr int S_X = S_P1 + 16384;
constexpr int S_SX = S_P1, S_OX = S_P1 + 2048;
constexpr int S_EM = S_X + 4096, S_TO = S_EM + 32, B_DONE = S_BAR + 224, B_P1 = S_BAR + 232, B_EPOCH = S_BAR + 240, S_EPOCH = S_BAR + 248;
static_assert(S_TO + 32 <= S_BAR && S_KV % 1024 == 0 && S_TOTAL <= 232448, "chain smem layout");

template <int V> struct IC { static constexpr int value = V; };
template <int B, int E, typename F> __device__ __forceinline__ void static_for(F&& f) { if constexpr (B < E) { f(IC<B>{}); static_for<B + 1, E>(f); } }
__device__ __forceinline__ uint32_t cluster_rank() { uint32_t r; asm volatile("mov.u32 %0, %%cluster_ctarank;" : "=r"(r)); return r; }
__device__ __forceinline__ void spin_fault() { asm volatile("st.global.u32 [%0], 0;" ::"l"(0ull) : "memory"); }
__device__ __forceinline__ uint32_t smem_u32(const void* p) { return (uint32_t)__cvta_generic_to_shared(p); }
__device__ __forceinline__ uint32_t opq(uint32_t x, int lane) { return __shfl_sync(0xffffffffu, x, lane); }
__device__ __forceinline__ uint32_t mapa(uint32_t a, uint32_t r) { uint32_t d; asm volatile("mapa.shared::cluster.u32 %0, %1, %2;" : "=r"(d) : "r"(a), "r"(r)); return d; }
__device__ __forceinline__ void mma16816(float* d, uint32_t a0, uint32_t a1, uint32_t a2, uint32_t a3, uint32_t b0, uint32_t b1) {
    asm("mma.sync.aligned.m16n8k16.row.col.f32.bf16.bf16.f32 {%0,%1,%2,%3}, {%4,%5,%6,%7}, {%8,%9}, {%0,%1,%2,%3};"
        : "+f"(d[0]), "+f"(d[1]), "+f"(d[2]), "+f"(d[3]) : "r"(a0), "r"(a1), "r"(a2), "r"(a3), "r"(b0), "r"(b1));
}
__device__ __forceinline__ void mma1688(float* d, uint32_t a0, uint32_t a1, uint32_t b0) {
    asm("mma.sync.aligned.m16n8k8.row.col.f32.bf16.bf16.f32 {%0,%1,%2,%3}, {%4,%5}, {%6}, {%0,%1,%2,%3};"
        : "+f"(d[0]), "+f"(d[1]), "+f"(d[2]), "+f"(d[3]) : "r"(a0), "r"(a1), "r"(b0));
}
__device__ __forceinline__ void ldsm4(uint32_t* r, uint32_t a) {
    asm volatile("ldmatrix.sync.aligned.m8n8.x4.shared.b16 {%0,%1,%2,%3}, [%4];" : "=r"(r[0]), "=r"(r[1]), "=r"(r[2]), "=r"(r[3]) : "r"(a));
}
__device__ __forceinline__ void ldsm4t(uint32_t* r, uint32_t a) {
    asm volatile("ldmatrix.sync.aligned.m8n8.x4.trans.shared.b16 {%0,%1,%2,%3}, [%4];" : "=r"(r[0]), "=r"(r[1]), "=r"(r[2]), "=r"(r[3]) : "r"(a));
}
__device__ __forceinline__ void stsm4(uint32_t a, uint32_t r0, uint32_t r1, uint32_t r2, uint32_t r3) {
    asm volatile("stmatrix.sync.aligned.m8n8.x4.shared.b16 [%0], {%1,%2,%3,%4};" ::"r"(a), "r"(r0), "r"(r1), "r"(r2), "r"(r3) : "memory");
}
__device__ __forceinline__ void stsm4t(uint32_t a, uint32_t r0, uint32_t r1, uint32_t r2, uint32_t r3) {
    asm volatile("stmatrix.sync.aligned.m8n8.x4.trans.shared.b16 [%0], {%1,%2,%3,%4};" ::"r"(a), "r"(r0), "r"(r1), "r"(r2), "r"(r3) : "memory");
}
__device__ __forceinline__ uint32_t movm(uint32_t a) { uint32_t d; asm volatile("movmatrix.sync.aligned.m8n8.trans.b16 %0, %1;" : "=r"(d) : "r"(a)); return d; }
__device__ __forceinline__ uint32_t pack2(float lo, float hi) { uint32_t d; asm("cvt.rn.bf16x2.f32 %0, %1, %2;" : "=r"(d) : "f"(hi), "f"(lo)); return d; }
__device__ __forceinline__ uint32_t prmt(uint32_t a, uint32_t b, uint32_t s) { uint32_t d; asm("prmt.b32 %0, %1, %2, %3;" : "=r"(d) : "r"(a), "r"(b), "r"(s)); return d; }
__device__ __forceinline__ uint32_t pack2h(float lo, float hi) { uint32_t d; asm("cvt.rn.f16x2.f32 %0, %1, %2;" : "=r"(d) : "f"(hi), "f"(lo)); return d; }
__device__ __forceinline__ uint32_t h2bf(uint32_t a, uint32_t b) {
    uint32_t d;
    asm("{\n.reg .b16 l, h, u;\n.reg .f32 x, y;\nmov.b32 {l, u}, %1;\ncvt.f32.f16 x, l;\nmov.b32 {u, h}, %2;\ncvt.f32.f16 y, h;\ncvt.rn.bf16x2.f32 %0, y, x;\n}" : "=r"(d) : "r"(a), "r"(b));
    return d;
}
__device__ __forceinline__ void cvt_block(uint32_t* u, uint32_t& x, uint32_t sel) {
    const uint32_t a = prmt(u[0], u[0], sel), b = prmt(u[1], u[1], sel), c = prmt(u[2], u[2], sel), d = prmt(u[3], x, sel);
    x ^= u[3] ^ d;
    u[0] = h2bf(a, a); u[1] = h2bf(b, b); u[2] = h2bf(c, c); u[3] = h2bf(d, d);
}
__device__ __forceinline__ uint32_t amax(uint32_t a, uint32_t b) { uint32_t d; asm("max.xorsign.abs.bf16x2 %0, %1, %2;" : "=r"(d) : "r"(a), "r"(b)); return d; }
__device__ __forceinline__ uint32_t amax4(uint32_t m, const uint32_t* v) { return amax(amax(m, amax(v[0], v[1])), amax(v[2], v[3])); }
__device__ __forceinline__ uint32_t warp_exp(uint32_t m) { return __reduce_max_sync(0xffffffffu, max(m & 0x7f80u, (m >> 16) & 0x7f80u)) >> 7; }
__device__ __forceinline__ void red_max_shared(uint32_t a, uint32_t x) { asm volatile("red.shared.max.u32 [%0], %1;" ::"r"(a), "r"(x) : "memory"); }
__device__ __forceinline__ uint32_t mul_bf2(uint32_t a, uint32_t b) { uint32_t d; asm("mul.rn.bf16x2 %0, %1, %2;" : "=r"(d) : "r"(a), "r"(b)); return d; }
__device__ __forceinline__ float bf_lo(uint32_t u) { return __uint_as_float(u << 16); }
__device__ __forceinline__ float bf_hi(uint32_t u) { return __uint_as_float(u & 0xffff0000u); }
__device__ __forceinline__ float ex2(float x) { float y; asm("ex2.approx.ftz.f32 %0, %1;" : "=f"(y) : "f"(x)); return y; }
__device__ __forceinline__ float rcp(float x) { float y; asm("rcp.approx.ftz.f32 %0, %1;" : "=f"(y) : "f"(x)); return y; }
__device__ __forceinline__ void st_relaxed4(const void* p, uint32_t a, uint32_t b, uint32_t c, uint32_t d) {
    asm volatile("{\n.reg .b128 t;\nmov.b128 t, {%1,%2,%3,%4};\nst.relaxed.gpu.global.b128 [%0], t;\n}" ::"l"(p), "r"(a), "r"(b), "r"(c), "r"(d) : "memory");
}
__device__ __forceinline__ void st_relaxed2(const void* p, uint32_t a, uint32_t b) {
    asm volatile("{\n.reg .b64 t;\nmov.b64 t, {%1,%2};\nst.relaxed.gpu.global.b64 [%0], t;\n}" ::"l"(p), "r"(a), "r"(b) : "memory");
}
__device__ __forceinline__ void ld_relaxed2_if(uint32_t& a, uint32_t& b, const void* p, bool on) {
    asm volatile("{\n.reg .pred P;\n.reg .b64 t;\nsetp.ne.u32 P, %3, 0;\nmov.b64 t, {%0,%1};\n@P ld.relaxed.gpu.global.b64 t, [%2];\nmov.b64 {%0,%1}, t;\n}" : "+r"(a), "+r"(b) : "l"(p), "r"((uint32_t)on) : "memory");
}
__device__ __forceinline__ void ld_relaxed4(uint32_t* v, const void* p) {
    asm volatile("ld.relaxed.gpu.global.L1::no_allocate.v4.b32 {%0,%1,%2,%3}, [%4];" : "=r"(v[0]), "=r"(v[1]), "=r"(v[2]), "=r"(v[3]) : "l"(p) : "memory");
}
__device__ __forceinline__ void ld_relaxed1n(uint32_t& v, const void* p) { asm volatile("ld.relaxed.gpu.global.L1::no_allocate.b32 %0, [%1];" : "=r"(v) : "l"(p) : "memory"); }
__device__ __forceinline__ void red_add4(const void* p, uint32_t a, uint32_t b, uint32_t c, uint32_t d) {
    asm volatile("red.relaxed.gpu.global.add.noftz.v4.f16x2 [%0], {%1,%2,%3,%4};" ::"l"(p), "r"(a), "r"(b), "r"(c), "r"(d) : "memory");
}
__device__ __forceinline__ void red_add1(const void* p, uint32_t a) { asm volatile("red.relaxed.gpu.global.add.noftz.f16x2 [%0], %1;" ::"l"(p), "r"(a) : "memory"); }
__device__ __forceinline__ void ld_relaxed2(uint32_t* v, const void* p) {
    asm volatile("{\n.reg .b64 t;\nld.relaxed.gpu.global.L1::no_allocate.b64 t, [%2];\nmov.b64 {%0,%1}, t;\n}" : "=r"(v[0]), "=r"(v[1]) : "l"(p) : "memory");
}
__device__ __forceinline__ uint32_t ld_relaxed1(const void* p) { uint32_t v; asm volatile("ld.relaxed.gpu.global.u32 %0, [%1];" : "=r"(v) : "l"(p) : "memory"); return v; }
__device__ __forceinline__ void st_relaxed1(const void* p, uint32_t v) { asm volatile("st.relaxed.gpu.global.u32 [%0], %1;" ::"l"(p), "r"(v) : "memory"); }
__device__ __forceinline__ uint32_t ld_acquire(const void* p) { uint32_t v; asm volatile("ld.acquire.gpu.global.u32 %0, [%1];" : "=r"(v) : "l"(p) : "memory"); return v; }
__device__ __forceinline__ void red_relaxed(void* p) { asm volatile("red.relaxed.gpu.global.add.u32 [%0], 1;" ::"l"(p) : "memory"); }
__device__ __forceinline__ void red_release(void* p) { asm volatile("red.release.gpu.global.add.u32 [%0], 1;" ::"l"(p) : "memory"); }
__device__ __forceinline__ void st_stream4(const void* p, float a, float b, float c, float d) { asm volatile("st.global.cs.v4.f32 [%0], {%1, %2, %3, %4};" ::"l"(p), "f"(a), "f"(b), "f"(c), "f"(d) : "memory"); }
__device__ __forceinline__ void fence_async() { asm volatile("fence.proxy.async.global;" ::: "memory"); }
__device__ __forceinline__ void fence_async_smem() { asm volatile("fence.proxy.async.shared::cta;" ::: "memory"); }
__device__ __forceinline__ void wait_count(const uint32_t* p, uint32_t target) {
    while ((int32_t)(ld_acquire(p) - target) < 0) __nanosleep(POLLNS);
}
__device__ __forceinline__ void bar_sync(int id, int n) { asm volatile("bar.sync %0, %1;" ::"r"(id), "r"(n) : "memory"); }
__device__ __forceinline__ bool bar_and(int id, bool v) {
    uint32_t r;
    asm volatile("{\n.reg .pred P, Q;\nsetp.ne.u32 Q, %2, 0;\nbar.red.and.pred P, %1, 128, Q;\nselp.u32 %0, 1, 0, P;\n}" : "=r"(r) : "r"(id), "r"((uint32_t)v) : "memory");
    return r;
}
__device__ __forceinline__ void bar_arrive(int id, int n) { asm volatile("bar.arrive %0, %1;" ::"r"(id), "r"(n) : "memory"); }
__device__ __forceinline__ void lds128(uint32_t* v, uint32_t a) { asm volatile("ld.shared.v4.b32 {%0,%1,%2,%3}, [%4];" : "=r"(v[0]), "=r"(v[1]), "=r"(v[2]), "=r"(v[3]) : "r"(a) : "memory"); }
__device__ __forceinline__ uint32_t lds32(uint32_t a) { uint32_t v; asm volatile("ld.shared.b32 %0, [%1];" : "=r"(v) : "r"(a) : "memory"); return v; }
__device__ __forceinline__ void lds64(uint32_t* v, uint32_t a) { asm volatile("ld.shared.v2.b32 {%0,%1}, [%2];" : "=r"(v[0]), "=r"(v[1]) : "r"(a) : "memory"); }
__device__ __forceinline__ void lds64f(float* v, uint32_t a) { asm volatile("ld.shared.v2.f32 {%0,%1}, [%2];" : "=f"(v[0]), "=f"(v[1]) : "r"(a) : "memory"); }
__device__ __forceinline__ void sts128(uint32_t a, const uint32_t* v) { asm volatile("st.shared.v4.b32 [%0], {%1,%2,%3,%4};" ::"r"(a), "r"(v[0]), "r"(v[1]), "r"(v[2]), "r"(v[3]) : "memory"); }
__device__ __forceinline__ void sts64(uint32_t a, uint32_t x, uint32_t y) { asm volatile("st.shared.v2.b32 [%0], {%1,%2};" ::"r"(a), "r"(x), "r"(y) : "memory"); }
__device__ __forceinline__ void sts32(uint32_t a, uint32_t x) { asm volatile("st.shared.b32 [%0], %1;" ::"r"(a), "r"(x) : "memory"); }
__device__ __forceinline__ bool mbar_try(uint32_t b, uint32_t par) {
    uint32_t ok;
    asm volatile("{\n.reg .pred P;\nmbarrier.test_wait.parity.shared::cta.b64 P, [%1], %2;\nselp.u32 %0, 1, 0, P;\n}" : "=r"(ok) : "r"(b), "r"(par) : "memory");
    return ok;
}
__device__ __forceinline__ void mbar_wait(uint32_t b, uint32_t par) {
    asm volatile("{\n.reg .pred P;\nW: mbarrier.try_wait.parity.shared::cta.b64 P, [%0], %1;\n@!P bra W;\n}" ::"r"(b), "r"(par) : "memory");
}
__device__ __forceinline__ void mbar_wait_bounded(uint32_t b, uint32_t par) {
    asm volatile("{\n.reg .pred P, Q;\n.reg .u32 t, u;\nmov.u32 t, %%globaltimer_lo;\nW: mbarrier.try_wait.parity.shared::cta.b64 P, [%0], %1;\n"
                 "mov.u32 u, %%globaltimer_lo;\nsub.u32 u, u, t;\nsetp.gt.u32 Q, u, 2000000000;\n@Q st.global.u32 [%2], 0;\n@!P bra W;\n}" ::"r"(b), "r"(par), "l"(0ull) : "memory");
}
__device__ __forceinline__ void declare_fence(int zero) { asm volatile(".reg .pred PNEVER;\nsetp.ne.u32 PNEVER, %0, 0;" ::"r"(zero)); }
__device__ __forceinline__ void sched_fence() { asm volatile("{\n.reg .pred Q;\n.reg .u32 x;\n@!PNEVER bra D;\nF: ld.volatile.global.u32 x, [%0];\nsetp.ne.u32 Q, x, 0;\n@Q bra F;\nD:\n}" ::"l"(0ull) : "memory"); }
__device__ __forceinline__ void mbar_init(uint32_t b, uint32_t n) { asm volatile("mbarrier.init.shared::cta.b64 [%0], %1;" ::"r"(b), "r"(n) : "memory"); }
__device__ __forceinline__ void mbar_expect(uint32_t b, uint32_t bytes) { asm volatile("mbarrier.arrive.expect_tx.shared::cta.b64 _, [%0], %1;" ::"r"(b), "r"(bytes) : "memory"); }
__device__ __forceinline__ void mbar_arrive(uint32_t b) { asm volatile("mbarrier.arrive.shared::cta.b64 _, [%0];" ::"r"(b) : "memory"); }
__device__ __forceinline__ void mbar_arrive_cluster(uint32_t b) { asm volatile("mbarrier.arrive.shared::cluster.b64 _, [%0];" ::"r"(b) : "memory"); }
__device__ __forceinline__ void cluster_sync() { asm volatile("barrier.cluster.arrive.relaxed.aligned;\nbarrier.cluster.wait.aligned;" ::: "memory"); }
__device__ __forceinline__ uint32_t get_epoch(uint32_t sb) { mbar_wait(sb + B_EPOCH, 0); return __shfl_sync(0xffffffffu, lds32(sb + S_EPOCH), 0); }
__device__ __forceinline__ void tma2d(uint32_t dst, const CUtensorMap* m, int c0, int c1, uint32_t bar) {
    asm volatile("cp.async.bulk.tensor.2d.shared::cluster.global.mbarrier::complete_tx::bytes [%0], [%1, {%2, %3}], [%4];" ::"r"(dst), "l"(m), "r"(c0), "r"(c1), "r"(bar) : "memory");
}
__device__ __forceinline__ void tma3d(uint32_t dst, const CUtensorMap* m, int c0, int c1, int c2, uint32_t bar) {
    asm volatile("cp.async.bulk.tensor.3d.shared::cluster.global.mbarrier::complete_tx::bytes [%0], [%1, {%2, %3, %4}], [%5];" ::"r"(dst), "l"(m), "r"(c0), "r"(c1), "r"(c2), "r"(bar) : "memory");
}
__device__ __forceinline__ void l2_prefetch(const void* src, uint32_t bytes) { asm volatile("cp.async.bulk.prefetch.L2.global [%0], %1;" ::"l"(src), "r"(bytes) : "memory"); }
__device__ __forceinline__ void mbar_expect_e(uint32_t b, uint32_t bytes) {
    asm volatile("{\n.reg .pred E;\nelect.sync _|E, 0xffffffff;\n@E mbarrier.arrive.expect_tx.shared::cta.b64 _, [%0], %1;\n}" ::"r"(b), "r"(bytes) : "memory");
}
__device__ __forceinline__ void tma3d_mc_e(uint32_t dst, const CUtensorMap* m, int c0, int c1, int c2, uint32_t bar, uint16_t mask, uint64_t pol) {
    asm volatile("{\n.reg .pred E;\nelect.sync _|E, 0xffffffff;\n@E cp.async.bulk.tensor.3d.shared::cluster.global.mbarrier::complete_tx::bytes.multicast::cluster.L2::cache_hint [%0], [%1, {%2, %3, %4}], [%5], %6, %7;\n}" ::"r"(dst), "l"(m), "r"(c0), "r"(c1), "r"(c2), "r"(bar), "h"(mask), "l"(pol) : "memory");
}
__device__ __forceinline__ void tma4d_e(uint32_t dst, const CUtensorMap* m, int c0, int c1, int c3, uint32_t bar, uint64_t pol) {
    asm volatile("{\n.reg .pred E;\nelect.sync _|E, 0xffffffff;\n@E cp.async.bulk.tensor.4d.shared::cluster.global.mbarrier::complete_tx::bytes.L2::cache_hint [%0], [%1, {%2, %3, 0, %4}], [%5], %6;\n}" ::"r"(dst), "l"(m), "r"(c0), "r"(c1), "r"(c3), "r"(bar), "l"(pol) : "memory");
}
__device__ __forceinline__ void tma4d_mc_e(uint32_t dst, const CUtensorMap* m, int c0, int c1, int c3, uint32_t bar, uint16_t mask, uint64_t pol) {
    asm volatile("{\n.reg .pred E;\nelect.sync _|E, 0xffffffff;\n@E cp.async.bulk.tensor.4d.shared::cluster.global.mbarrier::complete_tx::bytes.multicast::cluster.L2::cache_hint [%0], [%1, {%2, %3, 0, %4}], [%5], %6, %7;\n}" ::"r"(dst), "l"(m), "r"(c0), "r"(c1), "r"(c3), "r"(bar), "h"(mask), "l"(pol) : "memory");
}
__device__ __forceinline__ void tma_prefetch4d_e(const CUtensorMap* m, int c0, int c3) {
    asm volatile("{\n.reg .pred E;\nelect.sync _|E, 0xffffffff;\n@E cp.async.bulk.prefetch.tensor.4d.L2.global [%0, {%1, 0, 0, %2}];\n}" ::"l"(m), "r"(c0), "r"(c3) : "memory");
}
__device__ __forceinline__ void tma_prefetch3d_e(const CUtensorMap* m, int c0, int c1, int c2) {
    asm volatile("{\n.reg .pred E;\nelect.sync _|E, 0xffffffff;\n@E cp.async.bulk.prefetch.tensor.3d.L2.global [%0, {%1, %2, %3}];\n}" ::"l"(m), "r"(c0), "r"(c1), "r"(c2) : "memory");
}
__device__ __forceinline__ void l2_prefetch_e(const void* src, uint32_t bytes) {
    asm volatile("{\n.reg .pred E;\nelect.sync _|E, 0xffffffff;\n@E cp.async.bulk.prefetch.L2.global [%0], %1;\n}" ::"l"(src), "r"(bytes) : "memory");
}
__device__ __forceinline__ void bulk_g2s_e(uint32_t dst, const void* src, uint32_t bytes, uint32_t bar) {
    asm volatile("{\n.reg .pred E;\nelect.sync _|E, 0xffffffff;\n@E cp.async.bulk.shared::cluster.global.mbarrier::complete_tx::bytes [%0], [%1], %2, [%3];\n}" ::"r"(dst), "l"(src), "r"(bytes), "r"(bar) : "memory");
}
__device__ __forceinline__ bool elect_one() {
    uint32_t r;
    asm volatile("{\n.reg .pred E;\nelect.sync _|E, 0xffffffff;\nselp.u32 %0, 1, 0, E;\n}" : "=r"(r));
    return r;
}
__device__ __forceinline__ void tma_store2d(const CUtensorMap* m, int c0, int c1, uint32_t src, uint64_t pol) {
    asm volatile("cp.async.bulk.tensor.2d.global.shared::cta.bulk_group.L2::cache_hint [%0, {%1, %2}], [%3], %4;" ::"l"(m), "r"(c0), "r"(c1), "r"(src), "l"(pol) : "memory");
}
__device__ __forceinline__ void bulk_commit() { asm volatile("cp.async.bulk.commit_group;" ::: "memory"); }
__device__ __forceinline__ void bulk_wait_read() { asm volatile("cp.async.bulk.wait_group.read 0;" ::: "memory"); }
__device__ __forceinline__ void bulk_wait_all() { asm volatile("cp.async.bulk.wait_group 0;" ::: "memory"); }
__device__ __forceinline__ uint64_t mkdesc(uint32_t addr, uint32_t lbo, uint32_t sbo, uint32_t swz) {
    return (uint64_t)((addr & 0x3FFFF) >> 4) | ((uint64_t)(lbo >> 4) << 16) | ((uint64_t)(sbo >> 4) << 32) | ((uint64_t)swz << 62);
}
__device__ __forceinline__ void wg_fence() { asm volatile("wgmma.fence.sync.aligned;" ::: "memory"); }
__device__ __forceinline__ void wg_commit() { asm volatile("wgmma.commit_group.sync.aligned;" ::: "memory"); }
template <int N> __device__ __forceinline__ void wg_wait() { asm volatile("wgmma.wait_group.sync.aligned %0;" ::"n"(N) : "memory"); }
template <typename T> __device__ __forceinline__ void pin_ptr(T*& p) { asm volatile("" : "+l"(p)); }
template <int N> __device__ __forceinline__ void pin(uint32_t* d) {
#pragma unroll
    for (int i = 0; i < N; i++) asm volatile("" : "+r"(d[i])::"memory");
}
template <int N> __device__ __forceinline__ void pin(float* d) {
#pragma unroll
    for (int i = 0; i < N; i++) asm volatile("" : "+f"(d[i])::"memory");
}

template <int TA, int TB>
__device__ __forceinline__ void wgmma_ss256(float* d, uint64_t da, uint64_t db) {
    asm volatile("wgmma.mma_async.sync.aligned.m64n256k16.f32.bf16.bf16 "
        "{%0, %1, %2, %3, %4, %5, %6, %7, %8, %9, %10, %11, %12, %13, %14, %15, %16, %17, %18, %19, %20, %21, %22, %23, %24, %25, %26, %27, %28, %29, %30, %31, %32, %33, %34, %35, %36, %37, %38, %39, %40, %41, %42, %43, %44, %45, %46, %47, %48, %49, %50, %51, %52, %53, %54, %55, %56, %57, %58, %59, %60, %61, %62, %63, %64, %65, %66, %67, %68, %69, %70, %71, %72, %73, %74, %75, %76, %77, %78, %79, %80, %81, %82, %83, %84, %85, %86, %87, %88, %89, %90, %91, %92, %93, %94, %95, %96, %97, %98, %99, %100, %101, %102, %103, %104, %105, %106, %107, %108, %109, %110, %111, %112, %113, %114, %115, %116, %117, %118, %119, %120, %121, %122, %123, %124, %125, %126, %127}, %128, %129, 1, 1, 1, %130, %131;"
        : "+f"(d[0]), "+f"(d[1]), "+f"(d[2]), "+f"(d[3]), "+f"(d[4]), "+f"(d[5]), "+f"(d[6]), "+f"(d[7]), "+f"(d[8]), "+f"(d[9]), "+f"(d[10]), "+f"(d[11]), "+f"(d[12]), "+f"(d[13]), "+f"(d[14]), "+f"(d[15]), "+f"(d[16]), "+f"(d[17]), "+f"(d[18]), "+f"(d[19]), "+f"(d[20]), "+f"(d[21]), "+f"(d[22]), "+f"(d[23]), "+f"(d[24]), "+f"(d[25]), "+f"(d[26]), "+f"(d[27]), "+f"(d[28]), "+f"(d[29]), "+f"(d[30]), "+f"(d[31]), "+f"(d[32]), "+f"(d[33]), "+f"(d[34]), "+f"(d[35]), "+f"(d[36]), "+f"(d[37]), "+f"(d[38]), "+f"(d[39]), "+f"(d[40]), "+f"(d[41]), "+f"(d[42]), "+f"(d[43]), "+f"(d[44]), "+f"(d[45]), "+f"(d[46]), "+f"(d[47]), "+f"(d[48]), "+f"(d[49]), "+f"(d[50]), "+f"(d[51]), "+f"(d[52]), "+f"(d[53]), "+f"(d[54]), "+f"(d[55]), "+f"(d[56]), "+f"(d[57]), "+f"(d[58]), "+f"(d[59]), "+f"(d[60]), "+f"(d[61]), "+f"(d[62]), "+f"(d[63]), "+f"(d[64]), "+f"(d[65]), "+f"(d[66]), "+f"(d[67]), "+f"(d[68]), "+f"(d[69]), "+f"(d[70]), "+f"(d[71]), "+f"(d[72]), "+f"(d[73]), "+f"(d[74]), "+f"(d[75]), "+f"(d[76]), "+f"(d[77]), "+f"(d[78]), "+f"(d[79]), "+f"(d[80]), "+f"(d[81]), "+f"(d[82]), "+f"(d[83]), "+f"(d[84]), "+f"(d[85]), "+f"(d[86]), "+f"(d[87]), "+f"(d[88]), "+f"(d[89]), "+f"(d[90]), "+f"(d[91]), "+f"(d[92]), "+f"(d[93]), "+f"(d[94]), "+f"(d[95]), "+f"(d[96]), "+f"(d[97]), "+f"(d[98]), "+f"(d[99]), "+f"(d[100]), "+f"(d[101]), "+f"(d[102]), "+f"(d[103]), "+f"(d[104]), "+f"(d[105]), "+f"(d[106]), "+f"(d[107]), "+f"(d[108]), "+f"(d[109]), "+f"(d[110]), "+f"(d[111]), "+f"(d[112]), "+f"(d[113]), "+f"(d[114]), "+f"(d[115]), "+f"(d[116]), "+f"(d[117]), "+f"(d[118]), "+f"(d[119]), "+f"(d[120]), "+f"(d[121]), "+f"(d[122]), "+f"(d[123]), "+f"(d[124]), "+f"(d[125]), "+f"(d[126]), "+f"(d[127])
        : "l"(da), "l"(db), "n"(TA), "n"(TB));
}
template <int TA, int TB>
__device__ __forceinline__ void wgmma_ss256_first(float* d, uint64_t da, uint64_t db) {
    asm volatile("wgmma.mma_async.sync.aligned.m64n256k16.f32.bf16.bf16 "
        "{%0, %1, %2, %3, %4, %5, %6, %7, %8, %9, %10, %11, %12, %13, %14, %15, %16, %17, %18, %19, %20, %21, %22, %23, %24, %25, %26, %27, %28, %29, %30, %31, %32, %33, %34, %35, %36, %37, %38, %39, %40, %41, %42, %43, %44, %45, %46, %47, %48, %49, %50, %51, %52, %53, %54, %55, %56, %57, %58, %59, %60, %61, %62, %63, %64, %65, %66, %67, %68, %69, %70, %71, %72, %73, %74, %75, %76, %77, %78, %79, %80, %81, %82, %83, %84, %85, %86, %87, %88, %89, %90, %91, %92, %93, %94, %95, %96, %97, %98, %99, %100, %101, %102, %103, %104, %105, %106, %107, %108, %109, %110, %111, %112, %113, %114, %115, %116, %117, %118, %119, %120, %121, %122, %123, %124, %125, %126, %127}, %128, %129, 0, 1, 1, %130, %131;"
        : "=f"(d[0]), "=f"(d[1]), "=f"(d[2]), "=f"(d[3]), "=f"(d[4]), "=f"(d[5]), "=f"(d[6]), "=f"(d[7]), "=f"(d[8]), "=f"(d[9]), "=f"(d[10]), "=f"(d[11]), "=f"(d[12]), "=f"(d[13]), "=f"(d[14]), "=f"(d[15]), "=f"(d[16]), "=f"(d[17]), "=f"(d[18]), "=f"(d[19]), "=f"(d[20]), "=f"(d[21]), "=f"(d[22]), "=f"(d[23]), "=f"(d[24]), "=f"(d[25]), "=f"(d[26]), "=f"(d[27]), "=f"(d[28]), "=f"(d[29]), "=f"(d[30]), "=f"(d[31]), "=f"(d[32]), "=f"(d[33]), "=f"(d[34]), "=f"(d[35]), "=f"(d[36]), "=f"(d[37]), "=f"(d[38]), "=f"(d[39]), "=f"(d[40]), "=f"(d[41]), "=f"(d[42]), "=f"(d[43]), "=f"(d[44]), "=f"(d[45]), "=f"(d[46]), "=f"(d[47]), "=f"(d[48]), "=f"(d[49]), "=f"(d[50]), "=f"(d[51]), "=f"(d[52]), "=f"(d[53]), "=f"(d[54]), "=f"(d[55]), "=f"(d[56]), "=f"(d[57]), "=f"(d[58]), "=f"(d[59]), "=f"(d[60]), "=f"(d[61]), "=f"(d[62]), "=f"(d[63]), "=f"(d[64]), "=f"(d[65]), "=f"(d[66]), "=f"(d[67]), "=f"(d[68]), "=f"(d[69]), "=f"(d[70]), "=f"(d[71]), "=f"(d[72]), "=f"(d[73]), "=f"(d[74]), "=f"(d[75]), "=f"(d[76]), "=f"(d[77]), "=f"(d[78]), "=f"(d[79]), "=f"(d[80]), "=f"(d[81]), "=f"(d[82]), "=f"(d[83]), "=f"(d[84]), "=f"(d[85]), "=f"(d[86]), "=f"(d[87]), "=f"(d[88]), "=f"(d[89]), "=f"(d[90]), "=f"(d[91]), "=f"(d[92]), "=f"(d[93]), "=f"(d[94]), "=f"(d[95]), "=f"(d[96]), "=f"(d[97]), "=f"(d[98]), "=f"(d[99]), "=f"(d[100]), "=f"(d[101]), "=f"(d[102]), "=f"(d[103]), "=f"(d[104]), "=f"(d[105]), "=f"(d[106]), "=f"(d[107]), "=f"(d[108]), "=f"(d[109]), "=f"(d[110]), "=f"(d[111]), "=f"(d[112]), "=f"(d[113]), "=f"(d[114]), "=f"(d[115]), "=f"(d[116]), "=f"(d[117]), "=f"(d[118]), "=f"(d[119]), "=f"(d[120]), "=f"(d[121]), "=f"(d[122]), "=f"(d[123]), "=f"(d[124]), "=f"(d[125]), "=f"(d[126]), "=f"(d[127])
        : "l"(da), "l"(db), "n"(TA), "n"(TB));
}
template <int TB>
__device__ __forceinline__ void wgmma_rs128(float* d, const uint32_t* a, uint64_t db, uint32_t acc) {
    asm volatile("{\n.reg .pred P;\nsetp.ne.u32 P, %69, 0;\nwgmma.mma_async.sync.aligned.m64n128k16.f32.bf16.bf16 "
        "{%0, %1, %2, %3, %4, %5, %6, %7, %8, %9, %10, %11, %12, %13, %14, %15, %16, %17, %18, %19, %20, %21, %22, %23, %24, %25, %26, %27, %28, %29, %30, %31, %32, %33, %34, %35, %36, %37, %38, %39, %40, %41, %42, %43, %44, %45, %46, %47, %48, %49, %50, %51, %52, %53, %54, %55, %56, %57, %58, %59, %60, %61, %62, %63}, {%64, %65, %66, %67}, %68, P, 1, 1, %70;\n}"
        : "+f"(d[0]), "+f"(d[1]), "+f"(d[2]), "+f"(d[3]), "+f"(d[4]), "+f"(d[5]), "+f"(d[6]), "+f"(d[7]), "+f"(d[8]), "+f"(d[9]), "+f"(d[10]), "+f"(d[11]), "+f"(d[12]), "+f"(d[13]), "+f"(d[14]), "+f"(d[15]), "+f"(d[16]), "+f"(d[17]), "+f"(d[18]), "+f"(d[19]), "+f"(d[20]), "+f"(d[21]), "+f"(d[22]), "+f"(d[23]), "+f"(d[24]), "+f"(d[25]), "+f"(d[26]), "+f"(d[27]), "+f"(d[28]), "+f"(d[29]), "+f"(d[30]), "+f"(d[31]), "+f"(d[32]), "+f"(d[33]), "+f"(d[34]), "+f"(d[35]), "+f"(d[36]), "+f"(d[37]), "+f"(d[38]), "+f"(d[39]), "+f"(d[40]), "+f"(d[41]), "+f"(d[42]), "+f"(d[43]), "+f"(d[44]), "+f"(d[45]), "+f"(d[46]), "+f"(d[47]), "+f"(d[48]), "+f"(d[49]), "+f"(d[50]), "+f"(d[51]), "+f"(d[52]), "+f"(d[53]), "+f"(d[54]), "+f"(d[55]), "+f"(d[56]), "+f"(d[57]), "+f"(d[58]), "+f"(d[59]), "+f"(d[60]), "+f"(d[61]), "+f"(d[62]), "+f"(d[63])
        : "r"(a[0]), "r"(a[1]), "r"(a[2]), "r"(a[3]), "l"(db), "r"(acc), "n"(TB));
}
template <int TB>
__device__ __forceinline__ void wgmma_rs64(float* d, const uint32_t* a, uint64_t db, uint32_t acc) {
    asm volatile("{\n.reg .pred P;\nsetp.ne.u32 P, %37, 0;\nwgmma.mma_async.sync.aligned.m64n64k16.f32.bf16.bf16 "
        "{%0, %1, %2, %3, %4, %5, %6, %7, %8, %9, %10, %11, %12, %13, %14, %15, %16, %17, %18, %19, %20, %21, %22, %23, %24, %25, %26, %27, %28, %29, %30, %31}, {%32, %33, %34, %35}, %36, P, 1, 1, %38;\n}"
        : "+f"(d[0]), "+f"(d[1]), "+f"(d[2]), "+f"(d[3]), "+f"(d[4]), "+f"(d[5]), "+f"(d[6]), "+f"(d[7]), "+f"(d[8]), "+f"(d[9]), "+f"(d[10]), "+f"(d[11]), "+f"(d[12]), "+f"(d[13]), "+f"(d[14]), "+f"(d[15]), "+f"(d[16]), "+f"(d[17]), "+f"(d[18]), "+f"(d[19]), "+f"(d[20]), "+f"(d[21]), "+f"(d[22]), "+f"(d[23]), "+f"(d[24]), "+f"(d[25]), "+f"(d[26]), "+f"(d[27]), "+f"(d[28]), "+f"(d[29]), "+f"(d[30]), "+f"(d[31])
        : "r"(a[0]), "r"(a[1]), "r"(a[2]), "r"(a[3]), "l"(db), "r"(acc), "n"(TB));
}
template <int TB>
__device__ __forceinline__ void wgmma_rs16(float* d, const uint32_t* a, uint64_t db, uint32_t acc) {
    asm volatile("{\n.reg .pred P;\nsetp.ne.u32 P, %13, 0;\nwgmma.mma_async.sync.aligned.m64n16k16.f32.bf16.bf16 "
        "{%0, %1, %2, %3, %4, %5, %6, %7}, {%8, %9, %10, %11}, %12, P, 1, 1, %14;\n}"
        : "+f"(d[0]), "+f"(d[1]), "+f"(d[2]), "+f"(d[3]), "+f"(d[4]), "+f"(d[5]), "+f"(d[6]), "+f"(d[7])
        : "r"(a[0]), "r"(a[1]), "r"(a[2]), "r"(a[3]), "l"(db), "r"(acc), "n"(TB));
}

__device__ __forceinline__ uint32_t delay_loop(int n, uint32_t x0) {
    uint32_t z;
    asm volatile("{\n.reg .pred P;\n.reg .u32 c, x;\nmov.u32 c, %1;\nmov.u32 x, %2;\nDL: mad.lo.u32 x, x, 1664525, 1013904223;\nadd.u32 c, c, -1;\nsetp.gt.s32 P, c, 0;\n@P bra DL;\n"
                 "setp.eq.u32 P, x, 0x7fffffff;\nselp.u32 %0, 16, 0, P;\n}" : "=r"(z) : "r"(n), "r"(x0) : "memory");
    return z;
}
__device__ __forceinline__ void wait_clocks(uint32_t n) {
    asm volatile("{\n.reg .pred P;\n.reg .u32 a, b;\nmov.u32 a, %%clock;\nW: mov.u32 b, %%clock;\nsub.u32 b, b, a;\nsetp.lt.u32 P, b, %0;\n@P bra W;\n}" ::"r"(n) : "memory");
}
__device__ __forceinline__ uint32_t gtime() { uint32_t t; asm volatile("mov.u32 %0, %%globaltimer_lo;" : "=r"(t)); return t; }
#define COUNT_RETRY(i)
__device__ __forceinline__ uint32_t stamp_word(uint32_t seq) { return (gtime() & ~31u) | (seq & 31u); }
__device__ __forceinline__ void wait_time(uint32_t t, uint32_t sb) { while ((int32_t)(gtime() - t) < 0) {} }
#define NAPMODE 1
__device__ __forceinline__ void nap(uint32_t ns) { if (NAPMODE) wait_clocks(ns * 7 / 4); else __nanosleep(ns); }
template <int STRIDE>
__device__ __forceinline__ uint32_t latest_stamp(const uint32_t* p, uint32_t seq, uint32_t ref, uint32_t sb) {
#pragma unroll 1
    for (int n = opq(0, 0);; n++) {
        uint32_t bad = 0; int32_t m = INT32_MIN;
#pragma unroll
        for (int i = 0; i < 3; i++) { const uint32_t v = ld_relaxed1(p + i * STRIDE); bad |= (v ^ seq) & 31u; m = max(m, (int32_t)((v & ~31u) - ref)); }
        if (__all_sync(0xffffffffu, bad == 0)) return ref + __reduce_max_sync(0xffffffffu, m);
        nap(100);
        if (n > SPIN_LIMIT) spin_fault();
    }
}
constexpr uint32_t ONES = 0x3C003C00u, FULL = 0x50005000u;
__device__ __forceinline__ void pacer(const Params& P, const uint32_t sb, const int cta, const int lane, const uint32_t epoch) {
    uint8_t* const zp = P.xb + cta * 2048 + xg_lane(lane);
    if (lane < 3) asm volatile("prefetch.tensormap [%0];" ::"l"(&P.tm[lane == 0 ? M_C1 + cta % 3 : lane == 1 ? M_CO : M_SEG]) : "memory");
    uint32_t e0 = 0;
#pragma unroll 2
    for (int i = 0; i < 32; i++) { const uint4 u = __ldg((const uint4*)P.mem0 + i * 32 + lane); e0 = amax(amax(e0, amax(u.x, u.y)), amax(u.z, u.w)); }
    e0 = min(max(warp_exp(e0), 31u), 253u) - 14;
    if (cta < 32) {
        const uint32_t* m = (const uint32_t*)(P.mem0 + (lane >> 2) * 1024 + cta * 32 + (lane & 3) * 2);
        const float sc = __uint_as_float((254 - e0) << 23);
        auto cv = [&](uint32_t u) { return pack2h(bf_lo(u) * sc, bf_hi(u) * sc); };
        const uint32_t y = cv(m[12]);
        st_relaxed4(zp, cv(m[0]), cv(m[4]), cv(m[8]), prmt(y, FULL, 0x7610));
        st_relaxed1(P.xb + xg_side(cta) + lane * 4, prmt(y, FULL, 0x3254));
    }
    if (cta < 40) {
#pragma unroll 1
        for (int b = 1; b < 8; b++) st_relaxed4(zp + xg_buf(b), 0, 0, 0, 0);
    }
    __threadfence();
    const uint32_t* ts = (const uint32_t*)(P.xb + XG_T) + lane;
    int32_t d0 = P.dly;
    const uint32_t go = mapa(sb + B_GO, (cta / 3 & 1) * 3 + 1 + (lane & 1));
    auto free_segment = [&]() { if (lane == 0) mbar_expect(sb + B_KVFULL, 16384); __syncwarp(); if (lane < 2) mbar_arrive_cluster(go); };
    for (int n = 0; (int32_t)(ld_acquire(&g_cnt(C_XCNT)) - (epoch + 1) * 256) < 0; n++) { __nanosleep(500); if (n > SPIN_LIMIT) spin_fault(); }
    const uint32_t ex = max(ld_relaxed1(&g_cnt(C_XMAX)) & 255, 67u);
    mbar_wait_bounded(sb + B_READY, 0);
    free_segment();
    if (lane == 0) st_relaxed2(g_hint + cta * 32, stamp_word(epoch + 1), lds32(sb + S_EV) | lds32(sb + S_EO) << 16);
    uint32_t a = gtime();
    for (int n = 0;; n++) {
        uint32_t bad = 0, e = 0; int32_t m = INT32_MIN;
#pragma unroll
        for (int i = 0; i < 3; i++) {
            uint32_t v[2];
            ld_relaxed2(v, g_hint + lane * 32 + i * 1024);
            bad |= (v[0] ^ (epoch + 1)) & 31u; m = max(m, (int32_t)((v[0] & ~31u) - a)); e = __vmaxu2(e, v[1]);
        }
        if (__all_sync(0xffffffffu, bad == 0)) {
            a += __reduce_max_sync(0xffffffffu, m);
            const uint32_t ev = __reduce_max_sync(0xffffffffu, e & 255), eo = __reduce_max_sync(0xffffffffu, e >> 16);
            if (lane == 0) { sts64(sb + S_SC, max(ev, 97u) + max(eo, 97u) - 244, ex); sts32(sb + S_ISC, e0 * 0x800080u); }
            break;
        }
        wait_clocks(100);
        if (n > SPIN_LIMIT) spin_fault();
    }
    wait_time(a, sb);
    if (lane == 0) mbar_arrive(sb + B_RELM);
#pragma unroll 1
    for (int s = 0; s < 63; s++) {
        const uint32_t seq = epoch * 63 + s + 1;
        mbar_wait_bounded(sb + B_P1, s & 1);
        const uint32_t tx = gtime();
        if (lane == 0) st_relaxed1(ts + (s & 1) * 256 + cta, (tx & ~31u) | (seq & 31u));
        { const uint32_t t = tx; PROFP(3) }
        if (s > 0) {
            const int32_t e0 = latest_stamp<32>(ts + (~s & 1) * 256 + 128, seq - 1, a, sb) + P.mrg - a;
            d0 += min(max(e0, min(e0 + P.guard, -P.clamp0)), P.clampv) / 2;
        }
        while ((int32_t)(gtime() - tx) < P.rd) nap(20);
        a = latest_stamp<32>(ts + (s & 1) * 256, seq, tx, sb) + d0;
        { const uint32_t t = gtime(); PROFP(0) }
        while ((int32_t)(a - gtime()) > 250) nap(40);
        wait_time(a, sb);
        if (lane == 0) mbar_arrive(sb + B_RELM);
        { const uint32_t t = a; PROFP(2) }
        mbar_wait_bounded(sb + B_RED, s & 1);
        { const uint32_t t = gtime(); PROFP(1) }
        const uint32_t g = tx + __reduce_max_sync(0xffffffffu, lds32(sb + S_TO + (lane & 7) * 4) - tx);
        if (lane == 0) st_relaxed1(ts + (s & 1) * 256 + 128 + cta, (g & ~31u) | (seq & 31u));
        if (s < 62) { if (P.kvd) nap(P.kvd); free_segment(); }
    }
}
__device__ __forceinline__ void st_async2(uint32_t a, uint32_t x, uint32_t y, uint32_t bar) {
    asm volatile("st.async.weak.shared::cluster.mbarrier::complete_tx::bytes.v2.b32 [%0], {%1,%2}, [%3];" ::"r"(a), "r"(x), "r"(y), "r"(bar) : "memory");
}
__device__ __forceinline__ uint32_t xor_or(uint32_t a, uint32_t b, uint32_t t) { uint32_t d; asm("lop3.b32 %0, %1, %2, %3, 0x7E;" : "=r"(d) : "r"(a), "r"(b), "r"(t)); return d; }
__device__ __forceinline__ uint32_t or3(uint32_t a, uint32_t b, uint32_t c) { uint32_t d; asm("lop3.b32 %0, %1, %2, %3, 0xFE;" : "=r"(d) : "r"(a), "r"(b), "r"(c)); return d; }
__device__ __forceinline__ bool tags_ok(uint32_t bad, uint32_t mask = 1) {
    uint32_t r;
    asm volatile("{\n.reg .pred P;\n.reg .b32 x;\nand.b32 x, %1, %2;\nsetp.ne.b32 P, x, 0;\nvote.sync.any.pred P, P, 0xffffffff;\nselp.u32 %0, 0, 1, P;\n}" : "=r"(r) : "r"(bad), "r"(mask));
    return r;
}
constexpr int SROW = 56;
#define PREA 8
#define PREB 9
#define RING1 6
#define RING2 7
#define RING3 8
#define PRE2 10
#define PRE2A 0
#define PRE3 0
#define EFENCE 0
#define RFENCE 1
#define PROG 16
#define EARLY 0
#define PLATE 1
#define NDEP 0
#define EFENCE2 0
#define LAG2 8
#define LAG 4
#define PUT1 33
#define DEPS 3
#define ADELAY 120
#define BDELAY 0
#define HOLD 1
#define XDELAY 330
#define FENCEA 0x80
#define FENCEB 0x80
#define FENCE2 0x220
#define OFENCE 0
#define MASK3 0x57
#define MASK4 0x55
#define MASK5 0x25
#define OFF3 0x5320
#define OFF4 0x6420
#define OFF5 0x0520
#define RESA (NRA == 3 ? 15 : NRA == 4 ? 3 : 0)
#define RESB (NRB == 3 ? 0xcc : NRB == 4 ? 0x30 : 0)
#define RESB1 (NRB == 3 ? 0xcc : NRB == 4 ? 0xc : 0)
__host__ __device__ constexpr int smem_mask(int NR) { return NR == 3 ? MASK3 : NR == 4 ? MASK4 : MASK5; }
__host__ __device__ constexpr bool round_smem(int r, int NR) { return smem_mask(NR) >> r & 1; }
__host__ __device__ constexpr int kord(int r, int NR) { int c = 0; for (int i = 0; i < r; i++) c += round_smem(i, NR) == round_smem(r, NR); return round_smem(r, NR) ? NR + c : c; }
__host__ __device__ constexpr int slot_r(int n, int NR) { return n < 32 ? n >> 2 : (((n & 31) >> 2) + ((NR == 3 ? OFF3 : NR == 4 ? OFF4 : OFF5) >> (n & 3) * 4)) & 7; }
__host__ __device__ constexpr int slot_k(int n, int NR) { return kord(slot_r(n, NR), NR); }
__host__ __device__ constexpr int slot_sord(int n, int NR) { int c = 0; for (int i = 0; i < n; i++) c += slot_k(i, NR) >= NR; return c; }
__host__ __device__ constexpr int sfrag_slot(int q, int NR) { for (int n = 0; n < 64; n++) if (slot_k(n, NR) >= NR && slot_sord(n, NR) == q) return n; return -1; }
__host__ __device__ constexpr int w1_loaded(int n, int NR, int PRE) {
    int q = PRE;
    for (int i = 0; i <= n; i++) q += q < (8 - NR) * 8 && q - slot_sord(i + 1, NR) < (i < 32 ? RING1 : RING2);
    return q;
}
template <int Q, int NR>
__device__ __forceinline__ void load_w1(uint32_t* w, const uint32_t* a) {
    constexpr int n = sfrag_slot(Q, NR);
    ldsm4t(w, a[n & 3] + ((slot_k(n, NR) - NR) * 2 + (n >> 5)) * 2048);
}
constexpr int AB = NRA < 5, BB = 3 - AB;
__device__ __forceinline__ bool w2_full(int role, int warp) { return warp < (role == 2 ? 2 : 3); }
__device__ __forceinline__ int w2_nblk(int role, int warp) { return warp < 4 ? BB - !w2_full(role, warp) : AB; }
__host__ __device__ constexpr int w2_step(bool full, int i) { return AB ? (full ? 2 * i : 0) : full ? (i == 0 ? 0 : i == 1 ? 16 - 2 * EARLY : 18 - 2 * EARLY) : i; }
__device__ __forceinline__ int w2_block(int role, int warp) {
    const int f = role * 3 + warp, g = role == 2 ? warp : role;
    if (AB) return (warp >= 4 ? role * 4 + (warp - 4) : w2_full(role, warp) ? 16 + 4 * (f >> 1) + (f & 1) : 12 + g) ^ EARLY;
    return w2_full(role, warp) ? EARLY + 4 * (f >> 1) + (f & 1) : EARLY + 2 + 4 * g;
}
__device__ __forceinline__ int w2_res(int role, int warp) { return warp >= 4 ? RESA : w2_full(role, warp) ? RESB : RESB1; }
__device__ __forceinline__ int w2_units(int role, int warp) { return w2_nblk(role, warp) * 4 - (5 - (warp < 4 ? NRB : NRA)) * 2; }
constexpr int W2B = (BB * 4 - (5 - NRB) * 2) * 2048, W2A = (AB * 4 - (5 - NRA) * 2) * 2048;
static_assert(S_W2 + 4 * W2B - 8192 + 4 * W2A == S_KV, "weights");
__device__ __forceinline__ int w1_base(int warp) { return S_W1 + (warp < 4 ? warp * (8 - NRB) : 4 * (8 - NRB) + (warp - 4) * (8 - NRA)) * 4096; }
__device__ __forceinline__ int w2_base(int warp) { return S_W2 + (warp < 4 ? warp * W2B : 4 * W2B - 8192 + (warp - 4) * W2A); }
__device__ __forceinline__ void chain_load(const Params& P, uint32_t sb, int cta, int warp, int lane, int round) {
    const int role = cta % 3, h = cta / 3;
    mbar_expect_e(sb + B_INIT, round ? (8 - (warp < 4 ? NRB : NRA)) * 4096 : 20480);
    if (round) mbar_expect_e(sb + B_INIT2, w2_units(role, warp) * 2048);
    __syncwarp();
    const int m1 = (warp < 4 ? smem_mask(NRB) : smem_mask(NRA)) ^ (round ? 0 : 255), below = (1 << lane) - 1;
    const int m2 = (w2_res(role, warp) ^ (round ? 0xfff : 0)) & ((1 << w2_nblk(role, warp) * 4) - 1);
    const uint32_t d1 = sb + (round ? w1_base(warp) : warp * 20480), d2 = round ? sb + w2_base(warp) : d1 + __popc(m1) * 4096;
    if (m1 >> lane & 1) tma3d(d1 + __popc(m1 & below) * 4096, &P.tm[M_C1 + role], 0, warp * 128 + lane * 16, h * 2, sb + B_INIT);
    __syncwarp();
    if (m2 >> lane & 1)
        tma2d(d2 + __popc(m2 & below) * 2048, &P.tm[M_CO], (w2_block(role, warp) + w2_step(w2_full(role, warp), lane >> 2)) * 32, h * 128 + (lane & 3) * 32, sb + (round ? B_INIT2 : B_INIT));
    __syncwarp();
}

__device__ __forceinline__ void put_partials(bool TR, uint32_t a, const float* x, const float* y) {
    if (TR) stsm4t(a, pack2(x[0], x[1]), pack2(x[2], x[3]), pack2(y[0], y[1]), pack2(y[2], y[3]));
    else stsm4(a, pack2(x[0], x[1]), pack2(x[2], x[3]), pack2(y[0], y[1]), pack2(y[2], y[3]));
}
template <int NR, int PRE, int FM, int B, int E>
__device__ __forceinline__ void project(float (*acc)[4], bool TR, const uint32_t (*wr)[4], uint32_t (*as)[4], uint32_t (*v)[4], uint32_t* x, const uint32_t* w1a, uint32_t pp, uint32_t zero) {
    static_for<B, E>([&](auto I) {
        constexpr int n = I.value, kk = slot_k(n, NR), T = (n >> 5) * 4 + (n & 3), so = slot_sord(n, NR), q = w1_loaded(n - 1, NR, PRE);
        constexpr bool sm = kk >= NR;
        const uint32_t* w = sm ? as[so] : wr[sm ? 0 : (kk * 2 + (n >> 5)) * 4 + (n & 3)];
        if constexpr (n == 32 && PUT1 < 32) { put_partials(TR, pp, acc[0], acc[1]); put_partials(TR, pp + 4096, acc[2], acc[3]); }
        if constexpr (n == 0) {
            const uint32_t c = prmt(v[0][3], x[0], 0x3254);
            v[0][0] = h2bf(v[0][0], v[0][0]); v[0][1] = h2bf(v[0][1], v[0][1]); v[0][2] = h2bf(v[0][2], v[0][2]); v[0][3] = h2bf(v[0][3], x[0]);
            x[0] = c;
        }
        if constexpr ((n & 31) < 4) acc[T][0] = acc[T][1] = acc[T][2] = acc[T][3] = 0.f;
        mma16816(acc[T], w[0], w[1], w[2], w[3], v[slot_r(n, NR) >> 1][(slot_r(n, NR) & 1) * 2], v[slot_r(n, NR) >> 1][(slot_r(n, NR) & 1) * 2 + 1]);
        if constexpr (n == DEPS) {
            const uint32_t sel = __float_as_uint(acc[T][0]) * zero + 0x7610;
#pragma unroll
            for (int b = 1; b < 4; b++) {
                if (b <= NDEP) cvt_block(v[b], x[b], sel);
                else {
                    const uint32_t c = prmt(v[b][3], x[b], 0x3254);
                    v[b][0] = h2bf(v[b][0], v[b][0]); v[b][1] = h2bf(v[b][1], v[b][1]); v[b][2] = h2bf(v[b][2], v[b][2]); v[b][3] = h2bf(v[b][3], x[b]);
                    x[b] = c;
                }
            }
        }
        if constexpr (w1_loaded(n, NR, PRE) > q) load_w1<q, NR>(as[q], w1a);
        if constexpr (n == PUT1 && n >= 32) { put_partials(TR, pp, acc[0], acc[1]); put_partials(TR, pp + 4096, acc[2], acc[3]); }
        if constexpr (n % 4 == 3 && (FM >> (n / 4) & 1) && n != E - 1) sched_fence();
    });
    if constexpr (E == 64) { put_partials(TR, pp + 8192, acc[4], acc[5]); put_partials(TR, pp + 12288, acc[6], acc[7]); }
}
__device__ __forceinline__ void reduce8(const uint32_t (*x)[4], const uint32_t* sel, float sc, uint32_t& r0, uint32_t& r1) {
    float d[4][4];
#pragma unroll
    for (int i = 0; i < 4; i++) {
        d[i][0] = d[i][1] = d[i][2] = d[i][3] = 0.f;
        mma16816(d[i], x[i][0], x[i][1], x[i][2], x[i][3], sel[2 * i], sel[2 * i + 1]);
    }
    r0 = pack2(((d[0][0] + d[1][0]) + (d[2][0] + d[3][0])) * sc, ((d[0][1] + d[1][1]) + (d[2][1] + d[3][1])) * sc);
    r1 = pack2(((d[0][2] + d[1][2]) + (d[2][2] + d[3][2])) * sc, ((d[0][3] + d[1][3]) + (d[2][3] + d[3][3])) * sc);
}

#define ISTAMP(i)
__host__ __device__ constexpr int wo_count(int n, int RES, bool res) { int c = 0; for (int i = 0; i < n; i++) c += (RES >> (i >> 2) & 1) == res; return c; }
__host__ __device__ constexpr int wo_loaded(int n, int RES, int PRE, int end) { int q = PRE; for (int i = 0; i <= n; i++) q += q < end && q - wo_count(i + 1, RES, false) < RING3; return q; }
template <int Q>
__device__ __forceinline__ void load_w2(uint32_t* w, const uint32_t* a) { ldsm4t(w, a[Q & 1] + (Q >> 1) * 1024); }
template <int NB, int RES, int PRE, int FM>
__device__ __forceinline__ void wo_blocks(uint32_t (*w)[4], const uint32_t (*wp)[4], uint32_t oa, const uint32_t* wa, const uint8_t* dst, const uint8_t* dsd, bool odd) {
    float a[NB][4][4];
    uint32_t o[4][4], r[5];
    bar_sync(3, 256);
#pragma unroll
    for (int i = 0; i < 4; i++) ldsm4(o[i], oa + i * 512);
    if (FM & 1) sched_fence();
    static_for<0, NB * 16>([&](auto I) {
        constexpr int n = I.value, i = n & 15, end = wo_count(NB * 16, RES, false), q = wo_loaded(n - 1, RES, PRE, end);
        constexpr bool res = RES >> (n >> 2) & 1;
        const uint32_t* b = o[i >> 2] + (i & 2);
        const uint32_t* x = res ? wp[wo_count(n, RES, true)] : w[wo_count(n, RES, false)];
        float* d = a[n >> 4][i & 3];
        if constexpr (i < 4) d[0] = d[1] = d[2] = d[3] = 0.f;
        mma16816(d, x[0], x[1], x[2], x[3], b[0], b[1]);
        if constexpr (wo_loaded(n, RES, PRE, end) > q) load_w2<q>(w[q], wa);
        if constexpr (n == NB * 16 - 1 || (n >= 16 && i == LAG - 1)) {
            const float (*e)[4] = a[n == NB * 16 - 1 ? NB - 1 : (n >> 4) - 1];
            const uint32_t y = pack2h(e[1][2] + e[3][2], e[1][3] + e[3][3]);
            r[0] = movm(pack2h(e[0][0] + e[2][0], e[0][1] + e[2][1])); r[1] = movm(pack2h(e[0][2] + e[2][2], e[0][3] + e[2][3]));
            r[2] = movm(pack2h(e[1][0] + e[3][0], e[1][1] + e[3][1])); r[3] = movm(odd ? ONES : y); r[4] = movm(odd ? y : ONES);
        }
        if constexpr (n == NB * 16 - 1 || (n >= 16 && i == LAG2 - 1)) {
            constexpr int bs = w2_step(NB == BB, n == NB * 16 - 1 ? NB - 1 : (n >> 4) - 1);
            red_add4(dst + bs * 2048, r[0], r[1], r[2], r[3]);
            red_add1(dsd + (bs >> 1) * 1024 + (bs & 1) * 256, r[4]);
        }
        if constexpr (((FM >> (n / 4 + 1)) & 1) && (n & 3) == 3 && n != NB * 16 - 1) sched_fence();
    });
}
#define FRAG1(ln) ((((ln) & 7) + ((ln) >> 4) * 8) * 128 + ((((((ln) >> 3) & 1) << (ROLE == 1)) ^ ((ln) & 7)) << 4))
#define FRAG2(ln) ((((ln) & 7) + ((ln) >> 4) * 8) * 64 + (((((ln) >> 3) & 1) ^ (((ln) >> 1) & 3)) << 4))
#define TILE_X(i) (ROLE == 1 ? (((i) >> 1) << 6) | (((i) & 1) << 4) : (i) << 5)
__device__ __forceinline__ void chain_fetch(const Params& P, const uint32_t sb, const int cta, const int warp, const int lane, uint32_t (*wr)[4]) {
    const int ROLE = cta % 3, nr = warp < 4 ? NRB : NRA;
    mbar_wait(sb + B_INIT, 0);
    ISTAMP(0)
#pragma unroll
    for (int f = 0; f < 40; f++) {
        const bool w1 = f < (NRA < NRB ? NRA : NRB) * 8 || f < nr * 8;
        ldsm4t(wr[f], sb + warp * 20480 + (f >> 2) * 2048 + (w1 ? FRAG1(lane) ^ TILE_X(f & 3) : (f & 2) * 512 + (FRAG2(lane) ^ ((f & 1) << 5))));
    }
    fence_async_smem();
    mbar_wait(sb + B_SFREE + (warp >> 2) * 8, 0);
    bar_sync(1, 256);
    chain_load(P, sb, cta, warp, lane, 1);
    ISTAMP(1)
}
__device__ __forceinline__ void chain_bounds(const uint32_t sb, const int cta, const int warp, const int lane, const uint32_t (*wr)[4]) {
    const int ROLE = cta % 3, nr = warp < 4 ? NRB : NRA;
    uint32_t m[6] = {}, u[4];
#pragma unroll
    for (int f = 0; f < 40; f++) m[f < 24 ? 0 : f >> 3] = amax4(m[f < 24 ? 0 : f >> 3], wr[f]);
    uint32_t m1 = amax(m[0], amax(nr > 3 ? m[3] : 0, nr > 4 ? m[4] : 0)), m2 = amax(nr > 3 ? 0 : m[3], nr > 4 ? 0 : m[4]);
    ISTAMP(5)
    mbar_wait(sb + B_INIT, 1);
    ISTAMP(3)
    if (ROLE == 2) {
#pragma unroll 4
        for (int i = 0; i < S_W2 / 4096; i++) { lds128(u, sb + S_W1 + warp * (S_W2 / 8) + i * 512 + lane * 16); m1 = amax4(m1, u); }
    }
    mbar_wait(sb + B_INIT2, 0);
    ISTAMP(7)
    const int n = w2_units(ROLE, warp) * 4;
#pragma unroll 4
    for (int i = 0; i < n; i++) { lds128(u, sb + w2_base(warp) + i * 512 + lane * 16); m2 = amax4(m2, u); }
    m1 = warp_exp(m1); m2 = warp_exp(m2);
    if (lane == 0) { if (ROLE == 2) red_max_shared(sb + S_EV, m1); red_max_shared(sb + S_EO, m2); }
}
template <bool ATT>
__device__ __forceinline__ void chain_role(const Params& P, const uint32_t sb, const int cta, const int warp, const int lane, const uint32_t (*wr)[4]) {
    constexpr int NR = ATT ? NRA : NRB, PRE = ATT ? PREA : PREB;
    const int h = cta / 3, ROLE = cta - h * 3;
    ISTAMP(6)
    uint32_t l8 = opq(sb + lane * 8, lane);
    const uint8_t* persu = (const uint8_t*)((ROLE == 1 ? g_km : g_vmt) + h * 512) - (sb >> 1);
    auto persist = [&](int s, int tile, uint32_t r0, uint32_t r1) {
        uint32_t* pp = (uint32_t*)(persu + s * 65536 + (ROLE == 1 ? (tile >> 1) * 512 + (tile & 1) * 128 : tile * 256) + (l8 >> 1));
        pp[0] = r0; pp[ROLE == 1 ? 64 : 32] = r1;
    };
    const uint32_t rk0 = (h & 1) * 3, rd1 = __shfl_sync(0xffffffffu, mapa(sb, rk0 + (ROLE + 1) % 3) - sb, 0), rd2 = __shfl_sync(0xffffffffu, mapa(sb, rk0 + (ROLE + 2) % 3) - sb, 0);
    const uint32_t xo = (ROLE == 2 ? S_XV : S_X + ROLE * 2048) + warp * 256;
    const bool full = w2_full(ROLE, warp);
    const int blk = w2_block(ROLE, warp);
    const uint32_t om = blk * 2048, os = xg_side(blk);
    const uint32_t w1o = sb + w1_base(warp), w2o = sb + w2_base(warp);
    ISTAMP(2)
    if (lane == 0) mbar_arrive(sb + B_READY);
#pragma unroll 1
    for (int s = 0;; s++) {
        l8 += s & P.zero;
        uint32_t r0, r1;
        {
            uint32_t v[4][4], as[(8 - NR) * 8][4], w1a[4];
            float acc[8][4];
            const uint32_t pst = sb + S_P1 + (l8 - sb) * 16 + ((warp * 16) ^ ((l8 & 56) * 2));
#pragma unroll
            for (int i = 0; i < 4; i++) w1a[i] = w1o + (FRAG1((l8 - sb) >> 3) ^ TILE_X(i));
            auto preload = [&]() { static_for<0, PRE>([&](auto I) { load_w1<I.value, NR>(as[I.value], w1a); }); };
#pragma unroll 1
            while (true) {
                uint32_t x[4];
                if (!(PLATE >> ATT & 1)) preload();
                const uint32_t lm = opq(l8 - sb, (l8 - sb) >> 3);
                const uint8_t* pm = P.xb + xg_buf(s) + warp * 8192 + xg_lane(lm >> 3);
                const uint8_t* ps = P.xb + xg_buf(s) + XG_SIDE + warp * 2048 + (lm >> 1);
                pin_ptr(pm); pin_ptr(ps);
                mbar_wait(sb + B_RELM, s & 1);
                if (ATT ? ADELAY : BDELAY) wait_clocks(ATT ? ADELAY : BDELAY);
                PROF(10)
#pragma unroll
                for (int b = 0; b < 4; b++) { ld_relaxed4(v[b], pm + b * 2048); ld_relaxed1n(x[b], ps + (b >> 1) * 1024 + (b & 1) * 256); }
                if (PLATE >> ATT & 1) { preload(); if (PLATE >> (ATT + 2) & 1) sched_fence(); }
                project<NR, PRE, ATT ? FENCEA : FENCEB, 0, PROG>(acc, ROLE == 2, wr, as, v, x, w1a, pst, P.zero);
                const uint32_t bad = xor_or(x[0], x[1], FULL) | xor_or(x[2], x[3], FULL);
                if (tags_ok(bad, 0xffffffffu)) break;
                COUNT_RETRY(warp >> 1)
            }
            PROF(0)
            project<NR, PRE, ATT ? FENCEA : FENCEB, PROG, 64>(acc, ROLE == 2, wr, as, v, nullptr, w1a, pst, 0);
            PROF(1)
            const uint32_t isc = lds32(sb + S_ISC + (s & 1) * 4);
            const uint32_t lq = l8 + ((s >> 3) & P.zero), e1 = s == 63 ? 0 : rd1, e2 = s == 63 ? 0 : rd2;
            uint32_t x[4][4], sel[8], xd[6] = {l8 + xo, l8 + xo + e1, l8 + xo + e2, sb + B_X + e1, sb + B_X + e2, sb + S_P1 + warp * 2048 + (lq & 64) * 16 + (lq & 128) + (lq & 56) * 2};
#pragma unroll
            for (int i = 0; i < 8; i++) sel[i] = (lq & 224) == i * 32 ? 0x3F803F80u : 0u;
            pin<6>(xd); pin<8>(sel);
            if (RFENCE) sched_fence();
            bar_sync(1, 256);
#pragma unroll
            for (int i = 0; i < 4; i++) ldsm4t(x[i], xd[5] + i * 256);
            if (!ATT && l8 == sb + (warp - 3) * 1024) mbar_arrive(sb + B_P1);
            uint32_t em = warp_exp(amax(amax4(amax(amax(v[0][0], v[0][1]), amax(v[0][2], v[0][3])), v[1]), amax4(amax(amax(v[2][0], v[2][1]), amax(v[2][2], v[2][3])), v[3])));
            if (EFENCE2) sched_fence();
            reduce8(x, sel, bf_hi(isc), r0, r1);
            st_async2(xd[1], r0, r1, xd[3]);
            st_async2(xd[2], r0, r1, xd[4]);
            sts64(xd[0], r0, r1);
            if (s == 63) { persist(s, warp, r0, r1); break; }
            if (l8 == sb) sts32(sb + S_EM + warp * 4, em + (isc >> 23));
            __syncwarp();
            if (l8 == sb) mbar_arrive(sb + B_X);
            PROF(2)
        }
        uint32_t w[40][4], w2a[2], odd;
        const uint8_t *po, *pd;
        auto wo_addr = [&]() {
            const uint32_t lo = (l8 + ((s >> 2) & P.zero) - sb) >> 3;
            w2a[0] = w2o + FRAG2(lo); w2a[1] = w2o + (FRAG2(lo) ^ 32);
            po = P.xb + xg_buf(s + 1) + om + xg_lane(lo);
            pd = P.xb + xg_buf(s + 1) + os + lo * 4;
            odd = lo & 4;
            pin_ptr(po); pin_ptr(pd); pin<2>(w2a); pin<1>(&odd);
        };
        uint32_t oa = l8 * 2 + (S_OX - sb);
        if constexpr (ATT) {
            const uint32_t ln = (l8 + ((s >> 4) & P.zero) - sb) >> 3;
            const uint32_t va = sb + S_KV + 8192 + ((warp >> 1) & 1) * 4096 + ((ln & 7) + (ln >> 4) * 8) * 128 + ((((warp & 1) * 4 + ((ln >> 3) & 1)) ^ (ln & 7)) << 4);
            const uint32_t ka = sb + S_KV + (warp & 1) * 2048 + (ln & 15) * 128 + (((ln >> 4) ^ (ln & 7)) << 4);
            uint32_t ad[5] = {sb + S_SX + (ln & 3) * (8 * SROW) + (ln >> 2) * 4 + (warp < 6 ? (warp - 4) * 64 : 128 + (warp - 6) * 32), l8 + S_XV + (warp - 4) * 512,
                              l8 + S_SX + (ln >> 2) * (4 * SROW - 32), oa + (warp - 4) * 512, sb + S_ISC + (~s & 1) * 4};
            if constexpr (AB) { wo_addr(); pin<1>(&oa); }
            pin<5>(ad);
            const uint32_t sa = ad[0], sr = ad[2];
            uint32_t vf[4][4], vm[2][2], q[8][2];
            float S[8][4];
#pragma unroll
            for (int n = 0; n < 8; n++) { S[n][0] = S[n][1] = S[n][2] = S[n][3] = 0.f; }
            mbar_wait(sb + B_KVFULL, s & 1);
            if (warp < 6) {
                uint32_t kf[8][4];
#pragma unroll
                for (int k = 0; k < 8; k++) ldsm4(kf[k], (ka ^ ((k & 3) << 5)) + (k >> 2) * 4096);
#pragma unroll
                for (int i = 0; i < 4; i++) ldsm4t(vf[i], (va ^ ((i & 1) << 5)) + (i >> 1) * 2048);
                mbar_wait(sb + B_X, s & 1);
                PROF(11)
#pragma unroll
                for (int k = 0; k < 8; k++) lds64(q[k], l8 + S_X + k * 256);
#pragma unroll
                for (int k = 0; k < 8; k++) mma16816(S[k], kf[k][0], kf[k][1], kf[k][2], kf[k][3], q[k][0], q[k][1]);
#pragma unroll
                for (int k = 0; k < 4; k++) { S[k][0] = S[2 * k][0] + S[2 * k + 1][0]; S[k][1] = S[2 * k][1] + S[2 * k + 1][1]; S[k][2] = S[2 * k][2] + S[2 * k + 1][2]; S[k][3] = S[2 * k][3] + S[2 * k + 1][3]; }
                sts32(sa, __float_as_uint((S[0][0] + S[1][0]) + (S[2][0] + S[3][0])));
                sts32(sa + 4 * SROW, __float_as_uint((S[0][1] + S[1][1]) + (S[2][1] + S[3][1])));
                sts32(sa + 32, __float_as_uint((S[0][2] + S[1][2]) + (S[2][2] + S[3][2])));
                sts32(sa + 4 * SROW + 32, __float_as_uint((S[0][3] + S[1][3]) + (S[2][3] + S[3][3])));
            } else {
#pragma unroll
                for (int i = 0; i < 4; i++) ldsm4t(vf[i], (va ^ ((i & 1) << 5)) + (i >> 1) * 2048);
                uint32_t xa = l8 + S_X + (warp - 6) * 1024;
                pin<1>(&xa);
                mbar_wait(sb + B_X, s & 1);
                PROF(11)
#pragma unroll
                for (int k = 0; k < 8; k++) lds64(q[k], xa + (k >> 2) * 2048 + (k & 3) * 256);
#pragma unroll
                for (int k = 0; k < 4; k++) mma16816(S[k], q[4 + (k & 2)][0], q[4 + (k & 2)][1], q[5 + (k & 2)][0], q[5 + (k & 2)][1], q[k][0], q[k][1]);
                sts32(sa, __float_as_uint((S[0][0] + S[2][0]) + (S[1][2] + S[3][2])));
                sts32(sa + 4 * SROW, __float_as_uint((S[0][1] + S[2][1]) + (S[1][3] + S[3][3])));
            }
            lds64(vm[0], ad[1]); lds64(vm[1], ad[1] + 256);
            PROF(7)
            bar_sync(2, 160);
            const float cs = 0.08838834764831845f * 1.4426950408889634f;
            float E[6][2];
#pragma unroll
            for (int i = 0; i < 6; i++) lds64f(E[(i + 4) % 6], sr + ((i + 4) % 6) * 32);
            const uint32_t isn = lds32(ad[4]);
            E[4][0] += E[5][0]; E[4][1] += E[5][1];
            float m = fmaxf(fmaxf(fmaxf(fmaxf(E[0][0], E[0][1]), fmaxf(E[1][0], E[1][1])), fmaxf(fmaxf(E[2][0], E[2][1]), fmaxf(E[3][0], E[3][1]))), fmaxf(E[4][0], E[4][1]));
            m = fmaxf(m, __shfl_xor_sync(0xffffffffu, m, 1));
            m = fmaxf(m, __shfl_xor_sync(0xffffffffu, m, 2));
            m *= cs;
            if constexpr (AB) static_for<0, PRE3>([&](auto I) { load_w2<I.value>(w[I.value], w2a); });
            uint32_t pa[5];
#pragma unroll
            for (int i = 0; i < 5; i++) { const int k = (i + 4) % 5; E[k][0] = ex2(fmaf(E[k][0], cs, -m)); E[k][1] = ex2(fmaf(E[k][1], cs, -m)); pa[k] = pack2(E[k][0], E[k][1]); }
            if (EFENCE) sched_fence();
            float O[2][4], Z[4];
#pragma unroll
            for (int i = 0; i < 4; i++) { O[0][i] = O[1][i] = Z[i] = 0.f; }
            mma1688(Z, isn, isn, pa[4]);
            mma1688(O[0], vm[0][0], vm[0][1], pa[4]);
            mma1688(O[1], vm[1][0], vm[1][1], pa[4]);
#pragma unroll
            for (int k = 0; k < 2; k++) {
                mma16816(Z, isn, isn, isn, isn, pa[2 * k], pa[2 * k + 1]);
#pragma unroll
                for (int i = 0; i < 2; i++) mma16816(O[i], vf[2 * k + i][0], vf[2 * k + i][1], vf[2 * k + i][2], vf[2 * k + i][3], pa[2 * k], pa[2 * k + 1]);
            }
            const float i0 = rcp(Z[0]), i1 = rcp(Z[1]);
            stsm4t(ad[3], pack2(O[0][0] * i0, O[0][1] * i1), pack2(O[0][2] * i0, O[0][3] * i1), pack2(O[1][0] * i0, O[1][1] * i1), pack2(O[1][2] * i0, O[1][3] * i1));
            PROF(4)
            if constexpr (AB) wo_blocks<1, RESA, PRE3, OFENCE / 2>(w, wr + NR * 8, oa, w2a, po, pd, odd);
            else bar_arrive(3, 256);
            if (ROLE != 0) persist(s, warp, r0, r1);
            if (warp == 7 && l8 == sb) mbar_expect(sb + B_X, 4096);
        } else {
            if (ROLE != 0) persist(s, warp, r0, r1);
            wo_addr(); pin<1>(&oa);
            static_for<0, PRE2A>([&](auto I) { load_w2<I.value>(w[I.value], w2a); });
            mbar_wait(sb + B_X, s & 1);
            if (warp == 0) {
                uint32_t sc[2];
                lds64(sc, sb + S_SC);
                const int em = __reduce_max_sync(0xffffffffu, lds32(sb + S_EM + ((l8 >> 1) & 28)));
                if (l8 == sb) sts32(sb + S_ISC + (~s & 1) * 4, min(max(em - 127, (int)sc[1]) + (int)sc[0], 253) * 0x800080u);
                bar_arrive(2, 160);
            }
            wait_clocks(XDELAY - (warp == 0) * 100);
            constexpr int PRE1 = (BB - 1) * 16 - (5 - NRB) * 8 < PRE2 ? (BB - 1) * 16 - (5 - NRB) * 8 : PRE2;
            static_for<PRE2A, PRE1>([&](auto I) { load_w2<I.value>(w[I.value], w2a); });
            if (full) {
                static_for<PRE1, PRE2>([&](auto I) { load_w2<I.value>(w[I.value], w2a); });
                wo_blocks<BB, RESB, PRE2, FENCE2 * 2 + OFENCE % 2>(w, wr + NR * 8, oa, w2a, po, pd, odd);
            } else wo_blocks<BB - 1, RESB1, PRE1, FENCE2 * 2 + OFENCE % 2>(w, wr + NR * 8, oa, w2a, po, pd, odd);
        }
        PROF(5)
        if (l8 == sb) { sts32(sb + S_TO + warp * 4, gtime()); mbar_arrive(sb + B_RED); }
        if (HOLD && !(PLATE >> ATT & 1)) mbar_wait(sb + B_RED, s & 1);
        if (ROLE != 0 && (s & 3) == 3 && l8 == sb) mbar_arrive(sb + B_PERS);
        if (ROLE == 0 && s == 62) return;
    }
    __syncwarp();
    if (l8 == sb) mbar_arrive(sb + B_PERS);
}
#define IP(i)
struct Pipe { uint32_t stage, phase; };
struct Cons {
    uint32_t sb, rel;
    int wg, wq, lane, rank, pair;
    uint32_t nst;
    Pipe p;
};
__device__ __forceinline__ void pipe_next(Pipe& p) { p.stage = (p.stage + 1) & (NSTAGE - 1); p.phase ^= (p.stage == 0); }
__device__ __forceinline__ void release(const Cons& c, uint32_t stage) { if (c.lane < 2) mbar_arrive_cluster(c.rel + stage * 8); }
__device__ __forceinline__ void wait_full(const Cons& c) { mbar_wait(c.sb + B_FULL + c.p.stage * 8, c.p.phase); }

enum { PEND_NONE = 0, PEND_KVO = 1, PEND_HT = 2, PEND_OUT = 3, PEND_OUTA = 4 };
struct Pend { uint32_t pk[64]; int kind, row, col, cnt; };

__device__ __forceinline__ void staging_wait(const Cons& c) { if (c.nst) mbar_wait(c.sb + B_SFREE + c.wg * 8, (c.nst - 1) & 1); }
__device__ __forceinline__ void staging_post(Cons& c, int kind, int row, int col, int cnt) {
    __syncwarp();
    if (c.lane == 0) {
        if (c.wq == 0) { const uint32_t x[4] = {(uint32_t)kind, (uint32_t)row, (uint32_t)col, (uint32_t)cnt}; sts128(c.sb + S_DESC + c.wg * 16, x); }
        mbar_arrive(c.sb + B_SFULL + c.wg * 8);
    }
    c.nst++;
}
__device__ __forceinline__ void drain(const Params& P, Cons& c, Pend& d) {
    const uint32_t* pk = d.pk;
    const bool ht = d.kind == PEND_HT;
    const int hi = (c.lane >> 3) & 1;
    const uint32_t stg = c.sb + S_STG + c.wg * 16384, base = stg + ((ht ? hi * 32 + c.wq * 8 : c.wq * 16 + hi * 8) + (c.lane & 7)) * 128;
    staging_wait(c);
#pragma unroll
    for (int j = 0; j < 8; j++) {
        const int ch = (j & 3) * 2 + (c.lane >> 4);
        stsm4(base + (j >> 2) * 8192 + ((ch ^ (c.lane & 7)) << 4), pk[j * 4], pk[j * 4 + 1], pk[j * 4 + 2], pk[j * 4 + 3]);
    }
    if (d.kind >= PEND_OUT) {
        const uint32_t rd = stg + (c.lane >> 4) * 8192 + c.wq * 2048 + (c.lane & 15) * 8;
        const int s1 = d.kind == PEND_OUT ? 2 : 64, s2 = d.kind == PEND_OUT ? 8 : 2;
        const float* o = P.out + (size_t)(d.row + c.wq * 2 * s2) * 2048 + d.col + c.lane * 4;
        __syncwarp();
#pragma unroll
        for (int r = 0; r < 16; r++) {
            uint32_t u[2];
            lds64(u, (rd ^ ((r & 7) << 4)) + r * 128);
            st_stream4(o + ((r & 1) + (r >> 1 & 3) * s1 + (r >> 3) * s2) * 2048, bf_lo(u[0]), bf_hi(u[0]), bf_lo(u[1]), bf_hi(u[1]));
        }
        __syncwarp();
    } else {
        fence_async_smem();
        staging_post(c, d.kind, d.row, d.col, (d.col & 128) ? d.cnt : -1);
    }
    if (d.col & 128) d.kind = PEND_NONE;
    d.col += 128;
#pragma unroll
    for (int i = 0; i < 32; i++) d.pk[i] = d.pk[32 + i];
}

constexpr int S_STG2 = 8 * 20480, PEND_BOTH = 8;
__device__ __forceinline__ void drain_both(Cons& c, const Pend& d) {
    const uint32_t base = c.sb + c.wg * 16384 + (c.wq * 16 + ((c.lane >> 3) & 1) * 8 + (c.lane & 7)) * 128;
#pragma unroll
    for (int j = 0; j < 16; j++)
        stsm4(base + (j < 8 ? S_STG : S_STG2) + (j >> 2 & 1) * 8192 + ((((j & 3) * 2 + (c.lane >> 4)) ^ (c.lane & 7)) << 4), d.pk[j * 4], d.pk[j * 4 + 1], d.pk[j * 4 + 2], d.pk[j * 4 + 3]);
    fence_async_smem();
    staging_post(c, PEND_KVO | PEND_BOTH, d.row, d.col, d.cnt);
}

__device__ __forceinline__ void store_warp(const Params& P, uint32_t sb, int wg, int cta) {
    if (cta < 128) {
        for (int i = 0; i < P.xd; i++) __nanosleep(1000);
        const uint32_t e1 = get_epoch(sb) + 1;
        const uint4* x = (const uint4*)P.Bx + (cta * 2 + wg) * 1024 + (threadIdx.x & 31);
        uint32_t m = 0;
#pragma unroll 4
        for (int i = 0; i < 32; i++) { const uint4 u = __ldg(x + i * 32); m = amax(amax(m, amax(u.x, u.y)), amax(u.z, u.w)); }
        m = warp_exp(m);
        if (elect_one()) { atomicMax(&g_cnt(C_XMAX), e1 << 8 | m); red_release(&g_cnt(C_XCNT)); }
        __syncwarp();
    }
    const uint32_t stg = sb + S_STG + wg * 16384;
#pragma unroll 1
    for (uint32_t n = 0;; n++) {
        mbar_wait(sb + B_SFULL + wg * 8, n & 1);
        uint32_t x[4];
        lds128(x, sb + S_DESC + wg * 16);
#pragma unroll
        for (int i = 0; i < 4; i++) x[i] = __shfl_sync(0xffffffffu, x[i], 0);
        if (x[0] == PEND_NONE) break;
        const bool ht = x[0] == PEND_HT;
        const CUtensorMap* m = &P.tm[ht ? M_HTS : M_KVO];
        const uint64_t pol = P.pol[ht ? 2 : x[1] >= 4096 ? 1 : (x[1] & 2047) < 1536 ? 0 : 10];
        if (elect_one()) {
#pragma unroll
            for (int i = 0; i < 4; i++) tma_store2d(m, x[2] + (i >> 1) * 64, x[1] + (i & 1) * (ht ? 1024 : 32), stg + i * 4096, pol);
            if (x[0] & PEND_BOTH) {
#pragma unroll 1
                for (int i = 0; i < 4; i++) tma_store2d(m, x[2] + 128 + (i >> 1) * 64, x[1] + (i & 1) * 32, stg + (S_STG2 - S_STG) + i * 4096, pol);
            }
            bulk_commit();
            bulk_wait_read();
            mbar_arrive(sb + B_SFREE + wg * 8);
            if ((int)x[3] >= 0) { bulk_wait_all(); fence_async(); red_relaxed(&g_cnt(x[3])); }
        }
        __syncwarp();
    }
}

template <int TA, int TB, bool FIRST>
__device__ __forceinline__ void issue_ktile(float* acc, const Cons& c) {
    const uint32_t a = c.sb + c.p.stage * STAGE + c.wg * 8192, b = c.sb + c.p.stage * STAGE + 16384;
    const uint64_t da = mkdesc(a, TA ? 8192 : 16, 1024, 1), db = mkdesc(b, TB ? 8192 : 16, 1024, 1);
    wg_fence();
#pragma unroll
    for (int k = 0; k < 4; k++) {
        if (FIRST && k == 0) wgmma_ss256_first<TA, TB>(acc, da, db);
        else wgmma_ss256<TA, TB>(acc, da + (TA ? 128 : 2) * k, db + (TB ? 128 : 2) * k);
    }
    wg_commit();
}
template <bool KVONLY, bool FIRST>
__device__ __forceinline__ void issue_any(float* acc, const Cons& c, int type) {
    wait_full(c);
    if (!KVONLY && type == T_A1) issue_ktile<0, 0, FIRST>(acc, c);
    else if (!KVONLY && type == T_A2) issue_ktile<1, 0, FIRST>(acc, c);
    else issue_ktile<0, 1, FIRST>(acc, c);
}
template <bool KVONLY = false>
__device__ __forceinline__ void mainloop(float* acc, const Params& P, Cons& c, Pend& d, int type, int nk) {
    issue_any<KVONLY, true>(acc, c, type);
    if (!KVONLY) { IP(0) }
    uint32_t prev = c.p.stage;
    pipe_next(c.p);
#pragma unroll 1
    for (int kt = 1; kt < nk; kt++) {
        if (!KVONLY && d.kind != PEND_NONE && kt != 2) drain(P, c, d);
        issue_any<KVONLY, false>(acc, c, type);
        wg_wait<1>();
        release(c, prev);
        prev = c.p.stage;
        pipe_next(c.p);
    }
    d.kind = PEND_NONE;
    wg_wait<0>();
    pin<128>(acc);
    release(c, prev);
    if (!KVONLY) { IP(1) }
}
__device__ __forceinline__ void pack_half(uint32_t* pk, const float* a) {
#pragma unroll
    for (int i = 0; i < 32; i++) pk[i] = pack2(a[2 * i], a[2 * i + 1]);
}

__device__ __forceinline__ void epi_kv(const float* acc, const Cons& c, Pend& d, int mb, int nb) {
    pack_half(d.pk, acc); pack_half(d.pk + 32, acc + 64);
    d.kind = PEND_KVO; d.row = (nb >> 4) * 2048 + mb * 256 + c.rank * 128 + c.wg * 64; d.col = (nb & 15) * 256; d.cnt = C_KV + mb;
}

__device__ __forceinline__ void qa_scores(float* S, float* Sm, const uint32_t* q, Cons& c) {
    wait_full(c);
    const uint32_t st = c.sb + c.p.stage * STAGE;
    const uint64_t dk = mkdesc(st + c.wg * 8192, 16, 1024, 1), dm = mkdesc(st + 32768 + c.wg * 4096, 128, 2048, 0);
    wg_fence();
#pragma unroll
    for (int i = 0; i < 8; i++) wgmma_rs64<0>(S, q + i * 4, dk + (i >> 2) * 1024 + (i & 3) * 2, i != 0);
#pragma unroll
    for (int i = 0; i < 8; i++) wgmma_rs16<0>(Sm, q + i * 4, dm + i * 16, i != 0);
    wg_commit();
    pipe_next(c.p);
}
__device__ __forceinline__ void qa_softmax(uint32_t (*pa)[4], const float* S, const float* Sm, const Cons& c) {
    const int t = c.lane & 3, i0 = (c.wq & 1) * 16 + (c.lane >> 2) - 2 * t;
    const bool sg = c.wq >= 2;
    const float cs = 0.08838834764831845f * 1.4426950408889634f;
    float x[2][10];
#pragma unroll
    for (int r = 0; r < 2; r++) {
#pragma unroll
        for (int j = 0; j < 4; j++)
#pragma unroll
            for (int e = 0; e < 2; e++) {
                const float v = sg ? S[16 + j * 4 + r * 2 + e] : S[j * 4 + r * 2 + e];
                x[r][j * 2 + e] = (j * 8 + e - r * 8 > i0) ? -1e9f / 0.08838834764831845f : v;
            }
        x[r][8] = sg ? Sm[4 + r * 2] : Sm[r * 2];
        x[r][9] = sg ? Sm[5 + r * 2] : Sm[1 + r * 2];
        float m = fmaxf(fmaxf(fmaxf(fmaxf(x[r][0], x[r][1]), fmaxf(x[r][2], x[r][3])), fmaxf(fmaxf(x[r][4], x[r][5]), fmaxf(x[r][6], x[r][7]))), fmaxf(x[r][8], x[r][9]));
        m = fmaxf(m, __shfl_xor_sync(0xffffffffu, m, 1));
        m = fmaxf(m, __shfl_xor_sync(0xffffffffu, m, 2));
        m *= -cs;
#pragma unroll
        for (int i = 0; i < 10; i++) x[r][i] = ex2(fmaf(x[r][i], cs, m));
        float sum = (((x[r][0] + x[r][1]) + (x[r][2] + x[r][3])) + ((x[r][4] + x[r][5]) + (x[r][6] + x[r][7]))) + (x[r][8] + x[r][9]);
        sum += __shfl_xor_sync(0xffffffffu, sum, 1);
        sum += __shfl_xor_sync(0xffffffffu, sum, 2);
        const float inv = rcp(sum);
#pragma unroll
        for (int i = 0; i < 10; i++) x[r][i] *= inv;
    }
#pragma unroll
    for (int ks = 0; ks < 2; ks++)
#pragma unroll
        for (int i = 0; i < 4; i++) {
            const uint32_t p = pack2(x[i & 1][ks * 4 + (i >> 1) * 2], x[i & 1][ks * 4 + (i >> 1) * 2 + 1]);
            pa[ks][i] = sg ? 0u : p;
            pa[2 + ks][i] = sg ? p : 0u;
        }
#pragma unroll
    for (int r = 0; r < 2; r++) {
        const uint32_t p = pack2(x[r][8], x[r][9]);
        pa[4][r] = sg ? 0u : p;
        pa[4][2 + r] = sg ? p : 0u;
    }
}
__device__ __forceinline__ void qa_values(float* O, uint32_t (*pa)[4], Cons& c) {
    wait_full(c);
    const uint32_t st = c.sb + c.p.stage * STAGE;
    const uint64_t dv = mkdesc(st + c.wg * 8192, 16384, 1024, 1), dm = mkdesc(st + 32768 + c.wg * 4096, 2048, 128, 0);
    pin<20>(&pa[0][0]);
    wg_fence();
#pragma unroll
    for (int ks = 0; ks < 4; ks++) wgmma_rs128<1>(O, pa[ks], dv + ks * 128, ks != 0);
    wgmma_rs128<0>(O, pa[4], dm, 1);
    wg_commit();
    pipe_next(c.p);
}
__device__ __forceinline__ void epi_qa(const float* acc, Cons& c, Pend& d, int mb, int nb) {
    uint32_t q[64], pa[2][5][4];
    float S0[32] = {}, M0[8] = {}, S1[32] = {}, M1[8] = {}, O0[64] = {}, O1[64] = {};
    const uint32_t k0 = c.p.stage;
    pack_half(q, acc);
    pin<32>(q); pin<32>(S0); pin<8>(M0);
    qa_scores(S0, M0, q, c);
    pack_half(q + 32, acc + 64);
    pin<32>(q + 32); pin<32>(S1); pin<8>(M1);
    qa_scores(S1, M1, q + 32, c);
    wg_wait<1>();
    pin<32>(S0); pin<8>(M0);
    release(c, k0);
    qa_softmax(pa[0], S0, M0, c);
    wg_wait<0>();
    pin<32>(S1); pin<8>(M1); pin<64>(q);
    release(c, (k0 + 1) & (NSTAGE - 1));
    pin<64>(O0);
    qa_values(O0, pa[0], c);
    qa_softmax(pa[1], S1, M1, c);
    pin<64>(O1);
    qa_values(O1, pa[1], c);
    wg_wait<1>();
    pin<64>(O0); pin<20>(&pa[0][0][0]);
    release(c, (k0 + 2) & (NSTAGE - 1));
    pack_half(d.pk, O0);
    wg_wait<0>();
    pin<64>(O1); pin<20>(&pa[1][0][0]);
    release(c, (k0 + 3) & (NSTAGE - 1));
    pack_half(d.pk + 32, O1);
    d.kind = PEND_KVO; d.row = 4096 + mb * 256 + c.rank * 128 + c.wg * 64; d.col = nb * 256; d.cnt = C_O + mb * 16 + nb;
}

__device__ __forceinline__ void epi_op(const float* acc, const Cons& c, Pend& d, int mb, int nb) {
    pack_half(d.pk, acc); pack_half(d.pk + 32, acc + 64);
    d.kind = PEND_OUT; d.row = mb * 256 + c.rank * 128 + c.wg * 64; d.col = 1024 + nb * 256;
}

__device__ __forceinline__ void epi_a2(float* acc, const Params& P, Cons& c, Pend& d, int mb, int nb) {
    const int g = c.lane >> 2, t = c.lane & 3;
#pragma unroll
    for (int hf = 0; hf < 2; hf++) {
        wait_full(c);
        const uint32_t st = c.sb + c.p.stage * STAGE, xa = st + (c.wg * 64 + c.wq * 16 + g) * 128 + t * 4 + (g << 4), da = st + 32768 + t * 4;
#pragma unroll
        for (int j = 0; j < 16; j++) {
            const float* a = acc + hf * 64 + j * 4;
            const uint32_t ad = (xa ^ ((j & 7) << 4)) + (j >> 3) * 16384;
            const uint32_t dv = lds32(da + j * 16), u0 = mul_bf2(lds32(ad), dv), u1 = mul_bf2(lds32(ad + 1024), dv);
            d.pk[hf * 32 + j * 2] = pack2(a[0] + bf_lo(u0), a[1] + bf_hi(u0));
            d.pk[hf * 32 + j * 2 + 1] = pack2(a[2] + bf_lo(u1), a[3] + bf_hi(u1));
        }
        __syncwarp();
        release(c, c.p.stage);
        pipe_next(c.p);
    }
    d.kind = PEND_OUTA; d.row = mb * 256 + c.rank * 32 + c.wg * 16; d.col = nb * 256;
}

#define TSTAMP(i)
__device__ __forceinline__ float2 cmul(float2 a, float2 b) { return make_float2(fmaf(a.x, b.x, -a.y * b.y), fmaf(a.x, b.y, a.y * b.x)); }
__device__ __forceinline__ float2 cfma(float2 a, float2 b, float2 u) { return make_float2(fmaf(a.x, b.x, fmaf(-a.y, b.y, u.x)), fmaf(a.x, b.y, fmaf(a.y, b.x, u.y))); }
__device__ __forceinline__ float4 ssm_coef(float lre, float lim, float logdt) {
    const float dt = __bfloat162float(__float2bfloat16(expf(logdt)));
    const float ea = expf(dt * lre);
    float sn, cn;
    sincosf(dt * lim, &sn, &cn);
    const float br = ea * cn, bi = ea * sn, nr = br - 1.f;
    const bool sw = fabsf(lre) < fabsf(lim);
    const float big = sw ? lim : lre, r = __fdividef(sw ? lre : lim, big), inv = __fdividef(1.f, fmaf(sw ? lre : lim, r, big));
    const float cr = (sw ? fmaf(nr, r, bi) : fmaf(bi, r, nr)) * inv, ci = (sw ? fmaf(bi, r, -nr) : fmaf(-nr, r, bi)) * inv;
    return make_float4(br, bi, cr, ci);
}
__device__ __forceinline__ void epi_a1(const float* acc, const Params& P, const Cons& c, Pend& d, int mb, int nb) {
    const uint32_t atag = (get_epoch(c.sb) + 1) & 1;
    const int t = c.lane & 3;
    const int p = nb * 128 + c.rank * 64 + c.wg * 32 + c.wq * 8 + (c.lane >> 2);
    const float4 cf = __ldcg(&g_coef[p]);
    const float2 lam = make_float2(cf.x, P.swap_ri ? -cf.y : cf.y);
    const float a0 = P.swap_ri ? -2.f * cf.w : 2.f * cf.z, a1 = P.swap_ri ? 2.f * cf.z : -2.f * cf.w;
    const float b0 = P.swap_ri ? -2.f * cf.z : -2.f * cf.w, b1 = P.swap_ri ? -2.f * cf.w : -2.f * cf.z;
    float2 h = make_float2(0.f, 0.f);
#pragma unroll
    for (int round = 0; round < 2; round++) {
#pragma unroll
        for (int j = 0; j < 32; j++) {
            h = cfma(lam, h, make_float2(acc[j * 4], acc[j * 4 + 2]));
            const float r0 = fmaf(a0, h.x, a1 * h.y), m0 = fmaf(b0, h.x, b1 * h.y);
            h = cfma(lam, h, make_float2(acc[j * 4 + 1], acc[j * 4 + 3]));
            d.pk[j * 2] = pack2(r0, fmaf(a0, h.x, a1 * h.y));
            d.pk[j * 2 + 1] = pack2(m0, fmaf(b0, h.x, b1 * h.y));
        }
        if (round) break;
        float2 l64 = lam;
#pragma unroll
        for (int i = 0; i < 6; i++) l64 = cmul(l64, l64);
        const float2 l128 = cmul(l64, l64), l256 = cmul(l128, l128);
        float2 o = make_float2(__shfl_up_sync(0xffffffffu, h.x, 1), __shfl_up_sync(0xffffffffu, h.y, 1));
        if (t >= 1) h = cfma(l64, o, h);
        o = make_float2(__shfl_up_sync(0xffffffffu, h.x, 2), __shfl_up_sync(0xffffffffu, h.y, 2));
        if (t >= 2) h = cfma(l128, o, h);
        IP(2)
        if (t == 3) st_relaxed2(&g_agg[mb * 1024 + p], (__float_as_uint(h.x) & ~1u) | atag, __float_as_uint(h.y));
        h = make_float2(__shfl_up_sync(0xffffffffu, h.x, 1), __shfl_up_sync(0xffffffffu, h.y, 1));
        if (t == 0) h = make_float2(0.f, 0.f);
        uint32_t ax[7], ay[7];
        while (true) {
            uint32_t bad = 0;
#pragma unroll
            for (int j = 0; j < 7; j++) { ax[j] = atag; ay[j] = 0; ld_relaxed2_if(ax[j], ay[j], &g_agg[j * 1024 + p], j < mb); }
#pragma unroll
            for (int j = 0; j < 7; j++) bad |= ax[j] ^ atag;
            if (tags_ok(bad)) break;
            __nanosleep(2 * POLLNS);
        }
        float2 carry = make_float2(0.f, 0.f);
#pragma unroll
        for (int j = 0; j < 7; j++) if (j < mb) carry = cfma(l256, carry, make_float2(__uint_as_float(ax[j]), __uint_as_float(ay[j])));
        float2 w = (t & 1) ? l64 : make_float2(1.f, 0.f);
        if (t & 2) w = cmul(w, l128);
        h = cfma(w, carry, h);
        IP(3)
    }
    IP(4)
    d.kind = PEND_HT; d.row = nb * 128 + c.rank * 64 + c.wg * 32; d.col = mb * 256; d.cnt = C_HT + mb * 16 + nb;
}

__device__ __forceinline__ uint32_t fresh_tid() { uint32_t t; asm volatile("mov.u32 %0, %%tid.x;" : "=r"(t)); return t; }
__device__ __forceinline__ uint32_t acquire_stage(uint32_t sb, Pipe& p, uint32_t bytes) {
    mbar_wait(sb + B_EMPTY + p.stage * 8, p.phase ^ 1);
    mbar_expect_e(sb + B_FULL + p.stage * 8, bytes);
    return p.stage;
}
__device__ __forceinline__ void producer(const Params& P, const uint32_t sb, const int cta) {
    Pipe p = {0, 0};
    uint32_t resume = 1;
    const int rank = cta & 1;
    const uint16_t both = 3 << (__shfl_sync(0xffffffffu, cluster_rank(), 0) & ~1u);
    for (int it = ITEM_OFF(cta >> 1), item = 0; !(item & LAST); it++) {
        item = ITEM(it);
        const int type = (item >> 8) & 7, mb = (item >> 5) & 7, nb = item & 31, half = item >> 12 & 1, hw = item >> 13 & 1;
        const uint32_t epoch = type ? get_epoch(sb) : 0, e1 = epoch + 1;
        if (type == T_CHAIN) {
            const int h = cta / 3, role = cta - h * 3;
#pragma unroll 1
            for (int w = 0; w < 8; w++) {
                mbar_wait(sb + B_EMPTY + (w * 20480 + 20479) / STAGE * 8, 1);
                chain_load(P, sb, cta, w, threadIdx.x & 31, 0);
            }
            uint32_t* flag = &g_cnt(C_FLAG + (role == 2 ? 32 : 0) + h);
            if (role) { wait_count(&g_cnt(C_KV), e1 * 128); fence_async(); }
#pragma unroll 1
            for (int s = 0; s < 63 && role != 0; s++) {
                {
                    mbar_wait(sb + B_GO, s & 1);
                    tma3d_mc_e(sb + S_KV + (role - 1) * 8192, &P.tm[M_SEG], 0, (role - 1) * 2048 + s * 32, h * 2, sb + B_KVFULL, 7 << ((h & 1) * 3), P.pol[s < 48 ? 8 : 11]);
                    if ((s & 7) == 7) { wait_count(&g_cnt(C_KV + 1 + (s >> 3)), e1 * 128); fence_async(); }
                    tma_prefetch3d_e(&P.tm[M_SEG], 0, (role - 1) * 2048 + s * 32 + 32, h * 2);
                }
                if (s > 0 && (s & 3) == 0) {
                    const int i = (s - 1) >> 2;
                    mbar_wait(sb + B_PERS, i & 1);
                    asm volatile("{\n.reg .pred E;\nelect.sync _|E, 0xffffffff;\n@E st.release.gpu.global.u32 [%0], %1;\n}" ::"l"(flag), "r"(epoch * 64 + i * 4 + 4) : "memory");
                }
            }
            if (role == 0) {
                const int lane = threadIdx.x & 31;
                if (lane == 0) mbar_arrive(sb + B_RELM);
#pragma unroll 1
                for (int s = 0; s < 63; s++) {
                    mbar_wait(sb + B_P1, s & 1);
                    if (s > 0) {
                        st_relaxed4(P.xb + xg_buf(s - 1) + h * 2048 + xg_lane(lane), 0, 0, 0, 0);
                        st_relaxed1(P.xb + xg_buf(s - 1) + xg_side(h) + lane * 4, 0);
                        __threadfence();
                    }
                    __syncwarp();
                    if (lane == 0) mbar_arrive(sb + B_RELM);
                }
            }
            if ((threadIdx.x & 31) < M_C1 - 1) asm volatile("prefetch.tensormap [%0];" ::"l"(&P.tm[1 + (threadIdx.x & 31)]) : "memory");
            resume = 0;
            continue;
        }
        const int m0 = mb * 256 + rank * 128, ssm = type >= T_A1;
        const CUtensorMap* ma = &P.tm[max(type, 1) + half * M_HALF];
        const CUtensorMap* mw = &P.tm[type ? M_WV + type : M_WK + (nb >> 4)];
        const int nk = type == T_OP ? 64 : type == T_A2 ? 32 : 16;
        const int a3 = type == T_A1 ? nb * 16 + rank * 8 + hw * 4 : type == T_A2 ? mb * 4 + rank * 2 + hw : (type == T_OP ? 4096 : 0) + m0 + hw * 64;
        const int b3 = type == T_A1 ? mb * 128 + rank * 16 : type == T_A2 ? (nb * 2 + rank) * 128 : (nb & 15) * 4 + rank * 2;
        if (type & 1) {
            wait_count(&g_cnt(type == T_A1 ? C_COEF : C_KV + mb), e1 * (type == T_A1 ? 4 : 128));
            fence_async();
        }
        uint32_t ready = type == T_OP || type == T_A2 ? 0 : ~0u;
        if (type == T_A1) l2_prefetch_e(g_coef + nb * 128 + rank * 64, 1024);
        auto arrived = [&]() {
            const uint32_t t = fresh_tid();
            return __all_sync(0xffffffffu, (int32_t)(ld_acquire(&g_cnt(C_FLAG + (t & 2) * 16 + nb * 2 + (t & 1))) - (epoch * 64 + mb * 8 + rank * 4 + 4)) >= 0);
        };
        bool passed = false;
        mbar_wait(sb + B_RESUME, resume);
#pragma unroll 1
        for (int kt = 0; kt < nk; kt++) {
            if (type == T_QA && kt == 9) passed = arrived();
            while (~ready & (ssm ? 2 | 1 << ((kt & 15) >> 1) : 1 << (kt >> 2))) {
                if (ready) __nanosleep(POLLNS);
                ready = __ballot_sync(0xffffffffu, (int32_t)(ld_acquire(&g_cnt(type * 64 + mb * 16 + (fresh_tid() & 15))) - e1 * 4) >= 0) | 1u << 31;
                fence_async();
            }
            const uint32_t st = acquire_stage(sb, p, STAGE - half * 8192), bar = sb + B_FULL + st * 8;
            const int a1 = type == T_A2 ? kt * 64 : 0, b0 = ssm ? (kt & 15) * 64 : 0;
            tma4d_e(sb + st * STAGE + hw * 8192, ma, kt * 64 - a1, a1, a3, bar, P.pol[11]);
            tma4d_mc_e(sb + st * STAGE + 16384 + rank * 16384, mw + (ssm & kt >> 4), b0, ssm ? 0 : kt * 64, b3, bar, both, P.pol[(item & 0x7e0) == 224 ? 9 : 11]);
            if (type == T_QA && kt < 8) tma_prefetch4d_e(&P.tm[M_OA], nb * 256 + (kt & 3) * 64, (kt >> 2) * 2048 + m0);
            pipe_next(p);
        }
        if (type == T_QA) {
            while (!passed) { passed = arrived(); if (!passed) __nanosleep(POLLNS); }
            fence_async();
        }
        const int q = type == T_QA;
#pragma unroll 1
        for (int e = 0; e < (q ? 4 : type == T_A2 ? 2 : 0); e++) {
            const uint32_t st = acquire_stage(sb, p, q ? 40960 : 32768 + 256), bar = sb + B_FULL + st * 8, dst = sb + st * STAGE;
#pragma unroll 1
            for (int i = 0; i < 2; i++) tma4d_e(dst + i * 16384, &P.tm[q ? M_OA : M_AX], nb * 256 + (e & 1) * 128 + i * 64, 0, q ? (e >> 1) * 2048 + m0 : mb * 128 + rank * 16, bar, P.pol[q ? 3 : 11]);
            const uint8_t* src = q ? (const uint8_t*)(((e >> 1) ? g_vmt : g_km) + ((mb * 8 + rank * 4) * 32 + nb * 2 + (e & 1)) * 512) : (const uint8_t*)(P.Dskip + nb * 256 + e * 128);
#pragma unroll 1
            for (int i = 0; i < (q ? 4 : 1); i++) bulk_g2s_e(dst + 32768 + i * 2048, src + i * 65536, q ? 2048 : 256, bar);
            pipe_next(p);
        }
    }
#pragma unroll 1
    for (int i = 0; i < NSTAGE; i++) { mbar_wait(sb + B_EMPTY + p.stage * 8, p.phase ^ 1); pipe_next(p); }
}

__device__ __forceinline__ uint32_t fresh_ctaid() { uint32_t t; asm volatile("mov.u32 %0, %%ctaid.x;" : "=r"(t)); return t; }
__device__ __forceinline__ void reset_state(const Params& P, Cons& c, Pend& d, uint32_t sb, bool resumed) {
    const uint32_t t = fresh_tid(), b = fresh_ctaid() + P.cta0;
    const int w = __shfl_sync(0xffffffffu, t >> 5, 0);
    c.sb = sb; c.wg = w >> 2; c.wq = w & 3; c.lane = t & 31;
    c.rank = __shfl_sync(0xffffffffu, b & 1, 0); c.pair = __shfl_sync(0xffffffffu, b >> 1, 0);
    c.rel = mapa(sb + B_EMPTY, cluster_rank() ^ (c.lane & 1));
    c.p.stage = 0; c.p.phase = 0;
    c.nst = resumed && c.pair < NCHAIN;
    d = Pend{};
}
#define PROF_ITEM(i, item)

__global__ void __launch_bounds__(384, 1) fused_kernel(const __grid_constant__ Params P) {
    extern __shared__ __align__(1024) uint8_t smem[];
    const uint32_t sb = smem_u32(smem);
    asm volatile("griddepcontrol.launch_dependents;");
    declare_fence(P.zero);
    const int tid = threadIdx.x, lane = tid & 31;
    const int warp = __shfl_sync(0xffffffffu, tid >> 5, 0);
    const int cta = __shfl_sync(0xffffffffu, blockIdx.x + P.cta0, 0), pair = cta >> 1, rank = cta & 1;
    if (tid == 0) {
        if (sb & 1023) spin_fault();
        for (int i = 0; i < NSTAGE; i++) { mbar_init(sb + B_FULL + i * 8, 1); mbar_init(sb + B_EMPTY + i * 8, 16); }
        mbar_init(sb + B_RESUME, 2);
        mbar_init(sb + B_KVFULL, 1);
        mbar_init(sb + B_GO, 3); mbar_init(sb + B_RED, 8); mbar_init(sb + B_P1, 1); mbar_init(sb + B_EPOCH, 1); mbar_init(sb + B_PERS, 8); mbar_init(sb + B_INIT, 8); mbar_init(sb + B_INIT2, 8);
        mbar_init(sb + B_READY, 8);
        for (int i = 0; i < 2; i++) { mbar_init(sb + B_SFULL + i * 8, 4); mbar_init(sb + B_SFREE + i * 8, 1); }
        mbar_init(sb + B_RELM, cta % 3 ? 1 : 2); mbar_init(sb + B_X, 9);
        mbar_init(sb + B_DONE, 2);
        mbar_expect(sb + B_X, 4096);
        sts64(sb + S_EV, 0, 0);
        asm volatile("fence.mbarrier_init.release.cluster;" ::: "memory");
    }
    __syncthreads();
    cluster_sync();
    if (warp >= 8) {
        asm volatile("setmaxnreg.dec.sync.aligned.u32 24;");
        if (warp == 8) {
            producer(P, sb, cta);
        } else if (warp == 9) {
            const uint32_t epoch = __shfl_sync(0xffffffffu, ld_acquire(&g_cnt(C_EPOCH)), 0);
            if (lane == 0) { sts32(sb + S_EPOCH, epoch); mbar_arrive(sb + B_EPOCH); red_release(&g_cnt(C_READ)); }
            __syncwarp();
            if (pair < NCHAIN) pacer(P, sb, cta, lane, epoch);
            if (pair < NCHAIN && cta % 3) {
                mbar_wait_bounded(sb + B_PERS, 1);
                if (lane == 0) asm volatile("st.release.gpu.global.u32 [%0], %1;" ::"l"(&g_cnt(C_FLAG + (cta % 3 == 2 ? 32 : 0) + cta / 3)), "r"(epoch * 64 + 64) : "memory");
            }
            if (cta == 0 && lane == 0) {
                for (int n = 0; (int32_t)(ld_acquire(&g_cnt(C_READ)) - (epoch + 1) * (NPAIR * 2)) < 0; n++) if (n > SPIN_LIMIT) spin_fault();
                st_relaxed1(&g_cnt(C_EPOCH), epoch + 1);
            }
            __syncwarp();
            mbar_wait_bounded(sb + B_DONE, 0);
        } else {
            store_warp(P, sb, warp - 10, cta);
        }
    } else {
        asm volatile("setmaxnreg.inc.sync.aligned.u32 240;");
        Cons c;
        Pend d;
        if (pair < NCHAIN) {
            reset_state(P, c, d, sb, false);
            {
                const int item = ITEM(ITEM_OFF(pair));
                PROF_ITEM(0, item)
                float acc[128];
                mainloop<true>(acc, P, c, d, T_KV, 16);
                ISTAMP(4)
                epi_kv(acc, c, d, (item >> 5) & 7, item & 31);
            }
            ISTAMP(9)
            mbar_wait(sb + B_EMPTY + 3 * 8, 1);
            drain_both(c, d);
            ISTAMP(10)
            uint32_t wr[40][4];
            chain_fetch(P, sb, cta, warp, lane, wr);
            PROF_ITEM(1, T_CHAIN << 8)
            chain_bounds(sb, cta, warp, lane, wr);
            ISTAMP(11)
            if (warp < 4) chain_role<false>(P, sb, cta, warp, lane, wr);
            else chain_role<true>(P, sb, cta, warp, lane, wr);
            ISTAMP(14)
            bar_sync(1, 256);
            ISTAMP(15)
            const uint32_t t2 = fresh_tid();
            if (t2 < 2) mbar_arrive_cluster(mapa(sb + B_RESUME, cluster_rank() ^ t2));
        } else if (pair >= NPAIR - 2) {
            const int ch = (pair - (NPAIR - 2)) * 512 + rank * 256 + tid;
            g_coef[ch] = ssm_coef(__bfloat162float(P.Lre[ch]), __bfloat162float(P.Lim[ch]), __bfloat162float(P.logdt[ch]));
            bar_sync(1, 256);
            if (tid == 0) red_release(&g_cnt(C_COEF));
        }
        reset_state(P, c, d, sb, true);
        int it = ITEM_OFF(c.pair) + (c.pair < NCHAIN ? 2 : 0);
        for (int prev = c.pair < NCHAIN ? ITEM(it - 1) : 0;; prev = ITEM(it++)) {
            const bool last = prev & LAST;
            const int item = ITEM(it), type = (item >> 8) & 7, mb = (item >> 5) & 7, nb = item & 31;
            const bool idle = (item >> 12 & 3) == 3 - 2 * c.wg;
            if (d.kind != PEND_NONE && ((prev & (LAST | URGENT)) || idle || (type != T_KV && !bar_and(5 + c.wg, mbar_try(sb + B_FULL + c.p.stage * 8, c.p.phase))))) {
#pragma unroll 1
                while (d.kind != PEND_NONE) drain(P, c, d);
            }
            if (last) break;
            const int nk = type == T_OP ? 64 : type == T_A2 ? 32 : 16;
            PROF_ITEM(it - ITEM_OFF(c.pair), item)
            if (idle) {
#pragma unroll 1
                for (int kt = nk + (type == T_A2 ? 2 : type == T_QA ? 4 : 0); kt > 0; kt--) { wait_full(c); release(c, c.p.stage); pipe_next(c.p); }
                continue;
            }
            float acc[128];
            mainloop(acc, P, c, d, type, nk);
            if (type == T_KV) epi_kv(acc, c, d, mb, nb);
            else if (type == T_QA) epi_qa(acc, c, d, mb, nb);
            else if (type == T_OP) epi_op(acc, c, d, mb, nb);
            else if (type == T_A1) epi_a1(acc, P, c, d, mb, nb);
            else epi_a2(acc, P, c, d, mb, nb);
        }
        staging_wait(c);
        staging_post(c, PEND_NONE, 0, 0, 0);
        if (c.wq == 0 && c.lane == 0) mbar_arrive(sb + B_DONE);
    }
}

typedef CUresult (*EncodeFn)(CUtensorMap*, CUtensorMapDataType, cuuint32_t, void*, const cuuint64_t*, const cuuint64_t*, const cuuint32_t*, const cuuint32_t*,
                             CUtensorMapInterleave, CUtensorMapSwizzle, CUtensorMapL2promotion, CUtensorMapFloatOOBfill);
void encode(EncodeFn fn, CUtensorMap* m, const void* base, int rank, const uint64_t* dims, const uint64_t* strides, const uint32_t* box, CUtensorMapSwizzle swz = CU_TENSOR_MAP_SWIZZLE_128B) {
    cuuint64_t d[5], s[5]; cuuint32_t b[5], e[5];
    for (int i = 0; i < rank; i++) { d[i] = dims[i]; b[i] = box[i]; e[i] = 1; if (i) s[i - 1] = strides[i - 1]; }
    fn(m, CU_TENSOR_MAP_DATA_TYPE_BFLOAT16, rank, (void*)base, d, s, b, e, CU_TENSOR_MAP_INTERLEAVE_NONE, swz,
       CU_TENSOR_MAP_L2_PROMOTION_L2_256B, CU_TENSOR_MAP_FLOAT_OOB_FILL_NONE);
}
void map_kmajor(EncodeFn fn, CUtensorMap* m, const void* base, uint64_t rows, uint64_t cols, uint32_t box_rows) {
    const uint64_t d[4] = {cols, 1, 1, rows}, s[3] = {cols * 2, cols * 2, cols * 2}; const uint32_t b[4] = {64, 1, 1, box_rows};
    encode(fn, m, base, 4, d, s, b);
}
void map_mnmajor(EncodeFn fn, CUtensorMap* m, const void* base, uint64_t krows, uint64_t cols, uint32_t groups = 2) {
    const uint64_t d[4] = {64, krows, 1, cols / 64}, s[3] = {cols * 2, 128, 128}; const uint32_t b[4] = {64, 64, 1, groups};
    encode(fn, m, base, 4, d, s, b);
}
void map_store(EncodeFn fn, CUtensorMap* m, const void* base, uint64_t rows, uint64_t cols) {
    const uint64_t d[2] = {cols, rows}, s[1] = {cols * 2}; const uint32_t b[2] = {64, 32};
    encode(fn, m, base, 2, d, s, b);
}

}

extern "C" void kernel_launch(void* const* d_in, const int* in_sizes, int n_in, void* d_out, int out_size) {
    static Params P;
    static EncodeFn fn = nullptr;
    if (!fn) {
        cudaDriverEntryPointQueryResult q;
        cudaGetDriverEntryPoint("cuTensorMapEncodeTiled", (void**)&fn, cudaEnableDefault, &q);
        cudaFuncSetAttribute(fused_kernel, cudaFuncAttributeMaxDynamicSharedMemorySize, S_TOTAL);
    }
    const bf16* in[15];
    for (int i = 0; i < 15; i++) in[i] = (const bf16*)d_in[i];
    void *kvo, *ht;
    cudaGetSymbolAddress(&kvo, g_kvo);
    cudaGetSymbolAddress(&ht, g_ht);
    map_kmajor(fn, &P.tm[M_BX], in[9], 2048, 1024, 128);
    map_mnmajor(fn, &P.tm[M_WQ], in[11], 1024, 4096);
    map_mnmajor(fn, &P.tm[M_WK], in[12], 1024, 4096);
    map_mnmajor(fn, &P.tm[M_WV], in[13], 1024, 4096);
    map_mnmajor(fn, &P.tm[M_WO], in[14], 4096, 1024);
    map_kmajor(fn, &P.tm[M_OA], kvo, 3 * 2048, 4096, 128);
    P.swap_ri = in[4] < in[3];
    {
        const bf16* lo = P.swap_ri ? in[4] : in[3];
        const uint64_t diff = (uint64_t)((const char*)(P.swap_ri ? in[3] : in[4]) - (const char*)lo);
        const uint64_t d[4] = {1024, 8, 2, 128}, s[3] = {2048, diff, 16384}; const uint32_t b[4] = {64, 8, 2, 8}, bh[4] = {64, 8, 2, 4};
        encode(fn, &P.tm[M_AB], lo, 4, d, s, b);
        encode(fn, &P.tm[M_AB + M_HALF], lo, 4, d, s, bh);
    }
    {
        const uint64_t d[4] = {1024, 2, 4, 1024}, s[3] = {2048, 64 * 2048, 4096}; const uint32_t b[4] = {64, 2, 4, 16};
        encode(fn, &P.tm[M_AX], in[0], 4, d, s, b);
    }
    map_mnmajor(fn, &P.tm[M_HT], ht, 2048, 2048);
    map_kmajor(fn, &P.tm[M_CRE], in[5], 1024, 1024, 128);
    map_kmajor(fn, &P.tm[M_CIM], in[6], 1024, 1024, 128);
    map_store(fn, &P.tm[M_KVO], kvo, 3 * 2048, 4096);
    map_store(fn, &P.tm[M_HTS], ht, 2048, 2048);
    map_kmajor(fn, &P.tm[M_BX + M_HALF], in[9], 2048, 1024, 64);
    map_kmajor(fn, &P.tm[M_OA + M_HALF], kvo, 3 * 2048, 4096, 64);
    map_mnmajor(fn, &P.tm[M_HT + M_HALF], ht, 2048, 2048, 1);
    for (int i = 0; i < 3; i++) {
        const uint64_t d[3] = {64, 1024, 64}, s[2] = {8192, 128}; const uint32_t b[3] = {64, 16, 2};
        encode(fn, &P.tm[M_C1 + i], in[11 + i], 3, d, s, b);
    }
    {
        const uint64_t d[2] = {1024, 4096}, s[1] = {2048}; const uint32_t b[2] = {32, 32};
        encode(fn, &P.tm[M_CO], in[14], 2, d, s, b, CU_TENSOR_MAP_SWIZZLE_64B);
    }
    {
        const uint64_t d[3] = {64, 3 * 2048, 64}, s[2] = {8192, 128}; const uint32_t b[3] = {64, 32, 2};
        encode(fn, &P.tm[M_SEG], kvo, 3, d, s, b);
    }
    void* xs;
    cudaGetSymbolAddress(&xs, g_x);
    P.xb = (uint8_t*)(((uintptr_t)xs + (2u << 20) - 1) & ~(uintptr_t)((2u << 20) - 1));
    P.Wq = in[11]; P.Wk = in[12]; P.Wv = in[13]; P.Wo = in[14]; P.mem0 = in[10]; P.Bx = in[9];
    P.Ax = in[0]; P.Lre = in[1]; P.Lim = in[2]; P.logdt = in[7]; P.Dskip = in[8];
    P.out = (float*)d_out;
    int pv[10] = {1140, 0, 110, 0, 330, 64, 32, 32, 0, 0};
    int ef = 779;
    for (int i = 0; i < 12; i++) P.pol[i] = (ef >> i & 1) ? 0x12F0000000000000ull : 0x1000000000000000ull;
    P.dly = pv[0]; P.mrg = pv[2];
    P.rd = pv[4]; P.guard = pv[5]; P.clampv = pv[6]; P.clamp0 = pv[7]; P.kvd = pv[9]; P.xd = pv[8];
    cudaLaunchConfig_t cfg = {};
    cudaLaunchAttribute at[2];
    cfg.blockDim = dim3(384); cfg.dynamicSmemBytes = S_TOTAL; cfg.stream = cudaStreamPerThread; cfg.attrs = at;
    at[0].id = cudaLaunchAttributeClusterDimension;
    at[0].val.clusterDim.y = at[0].val.clusterDim.z = 1;
    at[1].id = cudaLaunchAttributeProgrammaticStreamSerialization;
    at[1].val.programmaticStreamSerializationAllowed = 1;
    for (int i = 0; i < 2; i++) {
        P.cta0 = i ? 2 * NCHAIN : 0;
        cfg.gridDim = dim3(i ? 2 * (NPAIR - NCHAIN) : 2 * NCHAIN);
        at[0].val.clusterDim.x = i ? 2 : 6;
        cfg.numAttrs = 1 + i;
        cudaLaunchKernelEx(&cfg, fused_kernel, P);
    }
}
```

```cpp
#include <cuda_runtime.h>
#include <cuda_bf16.h>
#include <cuda.h>
#include <stdint.h>
#include <string.h>

typedef __nv_bfloat16 bf16;

namespace {

constexpr int SPIN_LIMIT = 1 << 22;
#define POLLNS 100
constexpr int NPAIR = 66;
constexpr int NCHAIN = 48;
enum { T_KV = 0, T_QA = 1, T_OP = 2, T_A1 = 3, T_A2 = 4, T_CHAIN = 5 };
constexpr int URGENT = 2048;
constexpr int LAST = 16384;
constexpr int HALF = 4096;
enum { M_BX = 1, M_OA, M_AB, M_HT, M_HALF = 4, M_WK = 9, M_WV, M_WQ, M_WO, M_AX, M_CRE, M_CIM, M_KVO, M_HTS, M_C1, M_CO = M_C1 + 3, M_SEG, M_COUNT };
enum { C_KV = 0, C_O = 128, C_HT = 256, C_READ = 24, C_EPOCH = 25, C_COEF = 26, C_XMAX = 27, C_XCNT = 28, C_FLAG = 32 };

struct Params {
    CUtensorMap tm[M_COUNT];
    const bf16 *mem0, *Bx, *Ax, *Lre, *Lim, *logdt, *Dskip;
    float* out;
    uint8_t* xb;
    int swap_ri, zero;
    int dly, mrg, rd, guard, clampv, clamp0, kvd, xd;
    uint64_t pol[12];
    uint16_t cta0;
};

__constant__ uint16_t c_off[67] = {0, 4, 8, 14, 20, 26, 32, 38, 44, 49, 54, 59, 64, 69, 74, 79, 84, 89, 94, 98, 102, 106, 110, 114, 118, 122, 126, 130, 134, 138, 142, 146, 150, 154, 158, 162, 166, 170, 174, 178, 182, 186, 190, 194, 198, 202, 206, 210, 214, 234, 253, 272, 292, 312, 332, 352, 371, 391, 410, 430, 449, 468, 487, 506, 525, 545, 564};
__constant__ uint16_t c_items[700] = {
    0, 1280, 512, 21728, 16, 1280, 513, 29920, 32, 1280, 800, 898, 3042, 21729, 1, 1280, 801, 899, 3043, 29921, 17, 1280, 802, 900,
    3044, 21730, 33, 1280, 803, 901, 3045, 29922, 2, 1280, 804, 902, 3046, 21731, 18, 1280, 805, 903, 3047, 29923, 34, 1280, 2496, 2912,
    17408, 3, 1280, 2528, 2913, 17409, 19, 1280, 768, 2914, 17410, 35, 1280, 769, 2915, 17411, 4, 1280, 770, 2916, 17440, 20, 1280, 771,
    2917, 17441, 36, 1280, 772, 2918, 17442, 5, 1280, 773, 2919, 17443, 21, 1280, 774, 2944, 17472, 37, 1280, 775, 2945, 17473, 6, 1280,
    2497, 16898, 22, 1280, 2529, 16899, 38, 1280, 2498, 16928, 7, 1280, 2530, 16929, 23, 1280, 2499, 16930, 39, 1280, 2531, 16931, 8, 1280,
    2500, 16960, 24, 1280, 2532, 16961, 40, 1280, 2501, 16962, 9, 1280, 2533, 16963, 25, 1280, 2502, 16992, 41, 1280, 2534, 16993, 10, 1280,
    2503, 16994, 26, 1280, 2535, 16995, 42, 1280, 2504, 17024, 11, 1280, 2536, 17025, 27, 1280, 2505, 17026, 43, 1280, 2537, 17027, 12, 1280,
    2506, 17056, 28, 1280, 2538, 17057, 44, 1280, 2507, 17058, 13, 1280, 2539, 17059, 29, 1280, 2508, 17088, 45, 1280, 2540, 17089, 14, 1280,
    2509, 17090, 30, 1280, 2541, 17091, 46, 1280, 2510, 17120, 15, 1280, 2542, 17121, 31, 1280, 2511, 17122, 47, 1280, 2543, 17123, 48, 66,
    84, 102, 117, 131, 147, 161, 178, 194, 207, 222, 235, 248, 332, 366, 416, 835, 3010, 17568, 49, 67, 85, 256, 128, 141,
    155, 170, 187, 203, 215, 296, 301, 323, 357, 391, 425, 2979, 17505, 50, 68, 86, 103, 259, 142, 156, 171, 188, 288, 216,
    231, 302, 324, 358, 392, 806, 2976, 17474, 51, 69, 87, 104, 118, 132, 148, 162, 179, 195, 208, 223, 236, 249, 333, 367,
    417, 836, 3011, 17569, 52, 70, 88, 105, 119, 133, 149, 163, 180, 196, 209, 224, 237, 250, 334, 384, 418, 837, 3012, 17570,
    53, 71, 89, 106, 120, 134, 150, 164, 181, 197, 210, 225, 238, 251, 335, 385, 419, 838, 3013, 17571, 54, 72, 90, 107,
    121, 135, 151, 165, 182, 198, 211, 226, 239, 252, 352, 386, 420, 839, 3014, 17600, 55, 73, 91, 108, 260, 264, 160, 176,
    192, 291, 220, 299, 245, 328, 362, 396, 428, 3009, 17539, 56, 74, 92, 109, 122, 136, 152, 166, 183, 199, 212, 227, 240,
    253, 353, 387, 421, 429, 3015, 17601, 57, 75, 93, 110, 123, 263, 267, 175, 271, 206, 218, 233, 243, 322, 356, 390, 424,
    2978, 17504, 58, 76, 94, 111, 124, 137, 153, 167, 184, 200, 213, 228, 241, 254, 354, 388, 422, 430, 3040, 17602, 59, 77,
    95, 112, 125, 138, 265, 269, 191, 290, 219, 298, 246, 329, 363, 397, 832, 2982, 17536, 60, 78, 96, 113, 261, 143, 157,
    172, 270, 292, 221, 300, 247, 330, 364, 398, 833, 2983, 17537, 61, 79, 97, 257, 129, 144, 158, 173, 189, 204, 294, 297,
    244, 325, 359, 393, 426, 2980, 17506, 62, 80, 98, 258, 130, 145, 268, 177, 193, 205, 217, 232, 303, 326, 360, 394, 807,
    2977, 17475, 63, 81, 99, 114, 262, 146, 159, 174, 190, 289, 295, 234, 321, 331, 365, 399, 834, 3008, 17538, 64, 82, 100,
    115, 126, 139, 154, 168, 185, 201, 214, 229, 242, 255, 355, 389, 423, 431, 3041, 17603, 65, 83, 101, 116, 127, 140, 266,
    169, 186, 202, 293, 230, 320, 327, 361, 395, 427, 2981, 17507,
};
#define ITEM_OFF(p) c_off[p]
#define ITEM(i) c_items[i]

__device__ __align__(1024) bf16 g_kvo[3 * 2048 * 4096];
__device__ __align__(1024) bf16 g_ht[2048 * 2048];
__device__ __align__(1024) uint8_t g_x[4 << 20];
__device__ __align__(1024) uint32_t g_km[64 * 32 * 512];
__device__ __align__(1024) uint32_t g_vmt[64 * 32 * 512];
__device__ __align__(1024) float2 g_agg[8 * 1024];
__device__ __align__(1024) float4 g_coef[1024];
__device__ __align__(1024) uint32_t g_cntl[384 * 32];
#define g_cnt(i) g_cntl[(i) * 32]
__device__ __align__(1024) uint32_t g_hint[96 * 32];
constexpr int XG_SIDE = 65536, XG_T = 98304;
__device__ __forceinline__ uint32_t xg_buf(int b) { return (b & 1) * 128 + (b & 2) * 256 + (b & 4) * 32768; }
__device__ __forceinline__ uint32_t xg_lane(uint32_t lane) { return (lane >> 4) * 1024 + (lane & 8) * 32 + (lane & 7) * 16; }
__device__ __forceinline__ uint32_t xg_side(int b) { return XG_SIDE + (b >> 1) * 1024 + (b & 1) * 256; }

constexpr int STAGE = 49152, NSTAGE = 4;
constexpr int S_STG = NSTAGE * STAGE;
constexpr int S_BAR = S_STG + 32768;
constexpr int B_FULL = S_BAR, B_EMPTY = S_BAR + 32, B_RESUME = S_BAR + 64, B_KVFULL = S_BAR + 72, B_GO = S_BAR + 88, B_X = S_BAR + 96, B_PERS = S_BAR + 104,
              B_INIT = S_BAR + 112, B_RELM = S_BAR + 120, B_READY = S_BAR + 136, B_SFULL = S_BAR + 144, B_SFREE = S_BAR + 160, S_DESC = S_BAR + 176, B_RED = S_BAR + 216;
constexpr int S_EV = S_BAR + 80, S_EO = S_BAR + 84, B_INIT2 = S_BAR + 128, S_SC = S_BAR + 208, S_ISC = S_EV;
constexpr int S_XV = S_BAR + 256, S_LOG = S_XV + 2048;
constexpr int S_TOTAL = S_LOG + 768;
#define NRA 5
#define NRB 3
constexpr int S_W1 = 0;
constexpr int S_W2 = 4 * 4096 * (16 - NRA - NRB);
constexpr int S_KV = 188416;
constexpr int S_P1 = S_KV + 16384;
constexpr int S_X = S_P1 + 16384;
constexpr int S_SX = S_P1, S_OX = S_P1 + 2048;
constexpr int S_EM = S_X + 4096, S_TO = S_EM + 32, B_DONE = S_BAR + 224, B_P1 = S_BAR + 232, B_EPOCH = S_BAR + 240, S_EPOCH = S_BAR + 248;
static_assert(S_TO + 32 <= S_BAR && S_KV % 1024 == 0 && S_TOTAL <= 232448, "chain smem layout");

template <int V> struct IC { static constexpr int value = V; };
template <int B, int E, typename F> __device__ __forceinline__ void static_for(F&& f) { if constexpr (B < E) { f(IC<B>{}); static_for<B + 1, E>(f); } }
__device__ __forceinline__ uint32_t cluster_rank() { uint32_t r; asm volatile("mov.u32 %0, %%cluster_ctarank;" : "=r"(r)); return r; }
__device__ __forceinline__ void spin_fault() { asm volatile("st.global.u32 [%0], 0;" ::"l"(0ull) : "memory"); }
__device__ __forceinline__ uint32_t smem_u32(const void* p) { return (uint32_t)__cvta_generic_to_shared(p); }
__device__ __forceinline__ uint32_t opq(uint32_t x, int lane) { return __shfl_sync(0xffffffffu, x, lane); }
__device__ __forceinline__ uint32_t mapa(uint32_t a, uint32_t r) { uint32_t d; asm volatile("mapa.shared::cluster.u32 %0, %1, %2;" : "=r"(d) : "r"(a), "r"(r)); return d; }
__device__ __forceinline__ void mma16816(float* d, uint32_t a0, uint32_t a1, uint32_t a2, uint32_t a3, uint32_t b0, uint32_t b1) {
    asm("mma.sync.aligned.m16n8k16.row.col.f32.bf16.bf16.f32 {%0,%1,%2,%3}, {%4,%5,%6,%7}, {%8,%9}, {%0,%1,%2,%3};"
        : "+f"(d[0]), "+f"(d[1]), "+f"(d[2]), "+f"(d[3]) : "r"(a0), "r"(a1), "r"(a2), "r"(a3), "r"(b0), "r"(b1));
}
__device__ __forceinline__ void mma1688(float* d, uint32_t a0, uint32_t a1, uint32_t b0) {
    asm("mma.sync.aligned.m16n8k8.row.col.f32.bf16.bf16.f32 {%0,%1,%2,%3}, {%4,%5}, {%6}, {%0,%1,%2,%3};"
        : "+f"(d[0]), "+f"(d[1]), "+f"(d[2]), "+f"(d[3]) : "r"(a0), "r"(a1), "r"(b0));
}
__device__ __forceinline__ void ldsm4(uint32_t* r, uint32_t a) {
    asm volatile("ldmatrix.sync.aligned.m8n8.x4.shared.b16 {%0,%1,%2,%3}, [%4];" : "=r"(r[0]), "=r"(r[1]), "=r"(r[2]), "=r"(r[3]) : "r"(a));
}
__device__ __forceinline__ void ldsm4t(uint32_t* r, uint32_t a) {
    asm volatile("ldmatrix.sync.aligned.m8n8.x4.trans.shared.b16 {%0,%1,%2,%3}, [%4];" : "=r"(r[0]), "=r"(r[1]), "=r"(r[2]), "=r"(r[3]) : "r"(a));
}
__device__ __forceinline__ void stsm4(uint32_t a, uint32_t r0, uint32_t r1, uint32_t r2, uint32_t r3) {
    asm volatile("stmatrix.sync.aligned.m8n8.x4.shared.b16 [%0], {%1,%2,%3,%4};" ::"r"(a), "r"(r0), "r"(r1), "r"(r2), "r"(r3) : "memory");
}
__device__ __forceinline__ void stsm4t(uint32_t a, uint32_t r0, uint32_t r1, uint32_t r2, uint32_t r3) {
    asm volatile("stmatrix.sync.aligned.m8n8.x4.trans.shared.b16 [%0], {%1,%2,%3,%4};" ::"r"(a), "r"(r0), "r"(r1), "r"(r2), "r"(r3) : "memory");
}
__device__ __forceinline__ uint32_t movm(uint32_t a) { uint32_t d; asm volatile("movmatrix.sync.aligned.m8n8.trans.b16 %0, %1;" : "=r"(d) : "r"(a)); return d; }
__device__ __forceinline__ uint32_t pack2(float lo, float hi) { uint32_t d; asm("cvt.rn.bf16x2.f32 %0, %1, %2;" : "=r"(d) : "f"(hi), "f"(lo)); return d; }
__device__ __forceinline__ uint32_t prmt(uint32_t a, uint32_t b, uint32_t s) { uint32_t d; asm("prmt.b32 %0, %1, %2, %3;" : "=r"(d) : "r"(a), "r"(b), "r"(s)); return d; }
__device__ __forceinline__ uint32_t pack2h(float lo, float hi) { uint32_t d; asm("cvt.rn.f16x2.f32 %0, %1, %2;" : "=r"(d) : "f"(hi), "f"(lo)); return d; }
__device__ __forceinline__ uint32_t h2bf(uint32_t a, uint32_t b) {
    uint32_t d;
    asm("{\n.reg .b16 l, h, u;\n.reg .f32 x, y;\nmov.b32 {l, u}, %1;\ncvt.f32.f16 x, l;\nmov.b32 {u, h}, %2;\ncvt.f32.f16 y, h;\ncvt.rn.bf16x2.f32 %0, y, x;\n}" : "=r"(d) : "r"(a), "r"(b));
    return d;
}
__device__ __forceinline__ void cvt_block(uint32_t* u, uint32_t& x, uint32_t sel) {
    const uint32_t a = prmt(u[0], u[0], sel), b = prmt(u[1], u[1], sel), c = prmt(u[2], u[2], sel), d = prmt(u[3], x, sel);
    x ^= u[3] ^ d;
    u[0] = h2bf(a, a); u[1] = h2bf(b, b); u[2] = h2bf(c, c); u[3] = h2bf(d, d);
}
__device__ __forceinline__ uint32_t amax(uint32_t a, uint32_t b) { uint32_t d; asm("max.xorsign.abs.bf16x2 %0, %1, %2;" : "=r"(d) : "r"(a), "r"(b)); return d; }
__device__ __forceinline__ uint32_t amax4(uint32_t m, const uint32_t* v) { return amax(amax(m, amax(v[0], v[1])), amax(v[2], v[3])); }
__device__ __forceinline__ uint32_t warp_exp(uint32_t m) { return __reduce_max_sync(0xffffffffu, max(m & 0x7f80u, (m >> 16) & 0x7f80u)) >> 7; }
__device__ __forceinline__ void red_max_shared(uint32_t a, uint32_t x) { asm volatile("red.shared.max.u32 [%0], %1;" ::"r"(a), "r"(x) : "memory"); }
__device__ __forceinline__ uint32_t mul_bf2(uint32_t a, uint32_t b) { uint32_t d; asm("mul.rn.bf16x2 %0, %1, %2;" : "=r"(d) : "r"(a), "r"(b)); return d; }
__device__ __forceinline__ float bf_lo(uint32_t u) { return __uint_as_float(u << 16); }
__device__ __forceinline__ float bf_hi(uint32_t u) { return __uint_as_float(u & 0xffff0000u); }
__device__ __forceinline__ float ex2(float x) { float y; asm("ex2.approx.ftz.f32 %0, %1;" : "=f"(y) : "f"(x)); return y; }
__device__ __forceinline__ float rcp(float x) { float y; asm("rcp.approx.ftz.f32 %0, %1;" : "=f"(y) : "f"(x)); return y; }
__device__ __forceinline__ void st_relaxed4(const void* p, uint32_t a, uint32_t b, uint32_t c, uint32_t d) {
    asm volatile("{\n.reg .b128 t;\nmov.b128 t, {%1,%2,%3,%4};\nst.relaxed.gpu.global.b128 [%0], t;\n}" ::"l"(p), "r"(a), "r"(b), "r"(c), "r"(d) : "memory");
}
__device__ __forceinline__ void st_relaxed2(const void* p, uint32_t a, uint32_t b) {
    asm volatile("{\n.reg .b64 t;\nmov.b64 t, {%1,%2};\nst.relaxed.gpu.global.b64 [%0], t;\n}" ::"l"(p), "r"(a), "r"(b) : "memory");
}
__device__ __forceinline__ void ld_relaxed2_if(uint32_t& a, uint32_t& b, const void* p, bool on) {
    asm volatile("{\n.reg .pred P;\n.reg .b64 t;\nsetp.ne.u32 P, %3, 0;\nmov.b64 t, {%0,%1};\n@P ld.relaxed.gpu.global.b64 t, [%2];\nmov.b64 {%0,%1}, t;\n}" : "+r"(a), "+r"(b) : "l"(p), "r"((uint32_t)on) : "memory");
}
__device__ __forceinline__ void ld_relaxed4(uint32_t* v, const void* p) {
    asm volatile("ld.relaxed.gpu.global.L1::no_allocate.v4.b32 {%0,%1,%2,%3}, [%4];" : "=r"(v[0]), "=r"(v[1]), "=r"(v[2]), "=r"(v[3]) : "l"(p) : "memory");
}
__device__ __forceinline__ void ld_relaxed1n(uint32_t& v, const void* p) { asm volatile("ld.relaxed.gpu.global.L1::no_allocate.b32 %0, [%1];" : "=r"(v) : "l"(p) : "memory"); }
__device__ __forceinline__ void red_add4(const void* p, uint32_t a, uint32_t b, uint32_t c, uint32_t d) {
    asm volatile("red.relaxed.gpu.global.add.noftz.v4.f16x2 [%0], {%1,%2,%3,%4};" ::"l"(p), "r"(a), "r"(b), "r"(c), "r"(d) : "memory");
}
__device__ __forceinline__ void red_add1(const void* p, uint32_t a) { asm volatile("red.relaxed.gpu.global.add.noftz.f16x2 [%0], %1;" ::"l"(p), "r"(a) : "memory"); }
__device__ __forceinline__ void ld_relaxed2(uint32_t* v, const void* p) {
    asm volatile("{\n.reg .b64 t;\nld.relaxed.gpu.global.L1::no_allocate.b64 t, [%2];\nmov.b64 {%0,%1}, t;\n}" : "=r"(v[0]), "=r"(v[1]) : "l"(p) : "memory");
}
__device__ __forceinline__ uint32_t ld_relaxed1(const void* p) { uint32_t v; asm volatile("ld.relaxed.gpu.global.u32 %0, [%1];" : "=r"(v) : "l"(p) : "memory"); return v; }
__device__ __forceinline__ void st_relaxed1(const void* p, uint32_t v) { asm volatile("st.relaxed.gpu.global.u32 [%0], %1;" ::"l"(p), "r"(v) : "memory"); }
__device__ __forceinline__ uint32_t ld_acquire(const void* p) { uint32_t v; asm volatile("ld.acquire.gpu.global.u32 %0, [%1];" : "=r"(v) : "l"(p) : "memory"); return v; }
__device__ __forceinline__ void red_relaxed(void* p) { asm volatile("red.relaxed.gpu.global.add.u32 [%0], 1;" ::"l"(p) : "memory"); }
__device__ __forceinline__ void red_release(void* p) { asm volatile("red.release.gpu.global.add.u32 [%0], 1;" ::"l"(p) : "memory"); }
__device__ __forceinline__ void st_stream4(const void* p, float a, float b, float c, float d) { asm volatile("st.global.cs.v4.f32 [%0], {%1, %2, %3, %4};" ::"l"(p), "f"(a), "f"(b), "f"(c), "f"(d) : "memory"); }
__device__ __forceinline__ void fence_async() { asm volatile("fence.proxy.async.global;" ::: "memory"); }
__device__ __forceinline__ void fence_async_smem() { asm volatile("fence.proxy.async.shared::cta;" ::: "memory"); }
__device__ __forceinline__ void wait_count(const uint32_t* p, uint32_t target) {
    while ((int32_t)(ld_acquire(p) - target) < 0) __nanosleep(POLLNS);
}
__device__ __forceinline__ void bar_sync(int id, int n) { asm volatile("bar.sync %0, %1;" ::"r"(id), "r"(n) : "memory"); }
__device__ __forceinline__ bool bar_and(int id, bool v) {
    uint32_t r;
    asm volatile("{\n.reg .pred P, Q;\nsetp.ne.u32 Q, %2, 0;\nbar.red.and.pred P, %1, 128, Q;\nselp.u32 %0, 1, 0, P;\n}" : "=r"(r) : "r"(id), "r"((uint32_t)v) : "memory");
    return r;
}
__device__ __forceinline__ void bar_arrive(int id, int n) { asm volatile("bar.arrive %0, %1;" ::"r"(id), "r"(n) : "memory"); }
__device__ __forceinline__ void lds128(uint32_t* v, uint32_t a) { asm volatile("ld.shared.v4.b32 {%0,%1,%2,%3}, [%4];" : "=r"(v[0]), "=r"(v[1]), "=r"(v[2]), "=r"(v[3]) : "r"(a) : "memory"); }
__device__ __forceinline__ uint32_t lds32(uint32_t a) { uint32_t v; asm volatile("ld.shared.b32 %0, [%1];" : "=r"(v) : "r"(a) : "memory"); return v; }
__device__ __forceinline__ void lds64(uint32_t* v, uint32_t a) { asm volatile("ld.shared.v2.b32 {%0,%1}, [%2];" : "=r"(v[0]), "=r"(v[1]) : "r"(a) : "memory"); }
__device__ __forceinline__ void lds64f(float* v, uint32_t a) { asm volatile("ld.shared.v2.f32 {%0,%1}, [%2];" : "=f"(v[0]), "=f"(v[1]) : "r"(a) : "memory"); }
__device__ __forceinline__ void sts128(uint32_t a, const uint32_t* v) { asm volatile("st.shared.v4.b32 [%0], {%1,%2,%3,%4};" ::"r"(a), "r"(v[0]), "r"(v[1]), "r"(v[2]), "r"(v[3]) : "memory"); }
__device__ __forceinline__ void sts64(uint32_t a, uint32_t x, uint32_t y) { asm volatile("st.shared.v2.b32 [%0], {%1,%2};" ::"r"(a), "r"(x), "r"(y) : "memory"); }
__device__ __forceinline__ void sts32(uint32_t a, uint32_t x) { asm volatile("st.shared.b32 [%0], %1;" ::"r"(a), "r"(x) : "memory"); }
__device__ __forceinline__ bool mbar_try(uint32_t b, uint32_t par) {
    uint32_t ok;
    asm volatile("{\n.reg .pred P;\nmbarrier.test_wait.parity.shared::cta.b64 P, [%1], %2;\nselp.u32 %0, 1, 0, P;\n}" : "=r"(ok) : "r"(b), "r"(par) : "memory");
    return ok;
}
__device__ __forceinline__ void mbar_wait(uint32_t b, uint32_t par) {
    asm volatile("{\n.reg .pred P;\nW: mbarrier.try_wait.parity.shared::cta.b64 P, [%0], %1;\n@!P bra W;\n}" ::"r"(b), "r"(par) : "memory");
}
__device__ __forceinline__ void mbar_wait_bounded(uint32_t b, uint32_t par) {
    asm volatile("{\n.reg .pred P, Q;\n.reg .u32 t, u;\nmov.u32 t, %%globaltimer_lo;\nW: mbarrier.try_wait.parity.shared::cta.b64 P, [%0], %1;\n"
                 "mov.u32 u, %%globaltimer_lo;\nsub.u32 u, u, t;\nsetp.gt.u32 Q, u, 2000000000;\n@Q st.global.u32 [%2], 0;\n@!P bra W;\n}" ::"r"(b), "r"(par), "l"(0ull) : "memory");
}
__device__ __forceinline__ void declare_fence(int zero) { asm volatile(".reg .pred PNEVER;\nsetp.ne.u32 PNEVER, %0, 0;" ::"r"(zero)); }
__device__ __forceinline__ void sched_fence() { asm volatile("{\n.reg .pred Q;\n.reg .u32 x;\n@!PNEVER bra D;\nF: ld.volatile.global.u32 x, [%0];\nsetp.ne.u32 Q, x, 0;\n@Q bra F;\nD:\n}" ::"l"(0ull) : "memory"); }
__device__ __forceinline__ void mbar_init(uint32_t b, uint32_t n) { asm volatile("mbarrier.init.shared::cta.b64 [%0], %1;" ::"r"(b), "r"(n) : "memory"); }
__device__ __forceinline__ void mbar_expect(uint32_t b, uint32_t bytes) { asm volatile("mbarrier.arrive.expect_tx.shared::cta.b64 _, [%0], %1;" ::"r"(b), "r"(bytes) : "memory"); }
__device__ __forceinline__ void mbar_arrive(uint32_t b) { asm volatile("mbarrier.arrive.shared::cta.b64 _, [%0];" ::"r"(b) : "memory"); }
__device__ __forceinline__ void mbar_arrive_cluster(uint32_t b) { asm volatile("mbarrier.arrive.shared::cluster.b64 _, [%0];" ::"r"(b) : "memory"); }
__device__ __forceinline__ void cluster_sync() { asm volatile("barrier.cluster.arrive.relaxed.aligned;\nbarrier.cluster.wait.aligned;" ::: "memory"); }
__device__ __forceinline__ uint32_t get_epoch(uint32_t sb) { mbar_wait(sb + B_EPOCH, 0); return __shfl_sync(0xffffffffu, lds32(sb + S_EPOCH), 0); }
__device__ __forceinline__ void tma2d(uint32_t dst, const CUtensorMap* m, int c0, int c1, uint32_t bar) {
    asm volatile("cp.async.bulk.tensor.2d.shared::cluster.global.mbarrier::complete_tx::bytes [%0], [%1, {%2, %3}], [%4];" ::"r"(dst), "l"(m), "r"(c0), "r"(c1), "r"(bar) : "memory");
}
__device__ __forceinline__ void tma3d(uint32_t dst, const CUtensorMap* m, int c0, int c1, int c2, uint32_t bar) {
    asm volatile("cp.async.bulk.tensor.3d.shared::cluster.global.mbarrier::complete_tx::bytes [%0], [%1, {%2, %3, %4}], [%5];" ::"r"(dst), "l"(m), "r"(c0), "r"(c1), "r"(c2), "r"(bar) : "memory");
}
__device__ __forceinline__ void mbar_expect_e(uint32_t b, uint32_t bytes) {
    asm volatile("{\n.reg .pred E;\nelect.sync _|E, 0xffffffff;\n@E mbarrier.arrive.expect_tx.shared::cta.b64 _, [%0], %1;\n}" ::"r"(b), "r"(bytes) : "memory");
}
__device__ __forceinline__ void tma3d_mc_e(uint32_t dst, const CUtensorMap* m, int c0, int c1, int c2, uint32_t bar, uint16_t mask, uint64_t pol) {
    asm volatile("{\n.reg .pred E;\nelect.sync _|E, 0xffffffff;\n@E cp.async.bulk.tensor.3d.shared::cluster.global.mbarrier::complete_tx::bytes.multicast::cluster.L2::cache_hint [%0], [%1, {%2, %3, %4}], [%5], %6, %7;\n}" ::"r"(dst), "l"(m), "r"(c0), "r"(c1), "r"(c2), "r"(bar), "h"(mask), "l"(pol) : "memory");
}
__device__ __forceinline__ void tma4d_e(uint32_t dst, const CUtensorMap* m, int c0, int c1, int c3, uint32_t bar, uint64_t pol) {
    asm volatile("{\n.reg .pred E;\nelect.sync _|E, 0xffffffff;\n@E cp.async.bulk.tensor.4d.shared::cluster.global.mbarrier::complete_tx::bytes.L2::cache_hint [%0], [%1, {%2, %3, 0, %4}], [%5], %6;\n}" ::"r"(dst), "l"(m), "r"(c0), "r"(c1), "r"(c3), "r"(bar), "l"(pol) : "memory");
}
__device__ __forceinline__ void tma4d_mc_e(uint32_t dst, const CUtensorMap* m, int c0, int c1, int c3, uint32_t bar, uint16_t mask, uint64_t pol) {
    asm volatile("{\n.reg .pred E;\nelect.sync _|E, 0xffffffff;\n@E cp.async.bulk.tensor.4d.shared::cluster.global.mbarrier::complete_tx::bytes.multicast::cluster.L2::cache_hint [%0], [%1, {%2, %3, 0, %4}], [%5], %6, %7;\n}" ::"r"(dst), "l"(m), "r"(c0), "r"(c1), "r"(c3), "r"(bar), "h"(mask), "l"(pol) : "memory");
}
__device__ __forceinline__ void tma_prefetch4d_e(const CUtensorMap* m, int c0, int c3) {
    asm volatile("{\n.reg .pred E;\nelect.sync _|E, 0xffffffff;\n@E cp.async.bulk.prefetch.tensor.4d.L2.global [%0, {%1, 0, 0, %2}];\n}" ::"l"(m), "r"(c0), "r"(c3) : "memory");
}
__device__ __forceinline__ void tma_prefetch3d_e(const CUtensorMap* m, int c0, int c1, int c2) {
    asm volatile("{\n.reg .pred E;\nelect.sync _|E, 0xffffffff;\n@E cp.async.bulk.prefetch.tensor.3d.L2.global [%0, {%1, %2, %3}];\n}" ::"l"(m), "r"(c0), "r"(c1), "r"(c2) : "memory");
}
__device__ __forceinline__ void l2_prefetch_e(const void* src, uint32_t bytes) {
    asm volatile("{\n.reg .pred E;\nelect.sync _|E, 0xffffffff;\n@E cp.async.bulk.prefetch.L2.global [%0], %1;\n}" ::"l"(src), "r"(bytes) : "memory");
}
__device__ __forceinline__ void bulk_g2s_e(uint32_t dst, const void* src, uint32_t bytes, uint32_t bar) {
    asm volatile("{\n.reg .pred E;\nelect.sync _|E, 0xffffffff;\n@E cp.async.bulk.shared::cluster.global.mbarrier::complete_tx::bytes [%0], [%1], %2, [%3];\n}" ::"r"(dst), "l"(src), "r"(bytes), "r"(bar) : "memory");
}
__device__ __forceinline__ bool elect_one() {
    uint32_t r;
    asm volatile("{\n.reg .pred E;\nelect.sync _|E, 0xffffffff;\nselp.u32 %0, 1, 0, E;\n}" : "=r"(r));
    return r;
}
__device__ __forceinline__ void tma_store2d(const CUtensorMap* m, int c0, int c1, uint32_t src, uint64_t pol) {
    asm volatile("cp.async.bulk.tensor.2d.global.shared::cta.bulk_group.L2::cache_hint [%0, {%1, %2}], [%3], %4;" ::"l"(m), "r"(c0), "r"(c1), "r"(src), "l"(pol) : "memory");
}
__device__ __forceinline__ void bulk_commit() { asm volatile("cp.async.bulk.commit_group;" ::: "memory"); }
__device__ __forceinline__ void bulk_wait_read() { asm volatile("cp.async.bulk.wait_group.read 0;" ::: "memory"); }
__device__ __forceinline__ void bulk_wait_all() { asm volatile("cp.async.bulk.wait_group 0;" ::: "memory"); }
__device__ __forceinline__ uint64_t mkdesc(uint32_t addr, uint32_t lbo, uint32_t sbo, uint32_t swz) {
    return (uint64_t)((addr & 0x3FFFF) >> 4) | ((uint64_t)(lbo >> 4) << 16) | ((uint64_t)(sbo >> 4) << 32) | ((uint64_t)swz << 62);
}
__device__ __forceinline__ void wg_fence() { asm volatile("wgmma.fence.sync.aligned;" ::: "memory"); }
__device__ __forceinline__ void wg_commit() { asm volatile("wgmma.commit_group.sync.aligned;" ::: "memory"); }
template <int N> __device__ __forceinline__ void wg_wait() { asm volatile("wgmma.wait_group.sync.aligned %0;" ::"n"(N) : "memory"); }
template <typename T> __device__ __forceinline__ void pin_ptr(T*& p) { asm volatile("" : "+l"(p)); }
template <int N> __device__ __forceinline__ void pin(uint32_t* d) {
#pragma unroll
    for (int i = 0; i < N; i++) asm volatile("" : "+r"(d[i])::"memory");
}
template <int N> __device__ __forceinline__ void pin(float* d) {
#pragma unroll
    for (int i = 0; i < N; i++) asm volatile("" : "+f"(d[i])::"memory");
}

template <int TA, int TB>
__device__ __forceinline__ void wgmma_ss256(float* d, uint64_t da, uint64_t db) {
    asm volatile("wgmma.mma_async.sync.aligned.m64n256k16.f32.bf16.bf16 "
        "{%0, %1, %2, %3, %4, %5, %6, %7, %8, %9, %10, %11, %12, %13, %14, %15, %16, %17, %18, %19, %20, %21, %22, %23, %24, %25, %26, %27, %28, %29, %30, %31, %32, %33, %34, %35, %36, %37, %38, %39, %40, %41, %42, %43, %44, %45, %46, %47, %48, %49, %50, %51, %52, %53, %54, %55, %56, %57, %58, %59, %60, %61, %62, %63, %64, %65, %66, %67, %68, %69, %70, %71, %72, %73, %74, %75, %76, %77, %78, %79, %80, %81, %82, %83, %84, %85, %86, %87, %88, %89, %90, %91, %92, %93, %94, %95, %96, %97, %98, %99, %100, %101, %102, %103, %104, %105, %106, %107, %108, %109, %110, %111, %112, %113, %114, %115, %116, %117, %118, %119, %120, %121, %122, %123, %124, %125, %126, %127}, %128, %129, 1, 1, 1, %130, %131;"
        : "+f"(d[0]), "+f"(d[1]), "+f"(d[2]), "+f"(d[3]), "+f"(d[4]), "+f"(d[5]), "+f"(d[6]), "+f"(d[7]), "+f"(d[8]), "+f"(d[9]), "+f"(d[10]), "+f"(d[11]), "+f"(d[12]), "+f"(d[13]), "+f"(d[14]), "+f"(d[15]), "+f"(d[16]), "+f"(d[17]), "+f"(d[18]), "+f"(d[19]), "+f"(d[20]), "+f"(d[21]), "+f"(d[22]), "+f"(d[23]), "+f"(d[24]), "+f"(d[25]), "+f"(d[26]), "+f"(d[27]), "+f"(d[28]), "+f"(d[29]), "+f"(d[30]), "+f"(d[31]), "+f"(d[32]), "+f"(d[33]), "+f"(d[34]), "+f"(d[35]), "+f"(d[36]), "+f"(d[37]), "+f"(d[38]), "+f"(d[39]), "+f"(d[40]), "+f"(d[41]), "+f"(d[42]), "+f"(d[43]), "+f"(d[44]), "+f"(d[45]), "+f"(d[46]), "+f"(d[47]), "+f"(d[48]), "+f"(d[49]), "+f"(d[50]), "+f"(d[51]), "+f"(d[52]), "+f"(d[53]), "+f"(d[54]), "+f"(d[55]), "+f"(d[56]), "+f"(d[57]), "+f"(d[58]), "+f"(d[59]), "+f"(d[60]), "+f"(d[61]), "+f"(d[62]), "+f"(d[63]), "+f"(d[64]), "+f"(d[65]), "+f"(d[66]), "+f"(d[67]), "+f"(d[68]), "+f"(d[69]), "+f"(d[70]), "+f"(d[71]), "+f"(d[72]), "+f"(d[73]), "+f"(d[74]), "+f"(d[75]), "+f"(d[76]), "+f"(d[77]), "+f"(d[78]), "+f"(d[79]), "+f"(d[80]), "+f"(d[81]), "+f"(d[82]), "+f"(d[83]), "+f"(d[84]), "+f"(d[85]), "+f"(d[86]), "+f"(d[87]), "+f"(d[88]), "+f"(d[89]), "+f"(d[90]), "+f"(d[91]), "+f"(d[92]), "+f"(d[93]), "+f"(d[94]), "+f"(d[95]), "+f"(d[96]), "+f"(d[97]), "+f"(d[98]), "+f"(d[99]), "+f"(d[100]), "+f"(d[101]), "+f"(d[102]), "+f"(d[103]), "+f"(d[104]), "+f"(d[105]), "+f"(d[106]), "+f"(d[107]), "+f"(d[108]), "+f"(d[109]), "+f"(d[110]), "+f"(d[111]), "+f"(d[112]), "+f"(d[113]), "+f"(d[114]), "+f"(d[115]), "+f"(d[116]), "+f"(d[117]), "+f"(d[118]), "+f"(d[119]), "+f"(d[120]), "+f"(d[121]), "+f"(d[122]), "+f"(d[123]), "+f"(d[124]), "+f"(d[125]), "+f"(d[126]), "+f"(d[127])
        : "l"(da), "l"(db), "n"(TA), "n"(TB));
}
template <int TA, int TB>
__device__ __forceinline__ void wgmma_ss256_first(float* d, uint64_t da, uint64_t db) {
    asm volatile("wgmma.mma_async.sync.aligned.m64n256k16.f32.bf16.bf16 "
        "{%0, %1, %2, %3, %4, %5, %6, %7, %8, %9, %10, %11, %12, %13, %14, %15, %16, %17, %18, %19, %20, %21, %22, %23, %24, %25, %26, %27, %28, %29, %30, %31, %32, %33, %34, %35, %36, %37, %38, %39, %40, %41, %42, %43, %44, %45, %46, %47, %48, %49, %50, %51, %52, %53, %54, %55, %56, %57, %58, %59, %60, %61, %62, %63, %64, %65, %66, %67, %68, %69, %70, %71, %72, %73, %74, %75, %76, %77, %78, %79, %80, %81, %82, %83, %84, %85, %86, %87, %88, %89, %90, %91, %92, %93, %94, %95, %96, %97, %98, %99, %100, %101, %102, %103, %104, %105, %106, %107, %108, %109, %110, %111, %112, %113, %114, %115, %116, %117, %118, %119, %120, %121, %122, %123, %124, %125, %126, %127}, %128, %129, 0, 1, 1, %130, %131;"
        : "=f"(d[0]), "=f"(d[1]), "=f"(d[2]), "=f"(d[3]), "=f"(d[4]), "=f"(d[5]), "=f"(d[6]), "=f"(d[7]), "=f"(d[8]), "=f"(d[9]), "=f"(d[10]), "=f"(d[11]), "=f"(d[12]), "=f"(d[13]), "=f"(d[14]), "=f"(d[15]), "=f"(d[16]), "=f"(d[17]), "=f"(d[18]), "=f"(d[19]), "=f"(d[20]), "=f"(d[21]), "=f"(d[22]), "=f"(d[23]), "=f"(d[24]), "=f"(d[25]), "=f"(d[26]), "=f"(d[27]), "=f"(d[28]), "=f"(d[29]), "=f"(d[30]), "=f"(d[31]), "=f"(d[32]), "=f"(d[33]), "=f"(d[34]), "=f"(d[35]), "=f"(d[36]), "=f"(d[37]), "=f"(d[38]), "=f"(d[39]), "=f"(d[40]), "=f"(d[41]), "=f"(d[42]), "=f"(d[43]), "=f"(d[44]), "=f"(d[45]), "=f"(d[46]), "=f"(d[47]), "=f"(d[48]), "=f"(d[49]), "=f"(d[50]), "=f"(d[51]), "=f"(d[52]), "=f"(d[53]), "=f"(d[54]), "=f"(d[55]), "=f"(d[56]), "=f"(d[57]), "=f"(d[58]), "=f"(d[59]), "=f"(d[60]), "=f"(d[61]), "=f"(d[62]), "=f"(d[63]), "=f"(d[64]), "=f"(d[65]), "=f"(d[66]), "=f"(d[67]), "=f"(d[68]), "=f"(d[69]), "=f"(d[70]), "=f"(d[71]), "=f"(d[72]), "=f"(d[73]), "=f"(d[74]), "=f"(d[75]), "=f"(d[76]), "=f"(d[77]), "=f"(d[78]), "=f"(d[79]), "=f"(d[80]), "=f"(d[81]), "=f"(d[82]), "=f"(d[83]), "=f"(d[84]), "=f"(d[85]), "=f"(d[86]), "=f"(d[87]), "=f"(d[88]), "=f"(d[89]), "=f"(d[90]), "=f"(d[91]), "=f"(d[92]), "=f"(d[93]), "=f"(d[94]), "=f"(d[95]), "=f"(d[96]), "=f"(d[97]), "=f"(d[98]), "=f"(d[99]), "=f"(d[100]), "=f"(d[101]), "=f"(d[102]), "=f"(d[103]), "=f"(d[104]), "=f"(d[105]), "=f"(d[106]), "=f"(d[107]), "=f"(d[108]), "=f"(d[109]), "=f"(d[110]), "=f"(d[111]), "=f"(d[112]), "=f"(d[113]), "=f"(d[114]), "=f"(d[115]), "=f"(d[116]), "=f"(d[117]), "=f"(d[118]), "=f"(d[119]), "=f"(d[120]), "=f"(d[121]), "=f"(d[122]), "=f"(d[123]), "=f"(d[124]), "=f"(d[125]), "=f"(d[126]), "=f"(d[127])
        : "l"(da), "l"(db), "n"(TA), "n"(TB));
}
template <int TB>
__device__ __forceinline__ void wgmma_rs128(float* d, const uint32_t* a, uint64_t db, uint32_t acc) {
    asm volatile("{\n.reg .pred P;\nsetp.ne.u32 P, %69, 0;\nwgmma.mma_async.sync.aligned.m64n128k16.f32.bf16.bf16 "
        "{%0, %1, %2, %3, %4, %5, %6, %7, %8, %9, %10, %11, %12, %13, %14, %15, %16, %17, %18, %19, %20, %21, %22, %23, %24, %25, %26, %27, %28, %29, %30, %31, %32, %33, %34, %35, %36, %37, %38, %39, %40, %41, %42, %43, %44, %45, %46, %47, %48, %49, %50, %51, %52, %53, %54, %55, %56, %57, %58, %59, %60, %61, %62, %63}, {%64, %65, %66, %67}, %68, P, 1, 1, %70;\n}"
        : "+f"(d[0]), "+f"(d[1]), "+f"(d[2]), "+f"(d[3]), "+f"(d[4]), "+f"(d[5]), "+f"(d[6]), "+f"(d[7]), "+f"(d[8]), "+f"(d[9]), "+f"(d[10]), "+f"(d[11]), "+f"(d[12]), "+f"(d[13]), "+f"(d[14]), "+f"(d[15]), "+f"(d[16]), "+f"(d[17]), "+f"(d[18]), "+f"(d[19]), "+f"(d[20]), "+f"(d[21]), "+f"(d[22]), "+f"(d[23]), "+f"(d[24]), "+f"(d[25]), "+f"(d[26]), "+f"(d[27]), "+f"(d[28]), "+f"(d[29]), "+f"(d[30]), "+f"(d[31]), "+f"(d[32]), "+f"(d[33]), "+f"(d[34]), "+f"(d[35]), "+f"(d[36]), "+f"(d[37]), "+f"(d[38]), "+f"(d[39]), "+f"(d[40]), "+f"(d[41]), "+f"(d[42]), "+f"(d[43]), "+f"(d[44]), "+f"(d[45]), "+f"(d[46]), "+f"(d[47]), "+f"(d[48]), "+f"(d[49]), "+f"(d[50]), "+f"(d[51]), "+f"(d[52]), "+f"(d[53]), "+f"(d[54]), "+f"(d[55]), "+f"(d[56]), "+f"(d[57]), "+f"(d[58]), "+f"(d[59]), "+f"(d[60]), "+f"(d[61]), "+f"(d[62]), "+f"(d[63])
        : "r"(a[0]), "r"(a[1]), "r"(a[2]), "r"(a[3]), "l"(db), "r"(acc), "n"(TB));
}
template <int TB>
__device__ __forceinline__ void wgmma_rs64(float* d, const uint32_t* a, uint64_t db, uint32_t acc) {
    asm volatile("{\n.reg .pred P;\nsetp.ne.u32 P, %37, 0;\nwgmma.mma_async.sync.aligned.m64n64k16.f32.bf16.bf16 "
        "{%0, %1, %2, %3, %4, %5, %6, %7, %8, %9, %10, %11, %12, %13, %14, %15, %16, %17, %18, %19, %20, %21, %22, %23, %24, %25, %26, %27, %28, %29, %30, %31}, {%32, %33, %34, %35}, %36, P, 1, 1, %38;\n}"
        : "+f"(d[0]), "+f"(d[1]), "+f"(d[2]), "+f"(d[3]), "+f"(d[4]), "+f"(d[5]), "+f"(d[6]), "+f"(d[7]), "+f"(d[8]), "+f"(d[9]), "+f"(d[10]), "+f"(d[11]), "+f"(d[12]), "+f"(d[13]), "+f"(d[14]), "+f"(d[15]), "+f"(d[16]), "+f"(d[17]), "+f"(d[18]), "+f"(d[19]), "+f"(d[20]), "+f"(d[21]), "+f"(d[22]), "+f"(d[23]), "+f"(d[24]), "+f"(d[25]), "+f"(d[26]), "+f"(d[27]), "+f"(d[28]), "+f"(d[29]), "+f"(d[30]), "+f"(d[31])
        : "r"(a[0]), "r"(a[1]), "r"(a[2]), "r"(a[3]), "l"(db), "r"(acc), "n"(TB));
}
template <int TB>
__device__ __forceinline__ void wgmma_rs16(float* d, const uint32_t* a, uint64_t db, uint32_t acc) {
    asm volatile("{\n.reg .pred P;\nsetp.ne.u32 P, %13, 0;\nwgmma.mma_async.sync.aligned.m64n16k16.f32.bf16.bf16 "
        "{%0, %1, %2, %3, %4, %5, %6, %7}, {%8, %9, %10, %11}, %12, P, 1, 1, %14;\n}"
        : "+f"(d[0]), "+f"(d[1]), "+f"(d[2]), "+f"(d[3]), "+f"(d[4]), "+f"(d[5]), "+f"(d[6]), "+f"(d[7])
        : "r"(a[0]), "r"(a[1]), "r"(a[2]), "r"(a[3]), "l"(db), "r"(acc), "n"(TB));
}

__device__ __forceinline__ void wait_clocks(uint32_t n) {
    asm volatile("{\n.reg .pred P;\n.reg .u32 a, b;\nmov.u32 a, %%clock;\nW: mov.u32 b, %%clock;\nsub.u32 b, b, a;\nsetp.lt.u32 P, b, %0;\n@P bra W;\n}" ::"r"(n) : "memory");
}
__device__ __forceinline__ uint32_t gtime() { uint32_t t; asm volatile("mov.u32 %0, %%globaltimer_lo;" : "=r"(t)); return t; }
__device__ __forceinline__ uint32_t stamp_word(uint32_t seq) { return (gtime() & ~31u) | (seq & 31u); }
__device__ __forceinline__ void wait_time(uint32_t t, uint32_t sb) { while ((int32_t)(gtime() - t) < 0) {} }
#define NAPMODE 1
__device__ __forceinline__ void nap(uint32_t ns) { if (NAPMODE) wait_clocks(ns * 7 / 4); else __nanosleep(ns); }
template <int STRIDE>
__device__ __forceinline__ uint32_t latest_stamp(const uint32_t* p, uint32_t seq, uint32_t ref, uint32_t sb) {
#pragma unroll 1
    for (int n = opq(0, 0);; n++) {
        uint32_t bad = 0; int32_t m = INT32_MIN;
#pragma unroll
        for (int i = 0; i < 3; i++) { const uint32_t v = ld_relaxed1(p + i * STRIDE); bad |= (v ^ seq) & 31u; m = max(m, (int32_t)((v & ~31u) - ref)); }
        if (__all_sync(0xffffffffu, bad == 0)) return ref + __reduce_max_sync(0xffffffffu, m);
        nap(100);
        if (n > SPIN_LIMIT) spin_fault();
    }
}
constexpr uint32_t ONES = 0x3C003C00u, FULL = 0x50005000u;
__device__ __forceinline__ void pacer(const Params& P, const uint32_t sb, const int cta, const int lane, const uint32_t epoch) {
    uint8_t* const zp = P.xb + cta * 2048 + xg_lane(lane);
    if (lane < 3) asm volatile("prefetch.tensormap [%0];" ::"l"(&P.tm[lane == 0 ? M_C1 + cta % 3 : lane == 1 ? M_CO : M_SEG]) : "memory");
    uint32_t e0 = 0;
#pragma unroll 2
    for (int i = 0; i < 32; i++) { const uint4 u = __ldg((const uint4*)P.mem0 + i * 32 + lane); e0 = amax(amax(e0, amax(u.x, u.y)), amax(u.z, u.w)); }
    e0 = min(max(warp_exp(e0), 31u), 253u) - 14;
    if (cta < 32) {
        const uint32_t* m = (const uint32_t*)(P.mem0 + (lane >> 2) * 1024 + cta * 32 + (lane & 3) * 2);
        const float sc = __uint_as_float((254 - e0) << 23);
        auto cv = [&](uint32_t u) { return pack2h(bf_lo(u) * sc, bf_hi(u) * sc); };
        const uint32_t y = cv(m[12]);
        st_relaxed4(zp, cv(m[0]), cv(m[4]), cv(m[8]), prmt(y, FULL, 0x7610));
        st_relaxed1(P.xb + xg_side(cta) + lane * 4, prmt(y, FULL, 0x3254));
    }
    if (cta < 40) {
#pragma unroll 1
        for (int b = 1; b < 8; b++) st_relaxed4(zp + xg_buf(b), 0, 0, 0, 0);
    }
    __threadfence();
    const uint32_t* ts = (const uint32_t*)(P.xb + XG_T) + lane;
    int32_t d0 = P.dly;
    const uint32_t go = mapa(sb + B_GO, (cta / 3 & 1) * 3 + 1 + (lane & 1));
    auto free_segment = [&]() { if (lane == 0) mbar_expect(sb + B_KVFULL, 16384); __syncwarp(); if (lane < 2) mbar_arrive_cluster(go); };
    for (int n = 0; (int32_t)(ld_acquire(&g_cnt(C_XCNT)) - (epoch + 1) * 256) < 0; n++) { __nanosleep(500); if (n > SPIN_LIMIT) spin_fault(); }
    const uint32_t ex = max(ld_relaxed1(&g_cnt(C_XMAX)) & 255, 67u);
    mbar_wait_bounded(sb + B_READY, 0);
    free_segment();
    if (lane == 0) st_relaxed2(g_hint + cta * 32, stamp_word(epoch + 1), lds32(sb + S_EV) | lds32(sb + S_EO) << 16);
    uint32_t a = gtime();
    for (int n = 0;; n++) {
        uint32_t bad = 0, e = 0; int32_t m = INT32_MIN;
#pragma unroll
        for (int i = 0; i < 3; i++) {
            uint32_t v[2];
            ld_relaxed2(v, g_hint + lane * 32 + i * 1024);
            bad |= (v[0] ^ (epoch + 1)) & 31u; m = max(m, (int32_t)((v[0] & ~31u) - a)); e = __vmaxu2(e, v[1]);
        }
        if (__all_sync(0xffffffffu, bad == 0)) {
            a += __reduce_max_sync(0xffffffffu, m);
            const uint32_t ev = __reduce_max_sync(0xffffffffu, e & 255), eo = __reduce_max_sync(0xffffffffu, e >> 16);
            if (lane == 0) { sts64(sb + S_SC, max(ev, 97u) + max(eo, 97u) - 244, ex); sts32(sb + S_ISC, e0 * 0x800080u); }
            break;
        }
        wait_clocks(100);
        if (n > SPIN_LIMIT) spin_fault();
    }
    wait_time(a, sb);
    if (lane == 0) mbar_arrive(sb + B_RELM);
#pragma unroll 1
    for (int s = 0; s < 63; s++) {
        const uint32_t seq = epoch * 63 + s + 1;
        mbar_wait_bounded(sb + B_P1, s & 1);
        const uint32_t tx = gtime();
        if (lane == 0) st_relaxed1(ts + (s & 1) * 256 + cta, (tx & ~31u) | (seq & 31u));
        if (s > 0) {
            const int32_t e0 = latest_stamp<32>(ts + (~s & 1) * 256 + 128, seq - 1, a, sb) + P.mrg - a;
            d0 += min(max(e0, min(e0 + P.guard, -P.clamp0)), P.clampv) / 2;
        }
        while ((int32_t)(gtime() - tx) < P.rd) nap(20);
        a = latest_stamp<32>(ts + (s & 1) * 256, seq, tx, sb) + d0;
        while ((int32_t)(a - gtime()) > 250) nap(40);
        wait_time(a, sb);
        if (lane == 0) mbar_arrive(sb + B_RELM);
        mbar_wait_bounded(sb + B_RED, s & 1);
        const uint32_t g = tx + __reduce_max_sync(0xffffffffu, lds32(sb + S_TO + (lane & 7) * 4) - tx);
        if (lane == 0) st_relaxed1(ts + (s & 1) * 256 + 128 + cta, (g & ~31u) | (seq & 31u));
        if (s < 62) { if (P.kvd) nap(P.kvd); free_segment(); }
    }
}
__device__ __forceinline__ void st_async2(uint32_t a, uint32_t x, uint32_t y, uint32_t bar) {
    asm volatile("st.async.weak.shared::cluster.mbarrier::complete_tx::bytes.v2.b32 [%0], {%1,%2}, [%3];" ::"r"(a), "r"(x), "r"(y), "r"(bar) : "memory");
}
__device__ __forceinline__ uint32_t xor_or(uint32_t a, uint32_t b, uint32_t t) { uint32_t d; asm("lop3.b32 %0, %1, %2, %3, 0x7E;" : "=r"(d) : "r"(a), "r"(b), "r"(t)); return d; }
__device__ __forceinline__ bool tags_ok(uint32_t bad, uint32_t mask = 1) {
    uint32_t r;
    asm volatile("{\n.reg .pred P;\n.reg .b32 x;\nand.b32 x, %1, %2;\nsetp.ne.b32 P, x, 0;\nvote.sync.any.pred P, P, 0xffffffff;\nselp.u32 %0, 0, 1, P;\n}" : "=r"(r) : "r"(bad), "r"(mask));
    return r;
}
constexpr int SROW = 56;
#define PREA 8
#define PREB 9
#define RING1 6
#define RING2 7
#define RING3 8
#define PRE2 10
#define PRE2A 0
#define PRE3 0
#define EFENCE 0
#define RFENCE 1
#define PROG 16
#define EARLY 0
#define PLATE 1
#define NDEP 0
#define EFENCE2 0
#define LAG2 8
#define LAG 4
#define PUT1 33
#define DEPS 3
#define ADELAY 120
#define BDELAY 0
#define HOLD 1
#define XDELAY 330
#define FENCEA 0x80
#define FENCEB 0x80
#define FENCE2 0x220
#define OFENCE 0
#define MASK3 0x57
#define MASK4 0x55
#define MASK5 0x25
#define OFF3 0x5320
#define OFF4 0x6420
#define OFF5 0x0520
#define RESA (NRA == 3 ? 15 : NRA == 4 ? 3 : 0)
#define RESB (NRB == 3 ? 0xcc : NRB == 4 ? 0x30 : 0)
#define RESB1 (NRB == 3 ? 0xcc : NRB == 4 ? 0xc : 0)
__host__ __device__ constexpr int smem_mask(int NR) { return NR == 3 ? MASK3 : NR == 4 ? MASK4 : MASK5; }
__host__ __device__ constexpr bool round_smem(int r, int NR) { return smem_mask(NR) >> r & 1; }
__host__ __device__ constexpr int kord(int r, int NR) { int c = 0; for (int i = 0; i < r; i++) c += round_smem(i, NR) == round_smem(r, NR); return round_smem(r, NR) ? NR + c : c; }
__host__ __device__ constexpr int slot_r(int n, int NR) { return n < 32 ? n >> 2 : (((n & 31) >> 2) + ((NR == 3 ? OFF3 : NR == 4 ? OFF4 : OFF5) >> (n & 3) * 4)) & 7; }
__host__ __device__ constexpr int slot_k(int n, int NR) { return kord(slot_r(n, NR), NR); }
__host__ __device__ constexpr int slot_sord(int n, int NR) { int c = 0; for (int i = 0; i < n; i++) c += slot_k(i, NR) >= NR; return c; }
__host__ __device__ constexpr int sfrag_slot(int q, int NR) { for (int n = 0; n < 64; n++) if (slot_k(n, NR) >= NR && slot_sord(n, NR) == q) return n; return -1; }
__host__ __device__ constexpr int w1_loaded(int n, int NR, int PRE) {
    int q = PRE;
    for (int i = 0; i <= n; i++) q += q < (8 - NR) * 8 && q - slot_sord(i + 1, NR) < (i < 32 ? RING1 : RING2);
    return q;
}
template <int Q, int NR>
__device__ __forceinline__ void load_w1(uint32_t* w, const uint32_t* a) {
    constexpr int n = sfrag_slot(Q, NR);
    ldsm4t(w, a[n & 3] + ((slot_k(n, NR) - NR) * 2 + (n >> 5)) * 2048);
}
constexpr int AB = NRA < 5, BB = 3 - AB;
__device__ __forceinline__ bool w2_full(int role, int warp) { return warp < (role == 2 ? 2 : 3); }
__device__ __forceinline__ int w2_nblk(int role, int warp) { return warp < 4 ? BB - !w2_full(role, warp) : AB; }
__host__ __device__ constexpr int w2_step(bool full, int i) { return AB ? (full ? 2 * i : 0) : full ? (i == 0 ? 0 : i == 1 ? 16 - 2 * EARLY : 18 - 2 * EARLY) : i; }
__device__ __forceinline__ int w2_block(int role, int warp) {
    const int f = role * 3 + warp, g = role == 2 ? warp : role;
    if (AB) return (warp >= 4 ? role * 4 + (warp - 4) : w2_full(role, warp) ? 16 + 4 * (f >> 1) + (f & 1) : 12 + g) ^ EARLY;
    return w2_full(role, warp) ? EARLY + 4 * (f >> 1) + (f & 1) : EARLY + 2 + 4 * g;
}
__device__ __forceinline__ int w2_res(int role, int warp) { return warp >= 4 ? RESA : w2_full(role, warp) ? RESB : RESB1; }
__device__ __forceinline__ int w2_units(int role, int warp) { return w2_nblk(role, warp) * 4 - (5 - (warp < 4 ? NRB : NRA)) * 2; }
constexpr int W2B = (BB * 4 - (5 - NRB) * 2) * 2048, W2A = (AB * 4 - (5 - NRA) * 2) * 2048;
static_assert(S_W2 + 4 * W2B - 8192 + 4 * W2A == S_KV, "weights");
__device__ __forceinline__ int w1_base(int warp) { return S_W1 + (warp < 4 ? warp * (8 - NRB) : 4 * (8 - NRB) + (warp - 4) * (8 - NRA)) * 4096; }
__device__ __forceinline__ int w2_base(int warp) { return S_W2 + (warp < 4 ? warp * W2B : 4 * W2B - 8192 + (warp - 4) * W2A); }
__device__ __forceinline__ void chain_load(const Params& P, uint32_t sb, int cta, int warp, int lane, int round) {
    const int role = cta % 3, h = cta / 3;
    mbar_expect_e(sb + B_INIT, round ? (8 - (warp < 4 ? NRB : NRA)) * 4096 : 20480);
    if (round) mbar_expect_e(sb + B_INIT2, w2_units(role, warp) * 2048);
    __syncwarp();
    const int m1 = (warp < 4 ? smem_mask(NRB) : smem_mask(NRA)) ^ (round ? 0 : 255), below = (1 << lane) - 1;
    const int m2 = (w2_res(role, warp) ^ (round ? 0xfff : 0)) & ((1 << w2_nblk(role, warp) * 4) - 1);
    const uint32_t d1 = sb + (round ? w1_base(warp) : warp * 20480), d2 = round ? sb + w2_base(warp) : d1 + __popc(m1) * 4096;
    if (m1 >> lane & 1) tma3d(d1 + __popc(m1 & below) * 4096, &P.tm[M_C1 + role], 0, warp * 128 + lane * 16, h * 2, sb + B_INIT);
    __syncwarp();
    if (m2 >> lane & 1)
        tma2d(d2 + __popc(m2 & below) * 2048, &P.tm[M_CO], (w2_block(role, warp) + w2_step(w2_full(role, warp), lane >> 2)) * 32, h * 128 + (lane & 3) * 32, sb + (round ? B_INIT2 : B_INIT));
    __syncwarp();
}

__device__ __forceinline__ void put_partials(bool TR, uint32_t a, const float* x, const float* y) {
    if (TR) stsm4t(a, pack2(x[0], x[1]), pack2(x[2], x[3]), pack2(y[0], y[1]), pack2(y[2], y[3]));
    else stsm4(a, pack2(x[0], x[1]), pack2(x[2], x[3]), pack2(y[0], y[1]), pack2(y[2], y[3]));
}
template <int NR, int PRE, int FM, int B, int E>
__device__ __forceinline__ void project(float (*acc)[4], bool TR, const uint32_t (*wr)[4], uint32_t (*as)[4], uint32_t (*v)[4], uint32_t* x, const uint32_t* w1a, uint32_t pp, uint32_t zero) {
    static_for<B, E>([&](auto I) {
        constexpr int n = I.value, kk = slot_k(n, NR), T = (n >> 5) * 4 + (n & 3), so = slot_sord(n, NR), q = w1_loaded(n - 1, NR, PRE);
        constexpr bool sm = kk >= NR;
        const uint32_t* w = sm ? as[so] : wr[sm ? 0 : (kk * 2 + (n >> 5)) * 4 + (n & 3)];
        if constexpr (n == 32 && PUT1 < 32) { put_partials(TR, pp, acc[0], acc[1]); put_partials(TR, pp + 4096, acc[2], acc[3]); }
        if constexpr (n == 0) {
            const uint32_t c = prmt(v[0][3], x[0], 0x3254);
            v[0][0] = h2bf(v[0][0], v[0][0]); v[0][1] = h2bf(v[0][1], v[0][1]); v[0][2] = h2bf(v[0][2], v[0][2]); v[0][3] = h2bf(v[0][3], x[0]);
            x[0] = c;
        }
        if constexpr ((n & 31) < 4) acc[T][0] = acc[T][1] = acc[T][2] = acc[T][3] = 0.f;
        mma16816(acc[T], w[0], w[1], w[2], w[3], v[slot_r(n, NR) >> 1][(slot_r(n, NR) & 1) * 2], v[slot_r(n, NR) >> 1][(slot_r(n, NR) & 1) * 2 + 1]);
        if constexpr (n == DEPS) {
            const uint32_t sel = __float_as_uint(acc[T][0]) * zero + 0x7610;
#pragma unroll
            for (int b = 1; b < 4; b++) {
                if (b <= NDEP) cvt_block(v[b], x[b], sel);
                else {
                    const uint32_t c = prmt(v[b][3], x[b], 0x3254);
                    v[b][0] = h2bf(v[b][0], v[b][0]); v[b][1] = h2bf(v[b][1], v[b][1]); v[b][2] = h2bf(v[b][2], v[b][2]); v[b][3] = h2bf(v[b][3], x[b]);
                    x[b] = c;
                }
            }
        }
        if constexpr (w1_loaded(n, NR, PRE) > q) load_w1<q, NR>(as[q], w1a);
        if constexpr (n == PUT1 && n >= 32) { put_partials(TR, pp, acc[0], acc[1]); put_partials(TR, pp + 4096, acc[2], acc[3]); }
        if constexpr (n % 4 == 3 && (FM >> (n / 4) & 1) && n != E - 1) sched_fence();
    });
    if constexpr (E == 64) { put_partials(TR, pp + 8192, acc[4], acc[5]); put_partials(TR, pp + 12288, acc[6], acc[7]); }
}
__device__ __forceinline__ void reduce8(const uint32_t (*x)[4], const uint32_t* sel, float sc, uint32_t& r0, uint32_t& r1) {
    float d[4][4];
#pragma unroll
    for (int i = 0; i < 4; i++) {
        d[i][0] = d[i][1] = d[i][2] = d[i][3] = 0.f;
        mma16816(d[i], x[i][0], x[i][1], x[i][2], x[i][3], sel[2 * i], sel[2 * i + 1]);
    }
    r0 = pack2(((d[0][0] + d[1][0]) + (d[2][0] + d[3][0])) * sc, ((d[0][1] + d[1][1]) + (d[2][1] + d[3][1])) * sc);
    r1 = pack2(((d[0][2] + d[1][2]) + (d[2][2] + d[3][2])) * sc, ((d[0][3] + d[1][3]) + (d[2][3] + d[3][3])) * sc);
}

__host__ __device__ constexpr int wo_count(int n, int RES, bool res) { int c = 0; for (int i = 0; i < n; i++) c += (RES >> (i >> 2) & 1) == res; return c; }
__host__ __device__ constexpr int wo_loaded(int n, int RES, int PRE, int end) { int q = PRE; for (int i = 0; i <= n; i++) q += q < end && q - wo_count(i + 1, RES, false) < RING3; return q; }
template <int Q>
__device__ __forceinline__ void load_w2(uint32_t* w, const uint32_t* a) { ldsm4t(w, a[Q & 1] + (Q >> 1) * 1024); }
template <int NB, int RES, int PRE, int FM>
__device__ __forceinline__ void wo_blocks(uint32_t (*w)[4], const uint32_t (*wp)[4], uint32_t oa, const uint32_t* wa, const uint8_t* dst, const uint8_t* dsd, bool odd) {
    float a[NB][4][4];
    uint32_t o[4][4], r[5];
    bar_sync(3, 256);
#pragma unroll
    for (int i = 0; i < 4; i++) ldsm4(o[i], oa + i * 512);
    if (FM & 1) sched_fence();
    static_for<0, NB * 16>([&](auto I) {
        constexpr int n = I.value, i = n & 15, end = wo_count(NB * 16, RES, false), q = wo_loaded(n - 1, RES, PRE, end);
        constexpr bool res = RES >> (n >> 2) & 1;
        const uint32_t* b = o[i >> 2] + (i & 2);
        const uint32_t* x = res ? wp[wo_count(n, RES, true)] : w[wo_count(n, RES, false)];
        float* d = a[n >> 4][i & 3];
        if constexpr (i < 4) d[0] = d[1] = d[2] = d[3] = 0.f;
        mma16816(d, x[0], x[1], x[2], x[3], b[0], b[1]);
        if constexpr (wo_loaded(n, RES, PRE, end) > q) load_w2<q>(w[q], wa);
        if constexpr (n == NB * 16 - 1 || (n >= 16 && i == LAG - 1)) {
            const float (*e)[4] = a[n == NB * 16 - 1 ? NB - 1 : (n >> 4) - 1];
            const uint32_t y = pack2h(e[1][2] + e[3][2], e[1][3] + e[3][3]);
            r[0] = movm(pack2h(e[0][0] + e[2][0], e[0][1] + e[2][1])); r[1] = movm(pack2h(e[0][2] + e[2][2], e[0][3] + e[2][3]));
            r[2] = movm(pack2h(e[1][0] + e[3][0], e[1][1] + e[3][1])); r[3] = movm(odd ? ONES : y); r[4] = movm(odd ? y : ONES);
        }
        if constexpr (n == NB * 16 - 1 || (n >= 16 && i == LAG2 - 1)) {
            constexpr int bs = w2_step(NB == BB, n == NB * 16 - 1 ? NB - 1 : (n >> 4) - 1);
            red_add4(dst + bs * 2048, r[0], r[1], r[2], r[3]);
            red_add1(dsd + (bs >> 1) * 1024 + (bs & 1) * 256, r[4]);
        }
        if constexpr (((FM >> (n / 4 + 1)) & 1) && (n & 3) == 3 && n != NB * 16 - 1) sched_fence();
    });
}
#define FRAG1(ln) ((((ln) & 7) + ((ln) >> 4) * 8) * 128 + ((((((ln) >> 3) & 1) << (ROLE == 1)) ^ ((ln) & 7)) << 4))
#define FRAG2(ln) ((((ln) & 7) + ((ln) >> 4) * 8) * 64 + (((((ln) >> 3) & 1) ^ (((ln) >> 1) & 3)) << 4))
#define TILE_X(i) (ROLE == 1 ? (((i) >> 1) << 6) | (((i) & 1) << 4) : (i) << 5)
__device__ __forceinline__ void chain_fetch(const Params& P, const uint32_t sb, const int cta, const int warp, const int lane, uint32_t (*wr)[4]) {
    const int ROLE = cta % 3, nr = warp < 4 ? NRB : NRA;
    mbar_wait(sb + B_INIT, 0);
#pragma unroll
    for (int f = 0; f < 40; f++) {
        const bool w1 = f < (NRA < NRB ? NRA : NRB) * 8 || f < nr * 8;
        ldsm4t(wr[f], sb + warp * 20480 + (f >> 2) * 2048 + (w1 ? FRAG1(lane) ^ TILE_X(f & 3) : (f & 2) * 512 + (FRAG2(lane) ^ ((f & 1) << 5))));
    }
    fence_async_smem();
    mbar_wait(sb + B_SFREE + (warp >> 2) * 8, 0);
    bar_sync(1, 256);
    chain_load(P, sb, cta, warp, lane, 1);
}
__device__ __forceinline__ void chain_bounds(const uint32_t sb, const int cta, const int warp, const int lane, const uint32_t (*wr)[4]) {
    const int ROLE = cta % 3, nr = warp < 4 ? NRB : NRA;
    uint32_t m[6] = {}, u[4];
#pragma unroll
    for (int f = 0; f < 40; f++) m[f < 24 ? 0 : f >> 3] = amax4(m[f < 24 ? 0 : f >> 3], wr[f]);
    uint32_t m1 = amax(m[0], amax(nr > 3 ? m[3] : 0, nr > 4 ? m[4] : 0)), m2 = amax(nr > 3 ? 0 : m[3], nr > 4 ? 0 : m[4]);
    mbar_wait(sb + B_INIT, 1);
    if (ROLE == 2) {
#pragma unroll 4
        for (int i = 0; i < S_W2 / 4096; i++) { lds128(u, sb + S_W1 + warp * (S_W2 / 8) + i * 512 + lane * 16); m1 = amax4(m1, u); }
    }
    mbar_wait(sb + B_INIT2, 0);
    const int n = w2_units(ROLE, warp) * 4;
#pragma unroll 4
    for (int i = 0; i < n; i++) { lds128(u, sb + w2_base(warp) + i * 512 + lane * 16); m2 = amax4(m2, u); }
    m1 = warp_exp(m1); m2 = warp_exp(m2);
    if (lane == 0) { if (ROLE == 2) red_max_shared(sb + S_EV, m1); red_max_shared(sb + S_EO, m2); }
}
template <bool ATT>
__device__ __forceinline__ void chain_role(const Params& P, const uint32_t sb, const int cta, const int warp, const int lane, const uint32_t (*wr)[4]) {
    constexpr int NR = ATT ? NRA : NRB, PRE = ATT ? PREA : PREB;
    const int h = cta / 3, ROLE = cta - h * 3;
    uint32_t l8 = opq(sb + lane * 8, lane);
    const uint8_t* persu = (const uint8_t*)((ROLE == 1 ? g_km : g_vmt) + h * 512) - (sb >> 1);
    auto persist = [&](int s, int tile, uint32_t r0, uint32_t r1) {
        uint32_t* pp = (uint32_t*)(persu + s * 65536 + (ROLE == 1 ? (tile >> 1) * 512 + (tile & 1) * 128 : tile * 256) + (l8 >> 1));
        pp[0] = r0; pp[ROLE == 1 ? 64 : 32] = r1;
    };
    const uint32_t rk0 = (h & 1) * 3, rd1 = __shfl_sync(0xffffffffu, mapa(sb, rk0 + (ROLE + 1) % 3) - sb, 0), rd2 = __shfl_sync(0xffffffffu, mapa(sb, rk0 + (ROLE + 2) % 3) - sb, 0);
    const uint32_t xo = (ROLE == 2 ? S_XV : S_X + ROLE * 2048) + warp * 256;
    const bool full = w2_full(ROLE, warp);
    const int blk = w2_block(ROLE, warp);
    const uint32_t om = blk * 2048, os = xg_side(blk);
    const uint32_t w1o = sb + w1_base(warp), w2o = sb + w2_base(warp);
    if (lane == 0) mbar_arrive(sb + B_READY);
#pragma unroll 1
    for (int s = 0;; s++) {
        l8 += s & P.zero;
        uint32_t r0, r1;
        {
            uint32_t v[4][4], as[(8 - NR) * 8][4], w1a[4];
            float acc[8][4];
            const uint32_t pst = sb + S_P1 + (l8 - sb) * 16 + ((warp * 16) ^ ((l8 & 56) * 2));
#pragma unroll
            for (int i = 0; i < 4; i++) w1a[i] = w1o + (FRAG1((l8 - sb) >> 3) ^ TILE_X(i));
            auto preload = [&]() { static_for<0, PRE>([&](auto I) { load_w1<I.value, NR>(as[I.value], w1a); }); };
#pragma unroll 1
            while (true) {
                uint32_t x[4];
                if (!(PLATE >> ATT & 1)) preload();
                const uint32_t lm = opq(l8 - sb, (l8 - sb) >> 3);
                const uint8_t* pm = P.xb + xg_buf(s) + warp * 8192 + xg_lane(lm >> 3);
                const uint8_t* ps = P.xb + xg_buf(s) + XG_SIDE + warp * 2048 + (lm >> 1);
                pin_ptr(pm); pin_ptr(ps);
                mbar_wait(sb + B_RELM, s & 1);
                if (ATT ? ADELAY : BDELAY) wait_clocks(ATT ? ADELAY : BDELAY);
#pragma unroll
                for (int b = 0; b < 4; b++) { ld_relaxed4(v[b], pm + b * 2048); ld_relaxed1n(x[b], ps + (b >> 1) * 1024 + (b & 1) * 256); }
                if (PLATE >> ATT & 1) { preload(); if (PLATE >> (ATT + 2) & 1) sched_fence(); }
                project<NR, PRE, ATT ? FENCEA : FENCEB, 0, PROG>(acc, ROLE == 2, wr, as, v, x, w1a, pst, P.zero);
                const uint32_t bad = xor_or(x[0], x[1], FULL) | xor_or(x[2], x[3], FULL);
                if (tags_ok(bad, 0xffffffffu)) break;
            }
            project<NR, PRE, ATT ? FENCEA : FENCEB, PROG, 64>(acc, ROLE == 2, wr, as, v, nullptr, w1a, pst, 0);
            const uint32_t isc = lds32(sb + S_ISC + (s & 1) * 4);
            const uint32_t lq = l8 + ((s >> 3) & P.zero), e1 = s == 63 ? 0 : rd1, e2 = s == 63 ? 0 : rd2;
            uint32_t x[4][4], sel[8], xd[6] = {l8 + xo, l8 + xo + e1, l8 + xo + e2, sb + B_X + e1, sb + B_X + e2, sb + S_P1 + warp * 2048 + (lq & 64) * 16 + (lq & 128) + (lq & 56) * 2};
#pragma unroll
            for (int i = 0; i < 8; i++) sel[i] = (lq & 224) == i * 32 ? 0x3F803F80u : 0u;
            pin<6>(xd); pin<8>(sel);
            if (RFENCE) sched_fence();
            bar_sync(1, 256);
#pragma unroll
            for (int i = 0; i < 4; i++) ldsm4t(x[i], xd[5] + i * 256);
            if (!ATT && l8 == sb + (warp - 3) * 1024) mbar_arrive(sb + B_P1);
            uint32_t em = warp_exp(amax(amax4(amax(amax(v[0][0], v[0][1]), amax(v[0][2], v[0][3])), v[1]), amax4(amax(amax(v[2][0], v[2][1]), amax(v[2][2], v[2][3])), v[3])));
            if (EFENCE2) sched_fence();
            reduce8(x, sel, bf_hi(isc), r0, r1);
            st_async2(xd[1], r0, r1, xd[3]);
            st_async2(xd[2], r0, r1, xd[4]);
            sts64(xd[0], r0, r1);
            if (s == 63) { persist(s, warp, r0, r1); break; }
            if (l8 == sb) sts32(sb + S_EM + warp * 4, em + (isc >> 23));
            __syncwarp();
            if (l8 == sb) mbar_arrive(sb + B_X);
        }
        uint32_t w[40][4], w2a[2], odd;
        const uint8_t *po, *pd;
        auto wo_addr = [&]() {
            const uint32_t lo = (l8 + ((s >> 2) & P.zero) - sb) >> 3;
            w2a[0] = w2o + FRAG2(lo); w2a[1] = w2o + (FRAG2(lo) ^ 32);
            po = P.xb + xg_buf(s + 1) + om + xg_lane(lo);
            pd = P.xb + xg_buf(s + 1) + os + lo * 4;
            odd = lo & 4;
            pin_ptr(po); pin_ptr(pd); pin<2>(w2a); pin<1>(&odd);
        };
        uint32_t oa = l8 * 2 + (S_OX - sb);
        if constexpr (ATT) {
            const uint32_t ln = (l8 + ((s >> 4) & P.zero) - sb) >> 3;
            const uint32_t va = sb + S_KV + 8192 + ((warp >> 1) & 1) * 4096 + ((ln & 7) + (ln >> 4) * 8) * 128 + ((((warp & 1) * 4 + ((ln >> 3) & 1)) ^ (ln & 7)) << 4);
            const uint32_t ka = sb + S_KV + (warp & 1) * 2048 + (ln & 15) * 128 + (((ln >> 4) ^ (ln & 7)) << 4);
            uint32_t ad[5] = {sb + S_SX + (ln & 3) * (8 * SROW) + (ln >> 2) * 4 + (warp < 6 ? (warp - 4) * 64 : 128 + (warp - 6) * 32), l8 + S_XV + (warp - 4) * 512,
                              l8 + S_SX + (ln >> 2) * (4 * SROW - 32), oa + (warp - 4) * 512, sb + S_ISC + (~s & 1) * 4};
            if constexpr (AB) { wo_addr(); pin<1>(&oa); }
            pin<5>(ad);
            const uint32_t sa = ad[0], sr = ad[2];
            uint32_t vf[4][4], vm[2][2], q[8][2];
            float S[8][4];
#pragma unroll
            for (int n = 0; n < 8; n++) { S[n][0] = S[n][1] = S[n][2] = S[n][3] = 0.f; }
            mbar_wait(sb + B_KVFULL, s & 1);
            if (warp < 6) {
                uint32_t kf[8][4];
#pragma unroll
                for (int k = 0; k < 8; k++) ldsm4(kf[k], (ka ^ ((k & 3) << 5)) + (k >> 2) * 4096);
#pragma unroll
                for (int i = 0; i < 4; i++) ldsm4t(vf[i], (va ^ ((i & 1) << 5)) + (i >> 1) * 2048);
                mbar_wait(sb + B_X, s & 1);
#pragma unroll
                for (int k = 0; k < 8; k++) lds64(q[k], l8 + S_X + k * 256);
#pragma unroll
                for (int k = 0; k < 8; k++) mma16816(S[k], kf[k][0], kf[k][1], kf[k][2], kf[k][3], q[k][0], q[k][1]);
#pragma unroll
                for (int k = 0; k < 4; k++) { S[k][0] = S[2 * k][0] + S[2 * k + 1][0]; S[k][1] = S[2 * k][1] + S[2 * k + 1][1]; S[k][2] = S[2 * k][2] + S[2 * k + 1][2]; S[k][3] = S[2 * k][3] + S[2 * k + 1][3]; }
                sts32(sa, __float_as_uint((S[0][0] + S[1][0]) + (S[2][0] + S[3][0])));
                sts32(sa + 4 * SROW, __float_as_uint((S[0][1] + S[1][1]) + (S[2][1] + S[3][1])));
                sts32(sa + 32, __float_as_uint((S[0][2] + S[1][2]) + (S[2][2] + S[3][2])));
                sts32(sa + 4 * SROW + 32, __float_as_uint((S[0][3] + S[1][3]) + (S[2][3] + S[3][3])));
            } else {
#pragma unroll
                for (int i = 0; i < 4; i++) ldsm4t(vf[i], (va ^ ((i & 1) << 5)) + (i >> 1) * 2048);
                uint32_t xa = l8 + S_X + (warp - 6) * 1024;
                pin<1>(&xa);
                mbar_wait(sb + B_X, s & 1);
#pragma unroll
                for (int k = 0; k < 8; k++) lds64(q[k], xa + (k >> 2) * 2048 + (k & 3) * 256);
#pragma unroll
                for (int k = 0; k < 4; k++) mma16816(S[k], q[4 + (k & 2)][0], q[4 + (k & 2)][1], q[5 + (k & 2)][0], q[5 + (k & 2)][1], q[k][0], q[k][1]);
                sts32(sa, __float_as_uint((S[0][0] + S[2][0]) + (S[1][2] + S[3][2])));
                sts32(sa + 4 * SROW, __float_as_uint((S[0][1] + S[2][1]) + (S[1][3] + S[3][3])));
            }
            lds64(vm[0], ad[1]); lds64(vm[1], ad[1] + 256);
            bar_sync(2, 160);
            const float cs = 0.08838834764831845f * 1.4426950408889634f;
            float E[6][2];
#pragma unroll
            for (int i = 0; i < 6; i++) lds64f(E[(i + 4) % 6], sr + ((i + 4) % 6) * 32);
            const uint32_t isn = lds32(ad[4]);
            E[4][0] += E[5][0]; E[4][1] += E[5][1];
            float m = fmaxf(fmaxf(fmaxf(fmaxf(E[0][0], E[0][1]), fmaxf(E[1][0], E[1][1])), fmaxf(fmaxf(E[2][0], E[2][1]), fmaxf(E[3][0], E[3][1]))), fmaxf(E[4][0], E[4][1]));
            m = fmaxf(m, __shfl_xor_sync(0xffffffffu, m, 1));
            m = fmaxf(m, __shfl_xor_sync(0xffffffffu, m, 2));
            m *= cs;
            if constexpr (AB) static_for<0, PRE3>([&](auto I) { load_w2<I.value>(w[I.value], w2a); });
            uint32_t pa[5];
#pragma unroll
            for (int i = 0; i < 5; i++) { const int k = (i + 4) % 5; E[k][0] = ex2(fmaf(E[k][0], cs, -m)); E[k][1] = ex2(fmaf(E[k][1], cs, -m)); pa[k] = pack2(E[k][0], E[k][1]); }
            if (EFENCE) sched_fence();
            float O[2][4], Z[4];
#pragma unroll
            for (int i = 0; i < 4; i++) { O[0][i] = O[1][i] = Z[i] = 0.f; }
            mma1688(Z, isn, isn, pa[4]);
            mma1688(O[0], vm[0][0], vm[0][1], pa[4]);
            mma1688(O[1], vm[1][0], vm[1][1], pa[4]);
#pragma unroll
            for (int k = 0; k < 2; k++) {
                mma16816(Z, isn, isn, isn, isn, pa[2 * k], pa[2 * k + 1]);
#pragma unroll
                for (int i = 0; i < 2; i++) mma16816(O[i], vf[2 * k + i][0], vf[2 * k + i][1], vf[2 * k + i][2], vf[2 * k + i][3], pa[2 * k], pa[2 * k + 1]);
            }
            const float i0 = rcp(Z[0]), i1 = rcp(Z[1]);
            stsm4t(ad[3], pack2(O[0][0] * i0, O[0][1] * i1), pack2(O[0][2] * i0, O[0][3] * i1), pack2(O[1][0] * i0, O[1][1] * i1), pack2(O[1][2] * i0, O[1][3] * i1));
            if constexpr (AB) wo_blocks<1, RESA, PRE3, OFENCE / 2>(w, wr + NR * 8, oa, w2a, po, pd, odd);
            else bar_arrive(3, 256);
            if (ROLE != 0) persist(s, warp, r0, r1);
            if (warp == 7 && l8 == sb) mbar_expect(sb + B_X, 4096);
        } else {
            if (ROLE != 0) persist(s, warp, r0, r1);
            wo_addr(); pin<1>(&oa);
            static_for<0, PRE2A>([&](auto I) { load_w2<I.value>(w[I.value], w2a); });
            mbar_wait(sb + B_X, s & 1);
            if (warp == 0) {
                uint32_t sc[2];
                lds64(sc, sb + S_SC);
                const int em = __reduce_max_sync(0xffffffffu, lds32(sb + S_EM + ((l8 >> 1) & 28)));
                if (l8 == sb) sts32(sb + S_ISC + (~s & 1) * 4, min(max(em - 127, (int)sc[1]) + (int)sc[0], 253) * 0x800080u);
                bar_arrive(2, 160);
            }
            wait_clocks(XDELAY - (warp == 0) * 100);
            constexpr int PRE1 = (BB - 1) * 16 - (5 - NRB) * 8 < PRE2 ? (BB - 1) * 16 - (5 - NRB) * 8 : PRE2;
            static_for<PRE2A, PRE1>([&](auto I) { load_w2<I.value>(w[I.value], w2a); });
            if (full) {
                static_for<PRE1, PRE2>([&](auto I) { load_w2<I.value>(w[I.value], w2a); });
                wo_blocks<BB, RESB, PRE2, FENCE2 * 2 + OFENCE % 2>(w, wr + NR * 8, oa, w2a, po, pd, odd);
            } else wo_blocks<BB - 1, RESB1, PRE1, FENCE2 * 2 + OFENCE % 2>(w, wr + NR * 8, oa, w2a, po, pd, odd);
        }
        if (l8 == sb) { sts32(sb + S_TO + warp * 4, gtime()); mbar_arrive(sb + B_RED); }
        if (HOLD && !(PLATE >> ATT & 1)) mbar_wait(sb + B_RED, s & 1);
        if (ROLE != 0 && (s & 3) == 3 && l8 == sb) mbar_arrive(sb + B_PERS);
        if (ROLE == 0 && s == 62) return;
    }
    __syncwarp();
    if (l8 == sb) mbar_arrive(sb + B_PERS);
}
struct Pipe { uint32_t stage, phase; };
struct Cons {
    uint32_t sb, rel;
    int wg, wq, lane, rank, pair;
    uint32_t nst;
    Pipe p;
};
__device__ __forceinline__ void pipe_next(Pipe& p) { p.stage = (p.stage + 1) & (NSTAGE - 1); p.phase ^= (p.stage == 0); }
__device__ __forceinline__ void release(const Cons& c, uint32_t stage) { if (c.lane < 2) mbar_arrive_cluster(c.rel + stage * 8); }
__device__ __forceinline__ void wait_full(const Cons& c) { mbar_wait(c.sb + B_FULL + c.p.stage * 8, c.p.phase); }

enum { PEND_NONE = 0, PEND_KVO = 1, PEND_HT = 2, PEND_OUT = 3, PEND_OUTA = 4 };
struct Pend { uint32_t pk[64]; int kind, row, col, cnt; };

__device__ __forceinline__ void staging_wait(const Cons& c) { if (c.nst) mbar_wait(c.sb + B_SFREE + c.wg * 8, (c.nst - 1) & 1); }
__device__ __forceinline__ void staging_post(Cons& c, int kind, int row, int col, int cnt) {
    __syncwarp();
    if (c.lane == 0) {
        if (c.wq == 0) { const uint32_t x[4] = {(uint32_t)kind, (uint32_t)row, (uint32_t)col, (uint32_t)cnt}; sts128(c.sb + S_DESC + c.wg * 16, x); }
        mbar_arrive(c.sb + B_SFULL + c.wg * 8);
    }
    c.nst++;
}
__device__ __forceinline__ void drain(const Params& P, Cons& c, Pend& d) {
    const uint32_t* pk = d.pk;
    const bool ht = d.kind == PEND_HT;
    const int hi = (c.lane >> 3) & 1;
    const uint32_t stg = c.sb + S_STG + c.wg * 16384, base = stg + ((ht ? hi * 32 + c.wq * 8 : c.wq * 16 + hi * 8) + (c.lane & 7)) * 128;
    staging_wait(c);
#pragma unroll
    for (int j = 0; j < 8; j++) {
        const int ch = (j & 3) * 2 + (c.lane >> 4);
        stsm4(base + (j >> 2) * 8192 + ((ch ^ (c.lane & 7)) << 4), pk[j * 4], pk[j * 4 + 1], pk[j * 4 + 2], pk[j * 4 + 3]);
    }
    if (d.kind >= PEND_OUT) {
        const uint32_t rd = stg + (c.lane >> 4) * 8192 + c.wq * 2048 + (c.lane & 15) * 8;
        const int s1 = d.kind == PEND_OUT ? 2 : 64, s2 = d.kind == PEND_OUT ? 8 : 2;
        const float* o = P.out + (size_t)(d.row + c.wq * 2 * s2) * 2048 + d.col + c.lane * 4;
        __syncwarp();
#pragma unroll
        for (int r = 0; r < 16; r++) {
            uint32_t u[2];
            lds64(u, (rd ^ ((r & 7) << 4)) + r * 128);
            st_stream4(o + ((r & 1) + (r >> 1 & 3) * s1 + (r >> 3) * s2) * 2048, bf_lo(u[0]), bf_hi(u[0]), bf_lo(u[1]), bf_hi(u[1]));
        }
        __syncwarp();
    } else {
        fence_async_smem();
        staging_post(c, d.kind, d.row, d.col, (d.col & 128) ? d.cnt : -1);
    }
    if (d.col & 128) d.kind = PEND_NONE;
    d.col += 128;
#pragma unroll
    for (int i = 0; i < 32; i++) d.pk[i] = d.pk[32 + i];
}

constexpr int S_STG2 = 8 * 20480, PEND_BOTH = 8;
__device__ __forceinline__ void drain_both(Cons& c, const Pend& d) {
    const uint32_t base = c.sb + c.wg * 16384 + (c.wq * 16 + ((c.lane >> 3) & 1) * 8 + (c.lane & 7)) * 128;
#pragma unroll
    for (int j = 0; j < 16; j++)
        stsm4(base + (j < 8 ? S_STG : S_STG2) + (j >> 2 & 1) * 8192 + ((((j & 3) * 2 + (c.lane >> 4)) ^ (c.lane & 7)) << 4), d.pk[j * 4], d.pk[j * 4 + 1], d.pk[j * 4 + 2], d.pk[j * 4 + 3]);
    fence_async_smem();
    staging_post(c, PEND_KVO | PEND_BOTH, d.row, d.col, d.cnt);
}

__device__ __forceinline__ void store_warp(const Params& P, uint32_t sb, int wg, int cta) {
    if (cta < 128) {
        for (int i = 0; i < P.xd; i++) __nanosleep(1000);
        const uint32_t e1 = get_epoch(sb) + 1;
        const uint4* x = (const uint4*)P.Bx + (cta * 2 + wg) * 1024 + (threadIdx.x & 31);
        uint32_t m = 0;
#pragma unroll 4
        for (int i = 0; i < 32; i++) { const uint4 u = __ldg(x + i * 32); m = amax(amax(m, amax(u.x, u.y)), amax(u.z, u.w)); }
        m = warp_exp(m);
        if (elect_one()) { atomicMax(&g_cnt(C_XMAX), e1 << 8 | m); red_release(&g_cnt(C_XCNT)); }
        __syncwarp();
    }
    const uint32_t stg = sb + S_STG + wg * 16384;
#pragma unroll 1
    for (uint32_t n = 0;; n++) {
        mbar_wait(sb + B_SFULL + wg * 8, n & 1);
        uint32_t x[4];
        lds128(x, sb + S_DESC + wg * 16);
#pragma unroll
        for (int i = 0; i < 4; i++) x[i] = __shfl_sync(0xffffffffu, x[i], 0);
        if (x[0] == PEND_NONE) break;
        const bool ht = x[0] == PEND_HT;
        const CUtensorMap* m = &P.tm[ht ? M_HTS : M_KVO];
        const uint64_t pol = P.pol[ht ? 2 : x[1] >= 4096 ? 1 : (x[1] & 2047) < 1536 ? 0 : 10];
        if (elect_one()) {
#pragma unroll
            for (int i = 0; i < 4; i++) tma_store2d(m, x[2] + (i >> 1) * 64, x[1] + (i & 1) * (ht ? 1024 : 32), stg + i * 4096, pol);
            if (x[0] & PEND_BOTH) {
#pragma unroll 1
                for (int i = 0; i < 4; i++) tma_store2d(m, x[2] + 128 + (i >> 1) * 64, x[1] + (i & 1) * 32, stg + (S_STG2 - S_STG) + i * 4096, pol);
            }
            bulk_commit();
            bulk_wait_read();
            mbar_arrive(sb + B_SFREE + wg * 8);
            if ((int)x[3] >= 0) { bulk_wait_all(); fence_async(); red_relaxed(&g_cnt(x[3])); }
        }
        __syncwarp();
    }
}

template <int TA, int TB, bool FIRST>
__device__ __forceinline__ void issue_ktile(float* acc, const Cons& c) {
    const uint32_t a = c.sb + c.p.stage * STAGE + c.wg * 8192, b = c.sb + c.p.stage * STAGE + 16384;
    const uint64_t da = mkdesc(a, TA ? 8192 : 16, 1024, 1), db = mkdesc(b, TB ? 8192 : 16, 1024, 1);
    wg_fence();
#pragma unroll
    for (int k = 0; k < 4; k++) {
        if (FIRST && k == 0) wgmma_ss256_first<TA, TB>(acc, da, db);
        else wgmma_ss256<TA, TB>(acc, da + (TA ? 128 : 2) * k, db + (TB ? 128 : 2) * k);
    }
    wg_commit();
}
template <bool KVONLY, bool FIRST>
__device__ __forceinline__ void issue_any(float* acc, const Cons& c, int type) {
    wait_full(c);
    if (!KVONLY && type == T_A1) issue_ktile<0, 0, FIRST>(acc, c);
    else if (!KVONLY && type == T_A2) issue_ktile<1, 0, FIRST>(acc, c);
    else issue_ktile<0, 1, FIRST>(acc, c);
}
template <bool KVONLY = false>
__device__ __forceinline__ void mainloop(float* acc, const Params& P, Cons& c, Pend& d, int type, int nk) {
    issue_any<KVONLY, true>(acc, c, type);
    uint32_t prev = c.p.stage;
    pipe_next(c.p);
#pragma unroll 1
    for (int kt = 1; kt < nk; kt++) {
        if (!KVONLY && d.kind != PEND_NONE && kt != 2) drain(P, c, d);
        issue_any<KVONLY, false>(acc, c, type);
        wg_wait<1>();
        release(c, prev);
        prev = c.p.stage;
        pipe_next(c.p);
    }
    d.kind = PEND_NONE;
    wg_wait<0>();
    pin<128>(acc);
    release(c, prev);
}
__device__ __forceinline__ void pack_half(uint32_t* pk, const float* a) {
#pragma unroll
    for (int i = 0; i < 32; i++) pk[i] = pack2(a[2 * i], a[2 * i + 1]);
}

__device__ __forceinline__ void epi_kv(const float* acc, const Cons& c, Pend& d, int mb, int nb) {
    pack_half(d.pk, acc); pack_half(d.pk + 32, acc + 64);
    d.kind = PEND_KVO; d.row = (nb >> 4) * 2048 + mb * 256 + c.rank * 128 + c.wg * 64; d.col = (nb & 15) * 256; d.cnt = C_KV + mb;
}

__device__ __forceinline__ void qa_scores(float* S, float* Sm, const uint32_t* q, Cons& c) {
    wait_full(c);
    const uint32_t st = c.sb + c.p.stage * STAGE;
    const uint64_t dk = mkdesc(st + c.wg * 8192, 16, 1024, 1), dm = mkdesc(st + 32768 + c.wg * 4096, 128, 2048, 0);
    wg_fence();
#pragma unroll
    for (int i = 0; i < 8; i++) wgmma_rs64<0>(S, q + i * 4, dk + (i >> 2) * 1024 + (i & 3) * 2, i != 0);
#pragma unroll
    for (int i = 0; i < 8; i++) wgmma_rs16<0>(Sm, q + i * 4, dm + i * 16, i != 0);
    wg_commit();
    pipe_next(c.p);
}
__device__ __forceinline__ void qa_softmax(uint32_t (*pa)[4], const float* S, const float* Sm, const Cons& c) {
    const int t = c.lane & 3, i0 = (c.wq & 1) * 16 + (c.lane >> 2) - 2 * t;
    const bool sg = c.wq >= 2;
    const float cs = 0.08838834764831845f * 1.4426950408889634f;
    float x[2][10];
#pragma unroll
    for (int r = 0; r < 2; r++) {
#pragma unroll
        for (int j = 0; j < 4; j++)
#pragma unroll
            for (int e = 0; e < 2; e++) {
                const float v = sg ? S[16 + j * 4 + r * 2 + e] : S[j * 4 + r * 2 + e];
                x[r][j * 2 + e] = (j * 8 + e - r * 8 > i0) ? -1e9f / 0.08838834764831845f : v;
            }
        x[r][8] = sg ? Sm[4 + r * 2] : Sm[r * 2];
        x[r][9] = sg ? Sm[5 + r * 2] : Sm[1 + r * 2];
        float m = fmaxf(fmaxf(fmaxf(fmaxf(x[r][0], x[r][1]), fmaxf(x[r][2], x[r][3])), fmaxf(fmaxf(x[r][4], x[r][5]), fmaxf(x[r][6], x[r][7]))), fmaxf(x[r][8], x[r][9]));
        m = fmaxf(m, __shfl_xor_sync(0xffffffffu, m, 1));
        m = fmaxf(m, __shfl_xor_sync(0xffffffffu, m, 2));
        m *= -cs;
#pragma unroll
        for (int i = 0; i < 10; i++) x[r][i] = ex2(fmaf(x[r][i], cs, m));
        float sum = (((x[r][0] + x[r][1]) + (x[r][2] + x[r][3])) + ((x[r][4] + x[r][5]) + (x[r][6] + x[r][7]))) + (x[r][8] + x[r][9]);
        sum += __shfl_xor_sync(0xffffffffu, sum, 1);
        sum += __shfl_xor_sync(0xffffffffu, sum, 2);
        const float inv = rcp(sum);
#pragma unroll
        for (int i = 0; i < 10; i++) x[r][i] *= inv;
    }
#pragma unroll
    for (int ks = 0; ks < 2; ks++)
#pragma unroll
        for (int i = 0; i < 4; i++) {
            const uint32_t p = pack2(x[i & 1][ks * 4 + (i >> 1) * 2], x[i & 1][ks * 4 + (i >> 1) * 2 + 1]);
            pa[ks][i] = sg ? 0u : p;
            pa[2 + ks][i] = sg ? p : 0u;
        }
#pragma unroll
    for (int r = 0; r < 2; r++) {
        const uint32_t p = pack2(x[r][8], x[r][9]);
        pa[4][r] = sg ? 0u : p;
        pa[4][2 + r] = sg ? p : 0u;
    }
}
__device__ __forceinline__ void qa_values(float* O, uint32_t (*pa)[4], Cons& c) {
    wait_full(c);
    const uint32_t st = c.sb + c.p.stage * STAGE;
    const uint64_t dv = mkdesc(st + c.wg * 8192, 16384, 1024, 1), dm = mkdesc(st + 32768 + c.wg * 4096, 2048, 128, 0);
    pin<20>(&pa[0][0]);
    wg_fence();
#pragma unroll
    for (int ks = 0; ks < 4; ks++) wgmma_rs128<1>(O, pa[ks], dv + ks * 128, ks != 0);
    wgmma_rs128<0>(O, pa[4], dm, 1);
    wg_commit();
    pipe_next(c.p);
}
__device__ __forceinline__ void epi_qa(const float* acc, Cons& c, Pend& d, int mb, int nb) {
    uint32_t q[64], pa[2][5][4];
    float S0[32] = {}, M0[8] = {}, S1[32] = {}, M1[8] = {}, O0[64] = {}, O1[64] = {};
    const uint32_t k0 = c.p.stage;
    pack_half(q, acc);
    pin<32>(q); pin<32>(S0); pin<8>(M0);
    qa_scores(S0, M0, q, c);
    pack_half(q + 32, acc + 64);
    pin<32>(q + 32); pin<32>(S1); pin<8>(M1);
    qa_scores(S1, M1, q + 32, c);
    wg_wait<1>();
    pin<32>(S0); pin<8>(M0);
    release(c, k0);
    qa_softmax(pa[0], S0, M0, c);
    wg_wait<0>();
    pin<32>(S1); pin<8>(M1); pin<64>(q);
    release(c, (k0 + 1) & (NSTAGE - 1));
    pin<64>(O0);
    qa_values(O0, pa[0], c);
    qa_softmax(pa[1], S1, M1, c);
    pin<64>(O1);
    qa_values(O1, pa[1], c);
    wg_wait<1>();
    pin<64>(O0); pin<20>(&pa[0][0][0]);
    release(c, (k0 + 2) & (NSTAGE - 1));
    pack_half(d.pk, O0);
    wg_wait<0>();
    pin<64>(O1); pin<20>(&pa[1][0][0]);
    release(c, (k0 + 3) & (NSTAGE - 1));
    pack_half(d.pk + 32, O1);
    d.kind = PEND_KVO; d.row = 4096 + mb * 256 + c.rank * 128 + c.wg * 64; d.col = nb * 256; d.cnt = C_O + mb * 16 + nb;
}

__device__ __forceinline__ void epi_op(const float* acc, const Cons& c, Pend& d, int mb, int nb) {
    pack_half(d.pk, acc); pack_half(d.pk + 32, acc + 64);
    d.kind = PEND_OUT; d.row = mb * 256 + c.rank * 128 + c.wg * 64; d.col = 1024 + nb * 256;
}

__device__ __forceinline__ void epi_a2(float* acc, const Params& P, Cons& c, Pend& d, int mb, int nb) {
    const int g = c.lane >> 2, t = c.lane & 3;
#pragma unroll
    for (int i = 0; i < 32; i++) d.pk[32 + i] = 0;
#pragma unroll 1
    for (int hf = P.zero; hf < 2; hf++) {
        wait_full(c);
        const uint32_t st = c.sb + c.p.stage * STAGE, xa = st + (c.wg * 64 + c.wq * 16 + g) * 128 + t * 4 + (g << 4), da = st + 32768 + t * 4;
#pragma unroll
        for (int j = 0; j < 16; j++) {
            const float* a = acc + j * 4;
            const uint32_t ad = (xa ^ ((j & 7) << 4)) + (j >> 3) * 16384;
            const uint32_t dv = lds32(da + j * 16), u0 = mul_bf2(lds32(ad), dv), u1 = mul_bf2(lds32(ad + 1024), dv);
            d.pk[j * 2] = d.pk[32 + j * 2]; d.pk[j * 2 + 1] = d.pk[33 + j * 2];
            d.pk[32 + j * 2] = pack2(a[0] + bf_lo(u0), a[1] + bf_hi(u0));
            d.pk[33 + j * 2] = pack2(a[2] + bf_lo(u1), a[3] + bf_hi(u1));
        }
        __syncwarp();
        release(c, c.p.stage);
        pipe_next(c.p);
#pragma unroll
        for (int i = 0; i < 64; i++) acc[i] = acc[64 + i];
    }
    d.kind = PEND_OUTA; d.row = mb * 256 + c.rank * 32 + c.wg * 16; d.col = nb * 256;
}

__device__ __forceinline__ float2 cmul(float2 a, float2 b) { return make_float2(fmaf(a.x, b.x, -a.y * b.y), fmaf(a.x, b.y, a.y * b.x)); }
__device__ __forceinline__ float2 cfma(float2 a, float2 b, float2 u) { return make_float2(fmaf(a.x, b.x, fmaf(-a.y, b.y, u.x)), fmaf(a.x, b.y, fmaf(a.y, b.x, u.y))); }
__device__ __forceinline__ float4 ssm_coef(float lre, float lim, float logdt) {
    const float dt = __bfloat162float(__float2bfloat16(expf(logdt)));
    const float ea = expf(dt * lre);
    float sn, cn;
    sincosf(dt * lim, &sn, &cn);
    const float br = ea * cn, bi = ea * sn, nr = br - 1.f;
    const bool sw = fabsf(lre) < fabsf(lim);
    const float big = sw ? lim : lre, r = __fdividef(sw ? lre : lim, big), inv = __fdividef(1.f, fmaf(sw ? lre : lim, r, big));
    const float cr = (sw ? fmaf(nr, r, bi) : fmaf(bi, r, nr)) * inv, ci = (sw ? fmaf(bi, r, -nr) : fmaf(-nr, r, bi)) * inv;
    return make_float4(br, bi, cr, ci);
}
__device__ __forceinline__ void epi_a1(const float* acc, const Params& P, const Cons& c, Pend& d, int mb, int nb) {
    const uint32_t atag = (get_epoch(c.sb) + 1) & 1;
    const int t = c.lane & 3;
    const int p = nb * 128 + c.rank * 64 + c.wg * 32 + c.wq * 8 + (c.lane >> 2);
    const float4 cf = __ldcg(&g_coef[p]);
    const float2 lam = make_float2(cf.x, P.swap_ri ? -cf.y : cf.y);
    const float a0 = P.swap_ri ? -2.f * cf.w : 2.f * cf.z, a1 = P.swap_ri ? 2.f * cf.z : -2.f * cf.w;
    const float b0 = P.swap_ri ? -2.f * cf.z : -2.f * cf.w, b1 = P.swap_ri ? -2.f * cf.w : -2.f * cf.z;
    float2 h = make_float2(0.f, 0.f);
#pragma unroll
    for (int round = 0; round < 2; round++) {
#pragma unroll
        for (int j = 0; j < 32; j++) {
            h = cfma(lam, h, make_float2(acc[j * 4], acc[j * 4 + 2]));
            const float r0 = fmaf(a0, h.x, a1 * h.y), m0 = fmaf(b0, h.x, b1 * h.y);
            h = cfma(lam, h, make_float2(acc[j * 4 + 1], acc[j * 4 + 3]));
            d.pk[j * 2] = pack2(r0, fmaf(a0, h.x, a1 * h.y));
            d.pk[j * 2 + 1] = pack2(m0, fmaf(b0, h.x, b1 * h.y));
        }
        if (round) break;
        float2 l64 = lam;
#pragma unroll
        for (int i = 0; i < 6; i++) l64 = cmul(l64, l64);
        const float2 l128 = cmul(l64, l64), l256 = cmul(l128, l128);
        float2 o = make_float2(__shfl_up_sync(0xffffffffu, h.x, 1), __shfl_up_sync(0xffffffffu, h.y, 1));
        if (t >= 1) h = cfma(l64, o, h);
        o = make_float2(__shfl_up_sync(0xffffffffu, h.x, 2), __shfl_up_sync(0xffffffffu, h.y, 2));
        if (t >= 2) h = cfma(l128, o, h);
        if (t == 3) st_relaxed2(&g_agg[mb * 1024 + p], (__float_as_uint(h.x) & ~1u) | atag, __float_as_uint(h.y));
        h = make_float2(__shfl_up_sync(0xffffffffu, h.x, 1), __shfl_up_sync(0xffffffffu, h.y, 1));
        if (t == 0) h = make_float2(0.f, 0.f);
        uint32_t ax[7], ay[7];
        while (true) {
            uint32_t bad = 0;
#pragma unroll
            for (int j = 0; j < 7; j++) { ax[j] = atag; ay[j] = 0; ld_relaxed2_if(ax[j], ay[j], &g_agg[j * 1024 + p], j < mb); }
#pragma unroll
            for (int j = 0; j < 7; j++) bad |= ax[j] ^ atag;
            if (tags_ok(bad)) break;
            __nanosleep(2 * POLLNS);
        }
        float2 carry = make_float2(0.f, 0.f);
#pragma unroll
        for (int j = 0; j < 7; j++) if (j < mb) carry = cfma(l256, carry, make_float2(__uint_as_float(ax[j]), __uint_as_float(ay[j])));
        float2 w = (t & 1) ? l64 : make_float2(1.f, 0.f);
        if (t & 2) w = cmul(w, l128);
        h = cfma(w, carry, h);
    }
    d.kind = PEND_HT; d.row = nb * 128 + c.rank * 64 + c.wg * 32; d.col = mb * 256; d.cnt = C_HT + mb * 16 + nb;
}

__device__ __forceinline__ uint32_t fresh_tid() { uint32_t t; asm volatile("mov.u32 %0, %%tid.x;" : "=r"(t)); return t; }
__device__ __forceinline__ uint32_t acquire_stage(uint32_t sb, Pipe& p, uint32_t bytes) {
    mbar_wait(sb + B_EMPTY + p.stage * 8, p.phase ^ 1);
    mbar_expect_e(sb + B_FULL + p.stage * 8, bytes);
    return p.stage;
}
__device__ __forceinline__ void producer(const Params& P, const uint32_t sb, const int cta) {
    Pipe p = {0, 0};
    uint32_t resume = 1;
    const int rank = cta & 1;
    const uint16_t both = 3 << (__shfl_sync(0xffffffffu, cluster_rank(), 0) & ~1u);
    for (int it = ITEM_OFF(cta >> 1), item = 0; !(item & LAST); it++) {
        item = ITEM(it);
        const int type = (item >> 8) & 7, mb = (item >> 5) & 7, nb = item & 31, half = item / HALF & 1, hw = item >> 13 & 1;
        const uint32_t epoch = type ? get_epoch(sb) : 0, e1 = epoch + 1;
        if (type == T_CHAIN) {
            const int h = cta / 3, role = cta - h * 3;
#pragma unroll 1
            for (int w = 0; w < 8; w++) {
                mbar_wait(sb + B_EMPTY + (w * 20480 + 20479) / STAGE * 8, 1);
                chain_load(P, sb, cta, w, threadIdx.x & 31, 0);
            }
            uint32_t* flag = &g_cnt(C_FLAG + (role == 2 ? 32 : 0) + h);
            if (role) { wait_count(&g_cnt(C_KV), e1 * 128); fence_async(); }
#pragma unroll 1
            for (int s = 0; s < 63 && role != 0; s++) {
                {
                    mbar_wait(sb + B_GO, s & 1);
                    tma3d_mc_e(sb + S_KV + (role - 1) * 8192, &P.tm[M_SEG], 0, (role - 1) * 2048 + s * 32, h * 2, sb + B_KVFULL, 7 << ((h & 1) * 3), P.pol[s < 48 ? 8 : 11]);
                    if ((s & 7) == 7) { wait_count(&g_cnt(C_KV + 1 + (s >> 3)), e1 * 128); fence_async(); }
                    tma_prefetch3d_e(&P.tm[M_SEG], 0, (role - 1) * 2048 + s * 32 + 32, h * 2);
                }
                if (s > 0 && (s & 3) == 0) {
                    const int i = (s - 1) >> 2;
                    mbar_wait(sb + B_PERS, i & 1);
                    asm volatile("{\n.reg .pred E;\nelect.sync _|E, 0xffffffff;\n@E st.release.gpu.global.u32 [%0], %1;\n}" ::"l"(flag), "r"(epoch * 64 + i * 4 + 4) : "memory");
                }
            }
            if (role == 0) {
                const int lane = threadIdx.x & 31;
                if (lane == 0) mbar_arrive(sb + B_RELM);
#pragma unroll 1
                for (int s = 0; s < 63; s++) {
                    mbar_wait(sb + B_P1, s & 1);
                    if (s > 0) {
                        st_relaxed4(P.xb + xg_buf(s - 1) + h * 2048 + xg_lane(lane), 0, 0, 0, 0);
                        st_relaxed1(P.xb + xg_buf(s - 1) + xg_side(h) + lane * 4, 0);
                        __threadfence();
                    }
                    __syncwarp();
                    if (lane == 0) mbar_arrive(sb + B_RELM);
                }
            }
            if ((threadIdx.x & 31) < M_C1 - 1) asm volatile("prefetch.tensormap [%0];" ::"l"(&P.tm[1 + (threadIdx.x & 31)]) : "memory");
            resume = 0;
            continue;
        }
        const int m0 = mb * 256 + rank * 128, ssm = type >= T_A1;
        const CUtensorMap* ma = &P.tm[max(type, 1) + half * M_HALF];
        const CUtensorMap* mw = &P.tm[type ? M_WV + type : M_WK + (nb >> 4)];
        const int nk = type == T_OP ? 64 : type == T_A2 ? 32 : 16;
        const int a3 = type == T_A1 ? nb * 16 + rank * 8 + hw * 4 : type == T_A2 ? mb * 4 + rank * 2 + hw : (type == T_OP ? 4096 : 0) + m0 + hw * 64;
        const int b3 = type == T_A1 ? mb * 128 + rank * 16 : type == T_A2 ? (nb * 2 + rank) * 128 : (nb & 15) * 4 + rank * 2;
        if (type & 1) {
            wait_count(&g_cnt(type == T_A1 ? C_COEF : C_KV + mb), e1 * (type == T_A1 ? 4 : 128));
            fence_async();
        }
        uint32_t ready = type == T_OP || type == T_A2 ? 0 : ~0u;
        if (type == T_A1) l2_prefetch_e(g_coef + nb * 128 + rank * 64, 1024);
        auto arrived = [&]() {
            const uint32_t t = fresh_tid();
            return __all_sync(0xffffffffu, (int32_t)(ld_acquire(&g_cnt(C_FLAG + (t & 2) * 16 + nb * 2 + (t & 1))) - (epoch * 64 + mb * 8 + rank * 4 + 4)) >= 0);
        };
        bool passed = false;
        mbar_wait(sb + B_RESUME, resume);
#pragma unroll 1
        for (int kt = 0; kt < nk; kt++) {
            if (type == T_QA && kt == 9) passed = arrived();
            while (~ready & (ssm ? 2 | 1 << ((kt & 15) >> 1) : 1 << (kt >> 2))) {
                if (ready) __nanosleep(POLLNS);
                ready = __ballot_sync(0xffffffffu, (int32_t)(ld_acquire(&g_cnt(type * 64 + mb * 16 + (fresh_tid() & 15))) - e1 * 4) >= 0) | 1u << 31;
                fence_async();
            }
            const uint32_t st = acquire_stage(sb, p, STAGE - half * 8192), bar = sb + B_FULL + st * 8;
            const int a1 = type == T_A2 ? kt * 64 : 0, b0 = ssm ? (kt & 15) * 64 : 0;
            tma4d_e(sb + st * STAGE + hw * 8192, ma, kt * 64 - a1, a1, a3, bar, P.pol[11]);
            tma4d_mc_e(sb + st * STAGE + 16384 + rank * 16384, mw + (ssm & kt >> 4), b0, ssm ? 0 : kt * 64, b3, bar, both, P.pol[(item & 0x7e0) == 224 ? 9 : 11]);
            if (type == T_QA && kt < 8) tma_prefetch4d_e(&P.tm[M_OA], nb * 256 + (kt & 3) * 64, (kt >> 2) * 2048 + m0);
            pipe_next(p);
        }
        if (type == T_QA) {
            while (!passed) { passed = arrived(); if (!passed) __nanosleep(POLLNS); }
            fence_async();
        }
        const int q = type == T_QA;
#pragma unroll 1
        for (int e = 0; e < (q ? 4 : type == T_A2 ? 2 : 0); e++) {
            const uint32_t st = acquire_stage(sb, p, q ? 40960 : 32768 + 256), bar = sb + B_FULL + st * 8, dst = sb + st * STAGE;
#pragma unroll 1
            for (int i = 0; i < 2; i++) tma4d_e(dst + i * 16384, &P.tm[q ? M_OA : M_AX], nb * 256 + (e & 1) * 128 + i * 64, 0, q ? (e >> 1) * 2048 + m0 : mb * 128 + rank * 16, bar, P.pol[q ? 3 : 11]);
            const uint8_t* src = q ? (const uint8_t*)(((e >> 1) ? g_vmt : g_km) + ((mb * 8 + rank * 4) * 32 + nb * 2 + (e & 1)) * 512) : (const uint8_t*)(P.Dskip + nb * 256 + e * 128);
#pragma unroll 1
            for (int i = 0; i < (q ? 4 : 1); i++) bulk_g2s_e(dst + 32768 + i * 2048, src + i * 65536, q ? 2048 : 256, bar);
            pipe_next(p);
        }
    }
#pragma unroll 1
    for (int i = 0; i < NSTAGE; i++) { mbar_wait(sb + B_EMPTY + p.stage * 8, p.phase ^ 1); pipe_next(p); }
}

__device__ __forceinline__ uint32_t fresh_ctaid() { uint32_t t; asm volatile("mov.u32 %0, %%ctaid.x;" : "=r"(t)); return t; }
__device__ __forceinline__ void reset_state(const Params& P, Cons& c, Pend& d, uint32_t sb, bool resumed) {
    const uint32_t t = fresh_tid(), b = fresh_ctaid() + P.cta0;
    const int w = __shfl_sync(0xffffffffu, t >> 5, 0);
    c.sb = sb; c.wg = w >> 2; c.wq = w & 3; c.lane = t & 31;
    c.rank = __shfl_sync(0xffffffffu, b & 1, 0); c.pair = __shfl_sync(0xffffffffu, b >> 1, 0);
    c.rel = mapa(sb + B_EMPTY, cluster_rank() ^ (c.lane & 1));
    c.p.stage = 0; c.p.phase = 0;
    c.nst = resumed && c.pair < NCHAIN;
    d = Pend{};
}

__global__ void __launch_bounds__(384, 1) fused_kernel(const __grid_constant__ Params P) {
    extern __shared__ __align__(1024) uint8_t smem[];
    const uint32_t sb = smem_u32(smem);
    asm volatile("griddepcontrol.launch_dependents;");
    declare_fence(P.zero);
    const int tid = threadIdx.x, lane = tid & 31;
    const int warp = __shfl_sync(0xffffffffu, tid >> 5, 0);
    const int cta = __shfl_sync(0xffffffffu, blockIdx.x + P.cta0, 0), pair = cta >> 1, rank = cta & 1;
    if (tid == 0) {
        if (sb & 1023) spin_fault();
        for (int i = 0; i < NSTAGE; i++) { mbar_init(sb + B_FULL + i * 8, 1); mbar_init(sb + B_EMPTY + i * 8, 16); }
        mbar_init(sb + B_RESUME, 2);
        mbar_init(sb + B_KVFULL, 1);
        mbar_init(sb + B_GO, 3); mbar_init(sb + B_RED, 8); mbar_init(sb + B_P1, 1); mbar_init(sb + B_EPOCH, 1); mbar_init(sb + B_PERS, 8); mbar_init(sb + B_INIT, 8); mbar_init(sb + B_INIT2, 8);
        mbar_init(sb + B_READY, 8);
        for (int i = 0; i < 2; i++) { mbar_init(sb + B_SFULL + i * 8, 4); mbar_init(sb + B_SFREE + i * 8, 1); }
        mbar_init(sb + B_RELM, cta % 3 ? 1 : 2); mbar_init(sb + B_X, 9);
        mbar_init(sb + B_DONE, 2);
        mbar_expect(sb + B_X, 4096);
        sts64(sb + S_EV, 0, 0);
        asm volatile("fence.mbarrier_init.release.cluster;" ::: "memory");
    }
    __syncthreads();
    cluster_sync();
    if (warp >= 8) {
        asm volatile("setmaxnreg.dec.sync.aligned.u32 24;");
        if (warp == 8) {
            producer(P, sb, cta);
        } else if (warp == 9) {
            const uint32_t epoch = __shfl_sync(0xffffffffu, ld_acquire(&g_cnt(C_EPOCH)), 0);
            if (lane == 0) { sts32(sb + S_EPOCH, epoch); mbar_arrive(sb + B_EPOCH); red_release(&g_cnt(C_READ)); }
            __syncwarp();
            if (pair < NCHAIN) pacer(P, sb, cta, lane, epoch);
            if (pair < NCHAIN && cta % 3) {
                mbar_wait_bounded(sb + B_PERS, 1);
                if (lane == 0) asm volatile("st.release.gpu.global.u32 [%0], %1;" ::"l"(&g_cnt(C_FLAG + (cta % 3 == 2 ? 32 : 0) + cta / 3)), "r"(epoch * 64 + 64) : "memory");
            }
            if (cta == 0 && lane == 0) {
                for (int n = 0; (int32_t)(ld_acquire(&g_cnt(C_READ)) - (epoch + 1) * (NPAIR * 2)) < 0; n++) if (n > SPIN_LIMIT) spin_fault();
                st_relaxed1(&g_cnt(C_EPOCH), epoch + 1);
            }
            __syncwarp();
            mbar_wait_bounded(sb + B_DONE, 0);
        } else {
            store_warp(P, sb, warp - 10, cta);
        }
    } else {
        asm volatile("setmaxnreg.inc.sync.aligned.u32 240;");
        Cons c;
        Pend d;
        if (pair < NCHAIN) {
            reset_state(P, c, d, sb, false);
            {
                const int item = ITEM(ITEM_OFF(pair));
                float acc[128];
                mainloop<true>(acc, P, c, d, T_KV, 16);
                epi_kv(acc, c, d, (item >> 5) & 7, item & 31);
            }
            mbar_wait(sb + B_EMPTY + 3 * 8, 1);
            drain_both(c, d);
            uint32_t wr[40][4];
            chain_fetch(P, sb, cta, warp, lane, wr);
            chain_bounds(sb, cta, warp, lane, wr);
            if (warp < 4) chain_role<false>(P, sb, cta, warp, lane, wr);
            else chain_role<true>(P, sb, cta, warp, lane, wr);
            bar_sync(1, 256);
            const uint32_t t2 = fresh_tid();
            if (t2 < 2) mbar_arrive_cluster(mapa(sb + B_RESUME, cluster_rank() ^ t2));
        } else if (pair >= NPAIR - 2) {
            const int ch = (pair - (NPAIR - 2)) * 512 + rank * 256 + tid;
            g_coef[ch] = ssm_coef(__bfloat162float(P.Lre[ch]), __bfloat162float(P.Lim[ch]), __bfloat162float(P.logdt[ch]));
            bar_sync(1, 256);
            if (tid == 0) red_release(&g_cnt(C_COEF));
        }
        reset_state(P, c, d, sb, true);
        int it = ITEM_OFF(c.pair) + (c.pair < NCHAIN ? 2 : 0);
        for (int prev = c.pair < NCHAIN ? ITEM(it - 1) : 0;; prev = ITEM(it++)) {
            const bool last = prev & LAST;
            const int item = ITEM(it), type = (item >> 8) & 7, mb = (item >> 5) & 7, nb = item & 31;
            const bool idle = (item >> 12 & 3) == 3 - 2 * c.wg;
            if (d.kind != PEND_NONE && ((prev & (LAST | URGENT)) || idle || (type != T_KV && !bar_and(5 + c.wg, mbar_try(sb + B_FULL + c.p.stage * 8, c.p.phase))))) {
#pragma unroll 1
                while (d.kind != PEND_NONE) drain(P, c, d);
            }
            if (last) break;
            const int nk = type == T_OP ? 64 : type == T_A2 ? 32 : 16;
            if (idle) {
#pragma unroll 1
                for (int kt = nk + (type == T_A2 ? 2 : type == T_QA ? 4 : 0); kt > 0; kt--) { wait_full(c); release(c, c.p.stage); pipe_next(c.p); }
                continue;
            }
            float acc[128];
            mainloop(acc, P, c, d, type, nk);
            if (type == T_KV) epi_kv(acc, c, d, mb, nb);
            else if (type == T_QA) epi_qa(acc, c, d, mb, nb);
            else if (type == T_OP) epi_op(acc, c, d, mb, nb);
            else if (type == T_A1) epi_a1(acc, P, c, d, mb, nb);
            else epi_a2(acc, P, c, d, mb, nb);
        }
        staging_wait(c);
        staging_post(c, PEND_NONE, 0, 0, 0);
        if (c.wq == 0 && c.lane == 0) mbar_arrive(sb + B_DONE);
    }
}

typedef CUresult (*EncodeFn)(CUtensorMap*, CUtensorMapDataType, cuuint32_t, void*, const cuuint64_t*, const cuuint64_t*, const cuuint32_t*, const cuuint32_t*,
                             CUtensorMapInterleave, CUtensorMapSwizzle, CUtensorMapL2promotion, CUtensorMapFloatOOBfill);
void encode(EncodeFn fn, CUtensorMap* m, const void* base, int rank, const uint64_t* dims, const uint64_t* strides, const uint32_t* box, CUtensorMapSwizzle swz = CU_TENSOR_MAP_SWIZZLE_128B) {
    cuuint64_t d[5], s[5]; cuuint32_t b[5], e[5];
    for (int i = 0; i < rank; i++) { d[i] = dims[i]; b[i] = box[i]; e[i] = 1; if (i) s[i - 1] = strides[i - 1]; }
    fn(m, CU_TENSOR_MAP_DATA_TYPE_BFLOAT16, rank, (void*)base, d, s, b, e, CU_TENSOR_MAP_INTERLEAVE_NONE, swz,
       CU_TENSOR_MAP_L2_PROMOTION_L2_128B, CU_TENSOR_MAP_FLOAT_OOB_FILL_NONE);
}
void map_kmajor(EncodeFn fn, CUtensorMap* m, const void* base, uint64_t rows, uint64_t cols, uint32_t box_rows) {
    const uint64_t d[4] = {cols, 1, 1, rows}, s[3] = {cols * 2, cols * 2, cols * 2}; const uint32_t b[4] = {64, 1, 1, box_rows};
    encode(fn, m, base, 4, d, s, b);
}
void map_mnmajor(EncodeFn fn, CUtensorMap* m, const void* base, uint64_t krows, uint64_t cols, uint32_t groups = 2) {
    const uint64_t d[4] = {64, krows, 1, cols / 64}, s[3] = {cols * 2, 128, 128}; const uint32_t b[4] = {64, 64, 1, groups};
    encode(fn, m, base, 4, d, s, b);
}
void map_store(EncodeFn fn, CUtensorMap* m, const void* base, uint64_t rows, uint64_t cols) {
    const uint64_t d[2] = {cols, rows}, s[1] = {cols * 2}; const uint32_t b[2] = {64, 32};
    encode(fn, m, base, 2, d, s, b);
}

}

extern "C" void kernel_launch(void* const* d_in, const int* in_sizes, int n_in, void* d_out, int out_size) {
    static Params P;
    static EncodeFn fn = nullptr;
    if (!fn) {
        cudaDriverEntryPointQueryResult q;
        cudaGetDriverEntryPoint("cuTensorMapEncodeTiled", (void**)&fn, cudaEnableDefault, &q);
        cudaFuncSetAttribute(fused_kernel, cudaFuncAttributeMaxDynamicSharedMemorySize, S_TOTAL);
    }
    const bf16* in[15];
    for (int i = 0; i < 15; i++) in[i] = (const bf16*)d_in[i];
    void *kvo, *ht;
    cudaGetSymbolAddress(&kvo, g_kvo);
    cudaGetSymbolAddress(&ht, g_ht);
    map_kmajor(fn, &P.tm[M_BX], in[9], 2048, 1024, 128);
    map_mnmajor(fn, &P.tm[M_WQ], in[11], 1024, 4096);
    map_mnmajor(fn, &P.tm[M_WK], in[12], 1024, 4096);
    map_mnmajor(fn, &P.tm[M_WV], in[13], 1024, 4096);
    map_mnmajor(fn, &P.tm[M_WO], in[14], 4096, 1024);
    map_kmajor(fn, &P.tm[M_OA], kvo, 3 * 2048, 4096, 128);
    P.swap_ri = in[4] < in[3];
    {
        const bf16* lo = P.swap_ri ? in[4] : in[3];
        const uint64_t diff = (uint64_t)((const char*)(P.swap_ri ? in[3] : in[4]) - (const char*)lo);
        const uint64_t d[4] = {1024, 8, 2, 128}, s[3] = {2048, diff, 16384}; const uint32_t b[4] = {64, 8, 2, 8}, bh[4] = {64, 8, 2, 4};
        encode(fn, &P.tm[M_AB], lo, 4, d, s, b);
        encode(fn, &P.tm[M_AB + M_HALF], lo, 4, d, s, bh);
    }
    {
        const uint64_t d[4] = {1024, 2, 4, 1024}, s[3] = {2048, 64 * 2048, 4096}; const uint32_t b[4] = {64, 2, 4, 16};
        encode(fn, &P.tm[M_AX], in[0], 4, d, s, b);
    }
    map_mnmajor(fn, &P.tm[M_HT], ht, 2048, 2048);
    map_kmajor(fn, &P.tm[M_CRE], in[5], 1024, 1024, 128);
    map_kmajor(fn, &P.tm[M_CIM], in[6], 1024, 1024, 128);
    map_store(fn, &P.tm[M_KVO], kvo, 3 * 2048, 4096);
    map_store(fn, &P.tm[M_HTS], ht, 2048, 2048);
    map_kmajor(fn, &P.tm[M_BX + M_HALF], in[9], 2048, 1024, 64);
    map_kmajor(fn, &P.tm[M_OA + M_HALF], kvo, 3 * 2048, 4096, 64);
    map_mnmajor(fn, &P.tm[M_HT + M_HALF], ht, 2048, 2048, 1);
    for (int i = 0; i < 3; i++) {
        const uint64_t d[3] = {64, 1024, 64}, s[2] = {8192, 128}; const uint32_t b[3] = {64, 16, 2};
        encode(fn, &P.tm[M_C1 + i], in[11 + i], 3, d, s, b);
    }
    {
        const uint64_t d[2] = {1024, 4096}, s[1] = {2048}; const uint32_t b[2] = {32, 32};
        encode(fn, &P.tm[M_CO], in[14], 2, d, s, b, CU_TENSOR_MAP_SWIZZLE_64B);
    }
    {
        const uint64_t d[3] = {64, 3 * 2048, 64}, s[2] = {8192, 128}; const uint32_t b[3] = {64, 32, 2};
        encode(fn, &P.tm[M_SEG], kvo, 3, d, s, b);
    }
    void* xs;
    cudaGetSymbolAddress(&xs, g_x);
    P.xb = (uint8_t*)(((uintptr_t)xs + (2u << 20) - 1) & ~(uintptr_t)((2u << 20) - 1));
    P.mem0 = in[10]; P.Bx = in[9];
    P.Ax = in[0]; P.Lre = in[1]; P.Lim = in[2]; P.logdt = in[7]; P.Dskip = in[8];
    P.out = (float*)d_out;
    int pv[10] = {1140, 0, 110, 0, 330, 64, 32, 32, 0, 0};
    int ef = 779;
    for (int i = 0; i < 12; i++) P.pol[i] = (ef >> i & 1) ? 0x12F0000000000000ull : 0x1000000000000000ull;
    P.dly = pv[0]; P.mrg = pv[2];
    P.rd = pv[4]; P.guard = pv[5]; P.clampv = pv[6]; P.clamp0 = pv[7]; P.kvd = pv[9]; P.xd = pv[8];
    cudaLaunchConfig_t cfg = {};
    cudaLaunchAttribute at[2];
    cfg.blockDim = dim3(384); cfg.dynamicSmemBytes = S_TOTAL; cfg.stream = cudaStreamPerThread; cfg.attrs = at;
    at[0].id = cudaLaunchAttributeClusterDimension;
    at[0].val.clusterDim.y = at[0].val.clusterDim.z = 1;
    at[1].id = cudaLaunchAttributeProgrammaticStreamSerialization;
    at[1].val.programmaticStreamSerializationAllowed = 1;
    for (int i = 0; i < 2; i++) {
        P.cta0 = i ? 2 * NCHAIN : 0;
        cfg.gridDim = dim3(i ? 2 * (NPAIR - NCHAIN) : 2 * NCHAIN);
        at[0].val.clusterDim.x = i ? 2 : 6;
        cfg.numAttrs = 1 + i;
        cudaLaunchKernelEx(&cfg, fused_kernel, P);
    }
}
```

```cpp
#include <cuda_runtime.h>
#include <cuda_bf16.h>
#include <cuda.h>
#include <stdint.h>
#include <string.h>

typedef __nv_bfloat16 bf16;

namespace {

constexpr int SPIN_LIMIT = 1 << 22;
#define POLLNS 100
constexpr int NPAIR = 66;
constexpr int NCHAIN = 48;
enum { T_KV = 0, T_QA = 1, T_OP = 2, T_A1 = 3, T_A2 = 4, T_CHAIN = 5 };
constexpr int URGENT = 2048;
constexpr int LAST = 16384;
constexpr int HALF = 4096;
enum { M_BX = 1, M_OA, M_AB, M_HT, M_HALF = 4, M_WK = 9, M_WV, M_WQ, M_WO, M_AX, M_CRE, M_CIM, M_KVO, M_HTS, M_C1, M_CO = M_C1 + 3, M_SEG, M_COUNT };
enum { C_KV = 0, C_O = 128, C_HT = 256, C_READ = 24, C_EPOCH = 25, C_COEF = 26, C_XMAX = 27, C_XCNT = 28, C_FLAG = 32 };

struct Params {
    CUtensorMap tm[M_COUNT];
    const bf16 *mem0, *Bx, *Ax, *Lre, *Lim, *logdt, *Dskip;
    float* out;
    uint8_t* xb;
    int swap_ri, zero;
    int dly, mrg, rd, guard, clampv, clamp0, kvd, xd;
    uint64_t pol[12];
    uint16_t cta0;
};

__constant__ uint16_t c_off[67] = {0, 4, 8, 14, 20, 26, 32, 38, 44, 49, 54, 59, 64, 69, 74, 79, 84, 89, 94, 98, 102, 106, 110, 114, 118, 122, 126, 130, 134, 138, 142, 146, 150, 154, 158, 162, 166, 170, 174, 178, 182, 186, 190, 194, 198, 202, 206, 210, 214, 234, 253, 272, 292, 312, 332, 352, 371, 391, 410, 430, 449, 468, 487, 506, 525, 545, 564};
__constant__ uint16_t c_items[700] = {
    0, 1280, 512, 21728, 16, 1280, 513, 29920, 32, 1280, 800, 898, 3042, 21729, 1, 1280, 801, 899, 3043, 29921, 17, 1280, 802, 900,
    3044, 21730, 33, 1280, 803, 901, 3045, 29922, 2, 1280, 804, 902, 3046, 21731, 18, 1280, 805, 903, 3047, 29923, 34, 1280, 2496, 2912,
    17408, 3, 1280, 2528, 2913, 17409, 19, 1280, 768, 2914, 17410, 35, 1280, 769, 2915, 17411, 4, 1280, 770, 2916, 17440, 20, 1280, 771,
    2917, 17441, 36, 1280, 772, 2918, 17442, 5, 1280, 773, 2919, 17443, 21, 1280, 774, 2944, 17472, 37, 1280, 775, 2945, 17473, 6, 1280,
    2497, 16898, 22, 1280, 2529, 16899, 38, 1280, 2498, 16928, 7, 1280, 2530, 16929, 23, 1280, 2499, 16930, 39, 1280, 2531, 16931, 8, 1280,
    2500, 16960, 24, 1280, 2532, 16961, 40, 1280, 2501, 16962, 9, 1280, 2533, 16963, 25, 1280, 2502, 16992, 41, 1280, 2534, 16993, 10, 1280,
    2503, 16994, 26, 1280, 2535, 16995, 42, 1280, 2504, 17024, 11, 1280, 2536, 17025, 27, 1280, 2505, 17026, 43, 1280, 2537, 17027, 12, 1280,
    2506, 17056, 28, 1280, 2538, 17057, 44, 1280, 2507, 17058, 13, 1280, 2539, 17059, 29, 1280, 2508, 17088, 45, 1280, 2540, 17089, 14, 1280,
    2509, 17090, 30, 1280, 2541, 17091, 46, 1280, 2510, 17120, 15, 1280, 2542, 17121, 31, 1280, 2511, 17122, 47, 1280, 2543, 17123, 48, 66,
    84, 102, 117, 131, 147, 161, 178, 194, 207, 222, 235, 248, 332, 366, 416, 835, 3010, 17568, 49, 67, 85, 256, 128, 141,
    155, 170, 187, 203, 215, 296, 301, 323, 357, 391, 425, 2979, 17505, 50, 68, 86, 103, 259, 142, 156, 171, 188, 288, 216,
    231, 302, 324, 358, 392, 806, 2976, 17474, 51, 69, 87, 104, 118, 132, 148, 162, 179, 195, 208, 223, 236, 249, 333, 367,
    417, 836, 3011, 17569, 52, 70, 88, 105, 119, 133, 149, 163, 180, 196, 209, 224, 237, 250, 334, 384, 418, 837, 3012, 17570,
    53, 71, 89, 106, 120, 134, 150, 164, 181, 197, 210, 225, 238, 251, 335, 385, 419, 838, 3013, 17571, 54, 72, 90, 107,
    121, 135, 151, 165, 182, 198, 211, 226, 239, 252, 352, 386, 420, 839, 3014, 17600, 55, 73, 91, 108, 260, 264, 160, 176,
    192, 291, 220, 299, 245, 328, 362, 396, 428, 3009, 17539, 56, 74, 92, 109, 122, 136, 152, 166, 183, 199, 212, 227, 240,
    253, 353, 387, 421, 429, 3015, 17601, 57, 75, 93, 110, 123, 263, 267, 175, 271, 206, 218, 233, 243, 322, 356, 390, 424,
    2978, 17504, 58, 76, 94, 111, 124, 137, 153, 167, 184, 200, 213, 228, 241, 254, 354, 388, 422, 430, 3040, 17602, 59, 77,
    95, 112, 125, 138, 265, 269, 191, 290, 219, 298, 246, 329, 363, 397, 832, 2982, 17536, 60, 78, 96, 113, 261, 143, 157,
    172, 270, 292, 221, 300, 247, 330, 364, 398, 833, 2983, 17537, 61, 79, 97, 257, 129, 144, 158, 173, 189, 204, 294, 297,
    244, 325, 359, 393, 426, 2980, 17506, 62, 80, 98, 258, 130, 145, 268, 177, 193, 205, 217, 232, 303, 326, 360, 394, 807,
    2977, 17475, 63, 81, 99, 114, 262, 146, 159, 174, 190, 289, 295, 234, 321, 331, 365, 399, 834, 3008, 17538, 64, 82, 100,
    115, 126, 139, 154, 168, 185, 201, 214, 229, 242, 255, 355, 389, 423, 431, 3041, 17603, 65, 83, 101, 116, 127, 140, 266,
    169, 186, 202, 293, 230, 320, 327, 361, 395, 427, 2981, 17507,
};
#define ITEM_OFF(p) c_off[p]
#define ITEM(i) c_items[i]

__device__ __align__(1024) bf16 g_kvo[3 * 2048 * 4096];
__device__ __align__(1024) bf16 g_ht[2048 * 2048];
__device__ __align__(1024) uint8_t g_x[4 << 20];
__device__ __align__(1024) uint32_t g_km[64 * 32 * 512];
__device__ __align__(1024) uint32_t g_vmt[64 * 32 * 512];
__device__ __align__(1024) float2 g_agg[8 * 1024];
__device__ __align__(1024) float4 g_coef[1024];
__device__ __align__(1024) uint32_t g_cntl[384 * 32];
#define g_cnt(i) g_cntl[(i) * 32]
__device__ __align__(1024) uint32_t g_hint[96 * 32];
constexpr int XG_SIDE = 65536, XG_T = 98304;
__device__ __forceinline__ uint32_t xg_buf(int b) { return (b & 1) * 128 + (b & 2) * 256; }
__device__ __forceinline__ uint32_t xg_lane(uint32_t lane) { return (lane >> 4) * 1024 + (lane & 8) * 32 + (lane & 7) * 16; }
__device__ __forceinline__ uint32_t xg_side(int b) { return XG_SIDE + (b >> 1) * 1024 + (b & 1) * 256; }

constexpr int STAGE = 49152, NSTAGE = 4;
constexpr int S_STG = NSTAGE * STAGE;
constexpr int S_BAR = S_STG + 32768;
constexpr int B_FULL = S_BAR, B_EMPTY = S_BAR + 32, B_RESUME = S_BAR + 64, B_KVFULL = S_BAR + 72, B_GO = S_BAR + 88, B_X = S_BAR + 96, B_PERS = S_BAR + 104,
              B_INIT = S_BAR + 112, B_RELM = S_BAR + 120, B_READY = S_BAR + 136, B_SFULL = S_BAR + 144, B_SFREE = S_BAR + 160, S_DESC = S_BAR + 176, B_RED = S_BAR + 216;
constexpr int S_EV = S_BAR + 80, S_EO = S_BAR + 84, B_INIT2 = S_BAR + 128, S_SC = S_BAR + 208, S_ISC = S_EV;
constexpr int S_XV = S_BAR + 256, S_LOG = S_XV + 2048;
constexpr int S_TOTAL = S_LOG + 768;
#define NRA 5
#define NRB 3
constexpr int S_W1 = 0;
constexpr int S_W2 = 4 * 4096 * (16 - NRA - NRB);
constexpr int S_KV = 188416;
constexpr int S_P1 = S_KV + 16384;
constexpr int S_X = S_P1 + 16384;
constexpr int S_SX = S_P1, S_OX = S_P1 + 2048;
constexpr int S_EM = S_X + 4096, S_TO = S_EM + 32, S_INV = S_EM + 64, B_DONE = S_BAR + 224, B_P1 = S_BAR + 232, B_EPOCH = S_BAR + 240, S_EPOCH = S_BAR + 248;
static_assert(S_INV + 32 <= S_BAR && S_KV % 1024 == 0 && S_TOTAL <= 232448, "chain smem layout");

template <int V> struct IC { static constexpr int value = V; };
template <int B, int E, typename F> __device__ __forceinline__ void static_for(F&& f) { if constexpr (B < E) { f(IC<B>{}); static_for<B + 1, E>(f); } }
__device__ __forceinline__ uint32_t cluster_rank() { uint32_t r; asm volatile("mov.u32 %0, %%cluster_ctarank;" : "=r"(r)); return r; }
__device__ __forceinline__ void spin_fault() { asm volatile("st.global.u32 [%0], 0;" ::"l"(0ull) : "memory"); }
__device__ __forceinline__ uint32_t smem_u32(const void* p) { return (uint32_t)__cvta_generic_to_shared(p); }
__device__ __forceinline__ uint32_t opq(uint32_t x, int lane) { return __shfl_sync(0xffffffffu, x, lane); }
__device__ __forceinline__ uint32_t mapa(uint32_t a, uint32_t r) { uint32_t d; asm volatile("mapa.shared::cluster.u32 %0, %1, %2;" : "=r"(d) : "r"(a), "r"(r)); return d; }
__device__ __forceinline__ void mma16816(float* d, uint32_t a0, uint32_t a1, uint32_t a2, uint32_t a3, uint32_t b0, uint32_t b1) {
    asm("mma.sync.aligned.m16n8k16.row.col.f32.bf16.bf16.f32 {%0,%1,%2,%3}, {%4,%5,%6,%7}, {%8,%9}, {%0,%1,%2,%3};"
        : "+f"(d[0]), "+f"(d[1]), "+f"(d[2]), "+f"(d[3]) : "r"(a0), "r"(a1), "r"(a2), "r"(a3), "r"(b0), "r"(b1));
}
__device__ __forceinline__ void mma1688(float* d, uint32_t a0, uint32_t a1, uint32_t b0) {
    asm("mma.sync.aligned.m16n8k8.row.col.f32.bf16.bf16.f32 {%0,%1,%2,%3}, {%4,%5}, {%6}, {%0,%1,%2,%3};"
        : "+f"(d[0]), "+f"(d[1]), "+f"(d[2]), "+f"(d[3]) : "r"(a0), "r"(a1), "r"(b0));
}
__device__ __forceinline__ void ldsm4(uint32_t* r, uint32_t a) {
    asm volatile("ldmatrix.sync.aligned.m8n8.x4.shared.b16 {%0,%1,%2,%3}, [%4];" : "=r"(r[0]), "=r"(r[1]), "=r"(r[2]), "=r"(r[3]) : "r"(a));
}
__device__ __forceinline__ void ldsm4t(uint32_t* r, uint32_t a) {
    asm volatile("ldmatrix.sync.aligned.m8n8.x4.trans.shared.b16 {%0,%1,%2,%3}, [%4];" : "=r"(r[0]), "=r"(r[1]), "=r"(r[2]), "=r"(r[3]) : "r"(a));
}
__device__ __forceinline__ void stsm4(uint32_t a, uint32_t r0, uint32_t r1, uint32_t r2, uint32_t r3) {
    asm volatile("stmatrix.sync.aligned.m8n8.x4.shared.b16 [%0], {%1,%2,%3,%4};" ::"r"(a), "r"(r0), "r"(r1), "r"(r2), "r"(r3) : "memory");
}
__device__ __forceinline__ void stsm4t(uint32_t a, uint32_t r0, uint32_t r1, uint32_t r2, uint32_t r3) {
    asm volatile("stmatrix.sync.aligned.m8n8.x4.trans.shared.b16 [%0], {%1,%2,%3,%4};" ::"r"(a), "r"(r0), "r"(r1), "r"(r2), "r"(r3) : "memory");
}
__device__ __forceinline__ uint32_t movm(uint32_t a) { uint32_t d; asm volatile("movmatrix.sync.aligned.m8n8.trans.b16 %0, %1;" : "=r"(d) : "r"(a)); return d; }
__device__ __forceinline__ uint32_t pack2(float lo, float hi) { uint32_t d; asm("cvt.rn.bf16x2.f32 %0, %1, %2;" : "=r"(d) : "f"(hi), "f"(lo)); return d; }
__device__ __forceinline__ uint32_t prmt(uint32_t a, uint32_t b, uint32_t s) { uint32_t d; asm("prmt.b32 %0, %1, %2, %3;" : "=r"(d) : "r"(a), "r"(b), "r"(s)); return d; }
__device__ __forceinline__ uint32_t pack2h(float lo, float hi) { uint32_t d; asm("cvt.rn.f16x2.f32 %0, %1, %2;" : "=r"(d) : "f"(hi), "f"(lo)); return d; }
__device__ __forceinline__ uint32_t h2bf(uint32_t a, uint32_t b) {
    uint32_t d;
    asm("{\n.reg .b16 l, h, u;\n.reg .f32 x, y;\nmov.b32 {l, u}, %1;\ncvt.f32.f16 x, l;\nmov.b32 {u, h}, %2;\ncvt.f32.f16 y, h;\ncvt.rn.bf16x2.f32 %0, y, x;\n}" : "=r"(d) : "r"(a), "r"(b));
    return d;
}
__device__ __forceinline__ void cvt_block(uint32_t* u, uint32_t& x, uint32_t sel) {
    const uint32_t a = prmt(u[0], u[0], sel), b = prmt(u[1], u[1], sel), c = prmt(u[2], u[2], sel), d = prmt(u[3], x, sel);
    x ^= u[3] ^ d;
    u[0] = h2bf(a, a); u[1] = h2bf(b, b); u[2] = h2bf(c, c); u[3] = h2bf(d, d);
}
__device__ __forceinline__ uint32_t amax(uint32_t a, uint32_t b) { uint32_t d; asm("max.xorsign.abs.bf16x2 %0, %1, %2;" : "=r"(d) : "r"(a), "r"(b)); return d; }
__device__ __forceinline__ uint32_t amax4(uint32_t m, const uint32_t* v) { return amax(amax(m, amax(v[0], v[1])), amax(v[2], v[3])); }
__device__ __forceinline__ uint32_t warp_exp(uint32_t m) { return __reduce_max_sync(0xffffffffu, max(m & 0x7f80u, (m >> 16) & 0x7f80u)) >> 7; }
__device__ __forceinline__ void red_max_shared(uint32_t a, uint32_t x) { asm volatile("red.shared.max.u32 [%0], %1;" ::"r"(a), "r"(x) : "memory"); }
__device__ __forceinline__ uint32_t mul_bf2(uint32_t a, uint32_t b) { uint32_t d; asm("mul.rn.bf16x2 %0, %1, %2;" : "=r"(d) : "r"(a), "r"(b)); return d; }
__device__ __forceinline__ float bf_lo(uint32_t u) { return __uint_as_float(u << 16); }
__device__ __forceinline__ float bf_hi(uint32_t u) { return __uint_as_float(u & 0xffff0000u); }
__device__ __forceinline__ float ex2(float x) { float y; asm("ex2.approx.ftz.f32 %0, %1;" : "=f"(y) : "f"(x)); return y; }
__device__ __forceinline__ float rcp(float x) { float y; asm("rcp.approx.ftz.f32 %0, %1;" : "=f"(y) : "f"(x)); return y; }
__device__ __forceinline__ void st_relaxed4(const void* p, uint32_t a, uint32_t b, uint32_t c, uint32_t d) {
    asm volatile("{\n.reg .b128 t;\nmov.b128 t, {%1,%2,%3,%4};\nst.relaxed.gpu.global.b128 [%0], t;\n}" ::"l"(p), "r"(a), "r"(b), "r"(c), "r"(d) : "memory");
}
__device__ __forceinline__ void st_relaxed2(const void* p, uint32_t a, uint32_t b) {
    asm volatile("{\n.reg .b64 t;\nmov.b64 t, {%1,%2};\nst.relaxed.gpu.global.b64 [%0], t;\n}" ::"l"(p), "r"(a), "r"(b) : "memory");
}
__device__ __forceinline__ void ld_relaxed2_if(uint32_t& a, uint32_t& b, const void* p, bool on) {
    asm volatile("{\n.reg .pred P;\n.reg .b64 t;\nsetp.ne.u32 P, %3, 0;\nmov.b64 t, {%0,%1};\n@P ld.relaxed.gpu.global.b64 t, [%2];\nmov.b64 {%0,%1}, t;\n}" : "+r"(a), "+r"(b) : "l"(p), "r"((uint32_t)on) : "memory");
}
__device__ __forceinline__ void ld_relaxed4(uint32_t* v, const void* p) {
    asm volatile("ld.relaxed.gpu.global.L1::no_allocate.v4.b32 {%0,%1,%2,%3}, [%4];" : "=r"(v[0]), "=r"(v[1]), "=r"(v[2]), "=r"(v[3]) : "l"(p) : "memory");
}
__device__ __forceinline__ void ld_relaxed1n(uint32_t& v, const void* p) { asm volatile("ld.relaxed.gpu.global.L1::no_allocate.b32 %0, [%1];" : "=r"(v) : "l"(p) : "memory"); }
__device__ __forceinline__ void red_add4(const void* p, uint32_t a, uint32_t b, uint32_t c, uint32_t d) {
    asm volatile("red.relaxed.gpu.global.add.noftz.v4.f16x2 [%0], {%1,%2,%3,%4};" ::"l"(p), "r"(a), "r"(b), "r"(c), "r"(d) : "memory");
}
__device__ __forceinline__ void red_add1(const void* p, uint32_t a) { asm volatile("red.relaxed.gpu.global.add.noftz.f16x2 [%0], %1;" ::"l"(p), "r"(a) : "memory"); }
__device__ __forceinline__ void ld_relaxed2(uint32_t* v, const void* p) {
    asm volatile("{\n.reg .b64 t;\nld.relaxed.gpu.global.L1::no_allocate.b64 t, [%2];\nmov.b64 {%0,%1}, t;\n}" : "=r"(v[0]), "=r"(v[1]) : "l"(p) : "memory");
}
__device__ __forceinline__ uint32_t ld_relaxed1(const void* p) { uint32_t v; asm volatile("ld.relaxed.gpu.global.u32 %0, [%1];" : "=r"(v) : "l"(p) : "memory"); return v; }
__device__ __forceinline__ void st_relaxed1(const void* p, uint32_t v) { asm volatile("st.relaxed.gpu.global.u32 [%0], %1;" ::"l"(p), "r"(v) : "memory"); }
__device__ __forceinline__ uint32_t ld_acquire(const void* p) { uint32_t v; asm volatile("ld.acquire.gpu.global.u32 %0, [%1];" : "=r"(v) : "l"(p) : "memory"); return v; }
__device__ __forceinline__ void red_relaxed(void* p) { asm volatile("red.relaxed.gpu.global.add.u32 [%0], 1;" ::"l"(p) : "memory"); }
__device__ __forceinline__ void red_release(void* p) { asm volatile("red.release.gpu.global.add.u32 [%0], 1;" ::"l"(p) : "memory"); }
__device__ __forceinline__ void st_stream4(const void* p, float a, float b, float c, float d) { asm volatile("st.global.cs.v4.f32 [%0], {%1, %2, %3, %4};" ::"l"(p), "f"(a), "f"(b), "f"(c), "f"(d) : "memory"); }
__device__ __forceinline__ void fence_async() { asm volatile("fence.proxy.async.global;" ::: "memory"); }
__device__ __forceinline__ void fence_async_smem() { asm volatile("fence.proxy.async.shared::cta;" ::: "memory"); }
__device__ __forceinline__ void wait_count(const uint32_t* p, uint32_t target) {
    while ((int32_t)(ld_acquire(p) - target) < 0) __nanosleep(POLLNS);
}
__device__ __forceinline__ void bar_sync(int id, int n) { asm volatile("bar.sync %0, %1;" ::"r"(id), "r"(n) : "memory"); }
__device__ __forceinline__ bool bar_and(int id, bool v) {
    uint32_t r;
    asm volatile("{\n.reg .pred P, Q;\nsetp.ne.u32 Q, %2, 0;\nbar.red.and.pred P, %1, 128, Q;\nselp.u32 %0, 1, 0, P;\n}" : "=r"(r) : "r"(id), "r"((uint32_t)v) : "memory");
    return r;
}
__device__ __forceinline__ void bar_arrive(int id, int n) { asm volatile("bar.arrive %0, %1;" ::"r"(id), "r"(n) : "memory"); }
__device__ __forceinline__ void lds128(uint32_t* v, uint32_t a) { asm volatile("ld.shared.v4.b32 {%0,%1,%2,%3}, [%4];" : "=r"(v[0]), "=r"(v[1]), "=r"(v[2]), "=r"(v[3]) : "r"(a) : "memory"); }
__device__ __forceinline__ uint32_t lds32(uint32_t a) { uint32_t v; asm volatile("ld.shared.b32 %0, [%1];" : "=r"(v) : "r"(a) : "memory"); return v; }
__device__ __forceinline__ void lds64(uint32_t* v, uint32_t a) { asm volatile("ld.shared.v2.b32 {%0,%1}, [%2];" : "=r"(v[0]), "=r"(v[1]) : "r"(a) : "memory"); }
__device__ __forceinline__ void lds64f(float* v, uint32_t a) { asm volatile("ld.shared.v2.f32 {%0,%1}, [%2];" : "=f"(v[0]), "=f"(v[1]) : "r"(a) : "memory"); }
__device__ __forceinline__ void sts128(uint32_t a, const uint32_t* v) { asm volatile("st.shared.v4.b32 [%0], {%1,%2,%3,%4};" ::"r"(a), "r"(v[0]), "r"(v[1]), "r"(v[2]), "r"(v[3]) : "memory"); }
__device__ __forceinline__ void sts64(uint32_t a, uint32_t x, uint32_t y) { asm volatile("st.shared.v2.b32 [%0], {%1,%2};" ::"r"(a), "r"(x), "r"(y) : "memory"); }
__device__ __forceinline__ void sts32(uint32_t a, uint32_t x) { asm volatile("st.shared.b32 [%0], %1;" ::"r"(a), "r"(x) : "memory"); }
__device__ __forceinline__ bool mbar_try(uint32_t b, uint32_t par) {
    uint32_t ok;
    asm volatile("{\n.reg .pred P;\nmbarrier.test_wait.parity.shared::cta.b64 P, [%1], %2;\nselp.u32 %0, 1, 0, P;\n}" : "=r"(ok) : "r"(b), "r"(par) : "memory");
    return ok;
}
__device__ __forceinline__ void mbar_wait(uint32_t b, uint32_t par) {
    asm volatile("{\n.reg .pred P;\nW: mbarrier.try_wait.parity.shared::cta.b64 P, [%0], %1;\n@!P bra W;\n}" ::"r"(b), "r"(par) : "memory");
}
__device__ __forceinline__ void mbar_wait_bounded(uint32_t b, uint32_t par) {
    asm volatile("{\n.reg .pred P, Q;\n.reg .u32 t, u;\nmov.u32 t, %%globaltimer_lo;\nW: mbarrier.try_wait.parity.shared::cta.b64 P, [%0], %1;\n"
                 "mov.u32 u, %%globaltimer_lo;\nsub.u32 u, u, t;\nsetp.gt.u32 Q, u, 2000000000;\n@Q st.global.u32 [%2], 0;\n@!P bra W;\n}" ::"r"(b), "r"(par), "l"(0ull) : "memory");
}
__device__ __forceinline__ void declare_fence(int zero) { asm volatile(".reg .pred PNEVER;\nsetp.ne.u32 PNEVER, %0, 0;" ::"r"(zero)); }
__device__ __forceinline__ void sched_fence() { asm volatile("{\n.reg .pred Q;\n.reg .u32 x;\n@!PNEVER bra D;\nF: ld.volatile.global.u32 x, [%0];\nsetp.ne.u32 Q, x, 0;\n@Q bra F;\nD:\n}" ::"l"(0ull) : "memory"); }
__device__ __forceinline__ void mbar_init(uint32_t b, uint32_t n) { asm volatile("mbarrier.init.shared::cta.b64 [%0], %1;" ::"r"(b), "r"(n) : "memory"); }
__device__ __forceinline__ void mbar_expect(uint32_t b, uint32_t bytes) { asm volatile("mbarrier.arrive.expect_tx.shared::cta.b64 _, [%0], %1;" ::"r"(b), "r"(bytes) : "memory"); }
__device__ __forceinline__ void mbar_arrive(uint32_t b) { asm volatile("mbarrier.arrive.shared::cta.b64 _, [%0];" ::"r"(b) : "memory"); }
__device__ __forceinline__ void mbar_arrive_cluster(uint32_t b) { asm volatile("mbarrier.arrive.shared::cluster.b64 _, [%0];" ::"r"(b) : "memory"); }
__device__ __forceinline__ void cluster_sync() { asm volatile("barrier.cluster.arrive.relaxed.aligned;\nbarrier.cluster.wait.aligned;" ::: "memory"); }
__device__ __forceinline__ uint32_t get_epoch(uint32_t sb) { mbar_wait(sb + B_EPOCH, 0); return __shfl_sync(0xffffffffu, lds32(sb + S_EPOCH), 0); }
__device__ __forceinline__ void tma2d(uint32_t dst, const CUtensorMap* m, int c0, int c1, uint32_t bar) {
    asm volatile("cp.async.bulk.tensor.2d.shared::cluster.global.mbarrier::complete_tx::bytes [%0], [%1, {%2, %3}], [%4];" ::"r"(dst), "l"(m), "r"(c0), "r"(c1), "r"(bar) : "memory");
}
__device__ __forceinline__ void tma3d(uint32_t dst, const CUtensorMap* m, int c0, int c1, int c2, uint32_t bar) {
    asm volatile("cp.async.bulk.tensor.3d.shared::cluster.global.mbarrier::complete_tx::bytes [%0], [%1, {%2, %3, %4}], [%5];" ::"r"(dst), "l"(m), "r"(c0), "r"(c1), "r"(c2), "r"(bar) : "memory");
}
__device__ __forceinline__ void mbar_expect_e(uint32_t b, uint32_t bytes) {
    asm volatile("{\n.reg .pred E;\nelect.sync _|E, 0xffffffff;\n@E mbarrier.arrive.expect_tx.shared::cta.b64 _, [%0], %1;\n}" ::"r"(b), "r"(bytes) : "memory");
}
__device__ __forceinline__ void tma3d_mc_e(uint32_t dst, const CUtensorMap* m, int c0, int c1, int c2, uint32_t bar, uint16_t mask, uint64_t pol) {
    asm volatile("{\n.reg .pred E;\nelect.sync _|E, 0xffffffff;\n@E cp.async.bulk.tensor.3d.shared::cluster.global.mbarrier::complete_tx::bytes.multicast::cluster.L2::cache_hint [%0], [%1, {%2, %3, %4}], [%5], %6, %7;\n}" ::"r"(dst), "l"(m), "r"(c0), "r"(c1), "r"(c2), "r"(bar), "h"(mask), "l"(pol) : "memory");
}
__device__ __forceinline__ void tma4d_e(uint32_t dst, const CUtensorMap* m, int c0, int c1, int c3, uint32_t bar, uint64_t pol) {
    asm volatile("{\n.reg .pred E;\nelect.sync _|E, 0xffffffff;\n@E cp.async.bulk.tensor.4d.shared::cluster.global.mbarrier::complete_tx::bytes.L2::cache_hint [%0], [%1, {%2, %3, 0, %4}], [%5], %6;\n}" ::"r"(dst), "l"(m), "r"(c0), "r"(c1), "r"(c3), "r"(bar), "l"(pol) : "memory");
}
__device__ __forceinline__ void tma4d_mc_e(uint32_t dst, const CUtensorMap* m, int c0, int c1, int c3, uint32_t bar, uint16_t mask, uint64_t pol) {
    asm volatile("{\n.reg .pred E;\nelect.sync _|E, 0xffffffff;\n@E cp.async.bulk.tensor.4d.shared::cluster.global.mbarrier::complete_tx::bytes.multicast::cluster.L2::cache_hint [%0], [%1, {%2, %3, 0, %4}], [%5], %6, %7;\n}" ::"r"(dst), "l"(m), "r"(c0), "r"(c1), "r"(c3), "r"(bar), "h"(mask), "l"(pol) : "memory");
}
__device__ __forceinline__ void tma_prefetch4d_e(const CUtensorMap* m, int c0, int c3) {
    asm volatile("{\n.reg .pred E;\nelect.sync _|E, 0xffffffff;\n@E cp.async.bulk.prefetch.tensor.4d.L2.global [%0, {%1, 0, 0, %2}];\n}" ::"l"(m), "r"(c0), "r"(c3) : "memory");
}
__device__ __forceinline__ void tma_prefetch3d_e(const CUtensorMap* m, int c0, int c1, int c2) {
    asm volatile("{\n.reg .pred E;\nelect.sync _|E, 0xffffffff;\n@E cp.async.bulk.prefetch.tensor.3d.L2.global [%0, {%1, %2, %3}];\n}" ::"l"(m), "r"(c0), "r"(c1), "r"(c2) : "memory");
}
__device__ __forceinline__ void l2_prefetch_e(const void* src, uint32_t bytes) {
    asm volatile("{\n.reg .pred E;\nelect.sync _|E, 0xffffffff;\n@E cp.async.bulk.prefetch.L2.global [%0], %1;\n}" ::"l"(src), "r"(bytes) : "memory");
}
__device__ __forceinline__ void bulk_g2s_e(uint32_t dst, const void* src, uint32_t bytes, uint32_t bar) {
    asm volatile("{\n.reg .pred E;\nelect.sync _|E, 0xffffffff;\n@E cp.async.bulk.shared::cluster.global.mbarrier::complete_tx::bytes [%0], [%1], %2, [%3];\n}" ::"r"(dst), "l"(src), "r"(bytes), "r"(bar) : "memory");
}
__device__ __forceinline__ bool elect_one() {
    uint32_t r;
    asm volatile("{\n.reg .pred E;\nelect.sync _|E, 0xffffffff;\nselp.u32 %0, 1, 0, E;\n}" : "=r"(r));
    return r;
}
__device__ __forceinline__ void tma_store2d(const CUtensorMap* m, int c0, int c1, uint32_t src, uint64_t pol) {
    asm volatile("cp.async.bulk.tensor.2d.global.shared::cta.bulk_group.L2::cache_hint [%0, {%1, %2}], [%3], %4;" ::"l"(m), "r"(c0), "r"(c1), "r"(src), "l"(pol) : "memory");
}
__device__ __forceinline__ void bulk_commit() { asm volatile("cp.async.bulk.commit_group;" ::: "memory"); }
__device__ __forceinline__ void bulk_wait_read() { asm volatile("cp.async.bulk.wait_group.read 0;" ::: "memory"); }
__device__ __forceinline__ void bulk_wait_all() { asm volatile("cp.async.bulk.wait_group 0;" ::: "memory"); }
__device__ __forceinline__ uint64_t mkdesc(uint32_t addr, uint32_t lbo, uint32_t sbo, uint32_t swz) {
    return (uint64_t)((addr & 0x3FFFF) >> 4) | ((uint64_t)(lbo >> 4) << 16) | ((uint64_t)(sbo >> 4) << 32) | ((uint64_t)swz << 62);
}
__device__ __forceinline__ void wg_fence() { asm volatile("wgmma.fence.sync.aligned;" ::: "memory"); }
__device__ __forceinline__ void wg_commit() { asm volatile("wgmma.commit_group.sync.aligned;" ::: "memory"); }
template <int N> __device__ __forceinline__ void wg_wait() { asm volatile("wgmma.wait_group.sync.aligned %0;" ::"n"(N) : "memory"); }
template <typename T> __device__ __forceinline__ void pin_ptr(T*& p) { asm volatile("" : "+l"(p)); }
template <int N> __device__ __forceinline__ void pin(uint32_t* d) {
#pragma unroll
    for (int i = 0; i < N; i++) asm volatile("" : "+r"(d[i])::"memory");
}
template <int N> __device__ __forceinline__ void pin(float* d) {
#pragma unroll
    for (int i = 0; i < N; i++) asm volatile("" : "+f"(d[i])::"memory");
}

template <int TA, int TB>
__device__ __forceinline__ void wgmma_ss256(float* d, uint64_t da, uint64_t db) {
    asm volatile("wgmma.mma_async.sync.aligned.m64n256k16.f32.bf16.bf16 "
        "{%0, %1, %2, %3, %4, %5, %6, %7, %8, %9, %10, %11, %12, %13, %14, %15, %16, %17, %18, %19, %20, %21, %22, %23, %24, %25, %26, %27, %28, %29, %30, %31, %32, %33, %34, %35, %36, %37, %38, %39, %40, %41, %42, %43, %44, %45, %46, %47, %48, %49, %50, %51, %52, %53, %54, %55, %56, %57, %58, %59, %60, %61, %62, %63, %64, %65, %66, %67, %68, %69, %70, %71, %72, %73, %74, %75, %76, %77, %78, %79, %80, %81, %82, %83, %84, %85, %86, %87, %88, %89, %90, %91, %92, %93, %94, %95, %96, %97, %98, %99, %100, %101, %102, %103, %104, %105, %106, %107, %108, %109, %110, %111, %112, %113, %114, %115, %116, %117, %118, %119, %120, %121, %122, %123, %124, %125, %126, %127}, %128, %129, 1, 1, 1, %130, %131;"
        : "+f"(d[0]), "+f"(d[1]), "+f"(d[2]), "+f"(d[3]), "+f"(d[4]), "+f"(d[5]), "+f"(d[6]), "+f"(d[7]), "+f"(d[8]), "+f"(d[9]), "+f"(d[10]), "+f"(d[11]), "+f"(d[12]), "+f"(d[13]), "+f"(d[14]), "+f"(d[15]), "+f"(d[16]), "+f"(d[17]), "+f"(d[18]), "+f"(d[19]), "+f"(d[20]), "+f"(d[21]), "+f"(d[22]), "+f"(d[23]), "+f"(d[24]), "+f"(d[25]), "+f"(d[26]), "+f"(d[27]), "+f"(d[28]), "+f"(d[29]), "+f"(d[30]), "+f"(d[31]), "+f"(d[32]), "+f"(d[33]), "+f"(d[34]), "+f"(d[35]), "+f"(d[36]), "+f"(d[37]), "+f"(d[38]), "+f"(d[39]), "+f"(d[40]), "+f"(d[41]), "+f"(d[42]), "+f"(d[43]), "+f"(d[44]), "+f"(d[45]), "+f"(d[46]), "+f"(d[47]), "+f"(d[48]), "+f"(d[49]), "+f"(d[50]), "+f"(d[51]), "+f"(d[52]), "+f"(d[53]), "+f"(d[54]), "+f"(d[55]), "+f"(d[56]), "+f"(d[57]), "+f"(d[58]), "+f"(d[59]), "+f"(d[60]), "+f"(d[61]), "+f"(d[62]), "+f"(d[63]), "+f"(d[64]), "+f"(d[65]), "+f"(d[66]), "+f"(d[67]), "+f"(d[68]), "+f"(d[69]), "+f"(d[70]), "+f"(d[71]), "+f"(d[72]), "+f"(d[73]), "+f"(d[74]), "+f"(d[75]), "+f"(d[76]), "+f"(d[77]), "+f"(d[78]), "+f"(d[79]), "+f"(d[80]), "+f"(d[81]), "+f"(d[82]), "+f"(d[83]), "+f"(d[84]), "+f"(d[85]), "+f"(d[86]), "+f"(d[87]), "+f"(d[88]), "+f"(d[89]), "+f"(d[90]), "+f"(d[91]), "+f"(d[92]), "+f"(d[93]), "+f"(d[94]), "+f"(d[95]), "+f"(d[96]), "+f"(d[97]), "+f"(d[98]), "+f"(d[99]), "+f"(d[100]), "+f"(d[101]), "+f"(d[102]), "+f"(d[103]), "+f"(d[104]), "+f"(d[105]), "+f"(d[106]), "+f"(d[107]), "+f"(d[108]), "+f"(d[109]), "+f"(d[110]), "+f"(d[111]), "+f"(d[112]), "+f"(d[113]), "+f"(d[114]), "+f"(d[115]), "+f"(d[116]), "+f"(d[117]), "+f"(d[118]), "+f"(d[119]), "+f"(d[120]), "+f"(d[121]), "+f"(d[122]), "+f"(d[123]), "+f"(d[124]), "+f"(d[125]), "+f"(d[126]), "+f"(d[127])
        : "l"(da), "l"(db), "n"(TA), "n"(TB));
}
template <int TA, int TB>
__device__ __forceinline__ void wgmma_ss256_first(float* d, uint64_t da, uint64_t db) {
    asm volatile("wgmma.mma_async.sync.aligned.m64n256k16.f32.bf16.bf16 "
        "{%0, %1, %2, %3, %4, %5, %6, %7, %8, %9, %10, %11, %12, %13, %14, %15, %16, %17, %18, %19, %20, %21, %22, %23, %24, %25, %26, %27, %28, %29, %30, %31, %32, %33, %34, %35, %36, %37, %38, %39, %40, %41, %42, %43, %44, %45, %46, %47, %48, %49, %50, %51, %52, %53, %54, %55, %56, %57, %58, %59, %60, %61, %62, %63, %64, %65, %66, %67, %68, %69, %70, %71, %72, %73, %74, %75, %76, %77, %78, %79, %80, %81, %82, %83, %84, %85, %86, %87, %88, %89, %90, %91, %92, %93, %94, %95, %96, %97, %98, %99, %100, %101, %102, %103, %104, %105, %106, %107, %108, %109, %110, %111, %112, %113, %114, %115, %116, %117, %118, %119, %120, %121, %122, %123, %124, %125, %126, %127}, %128, %129, 0, 1, 1, %130, %131;"
        : "=f"(d[0]), "=f"(d[1]), "=f"(d[2]), "=f"(d[3]), "=f"(d[4]), "=f"(d[5]), "=f"(d[6]), "=f"(d[7]), "=f"(d[8]), "=f"(d[9]), "=f"(d[10]), "=f"(d[11]), "=f"(d[12]), "=f"(d[13]), "=f"(d[14]), "=f"(d[15]), "=f"(d[16]), "=f"(d[17]), "=f"(d[18]), "=f"(d[19]), "=f"(d[20]), "=f"(d[21]), "=f"(d[22]), "=f"(d[23]), "=f"(d[24]), "=f"(d[25]), "=f"(d[26]), "=f"(d[27]), "=f"(d[28]), "=f"(d[29]), "=f"(d[30]), "=f"(d[31]), "=f"(d[32]), "=f"(d[33]), "=f"(d[34]), "=f"(d[35]), "=f"(d[36]), "=f"(d[37]), "=f"(d[38]), "=f"(d[39]), "=f"(d[40]), "=f"(d[41]), "=f"(d[42]), "=f"(d[43]), "=f"(d[44]), "=f"(d[45]), "=f"(d[46]), "=f"(d[47]), "=f"(d[48]), "=f"(d[49]), "=f"(d[50]), "=f"(d[51]), "=f"(d[52]), "=f"(d[53]), "=f"(d[54]), "=f"(d[55]), "=f"(d[56]), "=f"(d[57]), "=f"(d[58]), "=f"(d[59]), "=f"(d[60]), "=f"(d[61]), "=f"(d[62]), "=f"(d[63]), "=f"(d[64]), "=f"(d[65]), "=f"(d[66]), "=f"(d[67]), "=f"(d[68]), "=f"(d[69]), "=f"(d[70]), "=f"(d[71]), "=f"(d[72]), "=f"(d[73]), "=f"(d[74]), "=f"(d[75]), "=f"(d[76]), "=f"(d[77]), "=f"(d[78]), "=f"(d[79]), "=f"(d[80]), "=f"(d[81]), "=f"(d[82]), "=f"(d[83]), "=f"(d[84]), "=f"(d[85]), "=f"(d[86]), "=f"(d[87]), "=f"(d[88]), "=f"(d[89]), "=f"(d[90]), "=f"(d[91]), "=f"(d[92]), "=f"(d[93]), "=f"(d[94]), "=f"(d[95]), "=f"(d[96]), "=f"(d[97]), "=f"(d[98]), "=f"(d[99]), "=f"(d[100]), "=f"(d[101]), "=f"(d[102]), "=f"(d[103]), "=f"(d[104]), "=f"(d[105]), "=f"(d[106]), "=f"(d[107]), "=f"(d[108]), "=f"(d[109]), "=f"(d[110]), "=f"(d[111]), "=f"(d[112]), "=f"(d[113]), "=f"(d[114]), "=f"(d[115]), "=f"(d[116]), "=f"(d[117]), "=f"(d[118]), "=f"(d[119]), "=f"(d[120]), "=f"(d[121]), "=f"(d[122]), "=f"(d[123]), "=f"(d[124]), "=f"(d[125]), "=f"(d[126]), "=f"(d[127])
        : "l"(da), "l"(db), "n"(TA), "n"(TB));
}
template <int TB>
__device__ __forceinline__ void wgmma_rs128(float* d, const uint32_t* a, uint64_t db, uint32_t acc) {
    asm volatile("{\n.reg .pred P;\nsetp.ne.u32 P, %69, 0;\nwgmma.mma_async.sync.aligned.m64n128k16.f32.bf16.bf16 "
        "{%0, %1, %2, %3, %4, %5, %6, %7, %8, %9, %10, %11, %12, %13, %14, %15, %16, %17, %18, %19, %20, %21, %22, %23, %24, %25, %26, %27, %28, %29, %30, %31, %32, %33, %34, %35, %36, %37, %38, %39, %40, %41, %42, %43, %44, %45, %46, %47, %48, %49, %50, %51, %52, %53, %54, %55, %56, %57, %58, %59, %60, %61, %62, %63}, {%64, %65, %66, %67}, %68, P, 1, 1, %70;\n}"
        : "+f"(d[0]), "+f"(d[1]), "+f"(d[2]), "+f"(d[3]), "+f"(d[4]), "+f"(d[5]), "+f"(d[6]), "+f"(d[7]), "+f"(d[8]), "+f"(d[9]), "+f"(d[10]), "+f"(d[11]), "+f"(d[12]), "+f"(d[13]), "+f"(d[14]), "+f"(d[15]), "+f"(d[16]), "+f"(d[17]), "+f"(d[18]), "+f"(d[19]), "+f"(d[20]), "+f"(d[21]), "+f"(d[22]), "+f"(d[23]), "+f"(d[24]), "+f"(d[25]), "+f"(d[26]), "+f"(d[27]), "+f"(d[28]), "+f"(d[29]), "+f"(d[30]), "+f"(d[31]), "+f"(d[32]), "+f"(d[33]), "+f"(d[34]), "+f"(d[35]), "+f"(d[36]), "+f"(d[37]), "+f"(d[38]), "+f"(d[39]), "+f"(d[40]), "+f"(d[41]), "+f"(d[42]), "+f"(d[43]), "+f"(d[44]), "+f"(d[45]), "+f"(d[46]), "+f"(d[47]), "+f"(d[48]), "+f"(d[49]), "+f"(d[50]), "+f"(d[51]), "+f"(d[52]), "+f"(d[53]), "+f"(d[54]), "+f"(d[55]), "+f"(d[56]), "+f"(d[57]), "+f"(d[58]), "+f"(d[59]), "+f"(d[60]), "+f"(d[61]), "+f"(d[62]), "+f"(d[63])
        : "r"(a[0]), "r"(a[1]), "r"(a[2]), "r"(a[3]), "l"(db), "r"(acc), "n"(TB));
}
template <int TB>
__device__ __forceinline__ void wgmma_rs64(float* d, const uint32_t* a, uint64_t db, uint32_t acc) {
    asm volatile("{\n.reg .pred P;\nsetp.ne.u32 P, %37, 0;\nwgmma.mma_async.sync.aligned.m64n64k16.f32.bf16.bf16 "
        "{%0, %1, %2, %3, %4, %5, %6, %7, %8, %9, %10, %11, %12, %13, %14, %15, %16, %17, %18, %19, %20, %21, %22, %23, %24, %25, %26, %27, %28, %29, %30, %31}, {%32, %33, %34, %35}, %36, P, 1, 1, %38;\n}"
        : "+f"(d[0]), "+f"(d[1]), "+f"(d[2]), "+f"(d[3]), "+f"(d[4]), "+f"(d[5]), "+f"(d[6]), "+f"(d[7]), "+f"(d[8]), "+f"(d[9]), "+f"(d[10]), "+f"(d[11]), "+f"(d[12]), "+f"(d[13]), "+f"(d[14]), "+f"(d[15]), "+f"(d[16]), "+f"(d[17]), "+f"(d[18]), "+f"(d[19]), "+f"(d[20]), "+f"(d[21]), "+f"(d[22]), "+f"(d[23]), "+f"(d[24]), "+f"(d[25]), "+f"(d[26]), "+f"(d[27]), "+f"(d[28]), "+f"(d[29]), "+f"(d[30]), "+f"(d[31])
        : "r"(a[0]), "r"(a[1]), "r"(a[2]), "r"(a[3]), "l"(db), "r"(acc), "n"(TB));
}
template <int TB>
__device__ __forceinline__ void wgmma_rs16(float* d, const uint32_t* a, uint64_t db, uint32_t acc) {
    asm volatile("{\n.reg .pred P;\nsetp.ne.u32 P, %13, 0;\nwgmma.mma_async.sync.aligned.m64n16k16.f32.bf16.bf16 "
        "{%0, %1, %2, %3, %4, %5, %6, %7}, {%8, %9, %10, %11}, %12, P, 1, 1, %14;\n}"
        : "+f"(d[0]), "+f"(d[1]), "+f"(d[2]), "+f"(d[3]), "+f"(d[4]), "+f"(d[5]), "+f"(d[6]), "+f"(d[7])
        : "r"(a[0]), "r"(a[1]), "r"(a[2]), "r"(a[3]), "l"(db), "r"(acc), "n"(TB));
}

__device__ __forceinline__ void wait_clocks(uint32_t n) {
    asm volatile("{\n.reg .pred P;\n.reg .u32 a, b;\nmov.u32 a, %%clock;\nW: mov.u32 b, %%clock;\nsub.u32 b, b, a;\nsetp.lt.u32 P, b, %0;\n@P bra W;\n}" ::"r"(n) : "memory");
}
__device__ __forceinline__ uint32_t gtime() { uint32_t t; asm volatile("mov.u32 %0, %%globaltimer_lo;" : "=r"(t)); return t; }
__device__ __forceinline__ uint32_t stamp_word(uint32_t seq) { return (gtime() & ~31u) | (seq & 31u); }
__device__ __forceinline__ void wait_time(uint32_t t, uint32_t sb) { while ((int32_t)(gtime() - t) < 0) {} }
#define NAPMODE 1
__device__ __forceinline__ void nap(uint32_t ns) { if (NAPMODE) wait_clocks(ns * 7 / 4); else __nanosleep(ns); }
template <int STRIDE>
__device__ __forceinline__ uint32_t latest_stamp(const uint32_t* p, uint32_t seq, uint32_t ref, uint32_t sb) {
#pragma unroll 1
    for (int n = opq(0, 0);; n++) {
        uint32_t bad = 0; int32_t m = INT32_MIN;
#pragma unroll
        for (int i = 0; i < 3; i++) { const uint32_t v = ld_relaxed1(p + i * STRIDE); bad |= (v ^ seq) & 31u; m = max(m, (int32_t)((v & ~31u) - ref)); }
        if (__all_sync(0xffffffffu, bad == 0)) return ref + __reduce_max_sync(0xffffffffu, m);
        nap(100);
        if (n > SPIN_LIMIT) spin_fault();
    }
}
constexpr uint32_t ONES = 0x3C003C00u, FULL = 0x50005000u;
__device__ __forceinline__ void pacer(const Params& P, const uint32_t sb, const int cta, const int lane, const uint32_t epoch) {
    uint8_t* const zp = P.xb + cta * 2048 + xg_lane(lane);
    if (lane < 3) asm volatile("prefetch.tensormap [%0];" ::"l"(&P.tm[lane == 0 ? M_C1 + cta % 3 : lane == 1 ? M_CO : M_SEG]) : "memory");
    uint32_t e0 = 0;
#pragma unroll 2
    for (int i = 0; i < 32; i++) { const uint4 u = __ldg((const uint4*)P.mem0 + i * 32 + lane); e0 = amax(amax(e0, amax(u.x, u.y)), amax(u.z, u.w)); }
    e0 = min(max(warp_exp(e0), 31u), 253u) - 14;
    if (cta < 32) {
        const uint32_t* m = (const uint32_t*)(P.mem0 + (lane >> 2) * 1024 + cta * 32 + (lane & 3) * 2);
        const float sc = __uint_as_float((254 - e0) << 23);
        auto cv = [&](uint32_t u) { return pack2h(bf_lo(u) * sc, bf_hi(u) * sc); };
        const uint32_t y = cv(m[12]);
        st_relaxed4(zp, cv(m[0]), cv(m[4]), cv(m[8]), prmt(y, FULL, 0x7610));
        st_relaxed1(P.xb + xg_side(cta) + lane * 4, prmt(y, FULL, 0x3254));
    }
    if (cta < 40) {
#pragma unroll 1
        for (int b = 1; b < 4; b++) st_relaxed4(zp + xg_buf(b), 0, 0, 0, 0);
    }
    __threadfence();
    const uint32_t* ts = (const uint32_t*)(P.xb + XG_T) + lane;
    int32_t d0 = P.dly;
    const uint32_t go = mapa(sb + B_GO, (cta / 3 & 1) * 3 + 1 + (lane & 1));
    auto free_segment = [&]() { if (lane == 0) mbar_expect(sb + B_KVFULL, 16384); __syncwarp(); if (lane < 2) mbar_arrive_cluster(go); };
    for (int n = 0; (int32_t)(ld_acquire(&g_cnt(C_XCNT)) - (epoch + 1) * 256) < 0; n++) { __nanosleep(500); if (n > SPIN_LIMIT) spin_fault(); }
    const uint32_t ex = max(ld_relaxed1(&g_cnt(C_XMAX)) & 255, 67u);
    mbar_wait_bounded(sb + B_READY, 0);
    free_segment();
    if (lane == 0) st_relaxed2(g_hint + cta * 32, stamp_word(epoch + 1), lds32(sb + S_EV) | lds32(sb + S_EO) << 16);
    uint32_t a = gtime();
    for (int n = 0;; n++) {
        uint32_t bad = 0, e = 0; int32_t m = INT32_MIN;
#pragma unroll
        for (int i = 0; i < 3; i++) {
            uint32_t v[2];
            ld_relaxed2(v, g_hint + lane * 32 + i * 1024);
            bad |= (v[0] ^ (epoch + 1)) & 31u; m = max(m, (int32_t)((v[0] & ~31u) - a)); e = __vmaxu2(e, v[1]);
        }
        if (__all_sync(0xffffffffu, bad == 0)) {
            a += __reduce_max_sync(0xffffffffu, m);
            const uint32_t ev = __reduce_max_sync(0xffffffffu, e & 255), eo = __reduce_max_sync(0xffffffffu, e >> 16);
            if (lane == 0) { sts64(sb + S_SC, max(ev, 97u) + max(eo, 97u) - 244, ex); sts32(sb + S_ISC, e0 * 0x800080u); }
            break;
        }
        wait_clocks(100);
        if (n > SPIN_LIMIT) spin_fault();
    }
    wait_time(a, sb);
    if (lane == 0) mbar_arrive(sb + B_RELM);
#pragma unroll 1
    for (int s = 0; s < 63; s++) {
        const uint32_t seq = epoch * 63 + s + 1;
        mbar_wait_bounded(sb + B_P1, s & 1);
        const uint32_t tx = gtime();
        if (lane == 0) st_relaxed1(ts + (s & 1) * 256 + cta, (tx & ~31u) | (seq & 31u));
        if (s > 0) {
            const int32_t e0 = latest_stamp<32>(ts + (~s & 1) * 256 + 128, seq - 1, a, sb) + P.mrg - a;
            d0 += min(max(e0, min(e0 + P.guard, -P.clamp0)), P.clampv) / 2;
        }
        while ((int32_t)(gtime() - tx) < P.rd) nap(20);
        a = latest_stamp<32>(ts + (s & 1) * 256, seq, tx, sb) + d0;
        while ((int32_t)(a - gtime()) > 250) nap(40);
        wait_time(a, sb);
        if (lane == 0) mbar_arrive(sb + B_RELM);
        mbar_wait_bounded(sb + B_RED, s & 1);
        const uint32_t g = tx + __reduce_max_sync(0xffffffffu, lds32(sb + S_TO + (lane & 7) * 4) - tx);
        if (lane == 0) st_relaxed1(ts + (s & 1) * 256 + 128 + cta, (g & ~31u) | (seq & 31u));
        if (s < 62) { if (P.kvd) nap(P.kvd); free_segment(); }
    }
}
__device__ __forceinline__ void st_async2(uint32_t a, uint32_t x, uint32_t y, uint32_t bar) {
    asm volatile("st.async.weak.shared::cluster.mbarrier::complete_tx::bytes.v2.b32 [%0], {%1,%2}, [%3];" ::"r"(a), "r"(x), "r"(y), "r"(bar) : "memory");
}
__device__ __forceinline__ uint32_t xor_or(uint32_t a, uint32_t b, uint32_t t) { uint32_t d; asm("lop3.b32 %0, %1, %2, %3, 0x7E;" : "=r"(d) : "r"(a), "r"(b), "r"(t)); return d; }
__device__ __forceinline__ bool tags_ok(uint32_t bad, uint32_t mask = 1) {
    uint32_t r;
    asm volatile("{\n.reg .pred P;\n.reg .b32 x;\nand.b32 x, %1, %2;\nsetp.ne.b32 P, x, 0;\nvote.sync.any.pred P, P, 0xffffffff;\nselp.u32 %0, 0, 1, P;\n}" : "=r"(r) : "r"(bad), "r"(mask));
    return r;
}
constexpr int SROW = 56;
#define PREA 8
#define PREB 9
#define RING1 6
#define RING2 7
#define RING3 8
#define PRE2 10
#define PRE2A 0
#define PRE3 0
#define EFENCE 0
#define RFENCE 1
#define PROG 16
#define EARLY 0
#define PLATE 1
#define NDEP 0
#define EFENCE2 0
#define IVSLOT 15
#define LAG2 8
#define LAG 4
#define PUT1 33
#define DEPS 3
#define ADELAY 120
#define BDELAY 0
#define HOLD 1
#define XDELAY 330
#define FENCEA 0x80
#define FENCEB 0x80
#define FENCE2 0x220
#define OFENCE 0
#define MASK3 0x57
#define MASK4 0x55
#define MASK5 0x25
#define OFF3 0x5320
#define OFF4 0x6420
#define OFF5 0x0520
#define RESA (NRA == 3 ? 15 : NRA == 4 ? 3 : 0)
#define RESB (NRB == 3 ? 0xcc : NRB == 4 ? 0x30 : 0)
#define RESB1 (NRB == 3 ? 0xcc : NRB == 4 ? 0xc : 0)
__host__ __device__ constexpr int smem_mask(int NR) { return NR == 3 ? MASK3 : NR == 4 ? MASK4 : MASK5; }
__host__ __device__ constexpr bool round_smem(int r, int NR) { return smem_mask(NR) >> r & 1; }
__host__ __device__ constexpr int kord(int r, int NR) { int c = 0; for (int i = 0; i < r; i++) c += round_smem(i, NR) == round_smem(r, NR); return round_smem(r, NR) ? NR + c : c; }
__host__ __device__ constexpr int slot_r(int n, int NR) { return n < 32 ? n >> 2 : (((n & 31) >> 2) + ((NR == 3 ? OFF3 : NR == 4 ? OFF4 : OFF5) >> (n & 3) * 4)) & 7; }
__host__ __device__ constexpr int slot_k(int n, int NR) { return kord(slot_r(n, NR), NR); }
__host__ __device__ constexpr int slot_sord(int n, int NR) { int c = 0; for (int i = 0; i < n; i++) c += slot_k(i, NR) >= NR; return c; }
__host__ __device__ constexpr int sfrag_slot(int q, int NR) { for (int n = 0; n < 64; n++) if (slot_k(n, NR) >= NR && slot_sord(n, NR) == q) return n; return -1; }
__host__ __device__ constexpr int w1_loaded(int n, int NR, int PRE) {
    int q = PRE;
    for (int i = 0; i <= n; i++) q += q < (8 - NR) * 8 && q - slot_sord(i + 1, NR) < (i < 32 ? RING1 : RING2);
    return q;
}
template <int Q, int NR>
__device__ __forceinline__ void load_w1(uint32_t* w, const uint32_t* a) {
    constexpr int n = sfrag_slot(Q, NR);
    ldsm4t(w, a[n & 3] + ((slot_k(n, NR) - NR) * 2 + (n >> 5)) * 2048);
}
constexpr int AB = NRA < 5, BB = 3 - AB;
__device__ __forceinline__ bool w2_full(int role, int warp) { return warp < (role == 2 ? 2 : 3); }
__device__ __forceinline__ int w2_nblk(int role, int warp) { return warp < 4 ? BB - !w2_full(role, warp) : AB; }
__host__ __device__ constexpr int w2_step(bool full, int i) { return AB ? (full ? 2 * i : 0) : full ? (i == 0 ? 0 : i == 1 ? 16 - 2 * EARLY : 18 - 2 * EARLY) : i; }
__device__ __forceinline__ int w2_block(int role, int warp) {
    const int f = role * 3 + warp, g = role == 2 ? warp : role;
    if (AB) return (warp >= 4 ? role * 4 + (warp - 4) : w2_full(role, warp) ? 16 + 4 * (f >> 1) + (f & 1) : 12 + g) ^ EARLY;
    return w2_full(role, warp) ? EARLY + 4 * (f >> 1) + (f & 1) : EARLY + 2 + 4 * g;
}
__device__ __forceinline__ int w2_res(int role, int warp) { return warp >= 4 ? RESA : w2_full(role, warp) ? RESB : RESB1; }
__device__ __forceinline__ int w2_units(int role, int warp) { return w2_nblk(role, warp) * 4 - (5 - (warp < 4 ? NRB : NRA)) * 2; }
constexpr int W2B = (BB * 4 - (5 - NRB) * 2) * 2048, W2A = (AB * 4 - (5 - NRA) * 2) * 2048;
static_assert(S_W2 + 4 * W2B - 8192 + 4 * W2A == S_KV, "weights");
__device__ __forceinline__ int w1_base(int warp) { return S_W1 + (warp < 4 ? warp * (8 - NRB) : 4 * (8 - NRB) + (warp - 4) * (8 - NRA)) * 4096; }
__device__ __forceinline__ int w2_base(int warp) { return S_W2 + (warp < 4 ? warp * W2B : 4 * W2B - 8192 + (warp - 4) * W2A); }
__device__ __forceinline__ void chain_load(const Params& P, uint32_t sb, int cta, int warp, int lane, int round) {
    const int role = cta % 3, h = cta / 3;
    mbar_expect_e(sb + B_INIT, round ? (8 - (warp < 4 ? NRB : NRA)) * 4096 : 20480);
    if (round) mbar_expect_e(sb + B_INIT2, w2_units(role, warp) * 2048);
    __syncwarp();
    const int m1 = (warp < 4 ? smem_mask(NRB) : smem_mask(NRA)) ^ (round ? 0 : 255), below = (1 << lane) - 1;
    const int m2 = (w2_res(role, warp) ^ (round ? 0xfff : 0)) & ((1 << w2_nblk(role, warp) * 4) - 1);
    const uint32_t d1 = sb + (round ? w1_base(warp) : warp * 20480), d2 = round ? sb + w2_base(warp) : d1 + __popc(m1) * 4096;
    if (m1 >> lane & 1) tma3d(d1 + __popc(m1 & below) * 4096, &P.tm[M_C1 + role], 0, warp * 128 + lane * 16, h * 2, sb + B_INIT);
    __syncwarp();
    if (m2 >> lane & 1)
        tma2d(d2 + __popc(m2 & below) * 2048, &P.tm[M_CO], (w2_block(role, warp) + w2_step(w2_full(role, warp), lane >> 2)) * 32, h * 128 + (lane & 3) * 32, sb + (round ? B_INIT2 : B_INIT));
    __syncwarp();
}

__device__ __forceinline__ void put_partials(bool TR, uint32_t a, const float* x, const float* y) {
    if (TR) stsm4t(a, pack2(x[0], x[1]), pack2(x[2], x[3]), pack2(y[0], y[1]), pack2(y[2], y[3]));
    else stsm4(a, pack2(x[0], x[1]), pack2(x[2], x[3]), pack2(y[0], y[1]), pack2(y[2], y[3]));
}
template <int NR, int PRE, int FM, int B, int E>
__device__ __forceinline__ void project(float (*acc)[4], bool TR, const uint32_t (*wr)[4], uint32_t (*as)[4], uint32_t (*v)[4], uint32_t* x, const uint32_t* w1a, uint32_t pp, uint32_t zero) {
    static_for<B, E>([&](auto I) {
        constexpr int n = I.value, kk = slot_k(n, NR), T = (n >> 5) * 4 + (n & 3), so = slot_sord(n, NR), q = w1_loaded(n - 1, NR, PRE);
        constexpr bool sm = kk >= NR;
        const uint32_t* w = sm ? as[so] : wr[sm ? 0 : (kk * 2 + (n >> 5)) * 4 + (n & 3)];
        if constexpr (n == 32 && PUT1 < 32) { put_partials(TR, pp, acc[0], acc[1]); put_partials(TR, pp + 4096, acc[2], acc[3]); }
        if constexpr (n == 0) {
            const uint32_t c = prmt(v[0][3], x[0], 0x3254);
            v[0][0] = h2bf(v[0][0], v[0][0]); v[0][1] = h2bf(v[0][1], v[0][1]); v[0][2] = h2bf(v[0][2], v[0][2]); v[0][3] = h2bf(v[0][3], x[0]);
            x[0] = c;
        }
        if constexpr ((n & 31) < 4) acc[T][0] = acc[T][1] = acc[T][2] = acc[T][3] = 0.f;
        mma16816(acc[T], w[0], w[1], w[2], w[3], v[slot_r(n, NR) >> 1][(slot_r(n, NR) & 1) * 2], v[slot_r(n, NR) >> 1][(slot_r(n, NR) & 1) * 2 + 1]);
        if constexpr (n == DEPS) {
            const uint32_t sel = __float_as_uint(acc[T][0]) * zero + 0x7610;
#pragma unroll
            for (int b = 1; b < 4; b++) {
                if (b <= NDEP) cvt_block(v[b], x[b], sel);
                else {
                    const uint32_t c = prmt(v[b][3], x[b], 0x3254);
                    v[b][0] = h2bf(v[b][0], v[b][0]); v[b][1] = h2bf(v[b][1], v[b][1]); v[b][2] = h2bf(v[b][2], v[b][2]); v[b][3] = h2bf(v[b][3], x[b]);
                    x[b] = c;
                }
            }
        }
        if constexpr (w1_loaded(n, NR, PRE) > q) load_w1<q, NR>(as[q], w1a);
        if constexpr (n == PUT1 && n >= 32) { put_partials(TR, pp, acc[0], acc[1]); put_partials(TR, pp + 4096, acc[2], acc[3]); }
        if constexpr (n % 4 == 3 && (FM >> (n / 4) & 1) && n != E - 1) sched_fence();
    });
    if constexpr (E == 64) { put_partials(TR, pp + 8192, acc[4], acc[5]); put_partials(TR, pp + 12288, acc[6], acc[7]); }
}
__device__ __forceinline__ void reduce8(const uint32_t (*x)[4], const uint32_t* sel, float sc, uint32_t& r0, uint32_t& r1) {
    float d[4][4];
#pragma unroll
    for (int i = 0; i < 4; i++) {
        d[i][0] = d[i][1] = d[i][2] = d[i][3] = 0.f;
        mma16816(d[i], x[i][0], x[i][1], x[i][2], x[i][3], sel[2 * i], sel[2 * i + 1]);
    }
    r0 = pack2(((d[0][0] + d[1][0]) + (d[2][0] + d[3][0])) * sc, ((d[0][1] + d[1][1]) + (d[2][1] + d[3][1])) * sc);
    r1 = pack2(((d[0][2] + d[1][2]) + (d[2][2] + d[3][2])) * sc, ((d[0][3] + d[1][3]) + (d[2][3] + d[3][3])) * sc);
}

__host__ __device__ constexpr int wo_count(int n, int RES, bool res) { int c = 0; for (int i = 0; i < n; i++) c += (RES >> (i >> 2) & 1) == res; return c; }
__host__ __device__ constexpr int wo_loaded(int n, int RES, int PRE, int end) { int q = PRE; for (int i = 0; i <= n; i++) q += q < end && q - wo_count(i + 1, RES, false) < RING3; return q; }
template <int Q>
__device__ __forceinline__ void load_w2(uint32_t* w, const uint32_t* a) { ldsm4t(w, a[Q & 1] + (Q >> 1) * 1024); }
template <int NB, int RES, int PRE, int FM>
__device__ __forceinline__ void wo_blocks(uint32_t (*w)[4], const uint32_t (*wp)[4], uint32_t oa, uint32_t ia, const uint32_t* wa, const uint8_t* dst, const uint8_t* dsd, bool odd) {
    float a[NB][4][4], iv[2];
    uint32_t o[4][4], r[5];
    bar_sync(3, 256);
#pragma unroll
    for (int i = 0; i < 4; i++) ldsm4(o[i], oa + i * 512);
    if (FM & 1) sched_fence();
    static_for<0, NB * 16>([&](auto I) {
        constexpr int n = I.value, i = n & 15, end = wo_count(NB * 16, RES, false), q = wo_loaded(n - 1, RES, PRE, end);
        constexpr bool res = RES >> (n >> 2) & 1;
        const uint32_t* b = o[i >> 2] + (i & 2);
        const uint32_t* x = res ? wp[wo_count(n, RES, true)] : w[wo_count(n, RES, false)];
        float* d = a[n >> 4][i & 3];
        if constexpr (i < 4) d[0] = d[1] = d[2] = d[3] = 0.f;
        mma16816(d, x[0], x[1], x[2], x[3], b[0], b[1]);
        if constexpr (wo_loaded(n, RES, PRE, end) > q) load_w2<q>(w[q], wa);
        if constexpr (n == IVSLOT) { bar_sync(4, 160); lds64f(iv, ia); }
        if constexpr (n == NB * 16 - 1 || (n >= 16 && i == LAG - 1)) {
            const float (*e)[4] = a[n == NB * 16 - 1 ? NB - 1 : (n >> 4) - 1];
            const uint32_t y = pack2h((e[1][2] + e[3][2]) * iv[0], (e[1][3] + e[3][3]) * iv[1]);
            r[0] = movm(pack2h((e[0][0] + e[2][0]) * iv[0], (e[0][1] + e[2][1]) * iv[1])); r[1] = movm(pack2h((e[0][2] + e[2][2]) * iv[0], (e[0][3] + e[2][3]) * iv[1]));
            r[2] = movm(pack2h((e[1][0] + e[3][0]) * iv[0], (e[1][1] + e[3][1]) * iv[1])); r[3] = movm(odd ? ONES : y); r[4] = movm(odd ? y : ONES);
        }
        if constexpr (n == NB * 16 - 1 || (n >= 16 && i == LAG2 - 1)) {
            constexpr int bs = w2_step(NB == BB, n == NB * 16 - 1 ? NB - 1 : (n >> 4) - 1);
            red_add4(dst + bs * 2048, r[0], r[1], r[2], r[3]);
            red_add1(dsd + (bs >> 1) * 1024 + (bs & 1) * 256, r[4]);
        }
        if constexpr (((FM >> (n / 4 + 1)) & 1) && (n & 3) == 3 && n != NB * 16 - 1) sched_fence();
    });
}
#define FRAG1(ln) ((((ln) & 7) + ((ln) >> 4) * 8) * 128 + ((((((ln) >> 3) & 1) << (ROLE == 1)) ^ ((ln) & 7)) << 4))
#define FRAG2(ln) ((((ln) & 7) + ((ln) >> 4) * 8) * 64 + (((((ln) >> 3) & 1) ^ (((ln) >> 1) & 3)) << 4))
#define TILE_X(i) (ROLE == 1 ? (((i) >> 1) << 6) | (((i) & 1) << 4) : (i) << 5)
__device__ __forceinline__ void chain_fetch(const Params& P, const uint32_t sb, const int cta, const int warp, const int lane, uint32_t (*wr)[4]) {
    const int ROLE = cta % 3, nr = warp < 4 ? NRB : NRA;
    mbar_wait(sb + B_INIT, 0);
#pragma unroll
    for (int f = 0; f < 40; f++) {
        const bool w1 = f < (NRA < NRB ? NRA : NRB) * 8 || f < nr * 8;
        ldsm4t(wr[f], sb + warp * 20480 + (f >> 2) * 2048 + (w1 ? FRAG1(lane) ^ TILE_X(f & 3) : (f & 2) * 512 + (FRAG2(lane) ^ ((f & 1) << 5))));
    }
    fence_async_smem();
    mbar_wait(sb + B_SFREE + (warp >> 2) * 8, 0);
    bar_sync(1, 256);
    chain_load(P, sb, cta, warp, lane, 1);
}
__device__ __forceinline__ void chain_bounds(const uint32_t sb, const int cta, const int warp, const int lane, const uint32_t (*wr)[4]) {
    const int ROLE = cta % 3, nr = warp < 4 ? NRB : NRA;
    uint32_t m[6] = {}, u[4];
#pragma unroll
    for (int f = 0; f < 40; f++) m[f < 24 ? 0 : f >> 3] = amax4(m[f < 24 ? 0 : f >> 3], wr[f]);
    uint32_t m1 = amax(m[0], amax(nr > 3 ? m[3] : 0, nr > 4 ? m[4] : 0)), m2 = amax(nr > 3 ? 0 : m[3], nr > 4 ? 0 : m[4]);
    mbar_wait(sb + B_INIT, 1);
    if (ROLE == 2) {
#pragma unroll 4
        for (int i = 0; i < S_W2 / 4096; i++) { lds128(u, sb + S_W1 + warp * (S_W2 / 8) + i * 512 + lane * 16); m1 = amax4(m1, u); }
    }
    mbar_wait(sb + B_INIT2, 0);
    const int n = w2_units(ROLE, warp) * 4;
#pragma unroll 4
    for (int i = 0; i < n; i++) { lds128(u, sb + w2_base(warp) + i * 512 + lane * 16); m2 = amax4(m2, u); }
    m1 = warp_exp(m1); m2 = warp_exp(m2);
    if (lane == 0) { if (ROLE == 2) red_max_shared(sb + S_EV, m1); red_max_shared(sb + S_EO, m2); }
}
template <bool ATT>
__device__ __forceinline__ void chain_role(const Params& P, const uint32_t sb, const int cta, const int warp, const int lane, const uint32_t (*wr)[4]) {
    constexpr int NR = ATT ? NRA : NRB, PRE = ATT ? PREA : PREB;
    const int h = cta / 3, ROLE = cta - h * 3;
    uint32_t l8 = opq(sb + lane * 8, lane);
    const uint8_t* persu = (const uint8_t*)((ROLE == 1 ? g_km : g_vmt) + h * 512) - (sb >> 1);
    auto persist = [&](int s, int tile, uint32_t r0, uint32_t r1) {
        uint32_t* pp = (uint32_t*)(persu + s * 65536 + (ROLE == 1 ? (tile >> 1) * 512 + (tile & 1) * 128 : tile * 256) + (l8 >> 1));
        pp[0] = r0; pp[ROLE == 1 ? 64 : 32] = r1;
    };
    const uint32_t rk0 = (h & 1) * 3, rd1 = __shfl_sync(0xffffffffu, mapa(sb, rk0 + (ROLE + 1) % 3) - sb, 0), rd2 = __shfl_sync(0xffffffffu, mapa(sb, rk0 + (ROLE + 2) % 3) - sb, 0);
    const uint32_t xo = (ROLE == 2 ? S_XV : S_X + ROLE * 2048) + warp * 256;
    const bool full = w2_full(ROLE, warp);
    const int blk = w2_block(ROLE, warp);
    const uint32_t om = blk * 2048, os = xg_side(blk);
    const uint32_t w1o = sb + w1_base(warp), w2o = sb + w2_base(warp);
    if (lane == 0) mbar_arrive(sb + B_READY);
#pragma unroll 1
    for (int s = 0;; s++) {
        l8 += s & P.zero;
        uint32_t r0, r1;
        {
            uint32_t v[4][4], as[(8 - NR) * 8][4], w1a[4];
            float acc[8][4];
            const uint32_t pst = sb + S_P1 + (l8 - sb) * 16 + ((warp * 16) ^ ((l8 & 56) * 2));
#pragma unroll
            for (int i = 0; i < 4; i++) w1a[i] = w1o + (FRAG1((l8 - sb) >> 3) ^ TILE_X(i));
            auto preload = [&]() { static_for<0, PRE>([&](auto I) { load_w1<I.value, NR>(as[I.value], w1a); }); };
#pragma unroll 1
            while (true) {
                uint32_t x[4];
                if (!(PLATE >> ATT & 1)) preload();
                const uint32_t lm = opq(l8 - sb, (l8 - sb) >> 3);
                const uint8_t* pm = P.xb + xg_buf(s) + warp * 8192 + xg_lane(lm >> 3);
                const uint8_t* ps = P.xb + xg_buf(s) + XG_SIDE + warp * 2048 + (lm >> 1);
                pin_ptr(pm); pin_ptr(ps);
                mbar_wait(sb + B_RELM, s & 1);
                if (ATT ? ADELAY : BDELAY) wait_clocks(ATT ? ADELAY : BDELAY);
#pragma unroll
                for (int b = 0; b < 4; b++) { ld_relaxed4(v[b], pm + b * 2048); ld_relaxed1n(x[b], ps + (b >> 1) * 1024 + (b & 1) * 256); }
                if (PLATE >> ATT & 1) { preload(); if (PLATE >> (ATT + 2) & 1) sched_fence(); }
                project<NR, PRE, ATT ? FENCEA : FENCEB, 0, PROG>(acc, ROLE == 2, wr, as, v, x, w1a, pst, P.zero);
                const uint32_t bad = xor_or(x[0], x[1], FULL) | xor_or(x[2], x[3], FULL);
                if (tags_ok(bad, 0xffffffffu)) break;
            }
            project<NR, PRE, ATT ? FENCEA : FENCEB, PROG, 64>(acc, ROLE == 2, wr, as, v, nullptr, w1a, pst, 0);
            const uint32_t isc = lds32(sb + S_ISC + (s & 1) * 4);
            const uint32_t lq = l8 + ((s >> 3) & P.zero), e1 = s == 63 ? 0 : rd1, e2 = s == 63 ? 0 : rd2;
            uint32_t x[4][4], sel[8], xd[6] = {l8 + xo, l8 + xo + e1, l8 + xo + e2, sb + B_X + e1, sb + B_X + e2, sb + S_P1 + warp * 2048 + (lq & 64) * 16 + (lq & 128) + (lq & 56) * 2};
#pragma unroll
            for (int i = 0; i < 8; i++) sel[i] = (lq & 224) == i * 32 ? 0x3F803F80u : 0u;
            pin<6>(xd); pin<8>(sel);
            if (RFENCE) sched_fence();
            bar_sync(1, 256);
#pragma unroll
            for (int i = 0; i < 4; i++) ldsm4t(x[i], xd[5] + i * 256);
            if (!ATT && l8 == sb + (warp - 3) * 1024) mbar_arrive(sb + B_P1);
            uint32_t em = warp_exp(amax(amax4(amax(amax(v[0][0], v[0][1]), amax(v[0][2], v[0][3])), v[1]), amax4(amax(amax(v[2][0], v[2][1]), amax(v[2][2], v[2][3])), v[3])));
            if (EFENCE2) sched_fence();
            reduce8(x, sel, bf_hi(isc), r0, r1);
            st_async2(xd[1], r0, r1, xd[3]);
            st_async2(xd[2], r0, r1, xd[4]);
            sts64(xd[0], r0, r1);
            if (s == 63) { persist(s, warp, r0, r1); break; }
            if (l8 == sb) sts32(sb + S_EM + warp * 4, em + (isc >> 23));
            __syncwarp();
            if (l8 == sb) mbar_arrive(sb + B_X);
        }
        uint32_t w[40][4], w2a[2], odd;
        const uint8_t *po, *pd;
        auto wo_addr = [&]() {
            const uint32_t lo = (l8 + ((s >> 2) & P.zero) - sb) >> 3;
            w2a[0] = w2o + FRAG2(lo); w2a[1] = w2o + (FRAG2(lo) ^ 32);
            po = P.xb + xg_buf(s + 1) + om + xg_lane(lo);
            pd = P.xb + xg_buf(s + 1) + os + lo * 4;
            odd = lo & 4;
            pin_ptr(po); pin_ptr(pd); pin<2>(w2a); pin<1>(&odd);
        };
        uint32_t oa = l8 * 2 + (S_OX - sb);
        if constexpr (ATT) {
            const uint32_t ln = (l8 + ((s >> 4) & P.zero) - sb) >> 3;
            const uint32_t va = sb + S_KV + 8192 + ((warp >> 1) & 1) * 4096 + ((ln & 7) + (ln >> 4) * 8) * 128 + ((((warp & 1) * 4 + ((ln >> 3) & 1)) ^ (ln & 7)) << 4);
            const uint32_t ka = sb + S_KV + (warp & 1) * 2048 + (ln & 15) * 128 + (((ln >> 4) ^ (ln & 7)) << 4);
            uint32_t ad[5] = {sb + S_SX + (ln & 3) * (8 * SROW) + (ln >> 2) * 4 + (warp < 6 ? (warp - 4) * 64 : 128 + (warp - 6) * 32), l8 + S_XV + (warp - 4) * 512,
                              l8 + S_SX + (ln >> 2) * (4 * SROW - 32), oa + (warp - 4) * 512, sb + S_ISC + (~s & 1) * 4};
            if constexpr (AB) { wo_addr(); pin<1>(&oa); }
            pin<5>(ad);
            const uint32_t sa = ad[0], sr = ad[2];
            uint32_t vf[4][4], vm[2][2], q[8][2];
            float S[8][4];
#pragma unroll
            for (int n = 0; n < 8; n++) { S[n][0] = S[n][1] = S[n][2] = S[n][3] = 0.f; }
            mbar_wait(sb + B_KVFULL, s & 1);
            if (warp < 6) {
                uint32_t kf[8][4];
#pragma unroll
                for (int k = 0; k < 8; k++) ldsm4(kf[k], (ka ^ ((k & 3) << 5)) + (k >> 2) * 4096);
#pragma unroll
                for (int i = 0; i < 4; i++) ldsm4t(vf[i], (va ^ ((i & 1) << 5)) + (i >> 1) * 2048);
                mbar_wait(sb + B_X, s & 1);
#pragma unroll
                for (int k = 0; k < 8; k++) lds64(q[k], l8 + S_X + k * 256);
#pragma unroll
                for (int k = 0; k < 8; k++) mma16816(S[k], kf[k][0], kf[k][1], kf[k][2], kf[k][3], q[k][0], q[k][1]);
#pragma unroll
                for (int k = 0; k < 4; k++) { S[k][0] = S[2 * k][0] + S[2 * k + 1][0]; S[k][1] = S[2 * k][1] + S[2 * k + 1][1]; S[k][2] = S[2 * k][2] + S[2 * k + 1][2]; S[k][3] = S[2 * k][3] + S[2 * k + 1][3]; }
                sts32(sa, __float_as_uint((S[0][0] + S[1][0]) + (S[2][0] + S[3][0])));
                sts32(sa + 4 * SROW, __float_as_uint((S[0][1] + S[1][1]) + (S[2][1] + S[3][1])));
                sts32(sa + 32, __float_as_uint((S[0][2] + S[1][2]) + (S[2][2] + S[3][2])));
                sts32(sa + 4 * SROW + 32, __float_as_uint((S[0][3] + S[1][3]) + (S[2][3] + S[3][3])));
            } else {
#pragma unroll
                for (int i = 0; i < 4; i++) ldsm4t(vf[i], (va ^ ((i & 1) << 5)) + (i >> 1) * 2048);
                uint32_t xa = l8 + S_X + (warp - 6) * 1024;
                pin<1>(&xa);
                mbar_wait(sb + B_X, s & 1);
#pragma unroll
                for (int k = 0; k < 8; k++) lds64(q[k], xa + (k >> 2) * 2048 + (k & 3) * 256);
#pragma unroll
                for (int k = 0; k < 4; k++) mma16816(S[k], q[4 + (k & 2)][0], q[4 + (k & 2)][1], q[5 + (k & 2)][0], q[5 + (k & 2)][1], q[k][0], q[k][1]);
                sts32(sa, __float_as_uint((S[0][0] + S[2][0]) + (S[1][2] + S[3][2])));
                sts32(sa + 4 * SROW, __float_as_uint((S[0][1] + S[2][1]) + (S[1][3] + S[3][3])));
            }
            lds64(vm[0], ad[1]); lds64(vm[1], ad[1] + 256);
            bar_sync(2, 160);
            const float cs = 0.08838834764831845f * 1.4426950408889634f;
            float E[6][2];
#pragma unroll
            for (int i = 0; i < 6; i++) lds64f(E[(i + 4) % 6], sr + ((i + 4) % 6) * 32);
            const uint32_t isn = lds32(ad[4]);
            E[4][0] += E[5][0]; E[4][1] += E[5][1];
            float m = fmaxf(fmaxf(fmaxf(fmaxf(E[0][0], E[0][1]), fmaxf(E[1][0], E[1][1])), fmaxf(fmaxf(E[2][0], E[2][1]), fmaxf(E[3][0], E[3][1]))), fmaxf(E[4][0], E[4][1]));
            m = fmaxf(m, __shfl_xor_sync(0xffffffffu, m, 1));
            m = fmaxf(m, __shfl_xor_sync(0xffffffffu, m, 2));
            m *= cs;
            if constexpr (AB) static_for<0, PRE3>([&](auto I) { load_w2<I.value>(w[I.value], w2a); });
            uint32_t pa[5];
#pragma unroll
            for (int i = 0; i < 5; i++) { const int k = (i + 4) % 5; E[k][0] = ex2(fmaf(E[k][0], cs, -m)); E[k][1] = ex2(fmaf(E[k][1], cs, -m)); pa[k] = pack2(E[k][0], E[k][1]); }
            if (EFENCE) sched_fence();
            float O[2][4], Z[4];
#pragma unroll
            for (int i = 0; i < 4; i++) { O[0][i] = O[1][i] = Z[i] = 0.f; }
            mma1688(Z, isn, isn, pa[4]);
            mma1688(O[0], vm[0][0], vm[0][1], pa[4]);
            mma1688(O[1], vm[1][0], vm[1][1], pa[4]);
#pragma unroll
            for (int k = 0; k < 2; k++) {
                mma16816(Z, isn, isn, isn, isn, pa[2 * k], pa[2 * k + 1]);
#pragma unroll
                for (int i = 0; i < 2; i++) mma16816(O[i], vf[2 * k + i][0], vf[2 * k + i][1], vf[2 * k + i][2], vf[2 * k + i][3], pa[2 * k], pa[2 * k + 1]);
            }
            stsm4t(ad[3], pack2(O[0][0], O[0][1]), pack2(O[0][2], O[0][3]), pack2(O[1][0], O[1][1]), pack2(O[1][2], O[1][3]));
            if constexpr (AB) wo_blocks<1, RESA, PRE3, OFENCE / 2>(w, wr + NR * 8, oa, sb + S_INV + (l8 & 24), w2a, po, pd, odd);
            else bar_arrive(3, 256);
            if (warp == 4) {
                if (l8 - sb < 32) sts64(l8 + S_INV, __float_as_uint(rcp(Z[0])), __float_as_uint(rcp(Z[1])));
                bar_arrive(4, 160);
            }
            if (ROLE != 0) persist(s, warp, r0, r1);
            if (warp == 7 && l8 == sb) mbar_expect(sb + B_X, 4096);
        } else {
            if (ROLE != 0) persist(s, warp, r0, r1);
            wo_addr(); pin<1>(&oa);
            static_for<0, PRE2A>([&](auto I) { load_w2<I.value>(w[I.value], w2a); });
            mbar_wait(sb + B_X, s & 1);
            if (warp == 0) {
                uint32_t sc[2];
                lds64(sc, sb + S_SC);
                const int em = __reduce_max_sync(0xffffffffu, lds32(sb + S_EM + ((l8 >> 1) & 28)));
                if (l8 == sb) sts32(sb + S_ISC + (~s & 1) * 4, min(max(em - 127, (int)sc[1]) + (int)sc[0], 253) * 0x800080u);
                bar_arrive(2, 160);
            }
            wait_clocks(XDELAY - (warp == 0) * 100);
            constexpr int PRE1 = (BB - 1) * 16 - (5 - NRB) * 8 < PRE2 ? (BB - 1) * 16 - (5 - NRB) * 8 : PRE2;
            static_for<PRE2A, PRE1>([&](auto I) { load_w2<I.value>(w[I.value], w2a); });
            if (full) {
                static_for<PRE1, PRE2>([&](auto I) { load_w2<I.value>(w[I.value], w2a); });
                wo_blocks<BB, RESB, PRE2, FENCE2 * 2 + OFENCE % 2>(w, wr + NR * 8, oa, sb + S_INV + (l8 & 24), w2a, po, pd, odd);
            } else wo_blocks<BB - 1, RESB1, PRE1, FENCE2 * 2 + OFENCE % 2>(w, wr + NR * 8, oa, sb + S_INV + (l8 & 24), w2a, po, pd, odd);
        }
        if (l8 == sb) { sts32(sb + S_TO + warp * 4, gtime()); mbar_arrive(sb + B_RED); }
        if (HOLD && !(PLATE >> ATT & 1)) mbar_wait(sb + B_RED, s & 1);
        if (ROLE != 0 && (s & 3) == 3 && l8 == sb) mbar_arrive(sb + B_PERS);
        if (ROLE == 0 && s == 62) return;
    }
    __syncwarp();
    if (l8 == sb) mbar_arrive(sb + B_PERS);
}
struct Pipe { uint32_t stage, phase; };
struct Cons {
    uint32_t sb, rel;
    int wg, wq, lane, rank, pair;
    uint32_t nst;
    Pipe p;
};
__device__ __forceinline__ void pipe_next(Pipe& p) { p.stage = (p.stage + 1) & (NSTAGE - 1); p.phase ^= (p.stage == 0); }
__device__ __forceinline__ void release(const Cons& c, uint32_t stage) { if (c.lane < 2) mbar_arrive_cluster(c.rel + stage * 8); }
__device__ __forceinline__ void wait_full(const Cons& c) { mbar_wait(c.sb + B_FULL + c.p.stage * 8, c.p.phase); }

enum { PEND_NONE = 0, PEND_KVO = 1, PEND_HT = 2, PEND_OUT = 3, PEND_OUTA = 4 };
struct Pend { uint32_t pk[64]; int kind, row, col, cnt; };

__device__ __forceinline__ void staging_wait(const Cons& c) { if (c.nst) mbar_wait(c.sb + B_SFREE + c.wg * 8, (c.nst - 1) & 1); }
__device__ __forceinline__ void staging_post(Cons& c, int kind, int row, int col, int cnt) {
    __syncwarp();
    if (c.lane == 0) {
        if (c.wq == 0) { const uint32_t x[4] = {(uint32_t)kind, (uint32_t)row, (uint32_t)col, (uint32_t)cnt}; sts128(c.sb + S_DESC + c.wg * 16, x); }
        mbar_arrive(c.sb + B_SFULL + c.wg * 8);
    }
    c.nst++;
}
__device__ __forceinline__ void drain(const Params& P, Cons& c, Pend& d) {
    const uint32_t* pk = d.pk;
    const bool ht = d.kind == PEND_HT;
    const int hi = (c.lane >> 3) & 1;
    const uint32_t stg = c.sb + S_STG + c.wg * 16384, base = stg + ((ht ? hi * 32 + c.wq * 8 : c.wq * 16 + hi * 8) + (c.lane & 7)) * 128;
    staging_wait(c);
#pragma unroll
    for (int j = 0; j < 8; j++) {
        const int ch = (j & 3) * 2 + (c.lane >> 4);
        stsm4(base + (j >> 2) * 8192 + ((ch ^ (c.lane & 7)) << 4), pk[j * 4], pk[j * 4 + 1], pk[j * 4 + 2], pk[j * 4 + 3]);
    }
    if (d.kind >= PEND_OUT) {
        const uint32_t rd = stg + (c.lane >> 4) * 8192 + c.wq * 2048 + (c.lane & 15) * 8;
        const int s1 = d.kind == PEND_OUT ? 2 : 64, s2 = d.kind == PEND_OUT ? 8 : 2;
        const float* o = P.out + (size_t)(d.row + c.wq * 2 * s2) * 2048 + d.col + c.lane * 4;
        __syncwarp();
#pragma unroll
        for (int r = 0; r < 16; r++) {
            uint32_t u[2];
            lds64(u, (rd ^ ((r & 7) << 4)) + r * 128);
            st_stream4(o + ((r & 1) + (r >> 1 & 3) * s1 + (r >> 3) * s2) * 2048, bf_lo(u[0]), bf_hi(u[0]), bf_lo(u[1]), bf_hi(u[1]));
        }
        __syncwarp();
    } else {
        fence_async_smem();
        staging_post(c, d.kind, d.row, d.col, (d.col & 128) ? d.cnt : -1);
    }
    if (d.col & 128) d.kind = PEND_NONE;
    d.col += 128;
#pragma unroll
    for (int i = 0; i < 32; i++) d.pk[i] = d.pk[32 + i];
}

constexpr int S_STG2 = 8 * 20480, PEND_BOTH = 8;
__device__ __forceinline__ void drain_both(Cons& c, const Pend& d) {
    const uint32_t base = c.sb + c.wg * 16384 + (c.wq * 16 + ((c.lane >> 3) & 1) * 8 + (c.lane & 7)) * 128;
#pragma unroll
    for (int j = 0; j < 16; j++)
        stsm4(base + (j < 8 ? S_STG : S_STG2) + (j >> 2 & 1) * 8192 + ((((j & 3) * 2 + (c.lane >> 4)) ^ (c.lane & 7)) << 4), d.pk[j * 4], d.pk[j * 4 + 1], d.pk[j * 4 + 2], d.pk[j * 4 + 3]);
    fence_async_smem();
    staging_post(c, PEND_KVO | PEND_BOTH, d.row, d.col, d.cnt);
}

__device__ __forceinline__ void store_warp(const Params& P, uint32_t sb, int wg, int cta) {
    if (cta < 128) {
        for (int i = 0; i < P.xd; i++) __nanosleep(1000);
        const uint32_t e1 = get_epoch(sb) + 1;
        const uint4* x = (const uint4*)P.Bx + (cta * 2 + wg) * 1024 + (threadIdx.x & 31);
        uint32_t m = 0;
#pragma unroll 4
        for (int i = 0; i < 32; i++) { const uint4 u = __ldg(x + i * 32); m = amax(amax(m, amax(u.x, u.y)), amax(u.z, u.w)); }
        m = warp_exp(m);
        if (elect_one()) { atomicMax(&g_cnt(C_XMAX), e1 << 8 | m); red_release(&g_cnt(C_XCNT)); }
        __syncwarp();
    }
    const uint32_t stg = sb + S_STG + wg * 16384;
#pragma unroll 1
    for (uint32_t n = 0;; n++) {
        mbar_wait(sb + B_SFULL + wg * 8, n & 1);
        uint32_t x[4];
        lds128(x, sb + S_DESC + wg * 16);
#pragma unroll
        for (int i = 0; i < 4; i++) x[i] = __shfl_sync(0xffffffffu, x[i], 0);
        if (x[0] == PEND_NONE) break;
        const bool ht = x[0] == PEND_HT;
        const CUtensorMap* m = &P.tm[ht ? M_HTS : M_KVO];
        const uint64_t pol = P.pol[ht ? 2 : x[1] >= 4096 ? 1 : (x[1] & 2047) < 1536 ? 0 : 10];
        if (elect_one()) {
#pragma unroll
            for (int i = 0; i < 4; i++) tma_store2d(m, x[2] + (i >> 1) * 64, x[1] + (i & 1) * (ht ? 1024 : 32), stg + i * 4096, pol);
            if (x[0] & PEND_BOTH) {
#pragma unroll 1
                for (int i = 0; i < 4; i++) tma_store2d(m, x[2] + 128 + (i >> 1) * 64, x[1] + (i & 1) * 32, stg + (S_STG2 - S_STG) + i * 4096, pol);
            }
            bulk_commit();
            bulk_wait_read();
            mbar_arrive(sb + B_SFREE + wg * 8);
            if ((int)x[3] >= 0) { bulk_wait_all(); fence_async(); red_relaxed(&g_cnt(x[3])); }
        }
        __syncwarp();
    }
}

template <int TA, int TB, bool FIRST>
__device__ __forceinline__ void issue_ktile(float* acc, const Cons& c) {
    const uint32_t a = c.sb + c.p.stage * STAGE + c.wg * 8192, b = c.sb + c.p.stage * STAGE + 16384;
    const uint64_t da = mkdesc(a, TA ? 8192 : 16, 1024, 1), db = mkdesc(b, TB ? 8192 : 16, 1024, 1);
    wg_fence();
#pragma unroll
    for (int k = 0; k < 4; k++) {
        if (FIRST && k == 0) wgmma_ss256_first<TA, TB>(acc, da, db);
        else wgmma_ss256<TA, TB>(acc, da + (TA ? 128 : 2) * k, db + (TB ? 128 : 2) * k);
    }
    wg_commit();
}
template <bool KVONLY, bool FIRST>
__device__ __forceinline__ void issue_any(float* acc, const Cons& c, int type) {
    wait_full(c);
    if (!KVONLY && type == T_A1) issue_ktile<0, 0, FIRST>(acc, c);
    else if (!KVONLY && type == T_A2) issue_ktile<1, 0, FIRST>(acc, c);
    else issue_ktile<0, 1, FIRST>(acc, c);
}
template <bool KVONLY = false>
__device__ __forceinline__ void mainloop(float* acc, const Params& P, Cons& c, Pend& d, int type, int nk) {
    issue_any<KVONLY, true>(acc, c, type);
    uint32_t prev = c.p.stage;
    pipe_next(c.p);
#pragma unroll 1
    for (int kt = 1; kt < nk; kt++) {
        if (!KVONLY && d.kind != PEND_NONE && kt != 2) drain(P, c, d);
        issue_any<KVONLY, false>(acc, c, type);
        wg_wait<1>();
        release(c, prev);
        prev = c.p.stage;
        pipe_next(c.p);
    }
    d.kind = PEND_NONE;
    wg_wait<0>();
    pin<128>(acc);
    release(c, prev);
}
__device__ __forceinline__ void pack_half(uint32_t* pk, const float* a) {
#pragma unroll
    for (int i = 0; i < 32; i++) pk[i] = pack2(a[2 * i], a[2 * i + 1]);
}

__device__ __forceinline__ void epi_kv(const float* acc, const Cons& c, Pend& d, int mb, int nb) {
    pack_half(d.pk, acc); pack_half(d.pk + 32, acc + 64);
    d.kind = PEND_KVO; d.row = (nb >> 4) * 2048 + mb * 256 + c.rank * 128 + c.wg * 64; d.col = (nb & 15) * 256; d.cnt = C_KV + mb;
}

__device__ __forceinline__ void qa_scores(float* S, float* Sm, const uint32_t* q, Cons& c) {
    wait_full(c);
    const uint32_t st = c.sb + c.p.stage * STAGE;
    const uint64_t dk = mkdesc(st + c.wg * 8192, 16, 1024, 1), dm = mkdesc(st + 32768 + c.wg * 4096, 128, 2048, 0);
    wg_fence();
#pragma unroll
    for (int i = 0; i < 8; i++) wgmma_rs64<0>(S, q + i * 4, dk + (i >> 2) * 1024 + (i & 3) * 2, i != 0);
#pragma unroll
    for (int i = 0; i < 8; i++) wgmma_rs16<0>(Sm, q + i * 4, dm + i * 16, i != 0);
    wg_commit();
    pipe_next(c.p);
}
__device__ __forceinline__ void qa_softmax(uint32_t (*pa)[4], const float* S, const float* Sm, const Cons& c) {
    const int t = c.lane & 3, i0 = (c.wq & 1) * 16 + (c.lane >> 2) - 2 * t;
    const bool sg = c.wq >= 2;
    const float cs = 0.08838834764831845f * 1.4426950408889634f;
    float x[2][10];
#pragma unroll
    for (int r = 0; r < 2; r++) {
#pragma unroll
        for (int j = 0; j < 4; j++)
#pragma unroll
            for (int e = 0; e < 2; e++) {
                const float v = sg ? S[16 + j * 4 + r * 2 + e] : S[j * 4 + r * 2 + e];
                x[r][j * 2 + e] = (j * 8 + e - r * 8 > i0) ? -1e9f / 0.08838834764831845f : v;
            }
        x[r][8] = sg ? Sm[4 + r * 2] : Sm[r * 2];
        x[r][9] = sg ? Sm[5 + r * 2] : Sm[1 + r * 2];
        float m = fmaxf(fmaxf(fmaxf(fmaxf(x[r][0], x[r][1]), fmaxf(x[r][2], x[r][3])), fmaxf(fmaxf(x[r][4], x[r][5]), fmaxf(x[r][6], x[r][7]))), fmaxf(x[r][8], x[r][9]));
        m = fmaxf(m, __shfl_xor_sync(0xffffffffu, m, 1));
        m = fmaxf(m, __shfl_xor_sync(0xffffffffu, m, 2));
        m *= -cs;
#pragma unroll
        for (int i = 0; i < 10; i++) x[r][i] = ex2(fmaf(x[r][i], cs, m));
        float sum = (((x[r][0] + x[r][1]) + (x[r][2] + x[r][3])) + ((x[r][4] + x[r][5]) + (x[r][6] + x[r][7]))) + (x[r][8] + x[r][9]);
        sum += __shfl_xor_sync(0xffffffffu, sum, 1);
        sum += __shfl_xor_sync(0xffffffffu, sum, 2);
        const float inv = rcp(sum);
#pragma unroll
        for (int i = 0; i < 10; i++) x[r][i] *= inv;
    }
#pragma unroll
    for (int ks = 0; ks < 2; ks++)
#pragma unroll
        for (int i = 0; i < 4; i++) {
            const uint32_t p = pack2(x[i & 1][ks * 4 + (i >> 1) * 2], x[i & 1][ks * 4 + (i >> 1) * 2 + 1]);
            pa[ks][i] = sg ? 0u : p;
            pa[2 + ks][i] = sg ? p : 0u;
        }
#pragma unroll
    for (int r = 0; r < 2; r++) {
        const uint32_t p = pack2(x[r][8], x[r][9]);
        pa[4][r] = sg ? 0u : p;
        pa[4][2 + r] = sg ? p : 0u;
    }
}
__device__ __forceinline__ void qa_values(float* O, uint32_t (*pa)[4], Cons& c) {
    wait_full(c);
    const uint32_t st = c.sb + c.p.stage * STAGE;
    const uint64_t dv = mkdesc(st + c.wg * 8192, 16384, 1024, 1), dm = mkdesc(st + 32768 + c.wg * 4096, 2048, 128, 0);
    pin<20>(&pa[0][0]);
    wg_fence();
#pragma unroll
    for (int ks = 0; ks < 4; ks++) wgmma_rs128<1>(O, pa[ks], dv + ks * 128, ks != 0);
    wgmma_rs128<0>(O, pa[4], dm, 1);
    wg_commit();
    pipe_next(c.p);
}
__device__ __forceinline__ void epi_qa(const float* acc, Cons& c, Pend& d, int mb, int nb) {
    uint32_t q[64], pa[2][5][4];
    float S0[32] = {}, M0[8] = {}, S1[32] = {}, M1[8] = {}, O0[64] = {}, O1[64] = {};
    const uint32_t k0 = c.p.stage;
    pack_half(q, acc);
    pin<32>(q); pin<32>(S0); pin<8>(M0);
    qa_scores(S0, M0, q, c);
    pack_half(q + 32, acc + 64);
    pin<32>(q + 32); pin<32>(S1); pin<8>(M1);
    qa_scores(S1, M1, q + 32, c);
    wg_wait<1>();
    pin<32>(S0); pin<8>(M0);
    release(c, k0);
    qa_softmax(pa[0], S0, M0, c);
    wg_wait<0>();
    pin<32>(S1); pin<8>(M1); pin<64>(q);
    release(c, (k0 + 1) & (NSTAGE - 1));
    pin<64>(O0);
    qa_values(O0, pa[0], c);
    qa_softmax(pa[1], S1, M1, c);
    pin<64>(O1);
    qa_values(O1, pa[1], c);
    wg_wait<1>();
    pin<64>(O0); pin<20>(&pa[0][0][0]);
    release(c, (k0 + 2) & (NSTAGE - 1));
    pack_half(d.pk, O0);
    wg_wait<0>();
    pin<64>(O1); pin<20>(&pa[1][0][0]);
    release(c, (k0 + 3) & (NSTAGE - 1));
    pack_half(d.pk + 32, O1);
    d.kind = PEND_KVO; d.row = 4096 + mb * 256 + c.rank * 128 + c.wg * 64; d.col = nb * 256; d.cnt = C_O + mb * 16 + nb;
}

__device__ __forceinline__ void epi_op(const float* acc, const Cons& c, Pend& d, int mb, int nb) {
    pack_half(d.pk, acc); pack_half(d.pk + 32, acc + 64);
    d.kind = PEND_OUT; d.row = mb * 256 + c.rank * 128 + c.wg * 64; d.col = 1024 + nb * 256;
}

__device__ __forceinline__ void epi_a2(float* acc, const Params& P, Cons& c, Pend& d, int mb, int nb) {
    const int g = c.lane >> 2, t = c.lane & 3;
#pragma unroll
    for (int i = 0; i < 32; i++) d.pk[32 + i] = 0;
#pragma unroll 1
    for (int hf = P.zero; hf < 2; hf++) {
        wait_full(c);
        const uint32_t st = c.sb + c.p.stage * STAGE, xa = st + (c.wg * 64 + c.wq * 16 + g) * 128 + t * 4 + (g << 4), da = st + 32768 + t * 4;
#pragma unroll
        for (int j = 0; j < 16; j++) {
            const float* a = acc + j * 4;
            const uint32_t ad = (xa ^ ((j & 7) << 4)) + (j >> 3) * 16384;
            const uint32_t dv = lds32(da + j * 16), u0 = mul_bf2(lds32(ad), dv), u1 = mul_bf2(lds32(ad + 1024), dv);
            d.pk[j * 2] = d.pk[32 + j * 2]; d.pk[j * 2 + 1] = d.pk[33 + j * 2];
            d.pk[32 + j * 2] = pack2(a[0] + bf_lo(u0), a[1] + bf_hi(u0));
            d.pk[33 + j * 2] = pack2(a[2] + bf_lo(u1), a[3] + bf_hi(u1));
        }
        __syncwarp();
        release(c, c.p.stage);
        pipe_next(c.p);
#pragma unroll
        for (int i = 0; i < 64; i++) acc[i] = acc[64 + i];
    }
    d.kind = PEND_OUTA; d.row = mb * 256 + c.rank * 32 + c.wg * 16; d.col = nb * 256;
}

__device__ __forceinline__ float2 cmul(float2 a, float2 b) { return make_float2(fmaf(a.x, b.x, -a.y * b.y), fmaf(a.x, b.y, a.y * b.x)); }
__device__ __forceinline__ float2 cfma(float2 a, float2 b, float2 u) { return make_float2(fmaf(a.x, b.x, fmaf(-a.y, b.y, u.x)), fmaf(a.x, b.y, fmaf(a.y, b.x, u.y))); }
__device__ __forceinline__ float4 ssm_coef(float lre, float lim, float logdt) {
    const float dt = __bfloat162float(__float2bfloat16(expf(logdt)));
    const float ea = expf(dt * lre);
    float sn, cn;
    sincosf(dt * lim, &sn, &cn);
    const float br = ea * cn, bi = ea * sn, nr = br - 1.f;
    const bool sw = fabsf(lre) < fabsf(lim);
    const float big = sw ? lim : lre, r = __fdividef(sw ? lre : lim, big), inv = __fdividef(1.f, fmaf(sw ? lre : lim, r, big));
    const float cr = (sw ? fmaf(nr, r, bi) : fmaf(bi, r, nr)) * inv, ci = (sw ? fmaf(bi, r, -nr) : fmaf(-nr, r, bi)) * inv;
    return make_float4(br, bi, cr, ci);
}
__device__ __forceinline__ void epi_a1(const float* acc, const Params& P, const Cons& c, Pend& d, int mb, int nb) {
    const uint32_t atag = (get_epoch(c.sb) + 1) & 1;
    const int t = c.lane & 3;
    const int p = nb * 128 + c.rank * 64 + c.wg * 32 + c.wq * 8 + (c.lane >> 2);
    const float4 cf = __ldcg(&g_coef[p]);
    const float2 lam = make_float2(cf.x, P.swap_ri ? -cf.y : cf.y);
    const float a0 = P.swap_ri ? -2.f * cf.w : 2.f * cf.z, a1 = P.swap_ri ? 2.f * cf.z : -2.f * cf.w;
    const float b0 = P.swap_ri ? -2.f * cf.z : -2.f * cf.w, b1 = P.swap_ri ? -2.f * cf.w : -2.f * cf.z;
    float2 h = make_float2(0.f, 0.f);
#pragma unroll
    for (int round = 0; round < 2; round++) {
#pragma unroll
        for (int j = 0; j < 32; j++) {
            h = cfma(lam, h, make_float2(acc[j * 4], acc[j * 4 + 2]));
            const float r0 = fmaf(a0, h.x, a1 * h.y), m0 = fmaf(b0, h.x, b1 * h.y);
            h = cfma(lam, h, make_float2(acc[j * 4 + 1], acc[j * 4 + 3]));
            d.pk[j * 2] = pack2(r0, fmaf(a0, h.x, a1 * h.y));
            d.pk[j * 2 + 1] = pack2(m0, fmaf(b0, h.x, b1 * h.y));
        }
        if (round) break;
        float2 l64 = lam;
#pragma unroll
        for (int i = 0; i < 6; i++) l64 = cmul(l64, l64);
        const float2 l128 = cmul(l64, l64), l256 = cmul(l128, l128);
        float2 o = make_float2(__shfl_up_sync(0xffffffffu, h.x, 1), __shfl_up_sync(0xffffffffu, h.y, 1));
        if (t >= 1) h = cfma(l64, o, h);
        o = make_float2(__shfl_up_sync(0xffffffffu, h.x, 2), __shfl_up_sync(0xffffffffu, h.y, 2));
        if (t >= 2) h = cfma(l128, o, h);
        if (t == 3) st_relaxed2(&g_agg[mb * 1024 + p], (__float_as_uint(h.x) & ~1u) | atag, __float_as_uint(h.y));
        h = make_float2(__shfl_up_sync(0xffffffffu, h.x, 1), __shfl_up_sync(0xffffffffu, h.y, 1));
        if (t == 0) h = make_float2(0.f, 0.f);
        uint32_t ax[7], ay[7];
        while (true) {
            uint32_t bad = 0;
#pragma unroll
            for (int j = 0; j < 7; j++) { ax[j] = atag; ay[j] = 0; ld_relaxed2_if(ax[j], ay[j], &g_agg[j * 1024 + p], j < mb); }
#pragma unroll
            for (int j = 0; j < 7; j++) bad |= ax[j] ^ atag;
            if (tags_ok(bad)) break;
            __nanosleep(2 * POLLNS);
        }
        float2 carry = make_float2(0.f, 0.f);
#pragma unroll
        for (int j = 0; j < 7; j++) if (j < mb) carry = cfma(l256, carry, make_float2(__uint_as_float(ax[j]), __uint_as_float(ay[j])));
        float2 w = (t & 1) ? l64 : make_float2(1.f, 0.f);
        if (t & 2) w = cmul(w, l128);
        h = cfma(w, carry, h);
    }
    d.kind = PEND_HT; d.row = nb * 128 + c.rank * 64 + c.wg * 32; d.col = mb * 256; d.cnt = C_HT + mb * 16 + nb;
}

__device__ __forceinline__ uint32_t fresh_tid() { uint32_t t; asm volatile("mov.u32 %0, %%tid.x;" : "=r"(t)); return t; }
__device__ __forceinline__ uint32_t acquire_stage(uint32_t sb, Pipe& p, uint32_t bytes) {
    mbar_wait(sb + B_EMPTY + p.stage * 8, p.phase ^ 1);
    mbar_expect_e(sb + B_FULL + p.stage * 8, bytes);
    return p.stage;
}
__device__ __forceinline__ void producer(const Params& P, const uint32_t sb, const int cta) {
    Pipe p = {0, 0};
    uint32_t resume = 1;
    const int rank = cta & 1;
    const uint16_t both = 3 << (__shfl_sync(0xffffffffu, cluster_rank(), 0) & ~1u);
    for (int it = ITEM_OFF(cta >> 1), item = 0; !(item & LAST); it++) {
        item = ITEM(it);
        const int type = (item >> 8) & 7, mb = (item >> 5) & 7, nb = item & 31, half = item / HALF & 1, hw = item >> 13 & 1;
        const uint32_t epoch = type ? get_epoch(sb) : 0, e1 = epoch + 1;
        if (type == T_CHAIN) {
            const int h = cta / 3, role = cta - h * 3;
#pragma unroll 1
            for (int w = 0; w < 8; w++) {
                mbar_wait(sb + B_EMPTY + (w * 20480 + 20479) / STAGE * 8, 1);
                chain_load(P, sb, cta, w, threadIdx.x & 31, 0);
            }
            uint32_t* flag = &g_cnt(C_FLAG + (role == 2 ? 32 : 0) + h);
            if (role) { wait_count(&g_cnt(C_KV), e1 * 128); fence_async(); }
#pragma unroll 1
            for (int s = 0; s < 63 && role != 0; s++) {
                {
                    mbar_wait(sb + B_GO, s & 1);
                    tma3d_mc_e(sb + S_KV + (role - 1) * 8192, &P.tm[M_SEG], 0, (role - 1) * 2048 + s * 32, h * 2, sb + B_KVFULL, 7 << ((h & 1) * 3), P.pol[s < 48 ? 8 : 11]);
                    if ((s & 7) == 7) { wait_count(&g_cnt(C_KV + 1 + (s >> 3)), e1 * 128); fence_async(); }
                    tma_prefetch3d_e(&P.tm[M_SEG], 0, (role - 1) * 2048 + s * 32 + 32, h * 2);
                }
                if (s > 0 && (s & 3) == 0) {
                    const int i = (s - 1) >> 2;
                    mbar_wait(sb + B_PERS, i & 1);
                    asm volatile("{\n.reg .pred E;\nelect.sync _|E, 0xffffffff;\n@E st.release.gpu.global.u32 [%0], %1;\n}" ::"l"(flag), "r"(epoch * 64 + i * 4 + 4) : "memory");
                }
            }
            if (role == 0) {
                const int lane = threadIdx.x & 31;
                if (lane == 0) mbar_arrive(sb + B_RELM);
#pragma unroll 1
                for (int s = 0; s < 63; s++) {
                    mbar_wait(sb + B_P1, s & 1);
                    if (s > 0) {
                        st_relaxed4(P.xb + xg_buf(s - 1) + h * 2048 + xg_lane(lane), 0, 0, 0, 0);
                        st_relaxed1(P.xb + xg_buf(s - 1) + xg_side(h) + lane * 4, 0);
                        __threadfence();
                    }
                    __syncwarp();
                    if (lane == 0) mbar_arrive(sb + B_RELM);
                }
            }
            if ((threadIdx.x & 31) < M_C1 - 1) asm volatile("prefetch.tensormap [%0];" ::"l"(&P.tm[1 + (threadIdx.x & 31)]) : "memory");
            resume = 0;
            continue;
        }
        const int m0 = mb * 256 + rank * 128, ssm = type >= T_A1;
        const CUtensorMap* ma = &P.tm[max(type, 1) + half * M_HALF];
        const CUtensorMap* mw = &P.tm[type ? M_WV + type : M_WK + (nb >> 4)];
        const int nk = type == T_OP ? 64 : type == T_A2 ? 32 : 16;
        const int a3 = type == T_A1 ? nb * 16 + rank * 8 + hw * 4 : type == T_A2 ? mb * 4 + rank * 2 + hw : (type == T_OP ? 4096 : 0) + m0 + hw * 64;
        const int b3 = type == T_A1 ? mb * 128 + rank * 16 : type == T_A2 ? (nb * 2 + rank) * 128 : (nb & 15) * 4 + rank * 2;
        if (type & 1) {
            wait_count(&g_cnt(type == T_A1 ? C_COEF : C_KV + mb), e1 * (type == T_A1 ? 4 : 128));
            fence_async();
        }
        uint32_t ready = type == T_OP || type == T_A2 ? 0 : ~0u;
        if (type == T_A1) l2_prefetch_e(g_coef + nb * 128 + rank * 64, 1024);
        auto arrived = [&]() {
            const uint32_t t = fresh_tid();
            return __all_sync(0xffffffffu, (int32_t)(ld_acquire(&g_cnt(C_FLAG + (t & 2) * 16 + nb * 2 + (t & 1))) - (epoch * 64 + mb * 8 + rank * 4 + 4)) >= 0);
        };
        bool passed = false;
        mbar_wait(sb + B_RESUME, resume);
#pragma unroll 1
        for (int kt = 0; kt < nk; kt++) {
            if (type == T_QA && kt == 9) passed = arrived();
            while (~ready & (ssm ? 2 | 1 << ((kt & 15) >> 1) : 1 << (kt >> 2))) {
                if (ready) __nanosleep(POLLNS);
                ready = __ballot_sync(0xffffffffu, (int32_t)(ld_acquire(&g_cnt(type * 64 + mb * 16 + (fresh_tid() & 15))) - e1 * 4) >= 0) | 1u << 31;
                fence_async();
            }
            const uint32_t st = acquire_stage(sb, p, STAGE - half * 8192), bar = sb + B_FULL + st * 8;
            const int a1 = type == T_A2 ? kt * 64 : 0, b0 = ssm ? (kt & 15) * 64 : 0;
            tma4d_e(sb + st * STAGE + hw * 8192, ma, kt * 64 - a1, a1, a3, bar, P.pol[11]);
            tma4d_mc_e(sb + st * STAGE + 16384 + rank * 16384, mw + (ssm & kt >> 4), b0, ssm ? 0 : kt * 64, b3, bar, both, P.pol[(item & 0x7e0) == 224 ? 9 : 11]);
            if (type == T_QA && kt < 8) tma_prefetch4d_e(&P.tm[M_OA], nb * 256 + (kt & 3) * 64, (kt >> 2) * 2048 + m0);
            pipe_next(p);
        }
        if (type == T_QA) {
            while (!passed) { passed = arrived(); if (!passed) __nanosleep(POLLNS); }
            fence_async();
        }
        const int q = type == T_QA;
#pragma unroll 1
        for (int e = 0; e < (q ? 4 : type == T_A2 ? 2 : 0); e++) {
            const uint32_t st = acquire_stage(sb, p, q ? 40960 : 32768 + 256), bar = sb + B_FULL + st * 8, dst = sb + st * STAGE;
#pragma unroll 1
            for (int i = 0; i < 2; i++) tma4d_e(dst + i * 16384, &P.tm[q ? M_OA : M_AX], nb * 256 + (e & 1) * 128 + i * 64, 0, q ? (e >> 1) * 2048 + m0 : mb * 128 + rank * 16, bar, P.pol[q ? 3 : 11]);
            const uint8_t* src = q ? (const uint8_t*)(((e >> 1) ? g_vmt : g_km) + ((mb * 8 + rank * 4) * 32 + nb * 2 + (e & 1)) * 512) : (const uint8_t*)(P.Dskip + nb * 256 + e * 128);
#pragma unroll 1
            for (int i = 0; i < (q ? 4 : 1); i++) bulk_g2s_e(dst + 32768 + i * 2048, src + i * 65536, q ? 2048 : 256, bar);
            pipe_next(p);
        }
    }
#pragma unroll 1
    for (int i = 0; i < NSTAGE; i++) { mbar_wait(sb + B_EMPTY + p.stage * 8, p.phase ^ 1); pipe_next(p); }
}

__device__ __forceinline__ uint32_t fresh_ctaid() { uint32_t t; asm volatile("mov.u32 %0, %%ctaid.x;" : "=r"(t)); return t; }
__device__ __forceinline__ void reset_state(const Params& P, Cons& c, Pend& d, uint32_t sb, bool resumed) {
    const uint32_t t = fresh_tid(), b = fresh_ctaid() + P.cta0;
    const int w = __shfl_sync(0xffffffffu, t >> 5, 0);
    c.sb = sb; c.wg = w >> 2; c.wq = w & 3; c.lane = t & 31;
    c.rank = __shfl_sync(0xffffffffu, b & 1, 0); c.pair = __shfl_sync(0xffffffffu, b >> 1, 0);
    c.rel = mapa(sb + B_EMPTY, cluster_rank() ^ (c.lane & 1));
    c.p.stage = 0; c.p.phase = 0;
    c.nst = resumed && c.pair < NCHAIN;
    d = Pend{};
}

__global__ void __launch_bounds__(384, 1) fused_kernel(const __grid_constant__ Params P) {
    extern __shared__ __align__(1024) uint8_t smem[];
    const uint32_t sb = smem_u32(smem);
    asm volatile("griddepcontrol.launch_dependents;");
    declare_fence(P.zero);
    const int tid = threadIdx.x, lane = tid & 31;
    const int warp = __shfl_sync(0xffffffffu, tid >> 5, 0);
    const int cta = __shfl_sync(0xffffffffu, blockIdx.x + P.cta0, 0), pair = cta >> 1, rank = cta & 1;
    if (tid == 0) {
        if (sb & 1023) spin_fault();
        for (int i = 0; i < NSTAGE; i++) { mbar_init(sb + B_FULL + i * 8, 1); mbar_init(sb + B_EMPTY + i * 8, 16); }
        mbar_init(sb + B_RESUME, 2);
        mbar_init(sb + B_KVFULL, 1);
        mbar_init(sb + B_GO, 3); mbar_init(sb + B_RED, 8); mbar_init(sb + B_P1, 1); mbar_init(sb + B_EPOCH, 1); mbar_init(sb + B_PERS, 8); mbar_init(sb + B_INIT, 8); mbar_init(sb + B_INIT2, 8);
        mbar_init(sb + B_READY, 8);
        for (int i = 0; i < 2; i++) { mbar_init(sb + B_SFULL + i * 8, 4); mbar_init(sb + B_SFREE + i * 8, 1); }
        mbar_init(sb + B_RELM, cta % 3 ? 1 : 2); mbar_init(sb + B_X, 9);
        mbar_init(sb + B_DONE, 2);
        mbar_expect(sb + B_X, 4096);
        sts64(sb + S_EV, 0, 0);
        asm volatile("fence.mbarrier_init.release.cluster;" ::: "memory");
    }
    __syncthreads();
    cluster_sync();
    if (warp >= 8) {
        asm volatile("setmaxnreg.dec.sync.aligned.u32 24;");
        if (warp == 8) {
            producer(P, sb, cta);
        } else if (warp == 9) {
            const uint32_t epoch = __shfl_sync(0xffffffffu, ld_acquire(&g_cnt(C_EPOCH)), 0);
            if (lane == 0) { sts32(sb + S_EPOCH, epoch); mbar_arrive(sb + B_EPOCH); red_release(&g_cnt(C_READ)); }
            __syncwarp();
            if (pair < NCHAIN) pacer(P, sb, cta, lane, epoch);
            if (pair < NCHAIN && cta % 3) {
                mbar_wait_bounded(sb + B_PERS, 1);
                if (lane == 0) asm volatile("st.release.gpu.global.u32 [%0], %1;" ::"l"(&g_cnt(C_FLAG + (cta % 3 == 2 ? 32 : 0) + cta / 3)), "r"(epoch * 64 + 64) : "memory");
            }
            if (cta == 0 && lane == 0) {
                for (int n = 0; (int32_t)(ld_acquire(&g_cnt(C_READ)) - (epoch + 1) * (NPAIR * 2)) < 0; n++) if (n > SPIN_LIMIT) spin_fault();
                st_relaxed1(&g_cnt(C_EPOCH), epoch + 1);
            }
            __syncwarp();
            mbar_wait_bounded(sb + B_DONE, 0);
        } else {
            store_warp(P, sb, warp - 10, cta);
        }
    } else {
        asm volatile("setmaxnreg.inc.sync.aligned.u32 240;");
        Cons c;
        Pend d;
        if (pair < NCHAIN) {
            reset_state(P, c, d, sb, false);
            {
                const int item = ITEM(ITEM_OFF(pair));
                float acc[128];
                mainloop<true>(acc, P, c, d, T_KV, 16);
                epi_kv(acc, c, d, (item >> 5) & 7, item & 31);
            }
            mbar_wait(sb + B_EMPTY + 3 * 8, 1);
            drain_both(c, d);
            uint32_t wr[40][4];
            chain_fetch(P, sb, cta, warp, lane, wr);
            chain_bounds(sb, cta, warp, lane, wr);
            if (warp < 4) chain_role<false>(P, sb, cta, warp, lane, wr);
            else chain_role<true>(P, sb, cta, warp, lane, wr);
            bar_sync(1, 256);
            const uint32_t t2 = fresh_tid();
            if (t2 < 2) mbar_arrive_cluster(mapa(sb + B_RESUME, cluster_rank() ^ t2));
        } else if (pair >= NPAIR - 2) {
            const int ch = (pair - (NPAIR - 2)) * 512 + rank * 256 + tid;
            g_coef[ch] = ssm_coef(__bfloat162float(P.Lre[ch]), __bfloat162float(P.Lim[ch]), __bfloat162float(P.logdt[ch]));
            bar_sync(1, 256);
            if (tid == 0) red_release(&g_cnt(C_COEF));
        }
        reset_state(P, c, d, sb, true);
        int it = ITEM_OFF(c.pair) + (c.pair < NCHAIN ? 2 : 0);
        for (int prev = c.pair < NCHAIN ? ITEM(it - 1) : 0;; prev = ITEM(it++)) {
            const bool last = prev & LAST;
            const int item = ITEM(it), type = (item >> 8) & 7, mb = (item >> 5) & 7, nb = item & 31;
            const bool idle = (item >> 12 & 3) == 3 - 2 * c.wg;
            if (d.kind != PEND_NONE && ((prev & (LAST | URGENT)) || idle || (type != T_KV && !bar_and(5 + c.wg, mbar_try(sb + B_FULL + c.p.stage * 8, c.p.phase))))) {
#pragma unroll 1
                while (d.kind != PEND_NONE) drain(P, c, d);
            }
            if (last) break;
            const int nk = type == T_OP ? 64 : type == T_A2 ? 32 : 16;
            if (idle) {
#pragma unroll 1
                for (int kt = nk + (type == T_A2 ? 2 : type == T_QA ? 4 : 0); kt > 0; kt--) { wait_full(c); release(c, c.p.stage); pipe_next(c.p); }
                continue;
            }
            float acc[128];
            mainloop(acc, P, c, d, type, nk);
            if (type == T_KV) epi_kv(acc, c, d, mb, nb);
            else if (type == T_QA) epi_qa(acc, c, d, mb, nb);
            else if (type == T_OP) epi_op(acc, c, d, mb, nb);
            else if (type == T_A1) epi_a1(acc, P, c, d, mb, nb);
            else epi_a2(acc, P, c, d, mb, nb);
        }
        staging_wait(c);
        staging_post(c, PEND_NONE, 0, 0, 0);
        if (c.wq == 0 && c.lane == 0) mbar_arrive(sb + B_DONE);
    }
}

typedef CUresult (*EncodeFn)(CUtensorMap*, CUtensorMapDataType, cuuint32_t, void*, const cuuint64_t*, const cuuint64_t*, const cuuint32_t*, const cuuint32_t*,
                             CUtensorMapInterleave, CUtensorMapSwizzle, CUtensorMapL2promotion, CUtensorMapFloatOOBfill);
void encode(EncodeFn fn, CUtensorMap* m, const void* base, int rank, const uint64_t* dims, const uint64_t* strides, const uint32_t* box, CUtensorMapSwizzle swz = CU_TENSOR_MAP_SWIZZLE_128B) {
    cuuint64_t d[5], s[5]; cuuint32_t b[5], e[5];
    for (int i = 0; i < rank; i++) { d[i] = dims[i]; b[i] = box[i]; e[i] = 1; if (i) s[i - 1] = strides[i - 1]; }
    fn(m, CU_TENSOR_MAP_DATA_TYPE_BFLOAT16, rank, (void*)base, d, s, b, e, CU_TENSOR_MAP_INTERLEAVE_NONE, swz,
       CU_TENSOR_MAP_L2_PROMOTION_L2_128B, CU_TENSOR_MAP_FLOAT_OOB_FILL_NONE);
}
void map_kmajor(EncodeFn fn, CUtensorMap* m, const void* base, uint64_t rows, uint64_t cols, uint32_t box_rows) {
    const uint64_t d[4] = {cols, 1, 1, rows}, s[3] = {cols * 2, cols * 2, cols * 2}; const uint32_t b[4] = {64, 1, 1, box_rows};
    encode(fn, m, base, 4, d, s, b);
}
void map_mnmajor(EncodeFn fn, CUtensorMap* m, const void* base, uint64_t krows, uint64_t cols, uint32_t groups = 2) {
    const uint64_t d[4] = {64, krows, 1, cols / 64}, s[3] = {cols * 2, 128, 128}; const uint32_t b[4] = {64, 64, 1, groups};
    encode(fn, m, base, 4, d, s, b);
}
void map_store(EncodeFn fn, CUtensorMap* m, const void* base, uint64_t rows, uint64_t cols) {
    const uint64_t d[2] = {cols, rows}, s[1] = {cols * 2}; const uint32_t b[2] = {64, 32};
    encode(fn, m, base, 2, d, s, b);
}

}

extern "C" void kernel_launch(void* const* d_in, const int* in_sizes, int n_in, void* d_out, int out_size) {
    static Params P;
    static EncodeFn fn = nullptr;
    if (!fn) {
        cudaDriverEntryPointQueryResult q;
        cudaGetDriverEntryPoint("cuTensorMapEncodeTiled", (void**)&fn, cudaEnableDefault, &q);
        cudaFuncSetAttribute(fused_kernel, cudaFuncAttributeMaxDynamicSharedMemorySize, S_TOTAL);
    }
    const bf16* in[15];
    for (int i = 0; i < 15; i++) in[i] = (const bf16*)d_in[i];
    void *kvo, *ht;
    cudaGetSymbolAddress(&kvo, g_kvo);
    cudaGetSymbolAddress(&ht, g_ht);
    map_kmajor(fn, &P.tm[M_BX], in[9], 2048, 1024, 128);
    map_mnmajor(fn, &P.tm[M_WQ], in[11], 1024, 4096);
    map_mnmajor(fn, &P.tm[M_WK], in[12], 1024, 4096);
    map_mnmajor(fn, &P.tm[M_WV], in[13], 1024, 4096);
    map_mnmajor(fn, &P.tm[M_WO], in[14], 4096, 1024);
    map_kmajor(fn, &P.tm[M_OA], kvo, 3 * 2048, 4096, 128);
    P.swap_ri = in[4] < in[3];
    {
        const bf16* lo = P.swap_ri ? in[4] : in[3];
        const uint64_t diff = (uint64_t)((const char*)(P.swap_ri ? in[3] : in[4]) - (const char*)lo);
        const uint64_t d[4] = {1024, 8, 2, 128}, s[3] = {2048, diff, 16384}; const uint32_t b[4] = {64, 8, 2, 8}, bh[4] = {64, 8, 2, 4};
        encode(fn, &P.tm[M_AB], lo, 4, d, s, b);
        encode(fn, &P.tm[M_AB + M_HALF], lo, 4, d, s, bh);
    }
    {
        const uint64_t d[4] = {1024, 2, 4, 1024}, s[3] = {2048, 64 * 2048, 4096}; const uint32_t b[4] = {64, 2, 4, 16};
        encode(fn, &P.tm[M_AX], in[0], 4, d, s, b);
    }
    map_mnmajor(fn, &P.tm[M_HT], ht, 2048, 2048);
    map_kmajor(fn, &P.tm[M_CRE], in[5], 1024, 1024, 128);
    map_kmajor(fn, &P.tm[M_CIM], in[6], 1024, 1024, 128);
    map_store(fn, &P.tm[M_KVO], kvo, 3 * 2048, 4096);
    map_store(fn, &P.tm[M_HTS], ht, 2048, 2048);
    map_kmajor(fn, &P.tm[M_BX + M_HALF], in[9], 2048, 1024, 64);
    map_kmajor(fn, &P.tm[M_OA + M_HALF], kvo, 3 * 2048, 4096, 64);
    map_mnmajor(fn, &P.tm[M_HT + M_HALF], ht, 2048, 2048, 1);
    for (int i = 0; i < 3; i++) {
        const uint64_t d[3] = {64, 1024, 64}, s[2] = {8192, 128}; const uint32_t b[3] = {64, 16, 2};
        encode(fn, &P.tm[M_C1 + i], in[11 + i], 3, d, s, b);
    }
    {
        const uint64_t d[2] = {1024, 4096}, s[1] = {2048}; const uint32_t b[2] = {32, 32};
        encode(fn, &P.tm[M_CO], in[14], 2, d, s, b, CU_TENSOR_MAP_SWIZZLE_64B);
    }
    {
        const uint64_t d[3] = {64, 3 * 2048, 64}, s[2] = {8192, 128}; const uint32_t b[3] = {64, 32, 2};
        encode(fn, &P.tm[M_SEG], kvo, 3, d, s, b);
    }
    void* xs;
    cudaGetSymbolAddress(&xs, g_x);
    P.xb = (uint8_t*)(((uintptr_t)xs + (2u << 20) - 1) & ~(uintptr_t)((2u << 20) - 1));
    P.mem0 = in[10]; P.Bx = in[9];
    P.Ax = in[0]; P.Lre = in[1]; P.Lim = in[2]; P.logdt = in[7]; P.Dskip = in[8];
    P.out = (float*)d_out;
    int pv[10] = {1140, 0, 110, 0, 330, 64, 32, 32, 0, 0};
    int ef = 779;
    for (int i = 0; i < 12; i++) P.pol[i] = (ef >> i & 1) ? 0x12F0000000000000ull : 0x1000000000000000ull;
    P.dly = pv[0]; P.mrg = pv[2];
    P.rd = pv[4]; P.guard = pv[5]; P.clampv = pv[6]; P.clamp0 = pv[7]; P.kvd = pv[9]; P.xd = pv[8];
    cudaLaunchConfig_t cfg = {};
    cudaLaunchAttribute at[2];
    cfg.blockDim = dim3(384); cfg.dynamicSmemBytes = S_TOTAL; cfg.stream = cudaStreamPerThread; cfg.attrs = at;
    at[0].id = cudaLaunchAttributeClusterDimension;
    at[0].val.clusterDim.y = at[0].val.clusterDim.z = 1;
    at[1].id = cudaLaunchAttributeProgrammaticStreamSerialization;
    at[1].val.programmaticStreamSerializationAllowed = 1;
    for (int i = 0; i < 2; i++) {
        P.cta0 = i ? 2 * NCHAIN : 0;
        cfg.gridDim = dim3(i ? 2 * (NPAIR - NCHAIN) : 2 * NCHAIN);
        at[0].val.clusterDim.x = i ? 2 : 6;
        cfg.numAttrs = 1 + i;
        cudaLaunchKernelEx(&cfg, fused_kernel, P);
    }
}
```

```cpp
#include <cuda_runtime.h>
#include <cuda_bf16.h>
#include <cuda.h>
#include <stdint.h>
#include <string.h>

typedef __nv_bfloat16 bf16;

namespace {

constexpr int SPIN_LIMIT = 1 << 22;
#define POLLNS 100
constexpr int NPAIR = 66;
constexpr int NCHAIN = 48;
enum { T_KV = 0, T_QA = 1, T_OP = 2, T_A1 = 3, T_A2 = 4, T_CHAIN = 5 };
constexpr int URGENT = 2048;
constexpr int LAST = 16384;
constexpr int HALF = 4096;
enum { M_BX = 1, M_OA, M_AB, M_HT, M_HALF = 4, M_WK = 9, M_WV, M_WQ, M_WO, M_AX, M_CRE, M_CIM, M_KVO, M_HTS, M_C1, M_CO = M_C1 + 3, M_SEG, M_COUNT };
enum { C_KV = 0, C_O = 128, C_HT = 256, C_READ = 24, C_EPOCH = 25, C_COEF = 26, C_XMAX = 27, C_XCNT = 28, C_FLAG = 32 };

struct Params {
    CUtensorMap tm[M_COUNT];
    const bf16 *mem0, *Bx, *Ax, *Lre, *Lim, *logdt, *Dskip;
    float* out;
    uint8_t* xb;
    int swap_ri, zero;
    int dly, mrg, rd, guard, clampv, clamp0, kvd, xd;
    uint64_t pol[12];
    uint16_t cta0;
};

__constant__ uint16_t c_off[67] = {0, 4, 8, 14, 20, 26, 32, 38, 44, 49, 54, 59, 64, 69, 74, 79, 84, 89, 94, 98, 102, 106, 110, 114, 118, 122, 126, 130, 134, 138, 142, 146, 150, 154, 158, 162, 166, 170, 174, 178, 182, 186, 190, 194, 198, 202, 206, 210, 214, 234, 253, 272, 292, 312, 332, 352, 371, 391, 410, 430, 449, 468, 487, 506, 525, 545, 564};
__constant__ uint16_t c_items[700] = {
    0, 1280, 512, 21728, 16, 1280, 513, 29920, 32, 1280, 800, 898, 3042, 21729, 1, 1280, 801, 899, 995, 29921, 17, 1280, 802, 900,
    996, 21730, 33, 1280, 803, 901, 997, 29922, 2, 1280, 804, 902, 998, 21731, 18, 1280, 805, 903, 999, 29923, 34, 1280, 495, 2912,
    17408, 3, 1280, 463, 2913, 17409, 19, 1280, 768, 2914, 17410, 35, 1280, 769, 867, 17411, 4, 1280, 770, 868, 17440, 20, 1280, 771,
    869, 17441, 36, 1280, 772, 870, 17442, 5, 1280, 773, 871, 17443, 21, 1280, 774, 2944, 17472, 37, 1280, 775, 2945, 17473, 6, 1280,
    494, 16898, 22, 1280, 462, 16899, 38, 1280, 493, 16928, 7, 1280, 461, 16929, 23, 1280, 492, 16930, 39, 1280, 460, 16931, 8, 1280,
    491, 16960, 24, 1280, 459, 16961, 40, 1280, 490, 16962, 9, 1280, 458, 16963, 25, 1280, 489, 16992, 41, 1280, 457, 16993, 10, 1280,
    488, 16994, 26, 1280, 456, 16995, 42, 1280, 487, 17024, 11, 1280, 455, 17025, 27, 1280, 486, 17026, 43, 1280, 454, 17027, 12, 1280,
    485, 17056, 28, 1280, 453, 17057, 44, 1280, 484, 17058, 13, 1280, 452, 17059, 29, 1280, 483, 17088, 45, 1280, 451, 17089, 14, 1280,
    482, 17090, 30, 1280, 450, 17091, 46, 1280, 2529, 17120, 15, 1280, 2497, 17121, 31, 1280, 2528, 17122, 47, 1280, 2496, 17123, 48, 66,
    84, 102, 117, 131, 147, 161, 178, 194, 207, 222, 235, 248, 332, 366, 416, 835, 3010, 17568, 49, 67, 85, 256, 128, 141,
    155, 170, 187, 203, 215, 296, 301, 323, 357, 391, 425, 931, 17505, 50, 68, 86, 103, 259, 142, 156, 171, 188, 288, 216,
    231, 302, 324, 358, 392, 806, 2976, 17474, 51, 69, 87, 104, 118, 132, 148, 162, 179, 195, 208, 223, 236, 249, 333, 367,
    417, 836, 963, 17569, 52, 70, 88, 105, 119, 133, 149, 163, 180, 196, 209, 224, 237, 250, 334, 384, 418, 837, 964, 17570,
    53, 71, 89, 106, 120, 134, 150, 164, 181, 197, 210, 225, 238, 251, 335, 385, 419, 838, 965, 17571, 54, 72, 90, 107,
    121, 135, 151, 165, 182, 198, 211, 226, 239, 252, 352, 386, 420, 839, 966, 17600, 55, 73, 91, 108, 260, 264, 160, 176,
    192, 291, 220, 299, 245, 328, 362, 396, 428, 3009, 17539, 56, 74, 92, 109, 122, 136, 152, 166, 183, 199, 212, 227, 240,
    253, 353, 387, 421, 429, 967, 17601, 57, 75, 93, 110, 123, 263, 267, 175, 271, 206, 218, 233, 243, 322, 356, 390, 424,
    2978, 17504, 58, 76, 94, 111, 124, 137, 153, 167, 184, 200, 213, 228, 241, 254, 354, 388, 422, 430, 3040, 17602, 59, 77,
    95, 112, 125, 138, 265, 269, 191, 290, 219, 298, 246, 329, 363, 397, 832, 934, 17536, 60, 78, 96, 113, 261, 143, 157,
    172, 270, 292, 221, 300, 247, 330, 364, 398, 833, 935, 17537, 61, 79, 97, 257, 129, 144, 158, 173, 189, 204, 294, 297,
    244, 325, 359, 393, 426, 932, 17506, 62, 80, 98, 258, 130, 145, 268, 177, 193, 205, 217, 232, 303, 326, 360, 394, 807,
    2977, 17475, 63, 81, 99, 114, 262, 146, 159, 174, 190, 289, 295, 234, 321, 331, 365, 399, 834, 3008, 17538, 64, 82, 100,
    115, 126, 139, 154, 168, 185, 201, 214, 229, 242, 255, 355, 389, 423, 431, 3041, 17603, 65, 83, 101, 116, 127, 140, 266,
    169, 186, 202, 293, 230, 320, 327, 361, 395, 427, 933, 17507,
};
#define ITEM_OFF(p) c_off[p]
#define ITEM(i) c_items[i]

__device__ __align__(1024) bf16 g_kvo[3 * 2048 * 4096];
__device__ __align__(1024) bf16 g_ht[2048 * 2048];
__device__ __align__(1024) uint8_t g_x[4 << 20];
__device__ __align__(1024) uint32_t g_km[64 * 32 * 512];
__device__ __align__(1024) uint32_t g_vmt[64 * 32 * 512];
__device__ __align__(1024) float2 g_agg[8 * 1024];
__device__ __align__(1024) float4 g_coef[1024];
__device__ __align__(1024) uint32_t g_cntl[384 * 32];
#define g_cnt(i) g_cntl[(i) * 32]
__device__ __align__(1024) uint32_t g_hint[96 * 32];
constexpr int XG_SIDE = 65536, XG_T = 98304;
__device__ __forceinline__ uint32_t xg_buf(int b) { return (b & 1) * 128 + (b & 2) * 256; }
__device__ __forceinline__ uint32_t xg_lane(uint32_t lane) { return (lane >> 4) * 1024 + (lane & 8) * 32 + (lane & 7) * 16; }
__device__ __forceinline__ uint32_t xg_side(int b) { return XG_SIDE + (b >> 1) * 1024 + (b & 1) * 256; }

constexpr int STAGE = 49152, NSTAGE = 4;
constexpr int S_STG = NSTAGE * STAGE;
constexpr int S_BAR = S_STG + 32768;
constexpr int B_FULL = S_BAR, B_EMPTY = S_BAR + 32, B_RESUME = S_BAR + 64, B_KVFULL = S_BAR + 72, B_GO = S_BAR + 88, B_X = S_BAR + 96, B_PERS = S_BAR + 104,
              B_INIT = S_BAR + 112, B_RELM = S_BAR + 120, B_READY = S_BAR + 136, B_SFULL = S_BAR + 144, B_SFREE = S_BAR + 160, S_DESC = S_BAR + 176, B_RED = S_BAR + 216;
constexpr int S_EV = S_BAR + 80, S_EO = S_BAR + 84, B_INIT2 = S_BAR + 128, S_SC = S_BAR + 208, S_ISC = S_EV;
constexpr int S_XV = S_BAR + 256, S_LOG = S_XV + 2048;
constexpr int S_TOTAL = S_LOG + 768;
#define NRA 5
#define NRB 3
constexpr int S_W1 = 0;
constexpr int S_W2 = 4 * 4096 * (16 - NRA - NRB);
constexpr int S_KV = 188416;
constexpr int S_P1 = S_KV + 16384;
constexpr int S_X = S_P1 + 16384;
constexpr int S_SX = S_P1, S_OX = S_P1 + 2048;
constexpr int S_EM = S_X + 4096, S_TO = S_EM + 32, S_INV = S_EM + 64, B_DONE = S_BAR + 224, B_P1 = S_BAR + 232, B_EPOCH = S_BAR + 240, S_EPOCH = S_BAR + 248;
static_assert(S_INV + 32 <= S_BAR && S_KV % 1024 == 0 && S_TOTAL <= 232448, "chain smem layout");

template <int V> struct IC { static constexpr int value = V; };
template <int B, int E, typename F> __device__ __forceinline__ void static_for(F&& f) { if constexpr (B < E) { f(IC<B>{}); static_for<B + 1, E>(f); } }
__device__ __forceinline__ uint32_t cluster_rank() { uint32_t r; asm volatile("mov.u32 %0, %%cluster_ctarank;" : "=r"(r)); return r; }
__device__ __forceinline__ void spin_fault() { asm volatile("st.global.u32 [%0], 0;" ::"l"(0ull) : "memory"); }
__device__ __forceinline__ uint32_t smem_u32(const void* p) { return (uint32_t)__cvta_generic_to_shared(p); }
__device__ __forceinline__ uint32_t opq(uint32_t x, int lane) { return __shfl_sync(0xffffffffu, x, lane); }
__device__ __forceinline__ uint32_t mapa(uint32_t a, uint32_t r) { uint32_t d; asm volatile("mapa.shared::cluster.u32 %0, %1, %2;" : "=r"(d) : "r"(a), "r"(r)); return d; }
__device__ __forceinline__ void mma16816(float* d, uint32_t a0, uint32_t a1, uint32_t a2, uint32_t a3, uint32_t b0, uint32_t b1) {
    asm("mma.sync.aligned.m16n8k16.row.col.f32.bf16.bf16.f32 {%0,%1,%2,%3}, {%4,%5,%6,%7}, {%8,%9}, {%0,%1,%2,%3};"
        : "+f"(d[0]), "+f"(d[1]), "+f"(d[2]), "+f"(d[3]) : "r"(a0), "r"(a1), "r"(a2), "r"(a3), "r"(b0), "r"(b1));
}
__device__ __forceinline__ void mma1688(float* d, uint32_t a0, uint32_t a1, uint32_t b0) {
    asm("mma.sync.aligned.m16n8k8.row.col.f32.bf16.bf16.f32 {%0,%1,%2,%3}, {%4,%5}, {%6}, {%0,%1,%2,%3};"
        : "+f"(d[0]), "+f"(d[1]), "+f"(d[2]), "+f"(d[3]) : "r"(a0), "r"(a1), "r"(b0));
}
__device__ __forceinline__ void ldsm4(uint32_t* r, uint32_t a) {
    asm volatile("ldmatrix.sync.aligned.m8n8.x4.shared.b16 {%0,%1,%2,%3}, [%4];" : "=r"(r[0]), "=r"(r[1]), "=r"(r[2]), "=r"(r[3]) : "r"(a));
}
__device__ __forceinline__ void ldsm4t(uint32_t* r, uint32_t a) {
    asm volatile("ldmatrix.sync.aligned.m8n8.x4.trans.shared.b16 {%0,%1,%2,%3}, [%4];" : "=r"(r[0]), "=r"(r[1]), "=r"(r[2]), "=r"(r[3]) : "r"(a));
}
__device__ __forceinline__ void stsm4(uint32_t a, uint32_t r0, uint32_t r1, uint32_t r2, uint32_t r3) {
    asm volatile("stmatrix.sync.aligned.m8n8.x4.shared.b16 [%0], {%1,%2,%3,%4};" ::"r"(a), "r"(r0), "r"(r1), "r"(r2), "r"(r3) : "memory");
}
__device__ __forceinline__ void stsm4t(uint32_t a, uint32_t r0, uint32_t r1, uint32_t r2, uint32_t r3) {
    asm volatile("stmatrix.sync.aligned.m8n8.x4.trans.shared.b16 [%0], {%1,%2,%3,%4};" ::"r"(a), "r"(r0), "r"(r1), "r"(r2), "r"(r3) : "memory");
}
__device__ __forceinline__ uint32_t movm(uint32_t a) { uint32_t d; asm volatile("movmatrix.sync.aligned.m8n8.trans.b16 %0, %1;" : "=r"(d) : "r"(a)); return d; }
__device__ __forceinline__ uint32_t pack2(float lo, float hi) { uint32_t d; asm("cvt.rn.bf16x2.f32 %0, %1, %2;" : "=r"(d) : "f"(hi), "f"(lo)); return d; }
__device__ __forceinline__ uint32_t prmt(uint32_t a, uint32_t b, uint32_t s) { uint32_t d; asm("prmt.b32 %0, %1, %2, %3;" : "=r"(d) : "r"(a), "r"(b), "r"(s)); return d; }
__device__ __forceinline__ uint32_t pack2h(float lo, float hi) { uint32_t d; asm("cvt.rn.f16x2.f32 %0, %1, %2;" : "=r"(d) : "f"(hi), "f"(lo)); return d; }
__device__ __forceinline__ uint32_t h2bf(uint32_t a, uint32_t b) {
    uint32_t d;
    asm("{\n.reg .b16 l, h, u;\n.reg .f32 x, y;\nmov.b32 {l, u}, %1;\ncvt.f32.f16 x, l;\nmov.b32 {u, h}, %2;\ncvt.f32.f16 y, h;\ncvt.rn.bf16x2.f32 %0, y, x;\n}" : "=r"(d) : "r"(a), "r"(b));
    return d;
}
__device__ __forceinline__ void cvt_block(uint32_t* u, uint32_t& x, uint32_t sel) {
    const uint32_t a = prmt(u[0], u[0], sel), b = prmt(u[1], u[1], sel), c = prmt(u[2], u[2], sel), d = prmt(u[3], x, sel);
    x ^= u[3] ^ d;
    u[0] = h2bf(a, a); u[1] = h2bf(b, b); u[2] = h2bf(c, c); u[3] = h2bf(d, d);
}
__device__ __forceinline__ uint32_t amax(uint32_t a, uint32_t b) { uint32_t d; asm("max.xorsign.abs.bf16x2 %0, %1, %2;" : "=r"(d) : "r"(a), "r"(b)); return d; }
__device__ __forceinline__ uint32_t amax4(uint32_t m, const uint32_t* v) { return amax(amax(m, amax(v[0], v[1])), amax(v[2], v[3])); }
__device__ __forceinline__ uint32_t warp_exp(uint32_t m) { return __reduce_max_sync(0xffffffffu, max(m & 0x7f80u, (m >> 16) & 0x7f80u)) >> 7; }
__device__ __forceinline__ void red_max_shared(uint32_t a, uint32_t x) { asm volatile("red.shared.max.u32 [%0], %1;" ::"r"(a), "r"(x) : "memory"); }
__device__ __forceinline__ uint32_t mul_bf2(uint32_t a, uint32_t b) { uint32_t d; asm("mul.rn.bf16x2 %0, %1, %2;" : "=r"(d) : "r"(a), "r"(b)); return d; }
__device__ __forceinline__ float bf_lo(uint32_t u) { return __uint_as_float(u << 16); }
__device__ __forceinline__ float bf_hi(uint32_t u) { return __uint_as_float(u & 0xffff0000u); }
__device__ __forceinline__ float ex2(float x) { float y; asm("ex2.approx.ftz.f32 %0, %1;" : "=f"(y) : "f"(x)); return y; }
__device__ __forceinline__ float rcp(float x) { float y; asm("rcp.approx.ftz.f32 %0, %1;" : "=f"(y) : "f"(x)); return y; }
__device__ __forceinline__ void st_relaxed4(const void* p, uint32_t a, uint32_t b, uint32_t c, uint32_t d) {
    asm volatile("{\n.reg .b128 t;\nmov.b128 t, {%1,%2,%3,%4};\nst.relaxed.gpu.global.b128 [%0], t;\n}" ::"l"(p), "r"(a), "r"(b), "r"(c), "r"(d) : "memory");
}
__device__ __forceinline__ void st_relaxed2(const void* p, uint32_t a, uint32_t b) {
    asm volatile("{\n.reg .b64 t;\nmov.b64 t, {%1,%2};\nst.relaxed.gpu.global.b64 [%0], t;\n}" ::"l"(p), "r"(a), "r"(b) : "memory");
}
__device__ __forceinline__ void ld_relaxed2_if(uint32_t& a, uint32_t& b, const void* p, bool on) {
    asm volatile("{\n.reg .pred P;\n.reg .b64 t;\nsetp.ne.u32 P, %3, 0;\nmov.b64 t, {%0,%1};\n@P ld.relaxed.gpu.global.b64 t, [%2];\nmov.b64 {%0,%1}, t;\n}" : "+r"(a), "+r"(b) : "l"(p), "r"((uint32_t)on) : "memory");
}
__device__ __forceinline__ void ld_relaxed4(uint32_t* v, const void* p) {
    asm volatile("ld.relaxed.gpu.global.L1::no_allocate.v4.b32 {%0,%1,%2,%3}, [%4];" : "=r"(v[0]), "=r"(v[1]), "=r"(v[2]), "=r"(v[3]) : "l"(p) : "memory");
}
__device__ __forceinline__ void ld_relaxed1n(uint32_t& v, const void* p) { asm volatile("ld.relaxed.gpu.global.L1::no_allocate.b32 %0, [%1];" : "=r"(v) : "l"(p) : "memory"); }
__device__ __forceinline__ void red_add4(const void* p, uint32_t a, uint32_t b, uint32_t c, uint32_t d) {
    asm volatile("red.relaxed.gpu.global.add.noftz.v4.f16x2 [%0], {%1,%2,%3,%4};" ::"l"(p), "r"(a), "r"(b), "r"(c), "r"(d) : "memory");
}
__device__ __forceinline__ void red_add1(const void* p, uint32_t a) { asm volatile("red.relaxed.gpu.global.add.noftz.f16x2 [%0], %1;" ::"l"(p), "r"(a) : "memory"); }
__device__ __forceinline__ void ld_relaxed2(uint32_t* v, const void* p) {
    asm volatile("{\n.reg .b64 t;\nld.relaxed.gpu.global.L1::no_allocate.b64 t, [%2];\nmov.b64 {%0,%1}, t;\n}" : "=r"(v[0]), "=r"(v[1]) : "l"(p) : "memory");
}
__device__ __forceinline__ uint32_t ld_relaxed1(const void* p) { uint32_t v; asm volatile("ld.relaxed.gpu.global.u32 %0, [%1];" : "=r"(v) : "l"(p) : "memory"); return v; }
__device__ __forceinline__ void st_relaxed1(const void* p, uint32_t v) { asm volatile("st.relaxed.gpu.global.u32 [%0], %1;" ::"l"(p), "r"(v) : "memory"); }
__device__ __forceinline__ uint32_t ld_acquire(const void* p) { uint32_t v; asm volatile("ld.acquire.gpu.global.u32 %0, [%1];" : "=r"(v) : "l"(p) : "memory"); return v; }
__device__ __forceinline__ void red_relaxed(void* p) { asm volatile("red.relaxed.gpu.global.add.u32 [%0], 1;" ::"l"(p) : "memory"); }
__device__ __forceinline__ void red_release(void* p) { asm volatile("red.release.gpu.global.add.u32 [%0], 1;" ::"l"(p) : "memory"); }
__device__ __forceinline__ void st_stream4(const void* p, float a, float b, float c, float d) { asm volatile("st.global.cs.v4.f32 [%0], {%1, %2, %3, %4};" ::"l"(p), "f"(a), "f"(b), "f"(c), "f"(d) : "memory"); }
__device__ __forceinline__ void fence_async() { asm volatile("fence.proxy.async.global;" ::: "memory"); }
__device__ __forceinline__ void fence_async_smem() { asm volatile("fence.proxy.async.shared::cta;" ::: "memory"); }
__device__ __forceinline__ void wait_count(const uint32_t* p, uint32_t target) {
    while ((int32_t)(ld_acquire(p) - target) < 0) __nanosleep(POLLNS);
}
__device__ __forceinline__ void bar_sync(int id, int n) { asm volatile("bar.sync %0, %1;" ::"r"(id), "r"(n) : "memory"); }
__device__ __forceinline__ bool bar_and(int id, bool v) {
    uint32_t r;
    asm volatile("{\n.reg .pred P, Q;\nsetp.ne.u32 Q, %2, 0;\nbar.red.and.pred P, %1, 128, Q;\nselp.u32 %0, 1, 0, P;\n}" : "=r"(r) : "r"(id), "r"((uint32_t)v) : "memory");
    return r;
}
__device__ __forceinline__ void bar_arrive(int id, int n) { asm volatile("bar.arrive %0, %1;" ::"r"(id), "r"(n) : "memory"); }
__device__ __forceinline__ void lds128(uint32_t* v, uint32_t a) { asm volatile("ld.shared.v4.b32 {%0,%1,%2,%3}, [%4];" : "=r"(v[0]), "=r"(v[1]), "=r"(v[2]), "=r"(v[3]) : "r"(a) : "memory"); }
__device__ __forceinline__ uint32_t lds32(uint32_t a) { uint32_t v; asm volatile("ld.shared.b32 %0, [%1];" : "=r"(v) : "r"(a) : "memory"); return v; }
__device__ __forceinline__ void lds64(uint32_t* v, uint32_t a) { asm volatile("ld.shared.v2.b32 {%0,%1}, [%2];" : "=r"(v[0]), "=r"(v[1]) : "r"(a) : "memory"); }
__device__ __forceinline__ void lds64f(float* v, uint32_t a) { asm volatile("ld.shared.v2.f32 {%0,%1}, [%2];" : "=f"(v[0]), "=f"(v[1]) : "r"(a) : "memory"); }
__device__ __forceinline__ void sts128(uint32_t a, const uint32_t* v) { asm volatile("st.shared.v4.b32 [%0], {%1,%2,%3,%4};" ::"r"(a), "r"(v[0]), "r"(v[1]), "r"(v[2]), "r"(v[3]) : "memory"); }
__device__ __forceinline__ void sts64(uint32_t a, uint32_t x, uint32_t y) { asm volatile("st.shared.v2.b32 [%0], {%1,%2};" ::"r"(a), "r"(x), "r"(y) : "memory"); }
__device__ __forceinline__ void sts32(uint32_t a, uint32_t x) { asm volatile("st.shared.b32 [%0], %1;" ::"r"(a), "r"(x) : "memory"); }
__device__ __forceinline__ bool mbar_try(uint32_t b, uint32_t par) {
    uint32_t ok;
    asm volatile("{\n.reg .pred P;\nmbarrier.test_wait.parity.shared::cta.b64 P, [%1], %2;\nselp.u32 %0, 1, 0, P;\n}" : "=r"(ok) : "r"(b), "r"(par) : "memory");
    return ok;
}
__device__ __forceinline__ void mbar_wait(uint32_t b, uint32_t par) {
    asm volatile("{\n.reg .pred P;\nW: mbarrier.try_wait.parity.shared::cta.b64 P, [%0], %1;\n@!P bra W;\n}" ::"r"(b), "r"(par) : "memory");
}
__device__ __forceinline__ void mbar_wait_bounded(uint32_t b, uint32_t par) {
    asm volatile("{\n.reg .pred P, Q;\n.reg .u32 t, u;\nmov.u32 t, %%globaltimer_lo;\nW: mbarrier.try_wait.parity.shared::cta.b64 P, [%0], %1;\n"
                 "mov.u32 u, %%globaltimer_lo;\nsub.u32 u, u, t;\nsetp.gt.u32 Q, u, 2000000000;\n@Q st.global.u32 [%2], 0;\n@!P bra W;\n}" ::"r"(b), "r"(par), "l"(0ull) : "memory");
}
__device__ __forceinline__ void declare_fence(int zero) { asm volatile(".reg .pred PNEVER;\nsetp.ne.u32 PNEVER, %0, 0;" ::"r"(zero)); }
__device__ __forceinline__ void sched_fence() { asm volatile("{\n.reg .pred Q;\n.reg .u32 x;\n@!PNEVER bra D;\nF: ld.volatile.global.u32 x, [%0];\nsetp.ne.u32 Q, x, 0;\n@Q bra F;\nD:\n}" ::"l"(0ull) : "memory"); }
__device__ __forceinline__ void mbar_init(uint32_t b, uint32_t n) { asm volatile("mbarrier.init.shared::cta.b64 [%0], %1;" ::"r"(b), "r"(n) : "memory"); }
__device__ __forceinline__ void mbar_expect(uint32_t b, uint32_t bytes) { asm volatile("mbarrier.arrive.expect_tx.shared::cta.b64 _, [%0], %1;" ::"r"(b), "r"(bytes) : "memory"); }
__device__ __forceinline__ void mbar_arrive(uint32_t b) { asm volatile("mbarrier.arrive.shared::cta.b64 _, [%0];" ::"r"(b) : "memory"); }
__device__ __forceinline__ void mbar_arrive_cluster(uint32_t b) { asm volatile("mbarrier.arrive.shared::cluster.b64 _, [%0];" ::"r"(b) : "memory"); }
__device__ __forceinline__ void cluster_sync() { asm volatile("barrier.cluster.arrive.relaxed.aligned;\nbarrier.cluster.wait.aligned;" ::: "memory"); }
__device__ __forceinline__ uint32_t get_epoch(uint32_t sb) { mbar_wait(sb + B_EPOCH, 0); return __shfl_sync(0xffffffffu, lds32(sb + S_EPOCH), 0); }
__device__ __forceinline__ void tma2d(uint32_t dst, const CUtensorMap* m, int c0, int c1, uint32_t bar) {
    asm volatile("cp.async.bulk.tensor.2d.shared::cluster.global.mbarrier::complete_tx::bytes [%0], [%1, {%2, %3}], [%4];" ::"r"(dst), "l"(m), "r"(c0), "r"(c1), "r"(bar) : "memory");
}
__device__ __forceinline__ void tma3d(uint32_t dst, const CUtensorMap* m, int c0, int c1, int c2, uint32_t bar) {
    asm volatile("cp.async.bulk.tensor.3d.shared::cluster.global.mbarrier::complete_tx::bytes [%0], [%1, {%2, %3, %4}], [%5];" ::"r"(dst), "l"(m), "r"(c0), "r"(c1), "r"(c2), "r"(bar) : "memory");
}
__device__ __forceinline__ void mbar_expect_e(uint32_t b, uint32_t bytes) {
    asm volatile("{\n.reg .pred E;\nelect.sync _|E, 0xffffffff;\n@E mbarrier.arrive.expect_tx.shared::cta.b64 _, [%0], %1;\n}" ::"r"(b), "r"(bytes) : "memory");
}
__device__ __forceinline__ void tma3d_mc_e(uint32_t dst, const CUtensorMap* m, int c0, int c1, int c2, uint32_t bar, uint16_t mask, uint64_t pol) {
    asm volatile("{\n.reg .pred E;\nelect.sync _|E, 0xffffffff;\n@E cp.async.bulk.tensor.3d.shared::cluster.global.mbarrier::complete_tx::bytes.multicast::cluster.L2::cache_hint [%0], [%1, {%2, %3, %4}], [%5], %6, %7;\n}" ::"r"(dst), "l"(m), "r"(c0), "r"(c1), "r"(c2), "r"(bar), "h"(mask), "l"(pol) : "memory");
}
__device__ __forceinline__ void tma4d_e(uint32_t dst, const CUtensorMap* m, int c0, int c1, int c3, uint32_t bar, uint64_t pol) {
    asm volatile("{\n.reg .pred E;\nelect.sync _|E, 0xffffffff;\n@E cp.async.bulk.tensor.4d.shared::cluster.global.mbarrier::complete_tx::bytes.L2::cache_hint [%0], [%1, {%2, %3, 0, %4}], [%5], %6;\n}" ::"r"(dst), "l"(m), "r"(c0), "r"(c1), "r"(c3), "r"(bar), "l"(pol) : "memory");
}
__device__ __forceinline__ void tma4d_mc_e(uint32_t dst, const CUtensorMap* m, int c0, int c1, int c3, uint32_t bar, uint16_t mask, uint64_t pol) {
    asm volatile("{\n.reg .pred E;\nelect.sync _|E, 0xffffffff;\n@E cp.async.bulk.tensor.4d.shared::cluster.global.mbarrier::complete_tx::bytes.multicast::cluster.L2::cache_hint [%0], [%1, {%2, %3, 0, %4}], [%5], %6, %7;\n}" ::"r"(dst), "l"(m), "r"(c0), "r"(c1), "r"(c3), "r"(bar), "h"(mask), "l"(pol) : "memory");
}
__device__ __forceinline__ void tma_prefetch4d_e(const CUtensorMap* m, int c0, int c3) {
    asm volatile("{\n.reg .pred E;\nelect.sync _|E, 0xffffffff;\n@E cp.async.bulk.prefetch.tensor.4d.L2.global [%0, {%1, 0, 0, %2}];\n}" ::"l"(m), "r"(c0), "r"(c3) : "memory");
}
__device__ __forceinline__ void tma_prefetch3d_e(const CUtensorMap* m, int c0, int c1, int c2) {
    asm volatile("{\n.reg .pred E;\nelect.sync _|E, 0xffffffff;\n@E cp.async.bulk.prefetch.tensor.3d.L2.global [%0, {%1, %2, %3}];\n}" ::"l"(m), "r"(c0), "r"(c1), "r"(c2) : "memory");
}
__device__ __forceinline__ void l2_prefetch_e(const void* src, uint32_t bytes) {
    asm volatile("{\n.reg .pred E;\nelect.sync _|E, 0xffffffff;\n@E cp.async.bulk.prefetch.L2.global [%0], %1;\n}" ::"l"(src), "r"(bytes) : "memory");
}
__device__ __forceinline__ void bulk_g2s_e(uint32_t dst, const void* src, uint32_t bytes, uint32_t bar) {
    asm volatile("{\n.reg .pred E;\nelect.sync _|E, 0xffffffff;\n@E cp.async.bulk.shared::cluster.global.mbarrier::complete_tx::bytes [%0], [%1], %2, [%3];\n}" ::"r"(dst), "l"(src), "r"(bytes), "r"(bar) : "memory");
}
__device__ __forceinline__ bool elect_one() {
    uint32_t r;
    asm volatile("{\n.reg .pred E;\nelect.sync _|E, 0xffffffff;\nselp.u32 %0, 1, 0, E;\n}" : "=r"(r));
    return r;
}
__device__ __forceinline__ void tma_store2d(const CUtensorMap* m, int c0, int c1, uint32_t src, uint64_t pol) {
    asm volatile("cp.async.bulk.tensor.2d.global.shared::cta.bulk_group.L2::cache_hint [%0, {%1, %2}], [%3], %4;" ::"l"(m), "r"(c0), "r"(c1), "r"(src), "l"(pol) : "memory");
}
__device__ __forceinline__ void bulk_commit() { asm volatile("cp.async.bulk.commit_group;" ::: "memory"); }
__device__ __forceinline__ void bulk_wait_read() { asm volatile("cp.async.bulk.wait_group.read 0;" ::: "memory"); }
__device__ __forceinline__ void bulk_wait_all() { asm volatile("cp.async.bulk.wait_group 0;" ::: "memory"); }
__device__ __forceinline__ uint64_t mkdesc(uint32_t addr, uint32_t lbo, uint32_t sbo, uint32_t swz) {
    return (uint64_t)((addr & 0x3FFFF) >> 4) | ((uint64_t)(lbo >> 4) << 16) | ((uint64_t)(sbo >> 4) << 32) | ((uint64_t)swz << 62);
}
__device__ __forceinline__ void wg_fence() { asm volatile("wgmma.fence.sync.aligned;" ::: "memory"); }
__device__ __forceinline__ void wg_commit() { asm volatile("wgmma.commit_group.sync.aligned;" ::: "memory"); }
template <int N> __device__ __forceinline__ void wg_wait() { asm volatile("wgmma.wait_group.sync.aligned %0;" ::"n"(N) : "memory"); }
template <typename T> __device__ __forceinline__ void pin_ptr(T*& p) { asm volatile("" : "+l"(p)); }
template <int N> __device__ __forceinline__ void pin(uint32_t* d) {
#pragma unroll
    for (int i = 0; i < N; i++) asm volatile("" : "+r"(d[i])::"memory");
}
template <int N> __device__ __forceinline__ void pin(float* d) {
#pragma unroll
    for (int i = 0; i < N; i++) asm volatile("" : "+f"(d[i])::"memory");
}

template <int TA, int TB>
__device__ __forceinline__ void wgmma_ss256(float* d, uint64_t da, uint64_t db) {
    asm volatile("wgmma.mma_async.sync.aligned.m64n256k16.f32.bf16.bf16 "
        "{%0, %1, %2, %3, %4, %5, %6, %7, %8, %9, %10, %11, %12, %13, %14, %15, %16, %17, %18, %19, %20, %21, %22, %23, %24, %25, %26, %27, %28, %29, %30, %31, %32, %33, %34, %35, %36, %37, %38, %39, %40, %41, %42, %43, %44, %45, %46, %47, %48, %49, %50, %51, %52, %53, %54, %55, %56, %57, %58, %59, %60, %61, %62, %63, %64, %65, %66, %67, %68, %69, %70, %71, %72, %73, %74, %75, %76, %77, %78, %79, %80, %81, %82, %83, %84, %85, %86, %87, %88, %89, %90, %91, %92, %93, %94, %95, %96, %97, %98, %99, %100, %101, %102, %103, %104, %105, %106, %107, %108, %109, %110, %111, %112, %113, %114, %115, %116, %117, %118, %119, %120, %121, %122, %123, %124, %125, %126, %127}, %128, %129, 1, 1, 1, %130, %131;"
        : "+f"(d[0]), "+f"(d[1]), "+f"(d[2]), "+f"(d[3]), "+f"(d[4]), "+f"(d[5]), "+f"(d[6]), "+f"(d[7]), "+f"(d[8]), "+f"(d[9]), "+f"(d[10]), "+f"(d[11]), "+f"(d[12]), "+f"(d[13]), "+f"(d[14]), "+f"(d[15]), "+f"(d[16]), "+f"(d[17]), "+f"(d[18]), "+f"(d[19]), "+f"(d[20]), "+f"(d[21]), "+f"(d[22]), "+f"(d[23]), "+f"(d[24]), "+f"(d[25]), "+f"(d[26]), "+f"(d[27]), "+f"(d[28]), "+f"(d[29]), "+f"(d[30]), "+f"(d[31]), "+f"(d[32]), "+f"(d[33]), "+f"(d[34]), "+f"(d[35]), "+f"(d[36]), "+f"(d[37]), "+f"(d[38]), "+f"(d[39]), "+f"(d[40]), "+f"(d[41]), "+f"(d[42]), "+f"(d[43]), "+f"(d[44]), "+f"(d[45]), "+f"(d[46]), "+f"(d[47]), "+f"(d[48]), "+f"(d[49]), "+f"(d[50]), "+f"(d[51]), "+f"(d[52]), "+f"(d[53]), "+f"(d[54]), "+f"(d[55]), "+f"(d[56]), "+f"(d[57]), "+f"(d[58]), "+f"(d[59]), "+f"(d[60]), "+f"(d[61]), "+f"(d[62]), "+f"(d[63]), "+f"(d[64]), "+f"(d[65]), "+f"(d[66]), "+f"(d[67]), "+f"(d[68]), "+f"(d[69]), "+f"(d[70]), "+f"(d[71]), "+f"(d[72]), "+f"(d[73]), "+f"(d[74]), "+f"(d[75]), "+f"(d[76]), "+f"(d[77]), "+f"(d[78]), "+f"(d[79]), "+f"(d[80]), "+f"(d[81]), "+f"(d[82]), "+f"(d[83]), "+f"(d[84]), "+f"(d[85]), "+f"(d[86]), "+f"(d[87]), "+f"(d[88]), "+f"(d[89]), "+f"(d[90]), "+f"(d[91]), "+f"(d[92]), "+f"(d[93]), "+f"(d[94]), "+f"(d[95]), "+f"(d[96]), "+f"(d[97]), "+f"(d[98]), "+f"(d[99]), "+f"(d[100]), "+f"(d[101]), "+f"(d[102]), "+f"(d[103]), "+f"(d[104]), "+f"(d[105]), "+f"(d[106]), "+f"(d[107]), "+f"(d[108]), "+f"(d[109]), "+f"(d[110]), "+f"(d[111]), "+f"(d[112]), "+f"(d[113]), "+f"(d[114]), "+f"(d[115]), "+f"(d[116]), "+f"(d[117]), "+f"(d[118]), "+f"(d[119]), "+f"(d[120]), "+f"(d[121]), "+f"(d[122]), "+f"(d[123]), "+f"(d[124]), "+f"(d[125]), "+f"(d[126]), "+f"(d[127])
        : "l"(da), "l"(db), "n"(TA), "n"(TB));
}
template <int TA, int TB>
__device__ __forceinline__ void wgmma_ss256_first(float* d, uint64_t da, uint64_t db) {
    asm volatile("wgmma.mma_async.sync.aligned.m64n256k16.f32.bf16.bf16 "
        "{%0, %1, %2, %3, %4, %5, %6, %7, %8, %9, %10, %11, %12, %13, %14, %15, %16, %17, %18, %19, %20, %21, %22, %23, %24, %25, %26, %27, %28, %29, %30, %31, %32, %33, %34, %35, %36, %37, %38, %39, %40, %41, %42, %43, %44, %45, %46, %47, %48, %49, %50, %51, %52, %53, %54, %55, %56, %57, %58, %59, %60, %61, %62, %63, %64, %65, %66, %67, %68, %69, %70, %71, %72, %73, %74, %75, %76, %77, %78, %79, %80, %81, %82, %83, %84, %85, %86, %87, %88, %89, %90, %91, %92, %93, %94, %95, %96, %97, %98, %99, %100, %101, %102, %103, %104, %105, %106, %107, %108, %109, %110, %111, %112, %113, %114, %115, %116, %117, %118, %119, %120, %121, %122, %123, %124, %125, %126, %127}, %128, %129, 0, 1, 1, %130, %131;"
        : "=f"(d[0]), "=f"(d[1]), "=f"(d[2]), "=f"(d[3]), "=f"(d[4]), "=f"(d[5]), "=f"(d[6]), "=f"(d[7]), "=f"(d[8]), "=f"(d[9]), "=f"(d[10]), "=f"(d[11]), "=f"(d[12]), "=f"(d[13]), "=f"(d[14]), "=f"(d[15]), "=f"(d[16]), "=f"(d[17]), "=f"(d[18]), "=f"(d[19]), "=f"(d[20]), "=f"(d[21]), "=f"(d[22]), "=f"(d[23]), "=f"(d[24]), "=f"(d[25]), "=f"(d[26]), "=f"(d[27]), "=f"(d[28]), "=f"(d[29]), "=f"(d[30]), "=f"(d[31]), "=f"(d[32]), "=f"(d[33]), "=f"(d[34]), "=f"(d[35]), "=f"(d[36]), "=f"(d[37]), "=f"(d[38]), "=f"(d[39]), "=f"(d[40]), "=f"(d[41]), "=f"(d[42]), "=f"(d[43]), "=f"(d[44]), "=f"(d[45]), "=f"(d[46]), "=f"(d[47]), "=f"(d[48]), "=f"(d[49]), "=f"(d[50]), "=f"(d[51]), "=f"(d[52]), "=f"(d[53]), "=f"(d[54]), "=f"(d[55]), "=f"(d[56]), "=f"(d[57]), "=f"(d[58]), "=f"(d[59]), "=f"(d[60]), "=f"(d[61]), "=f"(d[62]), "=f"(d[63]), "=f"(d[64]), "=f"(d[65]), "=f"(d[66]), "=f"(d[67]), "=f"(d[68]), "=f"(d[69]), "=f"(d[70]), "=f"(d[71]), "=f"(d[72]), "=f"(d[73]), "=f"(d[74]), "=f"(d[75]), "=f"(d[76]), "=f"(d[77]), "=f"(d[78]), "=f"(d[79]), "=f"(d[80]), "=f"(d[81]), "=f"(d[82]), "=f"(d[83]), "=f"(d[84]), "=f"(d[85]), "=f"(d[86]), "=f"(d[87]), "=f"(d[88]), "=f"(d[89]), "=f"(d[90]), "=f"(d[91]), "=f"(d[92]), "=f"(d[93]), "=f"(d[94]), "=f"(d[95]), "=f"(d[96]), "=f"(d[97]), "=f"(d[98]), "=f"(d[99]), "=f"(d[100]), "=f"(d[101]), "=f"(d[102]), "=f"(d[103]), "=f"(d[104]), "=f"(d[105]), "=f"(d[106]), "=f"(d[107]), "=f"(d[108]), "=f"(d[109]), "=f"(d[110]), "=f"(d[111]), "=f"(d[112]), "=f"(d[113]), "=f"(d[114]), "=f"(d[115]), "=f"(d[116]), "=f"(d[117]), "=f"(d[118]), "=f"(d[119]), "=f"(d[120]), "=f"(d[121]), "=f"(d[122]), "=f"(d[123]), "=f"(d[124]), "=f"(d[125]), "=f"(d[126]), "=f"(d[127])
        : "l"(da), "l"(db), "n"(TA), "n"(TB));
}
template <int TB>
__device__ __forceinline__ void wgmma_rs128(float* d, const uint32_t* a, uint64_t db, uint32_t acc) {
    asm volatile("{\n.reg .pred P;\nsetp.ne.u32 P, %69, 0;\nwgmma.mma_async.sync.aligned.m64n128k16.f32.bf16.bf16 "
        "{%0, %1, %2, %3, %4, %5, %6, %7, %8, %9, %10, %11, %12, %13, %14, %15, %16, %17, %18, %19, %20, %21, %22, %23, %24, %25, %26, %27, %28, %29, %30, %31, %32, %33, %34, %35, %36, %37, %38, %39, %40, %41, %42, %43, %44, %45, %46, %47, %48, %49, %50, %51, %52, %53, %54, %55, %56, %57, %58, %59, %60, %61, %62, %63}, {%64, %65, %66, %67}, %68, P, 1, 1, %70;\n}"
        : "+f"(d[0]), "+f"(d[1]), "+f"(d[2]), "+f"(d[3]), "+f"(d[4]), "+f"(d[5]), "+f"(d[6]), "+f"(d[7]), "+f"(d[8]), "+f"(d[9]), "+f"(d[10]), "+f"(d[11]), "+f"(d[12]), "+f"(d[13]), "+f"(d[14]), "+f"(d[15]), "+f"(d[16]), "+f"(d[17]), "+f"(d[18]), "+f"(d[19]), "+f"(d[20]), "+f"(d[21]), "+f"(d[22]), "+f"(d[23]), "+f"(d[24]), "+f"(d[25]), "+f"(d[26]), "+f"(d[27]), "+f"(d[28]), "+f"(d[29]), "+f"(d[30]), "+f"(d[31]), "+f"(d[32]), "+f"(d[33]), "+f"(d[34]), "+f"(d[35]), "+f"(d[36]), "+f"(d[37]), "+f"(d[38]), "+f"(d[39]), "+f"(d[40]), "+f"(d[41]), "+f"(d[42]), "+f"(d[43]), "+f"(d[44]), "+f"(d[45]), "+f"(d[46]), "+f"(d[47]), "+f"(d[48]), "+f"(d[49]), "+f"(d[50]), "+f"(d[51]), "+f"(d[52]), "+f"(d[53]), "+f"(d[54]), "+f"(d[55]), "+f"(d[56]), "+f"(d[57]), "+f"(d[58]), "+f"(d[59]), "+f"(d[60]), "+f"(d[61]), "+f"(d[62]), "+f"(d[63])
        : "r"(a[0]), "r"(a[1]), "r"(a[2]), "r"(a[3]), "l"(db), "r"(acc), "n"(TB));
}
template <int TB>
__device__ __forceinline__ void wgmma_rs64(float* d, const uint32_t* a, uint64_t db, uint32_t acc) {
    asm volatile("{\n.reg .pred P;\nsetp.ne.u32 P, %37, 0;\nwgmma.mma_async.sync.aligned.m64n64k16.f32.bf16.bf16 "
        "{%0, %1, %2, %3, %4, %5, %6, %7, %8, %9, %10, %11, %12, %13, %14, %15, %16, %17, %18, %19, %20, %21, %22, %23, %24, %25, %26, %27, %28, %29, %30, %31}, {%32, %33, %34, %35}, %36, P, 1, 1, %38;\n}"
        : "+f"(d[0]), "+f"(d[1]), "+f"(d[2]), "+f"(d[3]), "+f"(d[4]), "+f"(d[5]), "+f"(d[6]), "+f"(d[7]), "+f"(d[8]), "+f"(d[9]), "+f"(d[10]), "+f"(d[11]), "+f"(d[12]), "+f"(d[13]), "+f"(d[14]), "+f"(d[15]), "+f"(d[16]), "+f"(d[17]), "+f"(d[18]), "+f"(d[19]), "+f"(d[20]), "+f"(d[21]), "+f"(d[22]), "+f"(d[23]), "+f"(d[24]), "+f"(d[25]), "+f"(d[26]), "+f"(d[27]), "+f"(d[28]), "+f"(d[29]), "+f"(d[30]), "+f"(d[31])
        : "r"(a[0]), "r"(a[1]), "r"(a[2]), "r"(a[3]), "l"(db), "r"(acc), "n"(TB));
}
template <int TB>
__device__ __forceinline__ void wgmma_rs16(float* d, const uint32_t* a, uint64_t db, uint32_t acc) {
    asm volatile("{\n.reg .pred P;\nsetp.ne.u32 P, %13, 0;\nwgmma.mma_async.sync.aligned.m64n16k16.f32.bf16.bf16 "
        "{%0, %1, %2, %3, %4, %5, %6, %7}, {%8, %9, %10, %11}, %12, P, 1, 1, %14;\n}"
        : "+f"(d[0]), "+f"(d[1]), "+f"(d[2]), "+f"(d[3]), "+f"(d[4]), "+f"(d[5]), "+f"(d[6]), "+f"(d[7])
        : "r"(a[0]), "r"(a[1]), "r"(a[2]), "r"(a[3]), "l"(db), "r"(acc), "n"(TB));
}

__device__ __forceinline__ void wait_clocks(uint32_t n) {
    asm volatile("{\n.reg .pred P;\n.reg .u32 a, b;\nmov.u32 a, %%clock;\nW: mov.u32 b, %%clock;\nsub.u32 b, b, a;\nsetp.lt.u32 P, b, %0;\n@P bra W;\n}" ::"r"(n) : "memory");
}
__device__ __forceinline__ uint32_t gtime() { uint32_t t; asm volatile("mov.u32 %0, %%globaltimer_lo;" : "=r"(t)); return t; }
__device__ __forceinline__ uint32_t stamp_word(uint32_t seq) { return (gtime() & ~31u) | (seq & 31u); }
__device__ __forceinline__ void wait_time(uint32_t t, uint32_t sb) { while ((int32_t)(gtime() - t) < 0) {} }
#define NAPMODE 1
__device__ __forceinline__ void nap(uint32_t ns) { if (NAPMODE) wait_clocks(ns * 7 / 4); else __nanosleep(ns); }
template <int STRIDE>
__device__ __forceinline__ uint32_t latest_stamp(const uint32_t* p, uint32_t seq, uint32_t ref, uint32_t sb) {
#pragma unroll 1
    for (int n = opq(0, 0);; n++) {
        uint32_t bad = 0; int32_t m = INT32_MIN;
#pragma unroll
        for (int i = 0; i < 3; i++) { const uint32_t v = ld_relaxed1(p + i * STRIDE); bad |= (v ^ seq) & 31u; m = max(m, (int32_t)((v & ~31u) - ref)); }
        if (__all_sync(0xffffffffu, bad == 0)) return ref + __reduce_max_sync(0xffffffffu, m);
        nap(100);
        if (n > SPIN_LIMIT) spin_fault();
    }
}
constexpr uint32_t ONES = 0x3C003C00u, FULL = 0x50005000u;
__device__ __forceinline__ void pacer(const Params& P, const uint32_t sb, const int cta, const int lane, const uint32_t epoch) {
    uint8_t* const zp = P.xb + cta * 2048 + xg_lane(lane);
    if (lane < 3) asm volatile("prefetch.tensormap [%0];" ::"l"(&P.tm[lane == 0 ? M_C1 + cta % 3 : lane == 1 ? M_CO : M_SEG]) : "memory");
    uint32_t e0 = 0;
#pragma unroll 2
    for (int i = 0; i < 32; i++) { const uint4 u = __ldg((const uint4*)P.mem0 + i * 32 + lane); e0 = amax(amax(e0, amax(u.x, u.y)), amax(u.z, u.w)); }
    e0 = min(max(warp_exp(e0), 31u), 253u) - 14;
    if (cta < 32) {
        const uint32_t* m = (const uint32_t*)(P.mem0 + (lane >> 2) * 1024 + cta * 32 + (lane & 3) * 2);
        const float sc = __uint_as_float((254 - e0) << 23);
        auto cv = [&](uint32_t u) { return pack2h(bf_lo(u) * sc, bf_hi(u) * sc); };
        const uint32_t y = cv(m[12]);
        st_relaxed4(zp, cv(m[0]), cv(m[4]), cv(m[8]), prmt(y, FULL, 0x7610));
        st_relaxed1(P.xb + xg_side(cta) + lane * 4, prmt(y, FULL, 0x3254));
    }
    if (cta < 40) {
#pragma unroll 1
        for (int b = 1; b < 4; b++) st_relaxed4(zp + xg_buf(b), 0, 0, 0, 0);
    }
    __threadfence();
    const uint32_t* ts = (const uint32_t*)(P.xb + XG_T) + lane;
    int32_t d0 = P.dly;
    const uint32_t go = mapa(sb + B_GO, (cta / 3 & 1) * 3 + 1 + (lane & 1));
    auto free_segment = [&]() { if (lane == 0) mbar_expect(sb + B_KVFULL, 16384); __syncwarp(); if (lane < 2) mbar_arrive_cluster(go); };
    for (int n = 0; (int32_t)(ld_acquire(&g_cnt(C_XCNT)) - (epoch + 1) * 256) < 0; n++) { __nanosleep(500); if (n > SPIN_LIMIT) spin_fault(); }
    const uint32_t ex = max(ld_relaxed1(&g_cnt(C_XMAX)) & 255, 67u);
    mbar_wait_bounded(sb + B_READY, 0);
    free_segment();
    if (lane == 0) st_relaxed2(g_hint + cta * 32, stamp_word(epoch + 1), lds32(sb + S_EV) | lds32(sb + S_EO) << 16);
    uint32_t a = gtime();
    for (int n = 0;; n++) {
        uint32_t bad = 0, e = 0; int32_t m = INT32_MIN;
#pragma unroll
        for (int i = 0; i < 3; i++) {
            uint32_t v[2];
            ld_relaxed2(v, g_hint + lane * 32 + i * 1024);
            bad |= (v[0] ^ (epoch + 1)) & 31u; m = max(m, (int32_t)((v[0] & ~31u) - a)); e = __vmaxu2(e, v[1]);
        }
        if (__all_sync(0xffffffffu, bad == 0)) {
            a += __reduce_max_sync(0xffffffffu, m);
            const uint32_t ev = __reduce_max_sync(0xffffffffu, e & 255), eo = __reduce_max_sync(0xffffffffu, e >> 16);
            if (lane == 0) { sts64(sb + S_SC, max(ev, 97u) + max(eo, 97u) - 244, ex); sts32(sb + S_ISC, e0 * 0x800080u); }
            break;
        }
        wait_clocks(100);
        if (n > SPIN_LIMIT) spin_fault();
    }
    wait_time(a, sb);
    if (lane == 0) mbar_arrive(sb + B_RELM);
#pragma unroll 1
    for (int s = 0; s < 63; s++) {
        const uint32_t seq = epoch * 63 + s + 1;
        mbar_wait_bounded(sb + B_P1, s & 1);
        const uint32_t tx = gtime();
        if (lane == 0) st_relaxed1(ts + (s & 1) * 256 + cta, (tx & ~31u) | (seq & 31u));
        if (s > 0) {
            const int32_t e0 = latest_stamp<32>(ts + (~s & 1) * 256 + 128, seq - 1, a, sb) + P.mrg - a;
            d0 += min(max(e0, min(e0 + P.guard, -P.clamp0)), P.clampv) / 2;
        }
        while ((int32_t)(gtime() - tx) < P.rd) nap(20);
        a = latest_stamp<32>(ts + (s & 1) * 256, seq, tx, sb) + d0;
        while ((int32_t)(a - gtime()) > 250) nap(40);
        wait_time(a, sb);
        if (lane == 0) mbar_arrive(sb + B_RELM);
        mbar_wait_bounded(sb + B_RED, s & 1);
        const uint32_t g = tx + __reduce_max_sync(0xffffffffu, lds32(sb + S_TO + (lane & 7) * 4) - tx);
        if (lane == 0) st_relaxed1(ts + (s & 1) * 256 + 128 + cta, (g & ~31u) | (seq & 31u));
        if (s < 62) { if (P.kvd) nap(P.kvd); free_segment(); }
    }
}
__device__ __forceinline__ void st_async2(uint32_t a, uint32_t x, uint32_t y, uint32_t bar) {
    asm volatile("st.async.weak.shared::cluster.mbarrier::complete_tx::bytes.v2.b32 [%0], {%1,%2}, [%3];" ::"r"(a), "r"(x), "r"(y), "r"(bar) : "memory");
}
__device__ __forceinline__ uint32_t xor_or(uint32_t a, uint32_t b, uint32_t t) { uint32_t d; asm("lop3.b32 %0, %1, %2, %3, 0x7E;" : "=r"(d) : "r"(a), "r"(b), "r"(t)); return d; }
__device__ __forceinline__ bool tags_ok(uint32_t bad, uint32_t mask = 1) {
    uint32_t r;
    asm volatile("{\n.reg .pred P;\n.reg .b32 x;\nand.b32 x, %1, %2;\nsetp.ne.b32 P, x, 0;\nvote.sync.any.pred P, P, 0xffffffff;\nselp.u32 %0, 0, 1, P;\n}" : "=r"(r) : "r"(bad), "r"(mask));
    return r;
}
constexpr int SROW = 56;
#define PREA 8
#define PREB 9
#define RING1 6
#define RING2 7
#define RING3 8
#define PRE2 10
#define PRE2A 0
#define PRE3 0
#define EFENCE 0
#define RFENCE 1
#define PROG 16
#define EARLY 0
#define PLATE 1
#define NDEP 0
#define EFENCE2 0
#define IVSLOT 15
#define LAG2 8
#define LAG 4
#define PUT1 33
#define DEPS 3
#define ADELAY 120
#define BDELAY 0
#define HOLD 1
#define XDELAY 330
#define FENCEA 0x80
#define FENCEB 0x80
#define FENCE2 0x220
#define OFENCE 0
#define MASK3 0x57
#define MASK4 0x55
#define MASK5 0x25
#define OFF3 0x5320
#define OFF4 0x6420
#define OFF5 0x0520
#define RESA (NRA == 3 ? 15 : NRA == 4 ? 3 : 0)
#define RESB (NRB == 3 ? 0xcc : NRB == 4 ? 0x30 : 0)
#define RESB1 (NRB == 3 ? 0xcc : NRB == 4 ? 0xc : 0)
__host__ __device__ constexpr int smem_mask(int NR) { return NR == 3 ? MASK3 : NR == 4 ? MASK4 : MASK5; }
__host__ __device__ constexpr bool round_smem(int r, int NR) { return smem_mask(NR) >> r & 1; }
__host__ __device__ constexpr int kord(int r, int NR) { int c = 0; for (int i = 0; i < r; i++) c += round_smem(i, NR) == round_smem(r, NR); return round_smem(r, NR) ? NR + c : c; }
__host__ __device__ constexpr int slot_r(int n, int NR) { return n < 32 ? n >> 2 : (((n & 31) >> 2) + ((NR == 3 ? OFF3 : NR == 4 ? OFF4 : OFF5) >> (n & 3) * 4)) & 7; }
__host__ __device__ constexpr int slot_k(int n, int NR) { return kord(slot_r(n, NR), NR); }
__host__ __device__ constexpr int slot_sord(int n, int NR) { int c = 0; for (int i = 0; i < n; i++) c += slot_k(i, NR) >= NR; return c; }
__host__ __device__ constexpr int sfrag_slot(int q, int NR) { for (int n = 0; n < 64; n++) if (slot_k(n, NR) >= NR && slot_sord(n, NR) == q) return n; return -1; }
__host__ __device__ constexpr int w1_loaded(int n, int NR, int PRE) {
    int q = PRE;
    for (int i = 0; i <= n; i++) q += q < (8 - NR) * 8 && q - slot_sord(i + 1, NR) < (i < 32 ? RING1 : RING2);
    return q;
}
template <int Q, int NR>
__device__ __forceinline__ void load_w1(uint32_t* w, const uint32_t* a) {
    constexpr int n = sfrag_slot(Q, NR);
    ldsm4t(w, a[n & 3] + ((slot_k(n, NR) - NR) * 2 + (n >> 5)) * 2048);
}
constexpr int AB = NRA < 5, BB = 3 - AB;
__device__ __forceinline__ bool w2_full(int role, int warp) { return warp < (role == 2 ? 2 : 3); }
__device__ __forceinline__ int w2_nblk(int role, int warp) { return warp < 4 ? BB - !w2_full(role, warp) : AB; }
__host__ __device__ constexpr int w2_step(bool full, int i) { return AB ? (full ? 2 * i : 0) : full ? (i == 0 ? 0 : i == 1 ? 16 - 2 * EARLY : 18 - 2 * EARLY) : i; }
__device__ __forceinline__ int w2_block(int role, int warp) {
    const int f = role * 3 + warp, g = role == 2 ? warp : role;
    if (AB) return (warp >= 4 ? role * 4 + (warp - 4) : w2_full(role, warp) ? 16 + 4 * (f >> 1) + (f & 1) : 12 + g) ^ EARLY;
    return w2_full(role, warp) ? EARLY + 4 * (f >> 1) + (f & 1) : EARLY + 2 + 4 * g;
}
__device__ __forceinline__ int w2_res(int role, int warp) { return warp >= 4 ? RESA : w2_full(role, warp) ? RESB : RESB1; }
__device__ __forceinline__ int w2_units(int role, int warp) { return w2_nblk(role, warp) * 4 - (5 - (warp < 4 ? NRB : NRA)) * 2; }
constexpr int W2B = (BB * 4 - (5 - NRB) * 2) * 2048, W2A = (AB * 4 - (5 - NRA) * 2) * 2048;
static_assert(S_W2 + 4 * W2B - 8192 + 4 * W2A == S_KV, "weights");
__device__ __forceinline__ int w1_base(int warp) { return S_W1 + (warp < 4 ? warp * (8 - NRB) : 4 * (8 - NRB) + (warp - 4) * (8 - NRA)) * 4096; }
__device__ __forceinline__ int w2_base(int warp) { return S_W2 + (warp < 4 ? warp * W2B : 4 * W2B - 8192 + (warp - 4) * W2A); }
__device__ __forceinline__ void chain_load(const Params& P, uint32_t sb, int cta, int warp, int lane, int round) {
    const int role = cta % 3, h = cta / 3;
    mbar_expect_e(sb + B_INIT, round ? (8 - (warp < 4 ? NRB : NRA)) * 4096 : 20480);
    if (round) mbar_expect_e(sb + B_INIT2, w2_units(role, warp) * 2048);
    __syncwarp();
    const int m1 = (warp < 4 ? smem_mask(NRB) : smem_mask(NRA)) ^ (round ? 0 : 255), below = (1 << lane) - 1;
    const int m2 = (w2_res(role, warp) ^ (round ? 0xfff : 0)) & ((1 << w2_nblk(role, warp) * 4) - 1);
    const uint32_t d1 = sb + (round ? w1_base(warp) : warp * 20480), d2 = round ? sb + w2_base(warp) : d1 + __popc(m1) * 4096;
    if (m1 >> lane & 1) tma3d(d1 + __popc(m1 & below) * 4096, &P.tm[M_C1 + role], 0, warp * 128 + lane * 16, h * 2, sb + B_INIT);
    __syncwarp();
    if (m2 >> lane & 1)
        tma2d(d2 + __popc(m2 & below) * 2048, &P.tm[M_CO], (w2_block(role, warp) + w2_step(w2_full(role, warp), lane >> 2)) * 32, h * 128 + (lane & 3) * 32, sb + (round ? B_INIT2 : B_INIT));
    __syncwarp();
}

__device__ __forceinline__ void put_partials(bool TR, uint32_t a, const float* x, const float* y) {
    if (TR) stsm4t(a, pack2(x[0], x[1]), pack2(x[2], x[3]), pack2(y[0], y[1]), pack2(y[2], y[3]));
    else stsm4(a, pack2(x[0], x[1]), pack2(x[2], x[3]), pack2(y[0], y[1]), pack2(y[2], y[3]));
}
template <int NR, int PRE, int FM, int B, int E>
__device__ __forceinline__ void project(float (*acc)[4], bool TR, const uint32_t (*wr)[4], uint32_t (*as)[4], uint32_t (*v)[4], uint32_t* x, const uint32_t* w1a, uint32_t pp, uint32_t zero) {
    static_for<B, E>([&](auto I) {
        constexpr int n = I.value, kk = slot_k(n, NR), T = (n >> 5) * 4 + (n & 3), so = slot_sord(n, NR), q = w1_loaded(n - 1, NR, PRE);
        constexpr bool sm = kk >= NR;
        const uint32_t* w = sm ? as[so] : wr[sm ? 0 : (kk * 2 + (n >> 5)) * 4 + (n & 3)];
        if constexpr (n == 32 && PUT1 < 32) { put_partials(TR, pp, acc[0], acc[1]); put_partials(TR, pp + 4096, acc[2], acc[3]); }
        if constexpr (n == 0) {
            const uint32_t c = prmt(v[0][3], x[0], 0x3254);
            v[0][0] = h2bf(v[0][0], v[0][0]); v[0][1] = h2bf(v[0][1], v[0][1]); v[0][2] = h2bf(v[0][2], v[0][2]); v[0][3] = h2bf(v[0][3], x[0]);
            x[0] = c;
        }
        if constexpr ((n & 31) < 4) acc[T][0] = acc[T][1] = acc[T][2] = acc[T][3] = 0.f;
        mma16816(acc[T], w[0], w[1], w[2], w[3], v[slot_r(n, NR) >> 1][(slot_r(n, NR) & 1) * 2], v[slot_r(n, NR) >> 1][(slot_r(n, NR) & 1) * 2 + 1]);
        if constexpr (n == DEPS) {
            const uint32_t sel = __float_as_uint(acc[T][0]) * zero + 0x7610;
#pragma unroll
            for (int b = 1; b < 4; b++) {
                if (b <= NDEP) cvt_block(v[b], x[b], sel);
                else {
                    const uint32_t c = prmt(v[b][3], x[b], 0x3254);
                    v[b][0] = h2bf(v[b][0], v[b][0]); v[b][1] = h2bf(v[b][1], v[b][1]); v[b][2] = h2bf(v[b][2], v[b][2]); v[b][3] = h2bf(v[b][3], x[b]);
                    x[b] = c;
                }
            }
        }
        if constexpr (w1_loaded(n, NR, PRE) > q) load_w1<q, NR>(as[q], w1a);
        if constexpr (n == PUT1 && n >= 32) { put_partials(TR, pp, acc[0], acc[1]); put_partials(TR, pp + 4096, acc[2], acc[3]); }
        if constexpr (n % 4 == 3 && (FM >> (n / 4) & 1) && n != E - 1) sched_fence();
    });
    if constexpr (E == 64) { put_partials(TR, pp + 8192, acc[4], acc[5]); put_partials(TR, pp + 12288, acc[6], acc[7]); }
}
__device__ __forceinline__ void reduce8(const uint32_t (*x)[4], const uint32_t* sel, float sc, uint32_t& r0, uint32_t& r1) {
    float d[4][4];
#pragma unroll
    for (int i = 0; i < 4; i++) {
        d[i][0] = d[i][1] = d[i][2] = d[i][3] = 0.f;
        mma16816(d[i], x[i][0], x[i][1], x[i][2], x[i][3], sel[2 * i], sel[2 * i + 1]);
    }
    r0 = pack2(((d[0][0] + d[1][0]) + (d[2][0] + d[3][0])) * sc, ((d[0][1] + d[1][1]) + (d[2][1] + d[3][1])) * sc);
    r1 = pack2(((d[0][2] + d[1][2]) + (d[2][2] + d[3][2])) * sc, ((d[0][3] + d[1][3]) + (d[2][3] + d[3][3])) * sc);
}

__host__ __device__ constexpr int wo_count(int n, int RES, bool res) { int c = 0; for (int i = 0; i < n; i++) c += (RES >> (i >> 2) & 1) == res; return c; }
__host__ __device__ constexpr int wo_loaded(int n, int RES, int PRE, int end) { int q = PRE; for (int i = 0; i <= n; i++) q += q < end && q - wo_count(i + 1, RES, false) < RING3; return q; }
template <int Q>
__device__ __forceinline__ void load_w2(uint32_t* w, const uint32_t* a) { ldsm4t(w, a[Q & 1] + (Q >> 1) * 1024); }
template <int NB, int RES, int PRE, int FM>
__device__ __forceinline__ void wo_blocks(uint32_t (*w)[4], const uint32_t (*wp)[4], uint32_t oa, uint32_t ia, const uint32_t* wa, const uint8_t* dst, const uint8_t* dsd, bool odd) {
    float a[NB][4][4], iv[2];
    uint32_t o[4][4], r[5];
    bar_sync(3, 256);
#pragma unroll
    for (int i = 0; i < 4; i++) ldsm4(o[i], oa + i * 512);
    if (FM & 1) sched_fence();
    static_for<0, NB * 16>([&](auto I) {
        constexpr int n = I.value, i = n & 15, end = wo_count(NB * 16, RES, false), q = wo_loaded(n - 1, RES, PRE, end);
        constexpr bool res = RES >> (n >> 2) & 1;
        const uint32_t* b = o[i >> 2] + (i & 2);
        const uint32_t* x = res ? wp[wo_count(n, RES, true)] : w[wo_count(n, RES, false)];
        float* d = a[n >> 4][i & 3];
        if constexpr (i < 4) d[0] = d[1] = d[2] = d[3] = 0.f;
        mma16816(d, x[0], x[1], x[2], x[3], b[0], b[1]);
        if constexpr (wo_loaded(n, RES, PRE, end) > q) load_w2<q>(w[q], wa);
        if constexpr (n == IVSLOT) { bar_sync(4, 160); lds64f(iv, ia); }
        if constexpr (n == NB * 16 - 1 || (n >= 16 && i == LAG - 1)) {
            const float (*e)[4] = a[n == NB * 16 - 1 ? NB - 1 : (n >> 4) - 1];
            const uint32_t y = pack2h((e[1][2] + e[3][2]) * iv[0], (e[1][3] + e[3][3]) * iv[1]);
            r[0] = movm(pack2h((e[0][0] + e[2][0]) * iv[0], (e[0][1] + e[2][1]) * iv[1])); r[1] = movm(pack2h((e[0][2] + e[2][2]) * iv[0], (e[0][3] + e[2][3]) * iv[1]));
            r[2] = movm(pack2h((e[1][0] + e[3][0]) * iv[0], (e[1][1] + e[3][1]) * iv[1])); r[3] = movm(odd ? ONES : y); r[4] = movm(odd ? y : ONES);
        }
        if constexpr (n == NB * 16 - 1 || (n >= 16 && i == LAG2 - 1)) {
            constexpr int bs = w2_step(NB == BB, n == NB * 16 - 1 ? NB - 1 : (n >> 4) - 1);
            red_add4(dst + bs * 2048, r[0], r[1], r[2], r[3]);
            red_add1(dsd + (bs >> 1) * 1024 + (bs & 1) * 256, r[4]);
        }
        if constexpr (((FM >> (n / 4 + 1)) & 1) && (n & 3) == 3 && n != NB * 16 - 1) sched_fence();
    });
}
#define FRAG1(ln) ((((ln) & 7) + ((ln) >> 4) * 8) * 128 + ((((((ln) >> 3) & 1) << (ROLE == 1)) ^ ((ln) & 7)) << 4))
#define FRAG2(ln) ((((ln) & 7) + ((ln) >> 4) * 8) * 64 + (((((ln) >> 3) & 1) ^ (((ln) >> 1) & 3)) << 4))
#define TILE_X(i) (ROLE == 1 ? (((i) >> 1) << 6) | (((i) & 1) << 4) : (i) << 5)
__device__ __forceinline__ void chain_fetch(const Params& P, const uint32_t sb, const int cta, const int warp, const int lane, uint32_t (*wr)[4]) {
    const int ROLE = cta % 3, nr = warp < 4 ? NRB : NRA;
    mbar_wait(sb + B_INIT, 0);
#pragma unroll
    for (int f = 0; f < 40; f++) {
        const bool w1 = f < (NRA < NRB ? NRA : NRB) * 8 || f < nr * 8;
        ldsm4t(wr[f], sb + warp * 20480 + (f >> 2) * 2048 + (w1 ? FRAG1(lane) ^ TILE_X(f & 3) : (f & 2) * 512 + (FRAG2(lane) ^ ((f & 1) << 5))));
    }
    fence_async_smem();
    mbar_wait(sb + B_SFREE + (warp >> 2) * 8, 0);
    bar_sync(1, 256);
    chain_load(P, sb, cta, warp, lane, 1);
}
__device__ __forceinline__ void chain_bounds(const uint32_t sb, const int cta, const int warp, const int lane, const uint32_t (*wr)[4]) {
    const int ROLE = cta % 3, nr = warp < 4 ? NRB : NRA;
    uint32_t m[6] = {}, u[4];
#pragma unroll
    for (int f = 0; f < 40; f++) m[f < 24 ? 0 : f >> 3] = amax4(m[f < 24 ? 0 : f >> 3], wr[f]);
    uint32_t m1 = amax(m[0], amax(nr > 3 ? m[3] : 0, nr > 4 ? m[4] : 0)), m2 = amax(nr > 3 ? 0 : m[3], nr > 4 ? 0 : m[4]);
    mbar_wait(sb + B_INIT, 1);
    if (ROLE == 2) {
#pragma unroll 4
        for (int i = 0; i < S_W2 / 4096; i++) { lds128(u, sb + S_W1 + warp * (S_W2 / 8) + i * 512 + lane * 16); m1 = amax4(m1, u); }
    }
    mbar_wait(sb + B_INIT2, 0);
    const int n = w2_units(ROLE, warp) * 4;
#pragma unroll 4
    for (int i = 0; i < n; i++) { lds128(u, sb + w2_base(warp) + i * 512 + lane * 16); m2 = amax4(m2, u); }
    m1 = warp_exp(m1); m2 = warp_exp(m2);
    if (lane == 0) { if (ROLE == 2) red_max_shared(sb + S_EV, m1); red_max_shared(sb + S_EO, m2); }
}
template <bool ATT>
__device__ __forceinline__ void chain_role(const Params& P, const uint32_t sb, const int cta, const int warp, const int lane, const uint32_t (*wr)[4]) {
    constexpr int NR = ATT ? NRA : NRB, PRE = ATT ? PREA : PREB;
    const int h = cta / 3, ROLE = cta - h * 3;
    uint32_t l8 = opq(sb + lane * 8, lane);
    const uint8_t* persu = (const uint8_t*)((ROLE == 1 ? g_km : g_vmt) + h * 512) - (sb >> 1);
    auto persist = [&](int s, int tile, uint32_t r0, uint32_t r1) {
        uint32_t* pp = (uint32_t*)(persu + s * 65536 + (ROLE == 1 ? (tile >> 1) * 512 + (tile & 1) * 128 : tile * 256) + (l8 >> 1));
        pp[0] = r0; pp[ROLE == 1 ? 64 : 32] = r1;
    };
    const uint32_t rk0 = (h & 1) * 3, rd1 = __shfl_sync(0xffffffffu, mapa(sb, rk0 + (ROLE + 1) % 3) - sb, 0), rd2 = __shfl_sync(0xffffffffu, mapa(sb, rk0 + (ROLE + 2) % 3) - sb, 0);
    const uint32_t xo = (ROLE == 2 ? S_XV : S_X + ROLE * 2048) + warp * 256;
    const bool full = w2_full(ROLE, warp);
    const int blk = w2_block(ROLE, warp);
    const uint32_t om = blk * 2048, os = xg_side(blk);
    const uint32_t w1o = sb + w1_base(warp), w2o = sb + w2_base(warp);
    if (lane == 0) mbar_arrive(sb + B_READY);
#pragma unroll 1
    for (int s = 0;; s++) {
        l8 += s & P.zero;
        uint32_t r0, r1;
        {
            uint32_t v[4][4], as[(8 - NR) * 8][4], w1a[4];
            float acc[8][4];
            const uint32_t pst = sb + S_P1 + (l8 - sb) * 16 + ((warp * 16) ^ ((l8 & 56) * 2));
#pragma unroll
            for (int i = 0; i < 4; i++) w1a[i] = w1o + (FRAG1((l8 - sb) >> 3) ^ TILE_X(i));
            auto preload = [&]() { static_for<0, PRE>([&](auto I) { load_w1<I.value, NR>(as[I.value], w1a); }); };
#pragma unroll 1
            while (true) {
                uint32_t x[4];
                if (!(PLATE >> ATT & 1)) preload();
                const uint32_t lm = opq(l8 - sb, (l8 - sb) >> 3);
                const uint8_t* pm = P.xb + xg_buf(s) + warp * 8192 + xg_lane(lm >> 3);
                const uint8_t* ps = P.xb + xg_buf(s) + XG_SIDE + warp * 2048 + (lm >> 1);
                pin_ptr(pm); pin_ptr(ps);
                mbar_wait(sb + B_RELM, s & 1);
                if (ATT ? ADELAY : BDELAY) wait_clocks(ATT ? ADELAY : BDELAY);
#pragma unroll
                for (int b = 0; b < 4; b++) { ld_relaxed4(v[b], pm + b * 2048); ld_relaxed1n(x[b], ps + (b >> 1) * 1024 + (b & 1) * 256); }
                if (PLATE >> ATT & 1) { preload(); if (PLATE >> (ATT + 2) & 1) sched_fence(); }
                project<NR, PRE, ATT ? FENCEA : FENCEB, 0, PROG>(acc, ROLE == 2, wr, as, v, x, w1a, pst, P.zero);
                const uint32_t bad = xor_or(x[0], x[1], FULL) | xor_or(x[2], x[3], FULL);
                if (tags_ok(bad, 0xffffffffu)) break;
            }
            project<NR, PRE, ATT ? FENCEA : FENCEB, PROG, 64>(acc, ROLE == 2, wr, as, v, nullptr, w1a, pst, 0);
            const uint32_t isc = lds32(sb + S_ISC + (s & 1) * 4);
            const uint32_t lq = l8 + ((s >> 3) & P.zero), e1 = s == 63 ? 0 : rd1, e2 = s == 63 ? 0 : rd2;
            uint32_t x[4][4], sel[8], xd[6] = {l8 + xo, l8 + xo + e1, l8 + xo + e2, sb + B_X + e1, sb + B_X + e2, sb + S_P1 + warp * 2048 + (lq & 64) * 16 + (lq & 128) + (lq & 56) * 2};
#pragma unroll
            for (int i = 0; i < 8; i++) sel[i] = (lq & 224) == i * 32 ? 0x3F803F80u : 0u;
            pin<6>(xd); pin<8>(sel);
            if (RFENCE) sched_fence();
            bar_sync(1, 256);
#pragma unroll
            for (int i = 0; i < 4; i++) ldsm4t(x[i], xd[5] + i * 256);
            if (!ATT && l8 == sb + (warp - 3) * 1024) mbar_arrive(sb + B_P1);
            uint32_t em = warp_exp(amax(amax4(amax(amax(v[0][0], v[0][1]), amax(v[0][2], v[0][3])), v[1]), amax4(amax(amax(v[2][0], v[2][1]), amax(v[2][2], v[2][3])), v[3])));
            if (EFENCE2) sched_fence();
            reduce8(x, sel, bf_hi(isc), r0, r1);
            st_async2(xd[1], r0, r1, xd[3]);
            st_async2(xd[2], r0, r1, xd[4]);
            sts64(xd[0], r0, r1);
            if (s == 63) { persist(s, warp, r0, r1); break; }
            if (l8 == sb) sts32(sb + S_EM + warp * 4, em + (isc >> 23));
            __syncwarp();
            if (l8 == sb) mbar_arrive(sb + B_X);
        }
        uint32_t w[40][4], w2a[2], odd;
        const uint8_t *po, *pd;
        auto wo_addr = [&]() {
            const uint32_t lo = (l8 + ((s >> 2) & P.zero) - sb) >> 3;
            w2a[0] = w2o + FRAG2(lo); w2a[1] = w2o + (FRAG2(lo) ^ 32);
            po = P.xb + xg_buf(s + 1) + om + xg_lane(lo);
            pd = P.xb + xg_buf(s + 1) + os + lo * 4;
            odd = lo & 4;
            pin_ptr(po); pin_ptr(pd); pin<2>(w2a); pin<1>(&odd);
        };
        uint32_t oa = l8 * 2 + (S_OX - sb);
        if constexpr (ATT) {
            const uint32_t ln = (l8 + ((s >> 4) & P.zero) - sb) >> 3;
            const uint32_t va = sb + S_KV + 8192 + ((warp >> 1) & 1) * 4096 + ((ln & 7) + (ln >> 4) * 8) * 128 + ((((warp & 1) * 4 + ((ln >> 3) & 1)) ^ (ln & 7)) << 4);
            const uint32_t ka = sb + S_KV + (warp & 1) * 2048 + (ln & 15) * 128 + (((ln >> 4) ^ (ln & 7)) << 4);
            uint32_t ad[5] = {sb + S_SX + (ln & 3) * (8 * SROW) + (ln >> 2) * 4 + (warp < 6 ? (warp - 4) * 64 : 128 + (warp - 6) * 32), l8 + S_XV + (warp - 4) * 512,
                              l8 + S_SX + (ln >> 2) * (4 * SROW - 32), oa + (warp - 4) * 512, sb + S_ISC + (~s & 1) * 4};
            if constexpr (AB) { wo_addr(); pin<1>(&oa); }
            pin<5>(ad);
            const uint32_t sa = ad[0], sr = ad[2];
            uint32_t vf[4][4], vm[2][2], q[8][2];
            float S[8][4];
#pragma unroll
            for (int n = 0; n < 8; n++) { S[n][0] = S[n][1] = S[n][2] = S[n][3] = 0.f; }
            mbar_wait(sb + B_KVFULL, s & 1);
            if (warp < 6) {
                uint32_t kf[8][4];
#pragma unroll
                for (int k = 0; k < 8; k++) ldsm4(kf[k], (ka ^ ((k & 3) << 5)) + (k >> 2) * 4096);
#pragma unroll
                for (int i = 0; i < 4; i++) ldsm4t(vf[i], (va ^ ((i & 1) << 5)) + (i >> 1) * 2048);
                mbar_wait(sb + B_X, s & 1);
#pragma unroll
                for (int k = 0; k < 8; k++) lds64(q[k], l8 + S_X + k * 256);
#pragma unroll
                for (int k = 0; k < 8; k++) mma16816(S[k], kf[k][0], kf[k][1], kf[k][2], kf[k][3], q[k][0], q[k][1]);
#pragma unroll
                for (int k = 0; k < 4; k++) { S[k][0] = S[2 * k][0] + S[2 * k + 1][0]; S[k][1] = S[2 * k][1] + S[2 * k + 1][1]; S[k][2] = S[2 * k][2] + S[2 * k + 1][2]; S[k][3] = S[2 * k][3] + S[2 * k + 1][3]; }
                sts32(sa, __float_as_uint((S[0][0] + S[1][0]) + (S[2][0] + S[3][0])));
                sts32(sa + 4 * SROW, __float_as_uint((S[0][1] + S[1][1]) + (S[2][1] + S[3][1])));
                sts32(sa + 32, __float_as_uint((S[0][2] + S[1][2]) + (S[2][2] + S[3][2])));
                sts32(sa + 4 * SROW + 32, __float_as_uint((S[0][3] + S[1][3]) + (S[2][3] + S[3][3])));
            } else {
#pragma unroll
                for (int i = 0; i < 4; i++) ldsm4t(vf[i], (va ^ ((i & 1) << 5)) + (i >> 1) * 2048);
                uint32_t xa = l8 + S_X + (warp - 6) * 1024;
                pin<1>(&xa);
                mbar_wait(sb + B_X, s & 1);
#pragma unroll
                for (int k = 0; k < 8; k++) lds64(q[k], xa + (k >> 2) * 2048 + (k & 3) * 256);
#pragma unroll
                for (int k = 0; k < 4; k++) mma16816(S[k], q[4 + (k & 2)][0], q[4 + (k & 2)][1], q[5 + (k & 2)][0], q[5 + (k & 2)][1], q[k][0], q[k][1]);
                sts32(sa, __float_as_uint((S[0][0] + S[2][0]) + (S[1][2] + S[3][2])));
                sts32(sa + 4 * SROW, __float_as_uint((S[0][1] + S[2][1]) + (S[1][3] + S[3][3])));
            }
            lds64(vm[0], ad[1]); lds64(vm[1], ad[1] + 256);
            bar_sync(2, 160);
            const float cs = 0.08838834764831845f * 1.4426950408889634f;
            float E[6][2];
#pragma unroll
            for (int i = 0; i < 6; i++) lds64f(E[(i + 4) % 6], sr + ((i + 4) % 6) * 32);
            const uint32_t isn = lds32(ad[4]);
            E[4][0] += E[5][0]; E[4][1] += E[5][1];
            float m = fmaxf(fmaxf(fmaxf(fmaxf(E[0][0], E[0][1]), fmaxf(E[1][0], E[1][1])), fmaxf(fmaxf(E[2][0], E[2][1]), fmaxf(E[3][0], E[3][1]))), fmaxf(E[4][0], E[4][1]));
            m = fmaxf(m, __shfl_xor_sync(0xffffffffu, m, 1));
            m = fmaxf(m, __shfl_xor_sync(0xffffffffu, m, 2));
            m *= cs;
            if constexpr (AB) static_for<0, PRE3>([&](auto I) { load_w2<I.value>(w[I.value], w2a); });
            uint32_t pa[5];
#pragma unroll
            for (int i = 0; i < 5; i++) { const int k = (i + 4) % 5; E[k][0] = ex2(fmaf(E[k][0], cs, -m)); E[k][1] = ex2(fmaf(E[k][1], cs, -m)); pa[k] = pack2(E[k][0], E[k][1]); }
            if (EFENCE) sched_fence();
            float O[2][4], Z[4];
#pragma unroll
            for (int i = 0; i < 4; i++) { O[0][i] = O[1][i] = Z[i] = 0.f; }
            mma1688(Z, isn, isn, pa[4]);
            mma1688(O[0], vm[0][0], vm[0][1], pa[4]);
            mma1688(O[1], vm[1][0], vm[1][1], pa[4]);
#pragma unroll
            for (int k = 0; k < 2; k++) {
                mma16816(Z, isn, isn, isn, isn, pa[2 * k], pa[2 * k + 1]);
#pragma unroll
                for (int i = 0; i < 2; i++) mma16816(O[i], vf[2 * k + i][0], vf[2 * k + i][1], vf[2 * k + i][2], vf[2 * k + i][3], pa[2 * k], pa[2 * k + 1]);
            }
            stsm4t(ad[3], pack2(O[0][0], O[0][1]), pack2(O[0][2], O[0][3]), pack2(O[1][0], O[1][1]), pack2(O[1][2], O[1][3]));
            if constexpr (AB) wo_blocks<1, RESA, PRE3, OFENCE / 2>(w, wr + NR * 8, oa, sb + S_INV + (l8 & 24), w2a, po, pd, odd);
            else bar_arrive(3, 256);
            if (warp == 4) {
                if (l8 - sb < 32) sts64(l8 + S_INV, __float_as_uint(rcp(Z[0])), __float_as_uint(rcp(Z[1])));
                bar_arrive(4, 160);
            }
            if (ROLE != 0) persist(s, warp, r0, r1);
            if (warp == 7 && l8 == sb) mbar_expect(sb + B_X, 4096);
        } else {
            if (ROLE != 0) persist(s, warp, r0, r1);
            wo_addr(); pin<1>(&oa);
            static_for<0, PRE2A>([&](auto I) { load_w2<I.value>(w[I.value], w2a); });
            mbar_wait(sb + B_X, s & 1);
            if (warp == 0) {
                uint32_t sc[2];
                lds64(sc, sb + S_SC);
                const int em = __reduce_max_sync(0xffffffffu, lds32(sb + S_EM + ((l8 >> 1) & 28)));
                if (l8 == sb) sts32(sb + S_ISC + (~s & 1) * 4, min(max(em - 127, (int)sc[1]) + (int)sc[0], 253) * 0x800080u);
                bar_arrive(2, 160);
            }
            wait_clocks(XDELAY - (warp == 0) * 100);
            constexpr int PRE1 = (BB - 1) * 16 - (5 - NRB) * 8 < PRE2 ? (BB - 1) * 16 - (5 - NRB) * 8 : PRE2;
            static_for<PRE2A, PRE1>([&](auto I) { load_w2<I.value>(w[I.value], w2a); });
            if (full) {
                static_for<PRE1, PRE2>([&](auto I) { load_w2<I.value>(w[I.value], w2a); });
                wo_blocks<BB, RESB, PRE2, FENCE2 * 2 + OFENCE % 2>(w, wr + NR * 8, oa, sb + S_INV + (l8 & 24), w2a, po, pd, odd);
            } else wo_blocks<BB - 1, RESB1, PRE1, FENCE2 * 2 + OFENCE % 2>(w, wr + NR * 8, oa, sb + S_INV + (l8 & 24), w2a, po, pd, odd);
        }
        if (l8 == sb) { sts32(sb + S_TO + warp * 4, gtime()); mbar_arrive(sb + B_RED); }
        if (HOLD && !(PLATE >> ATT & 1)) mbar_wait(sb + B_RED, s & 1);
        if (ROLE != 0 && (s & 3) == 3 && l8 == sb) mbar_arrive(sb + B_PERS);
        if (ROLE == 0 && s == 62) return;
    }
    __syncwarp();
    if (l8 == sb) mbar_arrive(sb + B_PERS);
}
struct Pipe { uint32_t stage, phase; };
struct Cons {
    uint32_t sb, rel;
    int wg, wq, lane, rank, pair;
    uint32_t nst;
    Pipe p;
};
__device__ __forceinline__ void pipe_next(Pipe& p) { p.stage = (p.stage + 1) & (NSTAGE - 1); p.phase ^= (p.stage == 0); }
__device__ __forceinline__ void release(const Cons& c, uint32_t stage) { if (c.lane < 2) mbar_arrive_cluster(c.rel + stage * 8); }
__device__ __forceinline__ void wait_full(const Cons& c) { mbar_wait(c.sb + B_FULL + c.p.stage * 8, c.p.phase); }

enum { PEND_NONE = 0, PEND_KVO = 1, PEND_HT = 2, PEND_OUT = 3, PEND_OUTA = 4 };
struct Pend { uint32_t pk[64]; int kind, row, col, cnt; };

__device__ __forceinline__ void staging_wait(const Cons& c) { if (c.nst) mbar_wait(c.sb + B_SFREE + c.wg * 8, (c.nst - 1) & 1); }
__device__ __forceinline__ void staging_post(Cons& c, int kind, int row, int col, int cnt) {
    __syncwarp();
    if (c.lane == 0) {
        if (c.wq == 0) { const uint32_t x[4] = {(uint32_t)kind, (uint32_t)row, (uint32_t)col, (uint32_t)cnt}; sts128(c.sb + S_DESC + c.wg * 16, x); }
        mbar_arrive(c.sb + B_SFULL + c.wg * 8);
    }
    c.nst++;
}
__device__ __forceinline__ void drain(const Params& P, Cons& c, Pend& d) {
    const uint32_t* pk = d.pk;
    const bool ht = d.kind == PEND_HT;
    const int hi = (c.lane >> 3) & 1;
    const uint32_t stg = c.sb + S_STG + c.wg * 16384, base = stg + ((ht ? hi * 32 + c.wq * 8 : c.wq * 16 + hi * 8) + (c.lane & 7)) * 128;
    staging_wait(c);
#pragma unroll
    for (int j = 0; j < 8; j++) {
        const int ch = (j & 3) * 2 + (c.lane >> 4);
        stsm4(base + (j >> 2) * 8192 + ((ch ^ (c.lane & 7)) << 4), pk[j * 4], pk[j * 4 + 1], pk[j * 4 + 2], pk[j * 4 + 3]);
    }
    if (d.kind >= PEND_OUT) {
        const uint32_t rd = stg + (c.lane >> 4) * 8192 + c.wq * 2048 + (c.lane & 15) * 8;
        const int s1 = d.kind == PEND_OUT ? 2 : 64, s2 = d.kind == PEND_OUT ? 8 : 2;
        const float* o = P.out + (size_t)(d.row + c.wq * 2 * s2) * 2048 + d.col + c.lane * 4;
        __syncwarp();
#pragma unroll 1
        for (int q = 0; q < 4; q++) {
#pragma unroll
            for (int i = 0; i < 4; i++) {
                uint32_t u[2];
                lds64(u, (rd ^ ((q * 2 + (i & 1)) << 4)) + (q * 2 + (i & 1) + (i >> 1) * 8) * 128);
                st_stream4(o + ((i & 1) + (i >> 1) * s2) * 2048, bf_lo(u[0]), bf_hi(u[0]), bf_lo(u[1]), bf_hi(u[1]));
            }
            o += s1 * 2048;
        }
        __syncwarp();
    } else {
        fence_async_smem();
        staging_post(c, d.kind, d.row, d.col, (d.col & 128) ? d.cnt : -1);
    }
    if (d.col & 128) d.kind = PEND_NONE;
    d.col += 128;
#pragma unroll
    for (int i = 0; i < 32; i++) d.pk[i] = d.pk[32 + i];
}

constexpr int S_STG2 = 8 * 20480, PEND_BOTH = 8;
__device__ __forceinline__ void drain_both(Cons& c, const Pend& d) {
    const uint32_t base = c.sb + c.wg * 16384 + (c.wq * 16 + ((c.lane >> 3) & 1) * 8 + (c.lane & 7)) * 128;
#pragma unroll
    for (int j = 0; j < 16; j++)
        stsm4(base + (j < 8 ? S_STG : S_STG2) + (j >> 2 & 1) * 8192 + ((((j & 3) * 2 + (c.lane >> 4)) ^ (c.lane & 7)) << 4), d.pk[j * 4], d.pk[j * 4 + 1], d.pk[j * 4 + 2], d.pk[j * 4 + 3]);
    fence_async_smem();
    staging_post(c, PEND_KVO | PEND_BOTH, d.row, d.col, d.cnt);
}

__device__ __forceinline__ void store_warp(const Params& P, uint32_t sb, int wg, int cta) {
    if (cta < 128) {
        for (int i = 0; i < P.xd; i++) __nanosleep(1000);
        const uint32_t e1 = get_epoch(sb) + 1;
        const uint4* x = (const uint4*)P.Bx + (cta * 2 + wg) * 1024 + (threadIdx.x & 31);
        uint32_t m = 0;
#pragma unroll 4
        for (int i = 0; i < 32; i++) { const uint4 u = __ldg(x + i * 32); m = amax(amax(m, amax(u.x, u.y)), amax(u.z, u.w)); }
        m = warp_exp(m);
        if (elect_one()) { atomicMax(&g_cnt(C_XMAX), e1 << 8 | m); red_release(&g_cnt(C_XCNT)); }
        __syncwarp();
    }
    const uint32_t stg = sb + S_STG + wg * 16384;
#pragma unroll 1
    for (uint32_t n = 0;; n++) {
        mbar_wait(sb + B_SFULL + wg * 8, n & 1);
        uint32_t x[4];
        lds128(x, sb + S_DESC + wg * 16);
#pragma unroll
        for (int i = 0; i < 4; i++) x[i] = __shfl_sync(0xffffffffu, x[i], 0);
        if (x[0] == PEND_NONE) break;
        const bool ht = x[0] == PEND_HT;
        const CUtensorMap* m = &P.tm[ht ? M_HTS : M_KVO];
        const uint64_t pol = P.pol[ht ? 2 : x[1] >= 4096 ? 1 : (x[1] & 2047) < 1536 ? 0 : 10];
        if (elect_one()) {
#pragma unroll
            for (int i = 0; i < 4; i++) tma_store2d(m, x[2] + (i >> 1) * 64, x[1] + (i & 1) * (ht ? 1024 : 32), stg + i * 4096, pol);
            if (x[0] & PEND_BOTH) {
#pragma unroll 1
                for (int i = 0; i < 4; i++) tma_store2d(m, x[2] + 128 + (i >> 1) * 64, x[1] + (i & 1) * 32, stg + (S_STG2 - S_STG) + i * 4096, pol);
            }
            bulk_commit();
            bulk_wait_read();
            mbar_arrive(sb + B_SFREE + wg * 8);
            if ((int)x[3] >= 0) { bulk_wait_all(); fence_async(); red_relaxed(&g_cnt(x[3])); }
        }
        __syncwarp();
    }
}

template <int TA, int TB, bool FIRST>
__device__ __forceinline__ void issue_ktile(float* acc, const Cons& c) {
    const uint32_t a = c.sb + c.p.stage * STAGE + c.wg * 8192, b = c.sb + c.p.stage * STAGE + 16384;
    const uint64_t da = mkdesc(a, TA ? 8192 : 16, 1024, 1), db = mkdesc(b, TB ? 8192 : 16, 1024, 1);
    wg_fence();
#pragma unroll
    for (int k = 0; k < 4; k++) {
        if (FIRST && k == 0) wgmma_ss256_first<TA, TB>(acc, da, db);
        else wgmma_ss256<TA, TB>(acc, da + (TA ? 128 : 2) * k, db + (TB ? 128 : 2) * k);
    }
    wg_commit();
}
template <bool KVONLY, bool FIRST>
__device__ __forceinline__ void issue_any(float* acc, const Cons& c, int type) {
    wait_full(c);
    if (!KVONLY && type == T_A1) issue_ktile<0, 0, FIRST>(acc, c);
    else if (!KVONLY && type == T_A2) issue_ktile<1, 0, FIRST>(acc, c);
    else issue_ktile<0, 1, FIRST>(acc, c);
}
template <bool KVONLY = false>
__device__ __forceinline__ void mainloop(float* acc, const Params& P, Cons& c, Pend& d, int type, int nk) {
    issue_any<KVONLY, true>(acc, c, type);
    uint32_t prev = c.p.stage;
    pipe_next(c.p);
#pragma unroll 1
    for (int kt = 1; kt < nk; kt++) {
        if (!KVONLY && d.kind != PEND_NONE && kt != 2) drain(P, c, d);
        issue_any<KVONLY, false>(acc, c, type);
        wg_wait<1>();
        release(c, prev);
        prev = c.p.stage;
        pipe_next(c.p);
    }
    d.kind = PEND_NONE;
    wg_wait<0>();
    pin<128>(acc);
    release(c, prev);
}
__device__ __forceinline__ void pack_half(uint32_t* pk, const float* a) {
#pragma unroll
    for (int i = 0; i < 32; i++) pk[i] = pack2(a[2 * i], a[2 * i + 1]);
}

__device__ __forceinline__ void epi_kv(const float* acc, const Cons& c, Pend& d, int mb, int nb) {
    pack_half(d.pk, acc); pack_half(d.pk + 32, acc + 64);
    d.kind = PEND_KVO; d.row = (nb >> 4) * 2048 + mb * 256 + c.rank * 128 + c.wg * 64; d.col = (nb & 15) * 256; d.cnt = C_KV + mb;
}

__device__ __forceinline__ void qa_scores(float* S, float* Sm, const uint32_t* q, Cons& c) {
    wait_full(c);
    const uint32_t st = c.sb + c.p.stage * STAGE;
    const uint64_t dk = mkdesc(st + c.wg * 8192, 16, 1024, 1), dm = mkdesc(st + 32768 + c.wg * 4096, 128, 2048, 0);
    wg_fence();
#pragma unroll
    for (int i = 0; i < 8; i++) wgmma_rs64<0>(S, q + i * 4, dk + (i >> 2) * 1024 + (i & 3) * 2, i != 0);
#pragma unroll
    for (int i = 0; i < 8; i++) wgmma_rs16<0>(Sm, q + i * 4, dm + i * 16, i != 0);
    wg_commit();
    pipe_next(c.p);
}
__device__ __forceinline__ void qa_softmax(uint32_t (*pa)[4], const float* S, const float* Sm, const Cons& c) {
    const int t = c.lane & 3, i0 = (c.wq & 1) * 16 + (c.lane >> 2) - 2 * t;
    const bool sg = c.wq >= 2;
    const float cs = 0.08838834764831845f * 1.4426950408889634f;
    float x[2][10];
#pragma unroll
    for (int r = 0; r < 2; r++) {
#pragma unroll
        for (int j = 0; j < 4; j++)
#pragma unroll
            for (int e = 0; e < 2; e++) {
                const float v = sg ? S[16 + j * 4 + r * 2 + e] : S[j * 4 + r * 2 + e];
                x[r][j * 2 + e] = (j * 8 + e - r * 8 > i0) ? -1e9f / 0.08838834764831845f : v;
            }
        x[r][8] = sg ? Sm[4 + r * 2] : Sm[r * 2];
        x[r][9] = sg ? Sm[5 + r * 2] : Sm[1 + r * 2];
        float m = fmaxf(fmaxf(fmaxf(fmaxf(x[r][0], x[r][1]), fmaxf(x[r][2], x[r][3])), fmaxf(fmaxf(x[r][4], x[r][5]), fmaxf(x[r][6], x[r][7]))), fmaxf(x[r][8], x[r][9]));
        m = fmaxf(m, __shfl_xor_sync(0xffffffffu, m, 1));
        m = fmaxf(m, __shfl_xor_sync(0xffffffffu, m, 2));
        m *= -cs;
#pragma unroll
        for (int i = 0; i < 10; i++) x[r][i] = ex2(fmaf(x[r][i], cs, m));
        float sum = (((x[r][0] + x[r][1]) + (x[r][2] + x[r][3])) + ((x[r][4] + x[r][5]) + (x[r][6] + x[r][7]))) + (x[r][8] + x[r][9]);
        sum += __shfl_xor_sync(0xffffffffu, sum, 1);
        sum += __shfl_xor_sync(0xffffffffu, sum, 2);
        const float inv = rcp(sum);
#pragma unroll
        for (int i = 0; i < 10; i++) x[r][i] *= inv;
    }
#pragma unroll
    for (int ks = 0; ks < 2; ks++)
#pragma unroll
        for (int i = 0; i < 4; i++) {
            const uint32_t p = pack2(x[i & 1][ks * 4 + (i >> 1) * 2], x[i & 1][ks * 4 + (i >> 1) * 2 + 1]);
            pa[ks][i] = sg ? 0u : p;
            pa[2 + ks][i] = sg ? p : 0u;
        }
#pragma unroll
    for (int r = 0; r < 2; r++) {
        const uint32_t p = pack2(x[r][8], x[r][9]);
        pa[4][r] = sg ? 0u : p;
        pa[4][2 + r] = sg ? p : 0u;
    }
}
__device__ __forceinline__ void qa_values(float* O, uint32_t (*pa)[4], Cons& c) {
    wait_full(c);
    const uint32_t st = c.sb + c.p.stage * STAGE;
    const uint64_t dv = mkdesc(st + c.wg * 8192, 16384, 1024, 1), dm = mkdesc(st + 32768 + c.wg * 4096, 2048, 128, 0);
    pin<20>(&pa[0][0]);
    wg_fence();
#pragma unroll
    for (int ks = 0; ks < 4; ks++) wgmma_rs128<1>(O, pa[ks], dv + ks * 128, ks != 0);
    wgmma_rs128<0>(O, pa[4], dm, 1);
    wg_commit();
    pipe_next(c.p);
}
__device__ __forceinline__ void epi_qa(const float* acc, Cons& c, Pend& d, int mb, int nb) {
    uint32_t q[64], pa[2][5][4];
    float S0[32] = {}, M0[8] = {}, S1[32] = {}, M1[8] = {}, O0[64] = {}, O1[64] = {};
    const uint32_t k0 = c.p.stage;
    pack_half(q, acc);
    pin<32>(q); pin<32>(S0); pin<8>(M0);
    qa_scores(S0, M0, q, c);
    pack_half(q + 32, acc + 64);
    pin<32>(q + 32); pin<32>(S1); pin<8>(M1);
    qa_scores(S1, M1, q + 32, c);
    wg_wait<1>();
    pin<32>(S0); pin<8>(M0);
    release(c, k0);
    qa_softmax(pa[0], S0, M0, c);
    wg_wait<0>();
    pin<32>(S1); pin<8>(M1); pin<64>(q);
    release(c, (k0 + 1) & (NSTAGE - 1));
    pin<64>(O0);
    qa_values(O0, pa[0], c);
    qa_softmax(pa[1], S1, M1, c);
    pin<64>(O1);
    qa_values(O1, pa[1], c);
    wg_wait<1>();
    pin<64>(O0); pin<20>(&pa[0][0][0]);
    release(c, (k0 + 2) & (NSTAGE - 1));
    pack_half(d.pk, O0);
    wg_wait<0>();
    pin<64>(O1); pin<20>(&pa[1][0][0]);
    release(c, (k0 + 3) & (NSTAGE - 1));
    pack_half(d.pk + 32, O1);
    d.kind = PEND_KVO; d.row = 4096 + mb * 256 + c.rank * 128 + c.wg * 64; d.col = nb * 256; d.cnt = C_O + mb * 16 + nb;
}

__device__ __forceinline__ void epi_op(const float* acc, const Cons& c, Pend& d, int mb, int nb) {
    pack_half(d.pk, acc); pack_half(d.pk + 32, acc + 64);
    d.kind = PEND_OUT; d.row = mb * 256 + c.rank * 128 + c.wg * 64; d.col = 1024 + nb * 256;
}

__device__ __forceinline__ void epi_a2(float* acc, const Params& P, Cons& c, Pend& d, int mb, int nb) {
    const int g = c.lane >> 2, t = c.lane & 3;
#pragma unroll
    for (int i = 0; i < 32; i++) d.pk[32 + i] = 0;
#pragma unroll 1
    for (int hf = P.zero; hf < 2; hf++) {
        wait_full(c);
        const uint32_t st = c.sb + c.p.stage * STAGE, xa = st + (c.wg * 64 + c.wq * 16 + g) * 128 + t * 4 + (g << 4), da = st + 32768 + t * 4;
#pragma unroll
        for (int j = 0; j < 16; j++) {
            const float* a = acc + j * 4;
            const uint32_t ad = (xa ^ ((j & 7) << 4)) + (j >> 3) * 16384;
            const uint32_t dv = lds32(da + j * 16), u0 = mul_bf2(lds32(ad), dv), u1 = mul_bf2(lds32(ad + 1024), dv);
            d.pk[j * 2] = d.pk[32 + j * 2]; d.pk[j * 2 + 1] = d.pk[33 + j * 2];
            d.pk[32 + j * 2] = pack2(a[0] + bf_lo(u0), a[1] + bf_hi(u0));
            d.pk[33 + j * 2] = pack2(a[2] + bf_lo(u1), a[3] + bf_hi(u1));
        }
        __syncwarp();
        release(c, c.p.stage);
        pipe_next(c.p);
#pragma unroll
        for (int i = 0; i < 64; i++) acc[i] = acc[64 + i];
    }
    d.kind = PEND_OUTA; d.row = mb * 256 + c.rank * 32 + c.wg * 16; d.col = nb * 256;
}

__device__ __forceinline__ float2 cmul(float2 a, float2 b) { return make_float2(fmaf(a.x, b.x, -a.y * b.y), fmaf(a.x, b.y, a.y * b.x)); }
__device__ __forceinline__ float2 cfma(float2 a, float2 b, float2 u) { return make_float2(fmaf(a.x, b.x, fmaf(-a.y, b.y, u.x)), fmaf(a.x, b.y, fmaf(a.y, b.x, u.y))); }
__device__ __forceinline__ float4 ssm_coef(float lre, float lim, float logdt) {
    const float dt = __bfloat162float(__float2bfloat16(expf(logdt)));
    const float ea = expf(dt * lre);
    float sn, cn;
    sincosf(dt * lim, &sn, &cn);
    const float br = ea * cn, bi = ea * sn, nr = br - 1.f;
    const bool sw = fabsf(lre) < fabsf(lim);
    const float big = sw ? lim : lre, r = __fdividef(sw ? lre : lim, big), inv = __fdividef(1.f, fmaf(sw ? lre : lim, r, big));
    const float cr = (sw ? fmaf(nr, r, bi) : fmaf(bi, r, nr)) * inv, ci = (sw ? fmaf(bi, r, -nr) : fmaf(-nr, r, bi)) * inv;
    return make_float4(br, bi, cr, ci);
}
__device__ __forceinline__ void epi_a1(const float* acc, const Params& P, const Cons& c, Pend& d, int mb, int nb) {
    const uint32_t atag = (get_epoch(c.sb) + 1) & 1;
    const int t = c.lane & 3;
    const int p = nb * 128 + c.rank * 64 + c.wg * 32 + c.wq * 8 + (c.lane >> 2);
    const float4 cf = __ldcg(&g_coef[p]);
    const float2 lam = make_float2(cf.x, P.swap_ri ? -cf.y : cf.y);
    const float a0 = P.swap_ri ? -2.f * cf.w : 2.f * cf.z, a1 = P.swap_ri ? 2.f * cf.z : -2.f * cf.w;
    const float b0 = P.swap_ri ? -2.f * cf.z : -2.f * cf.w, b1 = P.swap_ri ? -2.f * cf.w : -2.f * cf.z;
    float2 h = make_float2(0.f, 0.f);
#pragma unroll
    for (int round = 0; round < 2; round++) {
#pragma unroll
        for (int j = 0; j < 32; j++) {
            h = cfma(lam, h, make_float2(acc[j * 4], acc[j * 4 + 2]));
            const float r0 = fmaf(a0, h.x, a1 * h.y), m0 = fmaf(b0, h.x, b1 * h.y);
            h = cfma(lam, h, make_float2(acc[j * 4 + 1], acc[j * 4 + 3]));
            d.pk[j * 2] = pack2(r0, fmaf(a0, h.x, a1 * h.y));
            d.pk[j * 2 + 1] = pack2(m0, fmaf(b0, h.x, b1 * h.y));
        }
        if (round) break;
        float2 l64 = lam;
#pragma unroll
        for (int i = 0; i < 6; i++) l64 = cmul(l64, l64);
        const float2 l128 = cmul(l64, l64), l256 = cmul(l128, l128);
        float2 o = make_float2(__shfl_up_sync(0xffffffffu, h.x, 1), __shfl_up_sync(0xffffffffu, h.y, 1));
        if (t >= 1) h = cfma(l64, o, h);
        o = make_float2(__shfl_up_sync(0xffffffffu, h.x, 2), __shfl_up_sync(0xffffffffu, h.y, 2));
        if (t >= 2) h = cfma(l128, o, h);
        if (t == 3) st_relaxed2(&g_agg[mb * 1024 + p], (__float_as_uint(h.x) & ~1u) | atag, __float_as_uint(h.y));
        h = make_float2(__shfl_up_sync(0xffffffffu, h.x, 1), __shfl_up_sync(0xffffffffu, h.y, 1));
        if (t == 0) h = make_float2(0.f, 0.f);
        uint32_t ax[7], ay[7];
        while (true) {
            uint32_t bad = 0;
#pragma unroll
            for (int j = 0; j < 7; j++) { ax[j] = atag; ay[j] = 0; ld_relaxed2_if(ax[j], ay[j], &g_agg[j * 1024 + p], j < mb); }
#pragma unroll
            for (int j = 0; j < 7; j++) bad |= ax[j] ^ atag;
            if (tags_ok(bad)) break;
            __nanosleep(2 * POLLNS);
        }
        float2 carry = make_float2(0.f, 0.f);
#pragma unroll
        for (int j = 0; j < 7; j++) if (j < mb) carry = cfma(l256, carry, make_float2(__uint_as_float(ax[j]), __uint_as_float(ay[j])));
        float2 w = (t & 1) ? l64 : make_float2(1.f, 0.f);
        if (t & 2) w = cmul(w, l128);
        h = cfma(w, carry, h);
    }
    d.kind = PEND_HT; d.row = nb * 128 + c.rank * 64 + c.wg * 32; d.col = mb * 256; d.cnt = C_HT + mb * 16 + nb;
}

__device__ __forceinline__ uint32_t fresh_tid() { uint32_t t; asm volatile("mov.u32 %0, %%tid.x;" : "=r"(t)); return t; }
__device__ __forceinline__ uint32_t acquire_stage(uint32_t sb, Pipe& p, uint32_t bytes) {
    mbar_wait(sb + B_EMPTY + p.stage * 8, p.phase ^ 1);
    mbar_expect_e(sb + B_FULL + p.stage * 8, bytes);
    return p.stage;
}
__device__ __forceinline__ void producer(const Params& P, const uint32_t sb, const int cta) {
    Pipe p = {0, 0};
    uint32_t resume = 1;
    const int rank = cta & 1;
    const uint16_t both = 3 << (__shfl_sync(0xffffffffu, cluster_rank(), 0) & ~1u);
    for (int it = ITEM_OFF(cta >> 1), item = 0; !(item & LAST); it++) {
        item = ITEM(it);
        const int type = (item >> 8) & 7, mb = (item >> 5) & 7, nb = item & 31, half = item / HALF & 1, hw = item >> 13 & 1;
        const uint32_t epoch = type ? get_epoch(sb) : 0, e1 = epoch + 1;
        if (type == T_CHAIN) {
            const int h = cta / 3, role = cta - h * 3;
#pragma unroll 1
            for (int w = 0; w < 8; w++) {
                mbar_wait(sb + B_EMPTY + (w * 20480 + 20479) / STAGE * 8, 1);
                chain_load(P, sb, cta, w, threadIdx.x & 31, 0);
            }
            uint32_t* flag = &g_cnt(C_FLAG + (role == 2 ? 32 : 0) + h);
            if (role) { wait_count(&g_cnt(C_KV), e1 * 128); fence_async(); }
#pragma unroll 1
            for (int s = 0; s < 63 && role != 0; s++) {
                {
                    mbar_wait(sb + B_GO, s & 1);
                    tma3d_mc_e(sb + S_KV + (role - 1) * 8192, &P.tm[M_SEG], 0, (role - 1) * 2048 + s * 32, h * 2, sb + B_KVFULL, 7 << ((h & 1) * 3), P.pol[s < 48 ? 8 : 11]);
                    if ((s & 7) == 7) { wait_count(&g_cnt(C_KV + 1 + (s >> 3)), e1 * 128); fence_async(); }
                    tma_prefetch3d_e(&P.tm[M_SEG], 0, (role - 1) * 2048 + s * 32 + 32, h * 2);
                }
                if (s > 0 && (s & 3) == 0) {
                    const int i = (s - 1) >> 2;
                    mbar_wait(sb + B_PERS, i & 1);
                    asm volatile("{\n.reg .pred E;\nelect.sync _|E, 0xffffffff;\n@E st.release.gpu.global.u32 [%0], %1;\n}" ::"l"(flag), "r"(epoch * 64 + i * 4 + 4) : "memory");
                }
            }
            if (role == 0) {
                const int lane = threadIdx.x & 31;
                if (lane == 0) mbar_arrive(sb + B_RELM);
#pragma unroll 1
                for (int s = 0; s < 63; s++) {
                    mbar_wait(sb + B_P1, s & 1);
                    if (s > 0) {
                        st_relaxed4(P.xb + xg_buf(s - 1) + h * 2048 + xg_lane(lane), 0, 0, 0, 0);
                        st_relaxed1(P.xb + xg_buf(s - 1) + xg_side(h) + lane * 4, 0);
                        __threadfence();
                    }
                    __syncwarp();
                    if (lane == 0) mbar_arrive(sb + B_RELM);
                }
            }
            if ((threadIdx.x & 31) < M_C1 - 1) asm volatile("prefetch.tensormap [%0];" ::"l"(&P.tm[1 + (threadIdx.x & 31)]) : "memory");
            resume = 0;
            continue;
        }
        const int m0 = mb * 256 + rank * 128, ssm = type >= T_A1;
        const CUtensorMap* ma = &P.tm[max(type, 1) + half * M_HALF];
        const CUtensorMap* mw = &P.tm[type ? M_WV + type : M_WK + (nb >> 4)];
        const int nk = type == T_OP ? 64 : type == T_A2 ? 32 : 16;
        const int a3 = type == T_A1 ? nb * 16 + rank * 8 + hw * 4 : type == T_A2 ? mb * 4 + rank * 2 + hw : (type == T_OP ? 4096 : 0) + m0 + hw * 64;
        const int b3 = type == T_A1 ? mb * 128 + rank * 16 : type == T_A2 ? (nb * 2 + rank) * 128 : (nb & 15) * 4 + rank * 2;
        if (type & 1) {
            wait_count(&g_cnt(type == T_A1 ? C_COEF : C_KV + mb), e1 * (type == T_A1 ? 4 : 128));
            fence_async();
        }
        uint32_t ready = type == T_OP || type == T_A2 ? 0 : ~0u;
        if (type == T_A1) l2_prefetch_e(g_coef + nb * 128 + rank * 64, 1024);
        auto arrived = [&]() {
            const uint32_t t = fresh_tid();
            return __all_sync(0xffffffffu, (int32_t)(ld_acquire(&g_cnt(C_FLAG + (t & 2) * 16 + nb * 2 + (t & 1))) - (epoch * 64 + mb * 8 + rank * 4 + 4)) >= 0);
        };
        bool passed = false;
        mbar_wait(sb + B_RESUME, resume);
#pragma unroll 1
        for (int kt = 0; kt < nk; kt++) {
            if (type == T_QA && kt == 9) passed = arrived();
            while (~ready & (ssm ? 2 | 1 << ((kt & 15) >> 1) : 1 << (kt >> 2))) {
                if (ready) __nanosleep(POLLNS);
                ready = __ballot_sync(0xffffffffu, (int32_t)(ld_acquire(&g_cnt(type * 64 + mb * 16 + (fresh_tid() & 15))) - e1 * 4) >= 0) | 1u << 31;
                fence_async();
            }
            const uint32_t st = acquire_stage(sb, p, STAGE - half * 8192), bar = sb + B_FULL + st * 8;
            const int a1 = type == T_A2 ? kt * 64 : 0, b0 = ssm ? (kt & 15) * 64 : 0;
            tma4d_e(sb + st * STAGE + hw * 8192, ma, kt * 64 - a1, a1, a3, bar, P.pol[11]);
            tma4d_mc_e(sb + st * STAGE + 16384 + rank * 16384, mw + (ssm & kt >> 4), b0, ssm ? 0 : kt * 64, b3, bar, both, P.pol[(item & 0x7e0) == 224 ? 9 : 11]);
            if (type == T_QA && kt < 8) tma_prefetch4d_e(&P.tm[M_OA], nb * 256 + (kt & 3) * 64, (kt >> 2) * 2048 + m0);
            pipe_next(p);
        }
        if (type == T_QA) {
            while (!passed) { passed = arrived(); if (!passed) __nanosleep(POLLNS); }
            fence_async();
        }
        const int q = type == T_QA;
#pragma unroll 1
        for (int e = 0; e < (q ? 4 : type == T_A2 ? 2 : 0); e++) {
            const uint32_t st = acquire_stage(sb, p, q ? 40960 : 32768 + 256), bar = sb + B_FULL + st * 8, dst = sb + st * STAGE;
#pragma unroll 1
            for (int i = 0; i < 2; i++) tma4d_e(dst + i * 16384, &P.tm[q ? M_OA : M_AX], nb * 256 + (e & 1) * 128 + i * 64, 0, q ? (e >> 1) * 2048 + m0 : mb * 128 + rank * 16, bar, P.pol[q ? 3 : 11]);
            const uint8_t* src = q ? (const uint8_t*)(((e >> 1) ? g_vmt : g_km) + ((mb * 8 + rank * 4) * 32 + nb * 2 + (e & 1)) * 512) : (const uint8_t*)(P.Dskip + nb * 256 + e * 128);
#pragma unroll 1
            for (int i = 0; i < (q ? 4 : 1); i++) bulk_g2s_e(dst + 32768 + i * 2048, src + i * 65536, q ? 2048 : 256, bar);
            pipe_next(p);
        }
    }
#pragma unroll 1
    for (int i = 0; i < NSTAGE; i++) { mbar_wait(sb + B_EMPTY + p.stage * 8, p.phase ^ 1); pipe_next(p); }
}

__device__ __forceinline__ uint32_t fresh_ctaid() { uint32_t t; asm volatile("mov.u32 %0, %%ctaid.x;" : "=r"(t)); return t; }
__device__ __forceinline__ void reset_state(const Params& P, Cons& c, Pend& d, uint32_t sb, bool resumed) {
    const uint32_t t = fresh_tid(), b = fresh_ctaid() + P.cta0;
    const int w = __shfl_sync(0xffffffffu, t >> 5, 0);
    c.sb = sb; c.wg = w >> 2; c.wq = w & 3; c.lane = t & 31;
    c.rank = __shfl_sync(0xffffffffu, b & 1, 0); c.pair = __shfl_sync(0xffffffffu, b >> 1, 0);
    c.rel = mapa(sb + B_EMPTY, cluster_rank() ^ (c.lane & 1));
    c.p.stage = 0; c.p.phase = 0;
    c.nst = resumed && c.pair < NCHAIN;
    d = Pend{};
}

__global__ void __launch_bounds__(384, 1) fused_kernel(const __grid_constant__ Params P) {
    extern __shared__ __align__(1024) uint8_t smem[];
    const uint32_t sb = smem_u32(smem);
    asm volatile("griddepcontrol.launch_dependents;");
    declare_fence(P.zero);
    const int tid = threadIdx.x, lane = tid & 31;
    const int warp = __shfl_sync(0xffffffffu, tid >> 5, 0);
    const int cta = __shfl_sync(0xffffffffu, blockIdx.x + P.cta0, 0), pair = cta >> 1, rank = cta & 1;
    if (tid == 0) {
        if (sb & 1023) spin_fault();
        for (int i = 0; i < NSTAGE; i++) { mbar_init(sb + B_FULL + i * 8, 1); mbar_init(sb + B_EMPTY + i * 8, 16); }
        mbar_init(sb + B_RESUME, 2);
        mbar_init(sb + B_KVFULL, 1);
        mbar_init(sb + B_GO, 3); mbar_init(sb + B_RED, 8); mbar_init(sb + B_P1, 1); mbar_init(sb + B_EPOCH, 1); mbar_init(sb + B_PERS, 8); mbar_init(sb + B_INIT, 8); mbar_init(sb + B_INIT2, 8);
        mbar_init(sb + B_READY, 8);
        for (int i = 0; i < 2; i++) { mbar_init(sb + B_SFULL + i * 8, 4); mbar_init(sb + B_SFREE + i * 8, 1); }
        mbar_init(sb + B_RELM, cta % 3 ? 1 : 2); mbar_init(sb + B_X, 9);
        mbar_init(sb + B_DONE, 2);
        mbar_expect(sb + B_X, 4096);
        sts64(sb + S_EV, 0, 0);
        asm volatile("fence.mbarrier_init.release.cluster;" ::: "memory");
    }
    __syncthreads();
    cluster_sync();
    if (warp >= 8) {
        asm volatile("setmaxnreg.dec.sync.aligned.u32 24;");
        if (warp == 8) {
            producer(P, sb, cta);
        } else if (warp == 9) {
            const uint32_t epoch = __shfl_sync(0xffffffffu, ld_acquire(&g_cnt(C_EPOCH)), 0);
            if (lane == 0) { sts32(sb + S_EPOCH, epoch); mbar_arrive(sb + B_EPOCH); red_release(&g_cnt(C_READ)); }
            __syncwarp();
            if (pair < NCHAIN) pacer(P, sb, cta, lane, epoch);
            if (pair < NCHAIN && cta % 3) {
                mbar_wait_bounded(sb + B_PERS, 1);
                if (lane == 0) asm volatile("st.release.gpu.global.u32 [%0], %1;" ::"l"(&g_cnt(C_FLAG + (cta % 3 == 2 ? 32 : 0) + cta / 3)), "r"(epoch * 64 + 64) : "memory");
            }
            if (cta == 0 && lane == 0) {
                for (int n = 0; (int32_t)(ld_acquire(&g_cnt(C_READ)) - (epoch + 1) * (NPAIR * 2)) < 0; n++) if (n > SPIN_LIMIT) spin_fault();
                st_relaxed1(&g_cnt(C_EPOCH), epoch + 1);
            }
            __syncwarp();
            mbar_wait_bounded(sb + B_DONE, 0);
        } else {
            store_warp(P, sb, warp - 10, cta);
        }
    } else {
        asm volatile("setmaxnreg.inc.sync.aligned.u32 240;");
        Cons c;
        Pend d;
        if (pair < NCHAIN) {
            reset_state(P, c, d, sb, false);
            {
                const int item = ITEM(ITEM_OFF(pair));
                float acc[128];
                mainloop<true>(acc, P, c, d, T_KV, 16);
                epi_kv(acc, c, d, (item >> 5) & 7, item & 31);
            }
            mbar_wait(sb + B_EMPTY + 3 * 8, 1);
            drain_both(c, d);
            uint32_t wr[40][4];
            chain_fetch(P, sb, cta, warp, lane, wr);
            chain_bounds(sb, cta, warp, lane, wr);
            if (warp < 4) chain_role<false>(P, sb, cta, warp, lane, wr);
            else chain_role<true>(P, sb, cta, warp, lane, wr);
            bar_sync(1, 256);
            const uint32_t t2 = fresh_tid();
            if (t2 < 2) mbar_arrive_cluster(mapa(sb + B_RESUME, cluster_rank() ^ t2));
        } else if (pair >= NPAIR - 2) {
            const int ch = (pair - (NPAIR - 2)) * 512 + rank * 256 + tid;
            g_coef[ch] = ssm_coef(__bfloat162float(P.Lre[ch]), __bfloat162float(P.Lim[ch]), __bfloat162float(P.logdt[ch]));
            bar_sync(1, 256);
            if (tid == 0) red_release(&g_cnt(C_COEF));
        }
        reset_state(P, c, d, sb, true);
        int it = ITEM_OFF(c.pair) + (c.pair < NCHAIN ? 2 : 0);
        for (int prev = c.pair < NCHAIN ? ITEM(it - 1) : 0;; prev = ITEM(it++)) {
            const bool last = prev & LAST;
            const int item = ITEM(it), type = (item >> 8) & 7, mb = (item >> 5) & 7, nb = item & 31;
            const bool idle = (item >> 12 & 3) == 3 - 2 * c.wg;
            if (d.kind != PEND_NONE && ((prev & (LAST | URGENT)) || idle || (type != T_KV && !bar_and(5 + c.wg, mbar_try(sb + B_FULL + c.p.stage * 8, c.p.phase))))) {
#pragma unroll 1
                while (d.kind != PEND_NONE) drain(P, c, d);
            }
            if (last) break;
            const int nk = type == T_OP ? 64 : type == T_A2 ? 32 : 16;
            if (idle) {
#pragma unroll 1
                for (int kt = nk + (type == T_A2 ? 2 : type == T_QA ? 4 : 0); kt > 0; kt--) { wait_full(c); release(c, c.p.stage); pipe_next(c.p); }
                continue;
            }
            float acc[128];
            mainloop(acc, P, c, d, type, nk);
            if (type == T_KV) epi_kv(acc, c, d, mb, nb);
            else if (type == T_QA) epi_qa(acc, c, d, mb, nb);
            else if (type == T_OP) epi_op(acc, c, d, mb, nb);
            else if (type == T_A1) epi_a1(acc, P, c, d, mb, nb);
            else epi_a2(acc, P, c, d, mb, nb);
        }
        staging_wait(c);
        staging_post(c, PEND_NONE, 0, 0, 0);
        if (c.wq == 0 && c.lane == 0) mbar_arrive(sb + B_DONE);
    }
}

typedef CUresult (*EncodeFn)(CUtensorMap*, CUtensorMapDataType, cuuint32_t, void*, const cuuint64_t*, const cuuint64_t*, const cuuint32_t*, const cuuint32_t*,
                             CUtensorMapInterleave, CUtensorMapSwizzle, CUtensorMapL2promotion, CUtensorMapFloatOOBfill);
void encode(EncodeFn fn, CUtensorMap* m, const void* base, int rank, const uint64_t* dims, const uint64_t* strides, const uint32_t* box, CUtensorMapSwizzle swz = CU_TENSOR_MAP_SWIZZLE_128B) {
    cuuint64_t d[5], s[5]; cuuint32_t b[5], e[5];
    for (int i = 0; i < rank; i++) { d[i] = dims[i]; b[i] = box[i]; e[i] = 1; if (i) s[i - 1] = strides[i - 1]; }
    fn(m, CU_TENSOR_MAP_DATA_TYPE_BFLOAT16, rank, (void*)base, d, s, b, e, CU_TENSOR_MAP_INTERLEAVE_NONE, swz,
       CU_TENSOR_MAP_L2_PROMOTION_L2_128B, CU_TENSOR_MAP_FLOAT_OOB_FILL_NONE);
}
void map_kmajor(EncodeFn fn, CUtensorMap* m, const void* base, uint64_t rows, uint64_t cols, uint32_t box_rows) {
    const uint64_t d[4] = {cols, 1, 1, rows}, s[3] = {cols * 2, cols * 2, cols * 2}; const uint32_t b[4] = {64, 1, 1, box_rows};
    encode(fn, m, base, 4, d, s, b);
}
void map_mnmajor(EncodeFn fn, CUtensorMap* m, const void* base, uint64_t krows, uint64_t cols, uint32_t groups = 2) {
    const uint64_t d[4] = {64, krows, 1, cols / 64}, s[3] = {cols * 2, 128, 128}; const uint32_t b[4] = {64, 64, 1, groups};
    encode(fn, m, base, 4, d, s, b);
}
void map_store(EncodeFn fn, CUtensorMap* m, const void* base, uint64_t rows, uint64_t cols) {
    const uint64_t d[2] = {cols, rows}, s[1] = {cols * 2}; const uint32_t b[2] = {64, 32};
    encode(fn, m, base, 2, d, s, b);
}

}

extern "C" void kernel_launch(void* const* d_in, const int* in_sizes, int n_in, void* d_out, int out_size) {
    static Params P;
    static EncodeFn fn = nullptr;
    if (!fn) {
        cudaDriverEntryPointQueryResult q;
        cudaGetDriverEntryPoint("cuTensorMapEncodeTiled", (void**)&fn, cudaEnableDefault, &q);
        cudaFuncSetAttribute(fused_kernel, cudaFuncAttributeMaxDynamicSharedMemorySize, S_TOTAL);
    }
    const bf16* in[15];
    for (int i = 0; i < 15; i++) in[i] = (const bf16*)d_in[i];
    void *kvo, *ht;
    cudaGetSymbolAddress(&kvo, g_kvo);
    cudaGetSymbolAddress(&ht, g_ht);
    map_kmajor(fn, &P.tm[M_BX], in[9], 2048, 1024, 128);
    map_mnmajor(fn, &P.tm[M_WQ], in[11], 1024, 4096);
    map_mnmajor(fn, &P.tm[M_WK], in[12], 1024, 4096);
    map_mnmajor(fn, &P.tm[M_WV], in[13], 1024, 4096);
    map_mnmajor(fn, &P.tm[M_WO], in[14], 4096, 1024);
    map_kmajor(fn, &P.tm[M_OA], kvo, 3 * 2048, 4096, 128);
    P.swap_ri = in[4] < in[3];
    {
        const bf16* lo = P.swap_ri ? in[4] : in[3];
        const uint64_t diff = (uint64_t)((const char*)(P.swap_ri ? in[3] : in[4]) - (const char*)lo);
        const uint64_t d[4] = {1024, 8, 2, 128}, s[3] = {2048, diff, 16384}; const uint32_t b[4] = {64, 8, 2, 8}, bh[4] = {64, 8, 2, 4};
        encode(fn, &P.tm[M_AB], lo, 4, d, s, b);
        encode(fn, &P.tm[M_AB + M_HALF], lo, 4, d, s, bh);
    }
    {
        const uint64_t d[4] = {1024, 2, 4, 1024}, s[3] = {2048, 64 * 2048, 4096}; const uint32_t b[4] = {64, 2, 4, 16};
        encode(fn, &P.tm[M_AX], in[0], 4, d, s, b);
    }
    map_mnmajor(fn, &P.tm[M_HT], ht, 2048, 2048);
    map_kmajor(fn, &P.tm[M_CRE], in[5], 1024, 1024, 128);
    map_kmajor(fn, &P.tm[M_CIM], in[6], 1024, 1024, 128);
    map_store(fn, &P.tm[M_KVO], kvo, 3 * 2048, 4096);
    map_store(fn, &P.tm[M_HTS], ht, 2048, 2048);
    map_kmajor(fn, &P.tm[M_BX + M_HALF], in[9], 2048, 1024, 64);
    map_kmajor(fn, &P.tm[M_OA + M_HALF], kvo, 3 * 2048, 4096, 64);
    map_mnmajor(fn, &P.tm[M_HT + M_HALF], ht, 2048, 2048, 1);
    for (int i = 0; i < 3; i++) {
        const uint64_t d[3] = {64, 1024, 64}, s[2] = {8192, 128}; const uint32_t b[3] = {64, 16, 2};
        encode(fn, &P.tm[M_C1 + i], in[11 + i], 3, d, s, b);
    }
    {
        const uint64_t d[2] = {1024, 4096}, s[1] = {2048}; const uint32_t b[2] = {32, 32};
        encode(fn, &P.tm[M_CO], in[14], 2, d, s, b, CU_TENSOR_MAP_SWIZZLE_64B);
    }
    {
        const uint64_t d[3] = {64, 3 * 2048, 64}, s[2] = {8192, 128}; const uint32_t b[3] = {64, 32, 2};
        encode(fn, &P.tm[M_SEG], kvo, 3, d, s, b);
    }
    void* xs;
    cudaGetSymbolAddress(&xs, g_x);
    P.xb = (uint8_t*)(((uintptr_t)xs + (2u << 20) - 1) & ~(uintptr_t)((2u << 20) - 1));
    P.mem0 = in[10]; P.Bx = in[9];
    P.Ax = in[0]; P.Lre = in[1]; P.Lim = in[2]; P.logdt = in[7]; P.Dskip = in[8];
    P.out = (float*)d_out;
    int pv[10] = {1140, 0, 110, 0, 330, 64, 32, 32, 0, 0};
    int ef = 779;
    for (int i = 0; i < 12; i++) P.pol[i] = (ef >> i & 1) ? 0x12F0000000000000ull : 0x1000000000000000ull;
    P.dly = pv[0]; P.mrg = pv[2];
    P.rd = pv[4]; P.guard = pv[5]; P.clampv = pv[6]; P.clamp0 = pv[7]; P.kvd = pv[9]; P.xd = pv[8];
    cudaLaunchConfig_t cfg = {};
    cudaLaunchAttribute at[2];
    cfg.blockDim = dim3(384); cfg.dynamicSmemBytes = S_TOTAL; cfg.stream = cudaStreamPerThread; cfg.attrs = at;
    at[0].id = cudaLaunchAttributeClusterDimension;
    at[0].val.clusterDim.y = at[0].val.clusterDim.z = 1;
    at[1].id = cudaLaunchAttributeProgrammaticStreamSerialization;
    at[1].val.programmaticStreamSerializationAllowed = 1;
    for (int i = 0; i < 2; i++) {
        P.cta0 = i ? 2 * NCHAIN : 0;
        cfg.gridDim = dim3(i ? 2 * (NPAIR - NCHAIN) : 2 * NCHAIN);
        at[0].val.clusterDim.x = i ? 2 : 6;
        cfg.numAttrs = 1 + i;
        cudaLaunchKernelEx(&cfg, fused_kernel, P);
    }
}
```
